```python
import torch

def _softmax(x, axis=-1):
    return torch.softmax(x, dim=axis)
def _gelu(x):
    return torch.nn.functional.gelu(x, approximate="tanh")
def _silu(x):
    return torch.nn.functional.silu(x)
def _sigmoid(x):
    return torch.sigmoid(x)
def _layernorm(x, axis=-1, eps=1e-5):
    m = x.mean(dim=axis, keepdim=True)
    v = x.var(dim=axis, keepdim=True, unbiased=False)
    return (x - m) / torch.sqrt(v + eps)
def _scatter_add(tgt, idx, src, axis=0):
    return tgt.clone().index_add_(axis, idx, src)
def _segment_sum(src, seg, n):
    out = torch.zeros((n,) + src.shape[1:], dtype=src.dtype)
    return out.index_add_(0, seg, src)
def _pad(x, pw):
    flat = tuple(v for pair in reversed(pw) for v in pair)
    return torch.nn.functional.pad(x, flat)

kernel_name = 'standalone__gqa_block_cached__near_ridge'

def setup_inputs():

    _w = (lambda a: (lambda t: t.to(torch.bfloat16) if t.is_floating_point() else t)(torch.as_tensor(a)))
    B, Sq, D = 16, 240, 640
    Hq, Hkv, Sk, Dh = 32, 32, 1024, 128
    assert Hq % Hkv == 0, (Hq, Hkv)
    return {
        "x": _w((lambda *s: torch.randn(*s, dtype=torch.bfloat16) * 0.8)(B, Sq, D)),
        "k_cache": _w((lambda *s: torch.randn(*s, dtype=torch.bfloat16) * 0.8)(B, Hkv, Sk, Dh)),
        "v_cache": _w((lambda *s: torch.randn(*s, dtype=torch.bfloat16) * 0.05)(B, Hkv, Sk, Dh)),
        "wq": _w((lambda *s: torch.randn(*s, dtype=torch.bfloat16) * 0.8)(D, Hq * Dh) * (D ** -0.5)),
        "wo": _w((lambda *s: torch.randn(*s, dtype=torch.bfloat16) * 0.05)(Hq * Dh, D) * ((Hq * Dh) ** -0.5)),
    }

def reference(x, k_cache, v_cache, wq, wo):
    B, Sq, D = x.shape
    Hq, Dh = 32, 128
    Hkv = k_cache.shape[1]
    rep = Hq // Hkv
    q = (lambda x, *d: x.permute(*d))((x @ wq).reshape(B, Sq, Hq, Dh), 0, 2, 1, 3)
    k = (lambda x, n, axis: torch.repeat_interleave(x, n, dim=axis))(k_cache, rep, axis=1)
    v = (lambda x, n, axis: torch.repeat_interleave(x, n, dim=axis))(v_cache, rep, axis=1)
    scores = torch.einsum("bhqd,bhkd->bhqk", q, k) * (Dh ** -0.5)
    p = _softmax(scores, axis=-1)
    o = torch.einsum("bhqk,bhkd->bhqd", p, v)
    return (lambda x, *d: x.permute(*d))(o, 0, 2, 1, 3).reshape(B, Sq, Hq * Dh) @ wo
```

```cpp
#include <cuda_runtime.h>
#include <cuda.h>
#include <cuda_bf16.h>
#include <stdint.h>

namespace {

constexpr int NB = 16, SQ = 240, DM = 640, NH = 32, SK = 1024, DH = 128, HD = NH * DH;
constexpr int NUNITS = 256;
constexpr int NOTILES = 60;
#define PF_ON 1
#define PF_LEAD 2
constexpr float QSCALE = 0.08838834764831845f * 1.4426950408889634f;
constexpr float L_MIN = 9.5367431640625e-07f;
constexpr float L_MAX = 1.152921504606846976e18f;

constexpr uint32_t RING_SLOTS = 6, RING_BYTES = 16384;
constexpr uint32_t XB = 15360;
constexpr uint32_t BB = 20480;
constexpr uint32_t OFF_Q = RING_SLOTS * RING_BYTES;
constexpr uint32_t OFF_P = OFF_Q + 4 * XB;
constexpr uint32_t OFF_INV = OFF_P + 4 * XB;
constexpr uint32_t OFF_BAR = OFF_INV + 1024;
constexpr uint32_t BAR_RFULL = OFF_BAR, BAR_REMPTY = BAR_RFULL + 48, BAR_XFULL = BAR_REMPTY + 48,
    BAR_XEMPTY = BAR_XFULL + 64, BAR_BFULL = BAR_XEMPTY + 32, BAR_BEMPTY = BAR_BFULL + 48, BAR_STAGE = BAR_BEMPTY + 48;
constexpr uint32_t SMEM_BYTES = BAR_STAGE + 16 + 1024;

constexpr uint32_t HI128 = (1u << 30) | (1024 >> 4);
constexpr uint32_t HI64 = (2u << 30) | (512 >> 4);

__device__ __nv_bfloat16 g_o[NB * SQ * HD];
__device__ unsigned g_cnt[64 * 8 + 8];
#define PROF_STAMP(i)

struct Params {
  const __nv_bfloat16 *x, *k, *v, *wq;
  __nv_bfloat16* out;
};

__device__ __forceinline__ void wg_fence() { asm volatile("wgmma.fence.sync.aligned;" ::: "memory"); }
__device__ __forceinline__ void wg_commit() { asm volatile("wgmma.commit_group.sync.aligned;" ::: "memory"); }
template <int N> __device__ __forceinline__ void wg_wait() { asm volatile("wgmma.wait_group.sync.aligned %0;" ::"n"(N) : "memory"); }
template <int N> __device__ __forceinline__ void reg_fence(float (&r)[N]) {
#pragma unroll
  for (int i = 0; i < N; i++) asm volatile("" : "+f"(r[i])::"memory");
}
template <int TA, int TB>
__device__ __forceinline__ void wgmma_n120(float (&d)[60], uint32_t a_lo, uint32_t a_hi, uint32_t b_lo, uint32_t b_hi, int acc) {
  asm volatile(
      "{\n.reg .pred p;\n.reg .b64 da, db;\nsetp.ne.b32 p, %64, 0;\n"
      "mov.b64 da, {%60, %61};\nmov.b64 db, {%62, %63};\n"
      "wgmma.mma_async.sync.aligned.m64n120k16.f32.bf16.bf16 {"
      "%0, %1, %2, %3, %4, %5, %6, %7, %8, %9, %10, %11, %12, %13, %14, %15, %16, %17, %18, %19, %20, %21, %22, %23, "
      "%24, %25, %26, %27, %28, %29, %30, %31, %32, %33, %34, %35, %36, %37, %38, %39, %40, %41, %42, %43, %44, %45, "
      "%46, %47, %48, %49, %50, %51, %52, %53, %54, %55, %56, %57, %58, %59"
      "}, da, db, p, 1, 1, %65, %66;\n}\n"
      : "+f"(d[0]), "+f"(d[1]), "+f"(d[2]), "+f"(d[3]), "+f"(d[4]), "+f"(d[5]), "+f"(d[6]), "+f"(d[7]), "+f"(d[8]),
        "+f"(d[9]), "+f"(d[10]), "+f"(d[11]), "+f"(d[12]), "+f"(d[13]), "+f"(d[14]), "+f"(d[15]), "+f"(d[16]),
        "+f"(d[17]), "+f"(d[18]), "+f"(d[19]), "+f"(d[20]), "+f"(d[21]), "+f"(d[22]), "+f"(d[23]), "+f"(d[24]),
        "+f"(d[25]), "+f"(d[26]), "+f"(d[27]), "+f"(d[28]), "+f"(d[29]), "+f"(d[30]), "+f"(d[31]), "+f"(d[32]),
        "+f"(d[33]), "+f"(d[34]), "+f"(d[35]), "+f"(d[36]), "+f"(d[37]), "+f"(d[38]), "+f"(d[39]), "+f"(d[40]),
        "+f"(d[41]), "+f"(d[42]), "+f"(d[43]), "+f"(d[44]), "+f"(d[45]), "+f"(d[46]), "+f"(d[47]), "+f"(d[48]),
        "+f"(d[49]), "+f"(d[50]), "+f"(d[51]), "+f"(d[52]), "+f"(d[53]), "+f"(d[54]), "+f"(d[55]), "+f"(d[56]),
        "+f"(d[57]), "+f"(d[58]), "+f"(d[59])
      : "r"(a_lo), "r"(a_hi), "r"(b_lo), "r"(b_hi), "r"(acc), "n"(TA), "n"(TB));
}

template <int TA, int TB>
__device__ __forceinline__ void wgmma_n160(float (&d)[80], uint32_t a_lo, uint32_t a_hi, uint32_t b_lo, uint32_t b_hi, int acc) {
  asm volatile(
      "{\n.reg .pred p;\n.reg .b64 da, db;\nsetp.ne.b32 p, %84, 0;\n"
      "mov.b64 da, {%80, %81};\nmov.b64 db, {%82, %83};\n"
      "wgmma.mma_async.sync.aligned.m64n160k16.f32.bf16.bf16 {"
      "%0, %1, %2, %3, %4, %5, %6, %7, %8, %9, %10, %11, %12, %13, %14, %15, %16, %17, %18, %19, %20, %21, %22, %23, "
      "%24, %25, %26, %27, %28, %29, %30, %31, %32, %33, %34, %35, %36, %37, %38, %39, %40, %41, %42, %43, %44, %45, "
      "%46, %47, %48, %49, %50, %51, %52, %53, %54, %55, %56, %57, %58, %59, %60, %61, %62, %63, %64, %65, %66, %67, "
      "%68, %69, %70, %71, %72, %73, %74, %75, %76, %77, %78, %79"
      "}, da, db, p, 1, 1, %85, %86;\n}\n"
      : "+f"(d[0]), "+f"(d[1]), "+f"(d[2]), "+f"(d[3]), "+f"(d[4]), "+f"(d[5]), "+f"(d[6]), "+f"(d[7]), "+f"(d[8]),
        "+f"(d[9]), "+f"(d[10]), "+f"(d[11]), "+f"(d[12]), "+f"(d[13]), "+f"(d[14]), "+f"(d[15]), "+f"(d[16]),
        "+f"(d[17]), "+f"(d[18]), "+f"(d[19]), "+f"(d[20]), "+f"(d[21]), "+f"(d[22]), "+f"(d[23]), "+f"(d[24]),
        "+f"(d[25]), "+f"(d[26]), "+f"(d[27]), "+f"(d[28]), "+f"(d[29]), "+f"(d[30]), "+f"(d[31]), "+f"(d[32]),
        "+f"(d[33]), "+f"(d[34]), "+f"(d[35]), "+f"(d[36]), "+f"(d[37]), "+f"(d[38]), "+f"(d[39]), "+f"(d[40]),
        "+f"(d[41]), "+f"(d[42]), "+f"(d[43]), "+f"(d[44]), "+f"(d[45]), "+f"(d[46]), "+f"(d[47]), "+f"(d[48]),
        "+f"(d[49]), "+f"(d[50]), "+f"(d[51]), "+f"(d[52]), "+f"(d[53]), "+f"(d[54]), "+f"(d[55]), "+f"(d[56]),
        "+f"(d[57]), "+f"(d[58]), "+f"(d[59]), "+f"(d[60]), "+f"(d[61]), "+f"(d[62]), "+f"(d[63]), "+f"(d[64]),
        "+f"(d[65]), "+f"(d[66]), "+f"(d[67]), "+f"(d[68]), "+f"(d[69]), "+f"(d[70]), "+f"(d[71]), "+f"(d[72]),
        "+f"(d[73]), "+f"(d[74]), "+f"(d[75]), "+f"(d[76]), "+f"(d[77]), "+f"(d[78]), "+f"(d[79])
      : "r"(a_lo), "r"(a_hi), "r"(b_lo), "r"(b_hi), "r"(acc), "n"(TA), "n"(TB));
}
__device__ __forceinline__ void mbar_init(uint32_t bar, int cnt) { asm volatile("mbarrier.init.shared::cta.b64 [%0], %1;" ::"r"(bar), "r"(cnt)); }
__device__ __forceinline__ void mbar_expect(uint32_t bar, uint32_t bytes) {
  asm volatile("mbarrier.arrive.expect_tx.shared::cta.b64 _, [%0], %1;" ::"r"(bar), "r"(bytes) : "memory");
}
__device__ __forceinline__ uint32_t mapa(uint32_t addr, uint32_t cta) {
  uint32_t r; asm("mapa.shared::cluster.u32 %0, %1, %2;" : "=r"(r) : "r"(addr), "r"(cta)); return r;
}
__device__ __forceinline__ void mbar_expect_cl(uint32_t cbar, uint32_t bytes) {
  asm volatile("mbarrier.arrive.expect_tx.shared::cluster.b64 _, [%0], %1;" ::"r"(cbar), "r"(bytes) : "memory");
}
__device__ __forceinline__ void mbar_arrive(uint32_t bar) { asm volatile("mbarrier.arrive.shared::cta.b64 _, [%0];" ::"r"(bar) : "memory"); }
__device__ __forceinline__ void mbar_arrive_cl(uint32_t cbar) { asm volatile("mbarrier.arrive.shared::cluster.b64 _, [%0];" ::"r"(cbar) : "memory"); }
__device__ __forceinline__ void mbar_wait(uint32_t bar, uint32_t parity) {
  asm volatile(
      "{\n.reg .pred p;\n.reg .u32 n;\n"
      "mbarrier.try_wait.parity.shared::cta.b64 p, [%0], %1;\n@p bra WAIT_DONE;\n"
      "mov.u32 n, 0;\n"
      "WAIT_LOOP:\n"
      "mbarrier.try_wait.parity.shared::cta.b64 p, [%0], %1;\n@p bra WAIT_DONE;\n"
      "add.u32 n, n, 1;\nsetp.lt.u32 p, n, 0x4000000;\n@p bra WAIT_LOOP;\ntrap;\n"
      "WAIT_DONE:\n}\n" ::"r"(bar), "r"(parity) : "memory");
}
__device__ __forceinline__ void tma2d(uint32_t dst, const CUtensorMap* m, int c0, int c1, uint32_t bar) {
  asm volatile("cp.async.bulk.tensor.2d.shared::cluster.global.mbarrier::complete_tx::bytes [%0], [%1, {%3, %4}], [%2];"
               ::"r"(dst), "l"(m), "r"(bar), "r"(c0), "r"(c1) : "memory");
}
__device__ __forceinline__ void tma3d(uint32_t dst, const CUtensorMap* m, int c0, int c1, int c2, uint32_t bar) {
  asm volatile("cp.async.bulk.tensor.3d.shared::cluster.global.mbarrier::complete_tx::bytes [%0], [%1, {%3, %4, %5}], [%2];"
               ::"r"(dst), "l"(m), "r"(bar), "r"(c0), "r"(c1), "r"(c2) : "memory");
}
__device__ __forceinline__ void tma3d_hint(uint32_t dst, const CUtensorMap* m, int c0, int c1, int c2, uint32_t bar, uint64_t pol) {
  asm volatile("cp.async.bulk.tensor.3d.shared::cluster.global.mbarrier::complete_tx::bytes.L2::cache_hint [%0], [%1, {%3, %4, %5}], [%2], %6;"
               ::"r"(dst), "l"(m), "r"(bar), "r"(c0), "r"(c1), "r"(c2), "l"(pol) : "memory");
}
__device__ __forceinline__ void tma2d_mc(uint32_t dst, const CUtensorMap* m, int c0, int c1, uint32_t bar) {
  asm volatile("cp.async.bulk.tensor.2d.shared::cluster.global.mbarrier::complete_tx::bytes.multicast::cluster [%0], [%1, {%3, %4}], [%2], %5;"
               ::"r"(dst), "l"(m), "r"(bar), "r"(c0), "r"(c1), "h"((uint16_t)3) : "memory");
}
__device__ __forceinline__ void tma3d_mc(uint32_t dst, const CUtensorMap* m, int c0, int c1, int c2, uint32_t bar) {
  asm volatile("cp.async.bulk.tensor.3d.shared::cluster.global.mbarrier::complete_tx::bytes.multicast::cluster [%0], [%1, {%3, %4, %5}], [%2], %6;"
               ::"r"(dst), "l"(m), "r"(bar), "r"(c0), "r"(c1), "r"(c2), "h"((uint16_t)3) : "memory");
}
__device__ __forceinline__ void tma3d_store(const CUtensorMap* m, int c0, int c1, int c2, uint32_t src) {
  asm volatile("cp.async.bulk.tensor.3d.global.shared::cta.bulk_group [%0, {%2, %3, %4}], [%1];"
               ::"l"(m), "r"(src), "r"(c0), "r"(c1), "r"(c2) : "memory");
}
__device__ __forceinline__ void l2_prefetch(const void* p, uint32_t bytes, uint64_t pol) {
  asm volatile("cp.async.bulk.prefetch.L2.global.L2::cache_hint [%0], %1, %2;" ::"l"(p), "r"(bytes), "l"(pol) : "memory");
}
__device__ __forceinline__ void fence_async_smem() { asm volatile("fence.proxy.async.shared::cta;" ::: "memory"); }
__device__ __forceinline__ void bar_sync(int id) { asm volatile("bar.sync %0, 128;" ::"r"(id) : "memory"); }
__device__ __forceinline__ bool bar_red_or(int id, bool v) {
  uint32_t r;
  asm volatile("{\n.reg .pred p, q;\nsetp.ne.u32 p, %2, 0;\nbar.red.or.pred q, %1, 128, p;\nselp.u32 %0, 1, 0, q;\n}\n"
               : "=r"(r) : "r"(id), "r"((uint32_t)v) : "memory");
  return r != 0;
}
__device__ __forceinline__ void cluster_sync() { asm volatile("barrier.cluster.arrive.aligned;\nbarrier.cluster.wait.aligned;" ::: "memory"); }
__device__ __forceinline__ float ex2(float x) { float y; asm("ex2.approx.ftz.f32 %0, %1;" : "=f"(y) : "f"(x)); return y; }
__device__ __forceinline__ uint32_t pack(float lo, float hi) { uint32_t r; asm("cvt.rn.bf16x2.f32 %0, %1, %2;" : "=r"(r) : "f"(hi), "f"(lo)); return r; }
__device__ __forceinline__ void stsm4t(uint32_t a, uint32_t r0, uint32_t r1, uint32_t r2, uint32_t r3) {
  asm volatile("stmatrix.sync.aligned.m8n8.x4.trans.shared.b16 [%0], {%1,%2,%3,%4};" ::"r"(a), "r"(r0), "r"(r1), "r"(r2), "r"(r3) : "memory");
}
__device__ __forceinline__ void stsm2t(uint32_t a, uint32_t r0, uint32_t r1) {
  asm volatile("stmatrix.sync.aligned.m8n8.x2.trans.shared.b16 [%0], {%1,%2};" ::"r"(a), "r"(r0), "r"(r1) : "memory");
}
__device__ __forceinline__ void mma16816(float (&d)[4], const uint32_t (&a)[4], uint32_t b0, uint32_t b1) {
  asm volatile("mma.sync.aligned.m16n8k16.row.col.f32.bf16.bf16.f32 {%0,%1,%2,%3}, {%4,%5,%6,%7}, {%8,%9}, {%0,%1,%2,%3};"
               : "+f"(d[0]), "+f"(d[1]), "+f"(d[2]), "+f"(d[3]) : "r"(a[0]), "r"(a[1]), "r"(a[2]), "r"(a[3]), "r"(b0), "r"(b1));
}

struct Ring {
  uint32_t slot = 0, phase = 0;
  __device__ __forceinline__ void next() { if (++slot == RING_SLOTS) { slot = 0; phase ^= 1; } }
};

__device__ __forceinline__ void mma_tn(float (&o0)[60], float (&o1)[60], uint32_t a, uint32_t b, int acc) {
#pragma unroll
  for (int k = 0; k < 4; k++) {
    wgmma_n120<1, 0>(o0, a + k * 128, HI128, b + k * 2, HI128, k == 0 ? acc : 1);
    wgmma_n120<1, 0>(o1, a + 512 + k * 128, HI128, b + k * 2, HI128, k == 0 ? acc : 1);
  }
}
__device__ __forceinline__ void mma_qk(float (&s)[60], uint32_t a, uint32_t q) {
#pragma unroll
  for (int k = 0; k < 8; k++)
    wgmma_n120<0, 0>(s, a + (k >> 2) * 512 + (k & 3) * 2, HI128, q + (k >> 2) * (XB >> 4) + (k & 3) * 2, HI128, k != 0);
}
__device__ __forceinline__ void exp_store(const float (&s)[60], float (&l)[30], uint32_t dst) {
#pragma unroll
  for (int j = 0; j < 15; j += 2) {
    uint32_t p[4];
#pragma unroll
    for (int jj = 0; jj < 2; jj++) {
      if (j + jj < 15) {
        const int c = j + jj;
        float e0 = ex2(s[4 * c]), e1 = ex2(s[4 * c + 1]), e2 = ex2(s[4 * c + 2]), e3 = ex2(s[4 * c + 3]);
        l[2 * c] += e0; l[2 * c + 1] += e1; l[2 * c] += e2; l[2 * c + 1] += e3;
        p[2 * jj] = pack(e0, e1); p[2 * jj + 1] = pack(e2, e3);
      }
    }
    if (j + 1 < 15) stsm4t(dst + j * 1024, p[0], p[1], p[2], p[3]);
    else stsm2t(dst + j * 1024, p[0], p[1]);
  }
}

__device__ __forceinline__ void slow_path(const Params& P, int b, int h, int row0, uint32_t stage, int w, int lane) {
  const int g = lane >> 2, q = lane & 3;
  const uint16_t* wq = reinterpret_cast<const uint16_t*>(P.wq) + h * DH + g;
  const __nv_bfloat16* kp = P.k + (size_t)(b * NH + h) * SK * DH;
  const uint16_t* vp = reinterpret_cast<const uint16_t*>(P.v) + (size_t)(b * NH + h) * SK * DH + g;
#pragma unroll 1
  for (int t = w; t < 8; t += 4) {
    const int r0 = 16 * t + g, r1 = r0 + 8;
    const __nv_bfloat16* x0 = P.x + (size_t)(b * SQ + row0 + r0) * DM + 2 * q;
    const __nv_bfloat16* x1 = P.x + (size_t)(b * SQ + row0 + min(r1, 119)) * DM + 2 * q;
    float o[16][4];
#pragma unroll
    for (int n = 0; n < 16; n++) o[n][0] = o[n][1] = o[n][2] = o[n][3] = 0.f;
#pragma unroll 1
    for (int k0 = 0; k0 < DM; k0 += 16) {
      uint32_t a[4] = {*(const uint32_t*)(x0 + k0), *(const uint32_t*)(x1 + k0), *(const uint32_t*)(x0 + k0 + 8), *(const uint32_t*)(x1 + k0 + 8)};
      const uint16_t* wr = wq + (size_t)(k0 + 2 * q) * HD;
#pragma unroll
      for (int n = 0; n < 16; n++)
        mma16816(o[n], a, wr[8 * n] | ((uint32_t)wr[8 * n + HD] << 16), wr[8 * n + 8 * HD] | ((uint32_t)wr[8 * n + 9 * HD] << 16));
    }
    uint32_t qa[8][4];
#pragma unroll
    for (int k = 0; k < 8; k++) {
      qa[k][0] = pack(o[2 * k][0] * QSCALE, o[2 * k][1] * QSCALE);
      qa[k][1] = pack(o[2 * k][2] * QSCALE, o[2 * k][3] * QSCALE);
      qa[k][2] = pack(o[2 * k + 1][0] * QSCALE, o[2 * k + 1][1] * QSCALE);
      qa[k][3] = pack(o[2 * k + 1][2] * QSCALE, o[2 * k + 1][3] * QSCALE);
    }
#pragma unroll
    for (int n = 0; n < 16; n++) o[n][0] = o[n][1] = o[n][2] = o[n][3] = 0.f;
    float m0 = -INFINITY, m1 = -INFINITY, l0 = 0.f, l1 = 0.f;
#pragma unroll 1
    for (int key0 = 0; key0 < SK; key0 += 16) {
      float s[2][4];
#pragma unroll
      for (int nt = 0; nt < 2; nt++) {
        s[nt][0] = s[nt][1] = s[nt][2] = s[nt][3] = 0.f;
        const __nv_bfloat16* kr = kp + (size_t)(key0 + 8 * nt + g) * DH + 2 * q;
#pragma unroll
        for (int k = 0; k < 8; k++) mma16816(s[nt], qa[k], *(const uint32_t*)(kr + 16 * k), *(const uint32_t*)(kr + 16 * k + 8));
      }
      float n0 = fmaxf(fmaxf(s[0][0], s[0][1]), fmaxf(s[1][0], s[1][1])), n1 = fmaxf(fmaxf(s[0][2], s[0][3]), fmaxf(s[1][2], s[1][3]));
      n0 = fmaxf(n0, __shfl_xor_sync(~0u, n0, 1)); n1 = fmaxf(n1, __shfl_xor_sync(~0u, n1, 1));
      n0 = fmaxf(n0, __shfl_xor_sync(~0u, n0, 2)); n1 = fmaxf(n1, __shfl_xor_sync(~0u, n1, 2));
      n0 = fmaxf(n0, m0); n1 = fmaxf(n1, m1);
      const float z0 = n0 == -INFINITY ? 0.f : n0, z1 = n1 == -INFINITY ? 0.f : n1;
      const float c0 = ex2(m0 - z0), c1 = ex2(m1 - z1);
      m0 = n0; m1 = n1;
#pragma unroll
      for (int nt = 0; nt < 2; nt++) {
        s[nt][0] = ex2(s[nt][0] - z0); s[nt][1] = ex2(s[nt][1] - z0);
        s[nt][2] = ex2(s[nt][2] - z1); s[nt][3] = ex2(s[nt][3] - z1);
      }
      l0 = l0 * c0 + s[0][0] + s[0][1] + s[1][0] + s[1][1];
      l1 = l1 * c1 + s[0][2] + s[0][3] + s[1][2] + s[1][3];
      uint32_t pa[4] = {pack(s[0][0], s[0][1]), pack(s[0][2], s[0][3]), pack(s[1][0], s[1][1]), pack(s[1][2], s[1][3])};
      const uint16_t* vr = vp + (size_t)(key0 + 2 * q) * DH;
#pragma unroll
      for (int n = 0; n < 16; n++) {
        o[n][0] *= c0; o[n][1] *= c0; o[n][2] *= c1; o[n][3] *= c1;
        mma16816(o[n], pa, vr[8 * n] | ((uint32_t)vr[8 * n + DH] << 16), vr[8 * n + 8 * DH] | ((uint32_t)vr[8 * n + 9 * DH] << 16));
      }
    }
    l0 += __shfl_xor_sync(~0u, l0, 1); l1 += __shfl_xor_sync(~0u, l1, 1);
    l0 += __shfl_xor_sync(~0u, l0, 2); l1 += __shfl_xor_sync(~0u, l1, 2);
    const float i0 = 1.f / l0, i1 = 1.f / l1;
#pragma unroll
    for (int n = 0; n < 16; n++) {
      const uint32_t a = stage + (n >> 3) * XB + r0 * 128 + (((n & 7) ^ g) << 4) + q * 4;
      asm volatile("st.shared.b32 [%0], %1;" ::"r"(a), "r"(pack(o[n][0] * i0, o[n][1] * i0)) : "memory");
      if (r1 < 120) asm volatile("st.shared.b32 [%0], %1;" ::"r"(a + 1024), "r"(pack(o[n][2] * i1, o[n][3] * i1)) : "memory");
    }
  }
}

__device__ __forceinline__ int unit_batch(int u) { return (u & 63) >> 2; }
__device__ __forceinline__ int unit_head(int u, int rank) { return (u >> 6) * 8 + (u & 3) * 2 + rank; }

__global__ void __cluster_dims__(2, 1, 1) __launch_bounds__(384, 1)
fused_attn_kernel(const __grid_constant__ CUtensorMap tm_x, const __grid_constant__ CUtensorMap tm_wq,
                  const __grid_constant__ CUtensorMap tm_k, const __grid_constant__ CUtensorMap tm_v,
                  const __grid_constant__ CUtensorMap tm_ost, const __grid_constant__ CUtensorMap tm_old,
                  const __grid_constant__ CUtensorMap tm_wo, const __grid_constant__ Params P) {
  extern __shared__ uint8_t smem_raw[];
  const uint32_t sb = ((uint32_t)__cvta_generic_to_shared(smem_raw) + 1023) & ~1023u;
  const int warp = __shfl_sync(~0u, threadIdx.x >> 5, 0);
  const int lane = threadIdx.x & 31;
  const int rank = blockIdx.x & 1, cl = blockIdx.x >> 1, ncl = gridDim.x >> 1;

  if (threadIdx.x == 0) {
    for (int i = 0; i < 6; i++) {
      mbar_init(sb + BAR_RFULL + 8 * i, 1); mbar_init(sb + BAR_REMPTY + 8 * i, 8);
      mbar_init(sb + BAR_BFULL + 8 * i, 1); mbar_init(sb + BAR_BEMPTY + 8 * i, 16);
    }
    for (int i = 0; i < 8; i++) mbar_init(sb + BAR_XFULL + 8 * i, 1);
    for (int i = 0; i < 4; i++) mbar_init(sb + BAR_XEMPTY + 8 * i, 8);
    for (int i = 0; i < 2; i++) mbar_init(sb + BAR_STAGE + 8 * i, 1);
    asm volatile("fence.mbarrier_init.release.cluster;" ::: "memory");
  }
  __syncthreads();
  cluster_sync();

  if (warp >= 8) {
    asm volatile("setmaxnreg.dec.sync.aligned.u32 24;");
    if (warp == 8) {
      if (lane == 0) {
        uint64_t pol;
        asm volatile("createpolicy.fractional.L2::evict_first.b64 %0, 1.0;" : "=l"(pol));
        Ring r;
        int pf_u = cl, pf_j = 0, pf_acc = PF_LEAD * 42;
        auto acquire = [&]() {
          pf_acc += 16;
          while (pf_acc >= 42) {
            pf_acc -= 42;
            if (PF_ON && pf_u < NUNITS) {
              const size_t off = ((size_t)(unit_batch(pf_u) * NH + unit_head(pf_u, rank)) * SK + pf_j * 64) * DH;
              l2_prefetch(P.k + off, 16384, pol);
              l2_prefetch(P.v + off, 16384, pol);
              if (++pf_j == 16) { pf_j = 0; pf_u += ncl; }
            }
          }
          mbar_wait(sb + BAR_REMPTY + 8 * r.slot, r.phase ^ 1);
          mbar_expect(sb + BAR_RFULL + 8 * r.slot, RING_BYTES);
        };
        for (int u = cl; u < NUNITS; u += ncl) {
          const int h = unit_head(u, rank);
          const int krow = (unit_batch(u) * NH + h) * SK;
#pragma unroll 1
          for (int s = 0; s < 10; s++) {
            acquire();
            tma3d(sb + r.slot * RING_BYTES, &tm_wq, 0, s * 64, 2 * h, sb + BAR_RFULL + 8 * r.slot);
            r.next();
          }
#pragma unroll 1
          for (int j = 0; j <= 16; j++) {
            if (j < 16) {
              acquire();
              tma3d_hint(sb + r.slot * RING_BYTES, &tm_k, 0, krow + j * 64, 0, sb + BAR_RFULL + 8 * r.slot, pol);
              r.next();
            }
            if (j > 0) {
              acquire();
              tma3d_hint(sb + r.slot * RING_BYTES, &tm_v, 0, krow + (j - 1) * 64, 0, sb + BAR_RFULL + 8 * r.slot, pol);
              r.next();
            }
          }
        }
        for (int t = cl; t < NOTILES; t += ncl) {
          const int row0 = (t >> 2) * 256 + rank * 128;
          const int b0 = row0 / SQ, b1 = (row0 + 127) / SQ;
#pragma unroll 1
          for (int ks = 0; ks < 64; ks++) {
            if ((ks & 15) == 0) {
              for (int bb = b0; bb <= b1; bb++) {
                const unsigned* c = &g_cnt[(bb * 4 + (ks >> 4)) * 8];
                unsigned v, n = 0;
                do {
                  asm volatile("ld.acquire.gpu.global.u32 %0, [%1];" : "=r"(v) : "l"(c) : "memory");
                  if (++n > (1u << 26)) __trap();
                } while (v < 16);
              }
              asm volatile("fence.proxy.async.global;" ::: "memory");
            }
            mbar_wait(sb + BAR_REMPTY + 8 * r.slot, r.phase ^ 1);
            mbar_expect(sb + BAR_RFULL + 8 * r.slot, RING_BYTES);
            tma2d(sb + r.slot * RING_BYTES, &tm_old, ks * 64, row0, sb + BAR_RFULL + 8 * r.slot);
            r.next();
          }
        }
      }
    } else if (warp == 9) {
      if (lane == 0) {
        uint32_t it = 0;
        for (int u = cl; u < NUNITS; u += ncl, it++) {
          const int row = unit_batch(u) * SQ + rank * 120;
#pragma unroll 1
          for (int s = 0; s < 10; s++) {
            const uint32_t j = s & 3, par = ((s >> 2) + (j < 2 ? it : 0)) & 1;
            mbar_wait(sb + BAR_XEMPTY + 8 * j, par ^ 1);
            const uint32_t fb = sb + BAR_XFULL + 32 * rank + 8 * j;
            mbar_expect(fb, XB);
            mbar_expect_cl(mapa(fb, rank ^ 1), XB);
            tma2d_mc(sb + OFF_Q + rank * 2 * XB + (j & 1) * XB + (j >> 1) * 4 * XB, &tm_x, s * 64, row, fb);
          }
        }
        uint32_t slot = rank, phase = 0;
        for (int t = cl; t < NOTILES; t += ncl) {
#pragma unroll 1
          for (int ks = rank; ks < 64; ks += 2) {
            mbar_wait(sb + BAR_BEMPTY + 8 * slot, phase);
            const uint32_t fb = sb + BAR_BFULL + 8 * slot;
            mbar_expect(fb, BB);
            mbar_expect_cl(mapa(fb, rank ^ 1), BB);
            tma3d_mc(sb + OFF_Q + slot * BB, &tm_wo, 0, ks * 64, (t & 3) * 5, fb);
            slot += 2;
            if (slot >= 6) { slot -= 6; phase ^= 1; }
          }
        }
      }
    } else {
      const int wg = warp - 10;
      uint32_t it = 0;
      for (int u = cl; u < NUNITS; u += ncl, it++) {
        const int b = unit_batch(u);
        if (lane == 0) {
          mbar_wait(sb + BAR_STAGE + 8 * wg, it & 1);
          tma3d_store(&tm_ost, 0, b * SQ + wg * 120, 2 * unit_head(u, rank), sb + OFF_P + wg * 2 * XB);
          asm volatile("cp.async.bulk.commit_group;" ::: "memory");
          asm volatile("cp.async.bulk.wait_group.read 0;" ::: "memory");
        }
        __syncwarp();
        if (u + ncl < NUNITS) {
          if (lane < 8) mbar_arrive_cl(mapa(sb + BAR_XEMPTY + 16 + 8 * (lane >> 2), wg));
        } else {
          if (lane < 12) mbar_arrive_cl(mapa(sb + BAR_BEMPTY + 24 + 8 * (lane >> 2), (3 + (lane >> 2)) & 1));
        }
        if (lane == 0) {
          asm volatile("cp.async.bulk.wait_group 0;" ::: "memory");
          asm volatile("fence.proxy.async.global;" ::: "memory");
          asm volatile("red.release.gpu.global.add.u32 [%0], 1;" ::"l"(&g_cnt[(b * 4 + (u >> 6)) * 8]) : "memory");
        }
      }
    }
  } else {
    asm volatile("setmaxnreg.inc.sync.aligned.u32 240;");
    const int wg = warp >> 2, w = warp & 3;
    const uint32_t qreg = sb + OFF_Q + wg * 2 * XB, preg = qreg + 4 * XB;
    const uint32_t st_off = ((lane >> 4) * 8 + (lane & 7)) * 128 + (((2 * w + ((lane >> 3) & 1)) ^ (lane & 7)) << 4);
    const uint32_t xempty = mapa(sb + BAR_XEMPTY, wg);
    const int bar_id = 1 + wg;
    Ring r;
    uint32_t it = 0;
    const uint32_t qd = (qreg & 0x3FFFF) >> 4, pd = qd + (4 * XB >> 4);
    auto ring_addr = [&]() { return ((sb & 0x3FFFF) + r.slot * RING_BYTES) >> 4; };
    auto ring_wait = [&]() { mbar_wait(sb + BAR_RFULL + 8 * r.slot, r.phase); };
    auto release = [&](uint32_t slot) { if (lane == 0) mbar_arrive(sb + BAR_REMPTY + 8 * slot); };
    PROF_STAMP(0);
    for (int u = cl; u < NUNITS; u += ncl, it++) {
      float o0[60], o1[60];
      ring_wait();
      mbar_wait(sb + BAR_XFULL + 32 * wg, it & 1);
      wg_fence();
      mma_tn(o0, o1, ring_addr(), qd, 0);
      wg_commit();
      uint32_t prev = r.slot;
      r.next();
#pragma unroll 1
      for (int s = 1; s < 10; s++) {
        const uint32_t j = s & 3, par = ((s >> 2) + (j < 2 ? it : 0)) & 1;
        ring_wait();
        mbar_wait(sb + BAR_XFULL + 32 * wg + 8 * j, par);
        wg_fence();
        mma_tn(o0, o1, ring_addr(), qd + (j & 1) * (XB >> 4) + (j >> 1) * (4 * XB >> 4), 1);
        wg_commit();
        wg_wait<1>();
        release(prev);
        if (s <= 6 && lane == 0) mbar_arrive_cl(xempty + 8 * ((s - 1) & 3));
        prev = r.slot;
        r.next();
      }
      wg_wait<0>();
      reg_fence(o0); reg_fence(o1);
      release(prev);
      PROF_STAMP(1 + it * 8);
      bar_sync(bar_id);
#pragma unroll
      for (int j = 0; j < 15; j += 2) {
        if (j + 1 < 15) {
          stsm4t(qreg + st_off + j * 1024, pack(o0[4 * j] * QSCALE, o0[4 * j + 1] * QSCALE), pack(o0[4 * j + 2] * QSCALE, o0[4 * j + 3] * QSCALE),
                 pack(o0[4 * j + 4] * QSCALE, o0[4 * j + 5] * QSCALE), pack(o0[4 * j + 6] * QSCALE, o0[4 * j + 7] * QSCALE));
          stsm4t(qreg + XB + st_off + j * 1024, pack(o1[4 * j] * QSCALE, o1[4 * j + 1] * QSCALE), pack(o1[4 * j + 2] * QSCALE, o1[4 * j + 3] * QSCALE),
                 pack(o1[4 * j + 4] * QSCALE, o1[4 * j + 5] * QSCALE), pack(o1[4 * j + 6] * QSCALE, o1[4 * j + 7] * QSCALE));
        } else {
          stsm2t(qreg + st_off + j * 1024, pack(o0[4 * j] * QSCALE, o0[4 * j + 1] * QSCALE), pack(o0[4 * j + 2] * QSCALE, o0[4 * j + 3] * QSCALE));
          stsm2t(qreg + XB + st_off + j * 1024, pack(o1[4 * j] * QSCALE, o1[4 * j + 1] * QSCALE), pack(o1[4 * j + 2] * QSCALE, o1[4 * j + 3] * QSCALE));
        }
      }
      fence_async_smem();
      bar_sync(bar_id);
      PROF_STAMP(2 + it * 8);

      float sc[60], l[30];
      ring_wait();
      wg_fence();
      mma_qk(sc, ring_addr(), qd);
      wg_commit();
#pragma unroll
      for (int i = 0; i < 30; i++) l[i] = 0.f;
#pragma unroll
      for (int i = 0; i < 60; i++) o0[i] = o1[i] = 0.f;
      wg_wait<0>();
      reg_fence(sc);
      release(r.slot);
      r.next();
      exp_store(sc, l, preg + st_off);
      fence_async_smem();
      bar_sync(bar_id);
      PROF_STAMP(3 + it * 8);
#pragma unroll 1
      for (int s = 1; s < 16; s++) {
        const uint32_t kslot = r.slot;
        ring_wait();
        wg_fence();
        mma_qk(sc, ring_addr(), qd);
        wg_commit();
        r.next();
        ring_wait();
        wg_fence();
        mma_tn(o0, o1, ring_addr(), pd + ((s - 1) & 1) * (XB >> 4), 1);
        wg_commit();
        wg_wait<1>();
        reg_fence(sc);
        release(kslot);
        if (s == 15) {
          if (u + ncl < NUNITS) { if (lane < 2) mbar_arrive_cl(xempty + 8 * lane); }
          else if (lane < 3) mbar_arrive_cl(mapa(sb + BAR_BEMPTY + 8 * lane, lane & 1));
        }
        exp_store(sc, l, preg + (s & 1) * XB + st_off);
        wg_wait<0>();
        reg_fence(o0); reg_fence(o1);
        release(r.slot);
        r.next();
        fence_async_smem();
        bar_sync(bar_id);
      }
      PROF_STAMP(4 + it * 8);
      ring_wait();
      wg_fence();
      mma_tn(o0, o1, ring_addr(), pd + (XB >> 4), 1);
      wg_commit();
      {
        const uint32_t a = preg + (8 * w + (lane >> 2)) * 480 + (lane & 3) * 8;
#pragma unroll
        for (int j = 0; j < 15; j++) asm volatile("st.shared.v2.f32 [%0], {%1, %2};" ::"r"(a + j * 32), "f"(l[2 * j]), "f"(l[2 * j + 1]) : "memory");
      }
      bar_sync(bar_id);
      bool bad = false;
      {
        const int t = min(32 * w + lane, 119);
        float a0 = 0.f, a1 = 0.f, a2 = 0.f, a3 = 0.f;
#pragma unroll
        for (int g = 0; g < 32; g += 4) {
          float v0, v1, v2, v3;
          asm volatile("ld.shared.f32 %0, [%1];" : "=f"(v0) : "r"(preg + g * 480 + t * 4) : "memory");
          asm volatile("ld.shared.f32 %0, [%1];" : "=f"(v1) : "r"(preg + (g + 1) * 480 + t * 4) : "memory");
          asm volatile("ld.shared.f32 %0, [%1];" : "=f"(v2) : "r"(preg + (g + 2) * 480 + t * 4) : "memory");
          asm volatile("ld.shared.f32 %0, [%1];" : "=f"(v3) : "r"(preg + (g + 3) * 480 + t * 4) : "memory");
          a0 += v0; a1 += v1; a2 += v2; a3 += v3;
        }
        const float lsum = (a0 + a1) + (a2 + a3);
        bad = !(lsum >= L_MIN && lsum <= L_MAX);
        asm volatile("st.shared.f32 [%0], %1;" ::"r"(sb + OFF_INV + wg * 512 + (32 * w + lane) * 4), "f"(1.f / lsum) : "memory");
      }
      wg_wait<0>();
      reg_fence(o0); reg_fence(o1);
      release(r.slot);
      r.next();
      bar_sync(bar_id);
      PROF_STAMP(5 + it * 8);
      {
        uint32_t mx_s = 0, mx_u = 0;
#pragma unroll
        for (int j = 0; j < 15; j += 2) {
          uint32_t pa[4], pb[4];
#pragma unroll
          for (int jj = 0; jj < 2; jj++) {
            if (j + jj < 15) {
              const int c = j + jj;
              float i0, i1;
              asm volatile("ld.shared.v2.f32 {%0, %1}, [%2];" : "=f"(i0), "=f"(i1) : "r"(sb + OFF_INV + wg * 512 + c * 32 + (lane & 3) * 8) : "memory");
              pa[2 * jj] = pack(o0[4 * c] * i0, o0[4 * c + 1] * i1); pa[2 * jj + 1] = pack(o0[4 * c + 2] * i0, o0[4 * c + 3] * i1);
              pb[2 * jj] = pack(o1[4 * c] * i0, o1[4 * c + 1] * i1); pb[2 * jj + 1] = pack(o1[4 * c + 2] * i0, o1[4 * c + 3] * i1);
              mx_s = __vimax3_s16x2(mx_s, pa[2 * jj], pa[2 * jj + 1]); mx_u = __vimax3_u16x2(mx_u, pa[2 * jj], pa[2 * jj + 1]);
              mx_s = __vimax3_s16x2(mx_s, pb[2 * jj], pb[2 * jj + 1]); mx_u = __vimax3_u16x2(mx_u, pb[2 * jj], pb[2 * jj + 1]);
            }
          }
          if (j + 1 < 15) {
            stsm4t(preg + st_off + j * 1024, pa[0], pa[1], pa[2], pa[3]);
            stsm4t(preg + XB + st_off + j * 1024, pb[0], pb[1], pb[2], pb[3]);
          } else {
            stsm2t(preg + st_off + j * 1024, pa[0], pa[1]);
            stsm2t(preg + XB + st_off + j * 1024, pb[0], pb[1]);
          }
        }
        bad = bad || (mx_s & 0xFFFF) >= 0x7F80 || (mx_s >> 16) >= 0x7F80 || (mx_u & 0xFFFF) >= 0xFF80 || (mx_u >> 16) >= 0xFF80;
      }
      fence_async_smem();
      if (bar_red_or(bar_id, bad)) {
        slow_path(P, unit_batch(u), unit_head(u, rank), wg * 120, preg, w, lane);
        fence_async_smem();
        bar_sync(bar_id);
      }
      if (w == 0 && lane == 0) mbar_arrive(sb + BAR_STAGE + 8 * wg);
      PROF_STAMP(6 + it * 8);
    }

    uint32_t bslot = 0, bphase = 0;
    for (int t = cl; t < NOTILES; t += ncl) {
      float acc[80];
#pragma unroll
      for (int i = 0; i < 80; i++) acc[i] = 0.f;
      uint32_t prev = 0, bprev = 0;
#pragma unroll 1
      for (int ks = 0; ks < 64; ks++) {
        ring_wait();
        mbar_wait(sb + BAR_BFULL + 8 * bslot, bphase);
        wg_fence();
        const uint32_t a = ring_addr() + wg * 512, bd = (((sb & 0x3FFFF) + OFF_Q + bslot * BB) >> 4) | ((4096u >> 4) << 16);
#pragma unroll
        for (int k = 0; k < 4; k++) wgmma_n160<0, 1>(acc, a + k * 2, HI128, bd + k * 64, HI64, 1);
        wg_commit();
        if (ks > 0) {
          wg_wait<1>();
          release(prev);
          if (lane == 0) mbar_arrive_cl(mapa(sb + BAR_BEMPTY + 8 * bprev, bprev & 1));
        }
        prev = r.slot; bprev = bslot;
        r.next();
        if (++bslot == 6) { bslot = 0; bphase ^= 1; }
      }
      wg_wait<0>();
      reg_fence(acc);
      release(prev);
      if (lane == 0) mbar_arrive_cl(mapa(sb + BAR_BEMPTY + 8 * bprev, bprev & 1));
      PROF_STAMP(40);
      __nv_bfloat16* op = P.out + (size_t)((t >> 2) * 256 + rank * 128 + wg * 64 + w * 16 + (lane >> 2)) * DM + (t & 3) * 160 + (lane & 3) * 2;
#pragma unroll
      for (int j = 0; j < 20; j++) {
        *reinterpret_cast<uint32_t*>(op + j * 8) = pack(acc[4 * j], acc[4 * j + 1]);
        *reinterpret_cast<uint32_t*>(op + 8 * DM + j * 8) = pack(acc[4 * j + 2], acc[4 * j + 3]);
      }
    }
    PROF_STAMP(41);
  }
  __syncthreads();
  cluster_sync();
  if (threadIdx.x == 0) {
    __threadfence();
    if (atomicAdd(&g_cnt[512], 1) == gridDim.x - 1) {
      for (int i = 0; i <= 64; i++) g_cnt[i * 8] = 0;
    }
  }
}

typedef CUresult (*EncodeFn)(CUtensorMap*, CUtensorMapDataType, cuuint32_t, void*, const cuuint64_t*, const cuuint64_t*,
                             const cuuint32_t*, const cuuint32_t*, CUtensorMapInterleave, CUtensorMapSwizzle,
                             CUtensorMapL2promotion, CUtensorMapFloatOOBfill);

void make_map(EncodeFn enc, CUtensorMap* m, const void* p, int rank, const cuuint64_t* dims, const cuuint64_t* strides,
              const cuuint32_t* box, CUtensorMapSwizzle sw, CUtensorMapL2promotion promo) {
  cuuint32_t es[3] = {1, 1, 1};
  enc(m, CU_TENSOR_MAP_DATA_TYPE_BFLOAT16, rank, const_cast<void*>(p), dims, strides, box, es, CU_TENSOR_MAP_INTERLEAVE_NONE, sw,
      promo, CU_TENSOR_MAP_FLOAT_OOB_FILL_NONE);
}

}

extern "C" void kernel_launch(void* const* d_in, const int* in_sizes, int n_in, void* d_out, int out_size) {
  static EncodeFn enc = nullptr;
  static int nclusters = 0;
  static void* o_ptr = nullptr;
  if (!enc) {
    cudaDriverEntryPointQueryResult qr;
    cudaGetDriverEntryPoint("cuTensorMapEncodeTiled", (void**)&enc, cudaEnableDefault, &qr);
    cudaFuncSetAttribute(fused_attn_kernel, cudaFuncAttributeMaxDynamicSharedMemorySize, SMEM_BYTES);
    cudaGetSymbolAddress(&o_ptr, g_o);
    cudaLaunchConfig_t cfg = {};
    cfg.gridDim = 128; cfg.blockDim = 384; cfg.dynamicSmemBytes = SMEM_BYTES;
    cudaLaunchAttribute at; at.id = cudaLaunchAttributeClusterDimension;
    at.val.clusterDim.x = 2; at.val.clusterDim.y = 1; at.val.clusterDim.z = 1;
    cfg.attrs = &at; cfg.numAttrs = 1;
    int n = 0;
    cudaOccupancyMaxActiveClusters(&n, fused_attn_kernel, &cfg);
    nclusters = n >= 64 || n <= 0 ? 64 : n;
  }
  const __nv_bfloat16* x = (const __nv_bfloat16*)d_in[0];
  const __nv_bfloat16* k = (const __nv_bfloat16*)d_in[1];
  const __nv_bfloat16* v = (const __nv_bfloat16*)d_in[2];
  const __nv_bfloat16* wq = (const __nv_bfloat16*)d_in[3];
  const __nv_bfloat16* wo = (const __nv_bfloat16*)d_in[4];
  CUtensorMap tm_x, tm_wq, tm_k, tm_v, tm_ost, tm_old, tm_wo;
  const auto S128 = CU_TENSOR_MAP_SWIZZLE_128B;
  const auto P128 = CU_TENSOR_MAP_L2_PROMOTION_L2_128B, P256 = CU_TENSOR_MAP_L2_PROMOTION_L2_256B;
  { cuuint64_t d[2] = {DM, NB * SQ}, s[1] = {DM * 2}; cuuint32_t b[2] = {64, 120}; make_map(enc, &tm_x, x, 2, d, s, b, S128, P128); }
  { cuuint64_t d[3] = {64, DM, HD / 64}, s[2] = {HD * 2, 128}; cuuint32_t b[3] = {64, 64, 2}; make_map(enc, &tm_wq, wq, 3, d, s, b, S128, P256); }
  { cuuint64_t d[3] = {64, NB * NH * SK, 2}, s[2] = {DH * 2, 128}; cuuint32_t b[3] = {64, 64, 2};
    make_map(enc, &tm_k, k, 3, d, s, b, S128, P256); make_map(enc, &tm_v, v, 3, d, s, b, S128, P256); }
  { cuuint64_t d[3] = {64, NB * SQ, HD / 64}, s[2] = {HD * 2, 128}; cuuint32_t b[3] = {64, 120, 2}; make_map(enc, &tm_ost, o_ptr, 3, d, s, b, S128, P128); }
  { cuuint64_t d[2] = {HD, NB * SQ}, s[1] = {HD * 2}; cuuint32_t b[2] = {64, 128}; make_map(enc, &tm_old, o_ptr, 2, d, s, b, S128, P128); }
  { cuuint64_t d[3] = {32, HD, DM / 32}, s[2] = {DM * 2, 64}; cuuint32_t b[3] = {32, 64, 5};
    make_map(enc, &tm_wo, wo, 3, d, s, b, CU_TENSOR_MAP_SWIZZLE_64B, P128); }
  Params P{x, k, v, wq, (__nv_bfloat16*)d_out};
  fused_attn_kernel<<<2 * nclusters, 384, SMEM_BYTES>>>(tm_x, tm_wq, tm_k, tm_v, tm_ost, tm_old, tm_wo, P);
}
```

```cpp
#include <cuda_runtime.h>
#include <cuda.h>
#include <cuda_bf16.h>
#include <stdint.h>

namespace {

constexpr int NB = 16, SQ = 240, DM = 640, NH = 32, SK = 1024, DH = 128, HD = NH * DH;
constexpr int NROWS = NB * SQ;
constexpr int NUNITS = 256;
#define WAITV 0
#define KV_PROMO P128
#define PF_POL 0
#define NOT 60
#define O_EF 1
#define PF_HOLD 4
#define VREL 8
#define PP_MODE 1
#define PF_N 4
#define PF_J0 3
#define PF_STEP 3
#define PF_WHAT 2
#define ROT 1
constexpr int NOTILES = NOT;
constexpr float QSCALE = 0.08838834764831845f * 1.4426950408889634f;
constexpr float L_MIN = 9.5367431640625e-07f;
constexpr float L_MAX = 1.152921504606846976e18f;

constexpr uint32_t RING_SLOTS = 6, RING_BYTES = 16384;
constexpr uint32_t XB = 15360;
constexpr uint32_t BB = 20480;
constexpr uint32_t OFF_Q = RING_SLOTS * RING_BYTES;
constexpr uint32_t OFF_P = OFF_Q + 4 * XB;
constexpr uint32_t OFF_INV = OFF_P + 4 * XB;
constexpr uint32_t OFF_BAR = OFF_INV + 1024;
constexpr uint32_t BAR_RFULL = OFF_BAR, BAR_REMPTY = BAR_RFULL + 48, BAR_XFULL = BAR_REMPTY + 48,
    BAR_XEMPTY = BAR_XFULL + 64, BAR_BFULL = BAR_XEMPTY + 32, BAR_BEMPTY = BAR_BFULL + 48, BAR_STAGE = BAR_BEMPTY + 48;
constexpr uint32_t OFF_TR = BAR_STAGE + 16;
constexpr uint32_t SMEM_BYTES = OFF_TR + 1024;

constexpr uint32_t HI128 = (1u << 30) | (1024 >> 4);
constexpr uint32_t HI64 = (2u << 30) | (512 >> 4);

__device__ __nv_bfloat16 g_o[HD * NROWS];
__device__ unsigned g_cnt[64 * 8 + 8];
#define TR(i)

struct Params {
  const __nv_bfloat16 *x, *k, *v, *wq;
  __nv_bfloat16* out;
};

__device__ __forceinline__ void wg_fence() { asm volatile("wgmma.fence.sync.aligned;" ::: "memory"); }
__device__ __forceinline__ void wg_commit() { asm volatile("wgmma.commit_group.sync.aligned;" ::: "memory"); }
template <int N> __device__ __forceinline__ void wg_wait() { asm volatile("wgmma.wait_group.sync.aligned %0;" ::"n"(N) : "memory"); }
template <int N> __device__ __forceinline__ void reg_fence(float (&r)[N]) {
#pragma unroll
  for (int i = 0; i < N; i++) asm volatile("" : "+f"(r[i])::"memory");
}
template <int TA, int TB>
__device__ __forceinline__ void wgmma_n120(float (&d)[60], uint32_t a_lo, uint32_t a_hi, uint32_t b_lo, uint32_t b_hi, int acc) {
  asm volatile(
      "{\n.reg .pred p;\n.reg .b64 da, db;\nsetp.ne.b32 p, %64, 0;\n"
      "mov.b64 da, {%60, %61};\nmov.b64 db, {%62, %63};\n"
      "wgmma.mma_async.sync.aligned.m64n120k16.f32.bf16.bf16 {"
      "%0, %1, %2, %3, %4, %5, %6, %7, %8, %9, %10, %11, %12, %13, %14, %15, %16, %17, %18, %19, %20, %21, %22, %23, "
      "%24, %25, %26, %27, %28, %29, %30, %31, %32, %33, %34, %35, %36, %37, %38, %39, %40, %41, %42, %43, %44, %45, "
      "%46, %47, %48, %49, %50, %51, %52, %53, %54, %55, %56, %57, %58, %59"
      "}, da, db, p, 1, 1, %65, %66;\n}\n"
      : "+f"(d[0]), "+f"(d[1]), "+f"(d[2]), "+f"(d[3]), "+f"(d[4]), "+f"(d[5]), "+f"(d[6]), "+f"(d[7]), "+f"(d[8]),
        "+f"(d[9]), "+f"(d[10]), "+f"(d[11]), "+f"(d[12]), "+f"(d[13]), "+f"(d[14]), "+f"(d[15]), "+f"(d[16]),
        "+f"(d[17]), "+f"(d[18]), "+f"(d[19]), "+f"(d[20]), "+f"(d[21]), "+f"(d[22]), "+f"(d[23]), "+f"(d[24]),
        "+f"(d[25]), "+f"(d[26]), "+f"(d[27]), "+f"(d[28]), "+f"(d[29]), "+f"(d[30]), "+f"(d[31]), "+f"(d[32]),
        "+f"(d[33]), "+f"(d[34]), "+f"(d[35]), "+f"(d[36]), "+f"(d[37]), "+f"(d[38]), "+f"(d[39]), "+f"(d[40]),
        "+f"(d[41]), "+f"(d[42]), "+f"(d[43]), "+f"(d[44]), "+f"(d[45]), "+f"(d[46]), "+f"(d[47]), "+f"(d[48]),
        "+f"(d[49]), "+f"(d[50]), "+f"(d[51]), "+f"(d[52]), "+f"(d[53]), "+f"(d[54]), "+f"(d[55]), "+f"(d[56]),
        "+f"(d[57]), "+f"(d[58]), "+f"(d[59])
      : "r"(a_lo), "r"(a_hi), "r"(b_lo), "r"(b_hi), "r"(acc), "n"(TA), "n"(TB));
}

template <int TA, int TB>
__device__ __forceinline__ void wgmma_n160(float (&d)[80], uint32_t a_lo, uint32_t a_hi, uint32_t b_lo, uint32_t b_hi, int acc) {
  asm volatile(
      "{\n.reg .pred p;\n.reg .b64 da, db;\nsetp.ne.b32 p, %84, 0;\n"
      "mov.b64 da, {%80, %81};\nmov.b64 db, {%82, %83};\n"
      "wgmma.mma_async.sync.aligned.m64n160k16.f32.bf16.bf16 {"
      "%0, %1, %2, %3, %4, %5, %6, %7, %8, %9, %10, %11, %12, %13, %14, %15, %16, %17, %18, %19, %20, %21, %22, %23, "
      "%24, %25, %26, %27, %28, %29, %30, %31, %32, %33, %34, %35, %36, %37, %38, %39, %40, %41, %42, %43, %44, %45, "
      "%46, %47, %48, %49, %50, %51, %52, %53, %54, %55, %56, %57, %58, %59, %60, %61, %62, %63, %64, %65, %66, %67, "
      "%68, %69, %70, %71, %72, %73, %74, %75, %76, %77, %78, %79"
      "}, da, db, p, 1, 1, %85, %86;\n}\n"
      : "+f"(d[0]), "+f"(d[1]), "+f"(d[2]), "+f"(d[3]), "+f"(d[4]), "+f"(d[5]), "+f"(d[6]), "+f"(d[7]), "+f"(d[8]),
        "+f"(d[9]), "+f"(d[10]), "+f"(d[11]), "+f"(d[12]), "+f"(d[13]), "+f"(d[14]), "+f"(d[15]), "+f"(d[16]),
        "+f"(d[17]), "+f"(d[18]), "+f"(d[19]), "+f"(d[20]), "+f"(d[21]), "+f"(d[22]), "+f"(d[23]), "+f"(d[24]),
        "+f"(d[25]), "+f"(d[26]), "+f"(d[27]), "+f"(d[28]), "+f"(d[29]), "+f"(d[30]), "+f"(d[31]), "+f"(d[32]),
        "+f"(d[33]), "+f"(d[34]), "+f"(d[35]), "+f"(d[36]), "+f"(d[37]), "+f"(d[38]), "+f"(d[39]), "+f"(d[40]),
        "+f"(d[41]), "+f"(d[42]), "+f"(d[43]), "+f"(d[44]), "+f"(d[45]), "+f"(d[46]), "+f"(d[47]), "+f"(d[48]),
        "+f"(d[49]), "+f"(d[50]), "+f"(d[51]), "+f"(d[52]), "+f"(d[53]), "+f"(d[54]), "+f"(d[55]), "+f"(d[56]),
        "+f"(d[57]), "+f"(d[58]), "+f"(d[59]), "+f"(d[60]), "+f"(d[61]), "+f"(d[62]), "+f"(d[63]), "+f"(d[64]),
        "+f"(d[65]), "+f"(d[66]), "+f"(d[67]), "+f"(d[68]), "+f"(d[69]), "+f"(d[70]), "+f"(d[71]), "+f"(d[72]),
        "+f"(d[73]), "+f"(d[74]), "+f"(d[75]), "+f"(d[76]), "+f"(d[77]), "+f"(d[78]), "+f"(d[79])
      : "r"(a_lo), "r"(a_hi), "r"(b_lo), "r"(b_hi), "r"(acc), "n"(TA), "n"(TB));
}
__device__ __forceinline__ void mbar_init(uint32_t bar, int cnt) { asm volatile("mbarrier.init.shared::cta.b64 [%0], %1;" ::"r"(bar), "r"(cnt)); }
__device__ __forceinline__ void mbar_expect(uint32_t bar, uint32_t bytes) {
  asm volatile("mbarrier.arrive.expect_tx.shared::cta.b64 _, [%0], %1;" ::"r"(bar), "r"(bytes) : "memory");
}
__device__ __forceinline__ uint32_t mapa(uint32_t addr, uint32_t cta) {
  uint32_t r; asm("mapa.shared::cluster.u32 %0, %1, %2;" : "=r"(r) : "r"(addr), "r"(cta)); return r;
}
__device__ __forceinline__ void mbar_expect_cl(uint32_t cbar, uint32_t bytes) {
  asm volatile("mbarrier.arrive.expect_tx.shared::cluster.b64 _, [%0], %1;" ::"r"(cbar), "r"(bytes) : "memory");
}
__device__ __forceinline__ void mbar_arrive(uint32_t bar) { asm volatile("mbarrier.arrive.shared::cta.b64 _, [%0];" ::"r"(bar) : "memory"); }
__device__ __forceinline__ void mbar_arrive_cl(uint32_t cbar) { asm volatile("mbarrier.arrive.shared::cluster.b64 _, [%0];" ::"r"(cbar) : "memory"); }
__device__ __forceinline__ void mbar_wait(uint32_t bar, uint32_t parity) {
  asm volatile(
      "{\n.reg .pred p;\n.reg .u32 n;\n"
      "mbarrier.try_wait.parity.shared::cta.b64 p, [%0], %1;\n@p bra WAIT_DONE;\n"
      "mov.u32 n, 0;\n"
      "WAIT_LOOP:\n"
      "mbarrier.try_wait.parity.shared::cta.b64 p, [%0], %1;\n@p bra WAIT_DONE;\n"
      "add.u32 n, n, 1;\nsetp.lt.u32 p, n, 0x4000000;\n@p bra WAIT_LOOP;\ntrap;\n"
      "WAIT_DONE:\n}\n" ::"r"(bar), "r"(parity) : "memory");
}
__device__ __forceinline__ void tma3d(uint32_t dst, const CUtensorMap* m, int c0, int c1, int c2, uint32_t bar) {
  asm volatile("cp.async.bulk.tensor.3d.shared::cluster.global.mbarrier::complete_tx::bytes [%0], [%1, {%3, %4, %5}], [%2];"
               ::"r"(dst), "l"(m), "r"(bar), "r"(c0), "r"(c1), "r"(c2) : "memory");
}
__device__ __forceinline__ void tma3d_hint(uint32_t dst, const CUtensorMap* m, int c0, int c1, int c2, uint32_t bar, uint64_t pol) {
  asm volatile("cp.async.bulk.tensor.3d.shared::cluster.global.mbarrier::complete_tx::bytes.L2::cache_hint [%0], [%1, {%3, %4, %5}], [%2], %6;"
               ::"r"(dst), "l"(m), "r"(bar), "r"(c0), "r"(c1), "r"(c2), "l"(pol) : "memory");
}
__device__ __forceinline__ void tma2d_mc(uint32_t dst, const CUtensorMap* m, int c0, int c1, uint32_t bar) {
  asm volatile("cp.async.bulk.tensor.2d.shared::cluster.global.mbarrier::complete_tx::bytes.multicast::cluster [%0], [%1, {%3, %4}], [%2], %5;"
               ::"r"(dst), "l"(m), "r"(bar), "r"(c0), "r"(c1), "h"((uint16_t)3) : "memory");
}
__device__ __forceinline__ void tma3d_mc(uint32_t dst, const CUtensorMap* m, int c0, int c1, int c2, uint32_t bar) {
  asm volatile("cp.async.bulk.tensor.3d.shared::cluster.global.mbarrier::complete_tx::bytes.multicast::cluster [%0], [%1, {%3, %4, %5}], [%2], %6;"
               ::"r"(dst), "l"(m), "r"(bar), "r"(c0), "r"(c1), "r"(c2), "h"((uint16_t)3) : "memory");
}
__device__ __forceinline__ void l2_prefetch(const void* p, uint32_t bytes, uint64_t pol) {
  if (PF_POL) asm volatile("cp.async.bulk.prefetch.L2.global.L2::cache_hint [%0], %1, %2;" ::"l"(p), "r"(bytes), "l"(pol) : "memory");
  else asm volatile("cp.async.bulk.prefetch.L2.global [%0], %1;" ::"l"(p), "r"(bytes) : "memory");
}
__device__ __forceinline__ void fence_async_smem() { asm volatile("fence.proxy.async.shared::cta;" ::: "memory"); }
__device__ __forceinline__ void bar_sync(int id) { asm volatile("bar.sync %0, 128;" ::"r"(id) : "memory"); }
__device__ __forceinline__ bool bar_red_or(int id, bool v) {
  uint32_t r;
  asm volatile("{\n.reg .pred p, q;\nsetp.ne.u32 p, %2, 0;\nbar.red.or.pred q, %1, 128, p;\nselp.u32 %0, 1, 0, q;\n}\n"
               : "=r"(r) : "r"(id), "r"((uint32_t)v) : "memory");
  return r != 0;
}
__device__ __forceinline__ void cluster_sync() { asm volatile("barrier.cluster.arrive.aligned;\nbarrier.cluster.wait.aligned;" ::: "memory"); }
__device__ __forceinline__ float ex2(float x) { float y; asm("ex2.approx.ftz.f32 %0, %1;" : "=f"(y) : "f"(x)); return y; }
__device__ __forceinline__ uint32_t pack(float lo, float hi) { uint32_t r; asm("cvt.rn.bf16x2.f32 %0, %1, %2;" : "=r"(r) : "f"(hi), "f"(lo)); return r; }
__device__ __forceinline__ void stsm4t(uint32_t a, uint32_t r0, uint32_t r1, uint32_t r2, uint32_t r3) {
  asm volatile("stmatrix.sync.aligned.m8n8.x4.trans.shared.b16 [%0], {%1,%2,%3,%4};" ::"r"(a), "r"(r0), "r"(r1), "r"(r2), "r"(r3) : "memory");
}
__device__ __forceinline__ void stsm2t(uint32_t a, uint32_t r0, uint32_t r1) {
  asm volatile("stmatrix.sync.aligned.m8n8.x2.trans.shared.b16 [%0], {%1,%2};" ::"r"(a), "r"(r0), "r"(r1) : "memory");
}
__device__ __forceinline__ void mma16816(float (&d)[4], const uint32_t (&a)[4], uint32_t b0, uint32_t b1) {
  asm volatile("mma.sync.aligned.m16n8k16.row.col.f32.bf16.bf16.f32 {%0,%1,%2,%3}, {%4,%5,%6,%7}, {%8,%9}, {%0,%1,%2,%3};"
               : "+f"(d[0]), "+f"(d[1]), "+f"(d[2]), "+f"(d[3]) : "r"(a[0]), "r"(a[1]), "r"(a[2]), "r"(a[3]), "r"(b0), "r"(b1));
}

template <int V> struct IC { static constexpr int value = V; };

struct Ring {
  uint32_t slot = 0, phase = 0;
  __device__ __forceinline__ void next() { if (++slot == RING_SLOTS) { slot = 0; phase ^= 1; } }
};

__device__ __forceinline__ void mma_tn(float (&o0)[60], float (&o1)[60], uint32_t a, uint32_t b, int acc) {
#pragma unroll
  for (int k = 0; k < 4; k++) {
    wgmma_n120<1, 0>(o0, a + k * 128, HI128, b + k * 2, HI128, k == 0 ? acc : 1);
    wgmma_n120<1, 0>(o1, a + 512 + k * 128, HI128, b + k * 2, HI128, k == 0 ? acc : 1);
  }
}
__device__ __forceinline__ void mma_qk(float (&s)[60], uint32_t a, uint32_t q) {
#pragma unroll
  for (int k = 0; k < 8; k++)
    wgmma_n120<0, 0>(s, a + (k >> 2) * 512 + (k & 3) * 2, HI128, q + (k >> 2) * (XB >> 4) + (k & 3) * 2, HI128, k != 0);
}
template <int J0, int J1, bool FIRST = false>
__device__ __forceinline__ void exp_store(const float (&s)[60], float (&l)[30], uint32_t dst) {
#pragma unroll
  for (int j = J0; j < J1; j += 2) {
    uint32_t p[4];
#pragma unroll
    for (int jj = 0; jj < 2; jj++) {
      if (j + jj < 15) {
        const int c = j + jj;
        float e0 = ex2(s[4 * c]), e1 = ex2(s[4 * c + 1]), e2 = ex2(s[4 * c + 2]), e3 = ex2(s[4 * c + 3]);
        if (FIRST) { l[2 * c] = e0 + e2; l[2 * c + 1] = e1 + e3; }
        else { l[2 * c] += e0; l[2 * c + 1] += e1; l[2 * c] += e2; l[2 * c + 1] += e3; }
        p[2 * jj] = pack(e0, e1); p[2 * jj + 1] = pack(e2, e3);
      }
    }
    if (j + 1 < 15) stsm4t(dst + j * 1024, p[0], p[1], p[2], p[3]);
    else stsm2t(dst + j * 1024, p[0], p[1]);
  }
}

__device__ __forceinline__ int o_pos(int wg, int r) {
  const int j = r >> 3, q = (r >> 1) & 3, c = r & 1;
  if (j < 12) return (wg ? 144 : 0) + (j >> 2) * 32 + q * 8 + (j & 3) * 2 + c;
  if (j < 14) return (wg ? 128 : 96) + q * 4 + (j - 12) * 2 + c;
  return (wg ? 120 : 112) + q * 2 + c;
}
__device__ __forceinline__ int o_row(int p) {
  const int b = p / SQ, r = p - b * SQ, wg = r >= 120, c = r & 1;
  const int a = r - (wg ? 144 : 0), m = r - (wg ? 128 : 96), e = r - (wg ? 120 : 112);
  int row;
  if (a >= 0 && a < 96) row = ((a >> 5) * 4 + ((a >> 1) & 3)) * 8 + ((a >> 3) & 3) * 2 + c;
  else if (m >= 0 && m < 16) row = (12 + ((m >> 1) & 1)) * 8 + (m >> 2) * 2 + c;
  else row = 112 + e;
  return b * SQ + wg * 120 + row;
}

__device__ __forceinline__ void slow_path(const Params& P, int b, int h, int wg, int w, int lane) {
  const int g = lane >> 2, q = lane & 3, row0 = wg * 120;
  const uint16_t* wq = reinterpret_cast<const uint16_t*>(P.wq) + h * DH + g;
  const __nv_bfloat16* kp = P.k + (size_t)(b * NH + h) * SK * DH;
  const uint16_t* vp = reinterpret_cast<const uint16_t*>(P.v) + (size_t)(b * NH + h) * SK * DH + g;
#pragma unroll 1
  for (int t = w; t < 8; t += 4) {
    const int r0 = 16 * t + g, r1 = r0 + 8;
    const __nv_bfloat16* x0 = P.x + (size_t)(b * SQ + row0 + r0) * DM + 2 * q;
    const __nv_bfloat16* x1 = P.x + (size_t)(b * SQ + row0 + min(r1, 119)) * DM + 2 * q;
    float o[16][4];
#pragma unroll
    for (int n = 0; n < 16; n++) o[n][0] = o[n][1] = o[n][2] = o[n][3] = 0.f;
#pragma unroll 1
    for (int k0 = 0; k0 < DM; k0 += 16) {
      uint32_t a[4] = {*(const uint32_t*)(x0 + k0), *(const uint32_t*)(x1 + k0), *(const uint32_t*)(x0 + k0 + 8), *(const uint32_t*)(x1 + k0 + 8)};
      const uint16_t* wr = wq + (size_t)(k0 + 2 * q) * HD;
#pragma unroll
      for (int n = 0; n < 16; n++)
        mma16816(o[n], a, wr[8 * n] | ((uint32_t)wr[8 * n + HD] << 16), wr[8 * n + 8 * HD] | ((uint32_t)wr[8 * n + 9 * HD] << 16));
    }
    uint32_t qa[8][4];
#pragma unroll
    for (int k = 0; k < 8; k++) {
      qa[k][0] = pack(o[2 * k][0] * QSCALE, o[2 * k][1] * QSCALE);
      qa[k][1] = pack(o[2 * k][2] * QSCALE, o[2 * k][3] * QSCALE);
      qa[k][2] = pack(o[2 * k + 1][0] * QSCALE, o[2 * k + 1][1] * QSCALE);
      qa[k][3] = pack(o[2 * k + 1][2] * QSCALE, o[2 * k + 1][3] * QSCALE);
    }
#pragma unroll
    for (int n = 0; n < 16; n++) o[n][0] = o[n][1] = o[n][2] = o[n][3] = 0.f;
    float m0 = -INFINITY, m1 = -INFINITY, l0 = 0.f, l1 = 0.f;
#pragma unroll 1
    for (int key0 = 0; key0 < SK; key0 += 16) {
      float s[2][4];
#pragma unroll
      for (int nt = 0; nt < 2; nt++) {
        s[nt][0] = s[nt][1] = s[nt][2] = s[nt][3] = 0.f;
        const __nv_bfloat16* kr = kp + (size_t)(key0 + 8 * nt + g) * DH + 2 * q;
#pragma unroll
        for (int k = 0; k < 8; k++) mma16816(s[nt], qa[k], *(const uint32_t*)(kr + 16 * k), *(const uint32_t*)(kr + 16 * k + 8));
      }
      float n0 = fmaxf(fmaxf(s[0][0], s[0][1]), fmaxf(s[1][0], s[1][1])), n1 = fmaxf(fmaxf(s[0][2], s[0][3]), fmaxf(s[1][2], s[1][3]));
      n0 = fmaxf(n0, __shfl_xor_sync(~0u, n0, 1)); n1 = fmaxf(n1, __shfl_xor_sync(~0u, n1, 1));
      n0 = fmaxf(n0, __shfl_xor_sync(~0u, n0, 2)); n1 = fmaxf(n1, __shfl_xor_sync(~0u, n1, 2));
      n0 = fmaxf(n0, m0); n1 = fmaxf(n1, m1);
      const float z0 = n0 == -INFINITY ? 0.f : n0, z1 = n1 == -INFINITY ? 0.f : n1;
      const float c0 = ex2(m0 - z0), c1 = ex2(m1 - z1);
      m0 = n0; m1 = n1;
#pragma unroll
      for (int nt = 0; nt < 2; nt++) {
        s[nt][0] = ex2(s[nt][0] - z0); s[nt][1] = ex2(s[nt][1] - z0);
        s[nt][2] = ex2(s[nt][2] - z1); s[nt][3] = ex2(s[nt][3] - z1);
      }
      l0 = l0 * c0 + s[0][0] + s[0][1] + s[1][0] + s[1][1];
      l1 = l1 * c1 + s[0][2] + s[0][3] + s[1][2] + s[1][3];
      uint32_t pa[4] = {pack(s[0][0], s[0][1]), pack(s[0][2], s[0][3]), pack(s[1][0], s[1][1]), pack(s[1][2], s[1][3])};
      const uint16_t* vr = vp + (size_t)(key0 + 2 * q) * DH;
#pragma unroll
      for (int n = 0; n < 16; n++) {
        o[n][0] *= c0; o[n][1] *= c0; o[n][2] *= c1; o[n][3] *= c1;
        mma16816(o[n], pa, vr[8 * n] | ((uint32_t)vr[8 * n + DH] << 16), vr[8 * n + 8 * DH] | ((uint32_t)vr[8 * n + 9 * DH] << 16));
      }
    }
    l0 += __shfl_xor_sync(~0u, l0, 1); l1 += __shfl_xor_sync(~0u, l1, 1);
    l0 += __shfl_xor_sync(~0u, l0, 2); l1 += __shfl_xor_sync(~0u, l1, 2);
    const float i0 = 1.f / l0, i1 = 1.f / l1;
    __nv_bfloat16* oc = g_o + (size_t)(h * DH + 2 * q) * NROWS + b * SQ;
    const int p0 = o_pos(wg, r0), p1 = o_pos(wg, min(r1, 119));
#pragma unroll
    for (int n = 0; n < 16; n++) {
      oc[(size_t)(8 * n) * NROWS + p0] = __float2bfloat16(o[n][0] * i0);
      oc[(size_t)(8 * n + 1) * NROWS + p0] = __float2bfloat16(o[n][1] * i0);
      if (r1 < 120) {
        oc[(size_t)(8 * n) * NROWS + p1] = __float2bfloat16(o[n][2] * i1);
        oc[(size_t)(8 * n + 1) * NROWS + p1] = __float2bfloat16(o[n][3] * i1);
      }
    }
  }
}

__device__ __forceinline__ int unit_batch(int u) { return (u & 63) >> 2; }
__device__ __forceinline__ int unit_head(int u, int rank) { return (u >> 6) * 8 + (u & 3) * 2 + rank; }

__global__ void __cluster_dims__(2, 1, 1) __launch_bounds__(384, 1)
fused_attn_kernel(const __grid_constant__ CUtensorMap tm_x, const __grid_constant__ CUtensorMap tm_wq,
                  const __grid_constant__ CUtensorMap tm_k, const __grid_constant__ CUtensorMap tm_v,
                  const __grid_constant__ CUtensorMap tm_o, const __grid_constant__ CUtensorMap tm_wo,
                  const __grid_constant__ Params P) {
  extern __shared__ uint8_t smem_raw[];
  const uint32_t sb = ((uint32_t)__cvta_generic_to_shared(smem_raw) + 1023) & ~1023u;
  const int warp = __shfl_sync(~0u, threadIdx.x >> 5, 0);
  const int lane = threadIdx.x & 31;
  const int rank = blockIdx.x & 1, cl = blockIdx.x >> 1, ncl = gridDim.x >> 1;

  if (threadIdx.x == 0) {
    for (int i = 0; i < 6; i++) {
      mbar_init(sb + BAR_RFULL + 8 * i, 1); mbar_init(sb + BAR_REMPTY + 8 * i, 8);
      mbar_init(sb + BAR_BFULL + 8 * i, 1); mbar_init(sb + BAR_BEMPTY + 8 * i, 16);
    }
    for (int i = 0; i < 8; i++) mbar_init(sb + BAR_XFULL + 8 * i, 1);
    for (int i = 0; i < 4; i++) mbar_init(sb + BAR_XEMPTY + 8 * i, 8);
    for (int i = 0; i < 2; i++) mbar_init(sb + BAR_STAGE + 8 * i, 4);
    asm volatile("fence.mbarrier_init.release.cluster;" ::: "memory");
  }
  __syncthreads();
  cluster_sync();

  if (warp >= 8) {
    asm volatile("setmaxnreg.dec.sync.aligned.u32 24;");
    if (warp == 8) {
      uint64_t pol;
      asm volatile("createpolicy.fractional.L2::evict_first.b64 %0, 1.0;" : "=l"(pol));
      Ring r;
      auto load = [&](const CUtensorMap* m, int c1, int c2, bool ef) {
        mbar_wait(sb + BAR_REMPTY + 8 * r.slot, r.phase ^ 1);
        if (lane == 0) {
          mbar_expect(sb + BAR_RFULL + 8 * r.slot, RING_BYTES);
          if (ef) tma3d_hint(sb + r.slot * RING_BYTES, m, 0, c1, c2, sb + BAR_RFULL + 8 * r.slot, pol);
          else tma3d(sb + r.slot * RING_BYTES, m, 0, c1, c2, sb + BAR_RFULL + 8 * r.slot);
        }
        r.next();
      };
      const int rot = ROT * (blockIdx.x * 5 + (blockIdx.x >> 4));
      for (int u = cl; u < NUNITS; u += ncl) {
        const int h = unit_head(u, rank);
        const int krow = (unit_batch(u) * NH + h) * SK;
#pragma unroll 1
        for (int s = 0; s < 10; s++) {
          load(&tm_wq, s * 64, 2 * h, false);
          const int sp = u == cl ? s - PF_HOLD : s;
          if (sp >= 0 && sp < PF_N && lane == 0) {
            const size_t off = (size_t)(krow + ((PF_J0 + sp * PF_STEP + rot) & 15) * 64) * DH;
            if (PF_WHAT & 1) l2_prefetch(P.k + off, 16384, pol);
            if (PF_WHAT & 2) l2_prefetch(P.v + off, 16384, pol);
          }
        }
#pragma unroll 1
        for (int j = 0; j <= 16; j++) {
          if (j < 16) load(&tm_k, krow + ((j + rot) & 15) * 64, 0, true);
          if (j > 0) load(&tm_v, krow + ((j - 1 + rot) & 15) * 64, 0, true);
        }
      }
      for (int t = cl; t < NOTILES; t += ncl) {
        const int row0 = (t >> 2) * 256 + rank * 128;
        const int b0 = row0 / SQ, b1 = (row0 + 127) / SQ;
#pragma unroll 1
        for (int ks = 0; ks < 64; ks++) {
          if ((ks & 15) == 0) {
            const unsigned* c = &g_cnt[((lane & 1 ? b1 : b0) * 4 + (ks >> 4)) * 8];
            unsigned v, n = 0;
            do {
              asm volatile("ld.acquire.gpu.global.u32 %0, [%1];" : "=r"(v) : "l"(c) : "memory");
              if (++n > (1u << 26)) __trap();
            } while (v < 16);
            __syncwarp();
            asm volatile("fence.proxy.async.global;" ::: "memory");
          }
          load(&tm_o, ks * 64, row0 >> 6, O_EF);
        }
      }
    } else if (warp == 9) {
      if (lane == 0) {
        uint32_t it = 0;
        for (int u = cl; u < NUNITS; u += ncl, it++) {
          const int row = unit_batch(u) * SQ + rank * 120;
#pragma unroll 1
          for (int s = 0; s < 10; s++) {
            const uint32_t j = s & 3, par = ((s >> 2) + (j < 2 ? it : 0)) & 1;
            mbar_wait(sb + BAR_XEMPTY + 8 * j, par ^ 1);
            const uint32_t fb = sb + BAR_XFULL + 32 * rank + 8 * j;
            mbar_expect(fb, XB);
            mbar_expect_cl(mapa(fb, rank ^ 1), XB);
            tma2d_mc(sb + OFF_Q + rank * 2 * XB + (j & 1) * XB + (j >> 1) * 4 * XB, &tm_x, s * 64, row, fb);
          }
        }
        uint32_t slot = rank, phase = 0;
        for (int t = cl; t < NOTILES; t += ncl) {
#pragma unroll 1
          for (int ks = rank; ks < 64; ks += 2) {
            mbar_wait(sb + BAR_BEMPTY + 8 * slot, phase);
            const uint32_t fb = sb + BAR_BFULL + 8 * slot;
            mbar_expect(fb, BB);
            mbar_expect_cl(mapa(fb, rank ^ 1), BB);
            tma3d_mc(sb + OFF_Q + slot * BB, &tm_wo, 0, ks * 64, (t & 3) * 5, fb);
            slot += 2;
            if (slot >= 6) { slot -= 6; phase ^= 1; }
          }
        }
      }
    } else {
      const int wg = warp - 10;
      if (lane == 0) {
        uint32_t it = 0;
        for (int u = cl; u < NUNITS; u += ncl, it++) {
          mbar_wait(sb + BAR_STAGE + 8 * wg, it & 1);
          __threadfence();
          asm volatile("red.relaxed.gpu.global.add.u32 [%0], 1;" ::"l"(&g_cnt[(unit_batch(u) * 4 + (u >> 6)) * 8]) : "memory");
        }
      }
    }
  } else {
    asm volatile("setmaxnreg.inc.sync.aligned.u32 240;");
    const int wg = warp >> 2, w = warp & 3;
    const uint32_t qreg = sb + OFF_Q + wg * 2 * XB, preg = qreg + 4 * XB;
    const uint32_t st_off = ((lane >> 4) * 8 + (lane & 7)) * 128 + (((2 * w + ((lane >> 3) & 1)) ^ (lane & 7)) << 4);
    const uint32_t xempty = mapa(sb + BAR_XEMPTY, wg);
    const int bar_id = 1 + wg;
    Ring r;
    uint32_t it = 0;
    const uint32_t qd = (qreg & 0x3FFFF) >> 4, pd = qd + (4 * XB >> 4);
    auto ring_addr = [&]() { return ((sb & 0x3FFFF) + r.slot * RING_BYTES) >> 4; };
    auto ring_wait = [&]() { mbar_wait(sb + BAR_RFULL + 8 * r.slot, r.phase); };
    auto release = [&](uint32_t slot) { if (lane == 0) mbar_arrive(sb + BAR_REMPTY + 8 * slot); };
    auto turn_wait = [&]() { if (PP_MODE) asm volatile("bar.sync %0, 256;" ::"r"(3 + wg) : "memory"); };
    auto turn_pass = [&]() { if (PP_MODE) asm volatile("bar.arrive %0, 256;" ::"r"(4 - wg) : "memory"); };
    if (wg == 1) turn_pass();

    uint32_t po[60];
#pragma unroll
    for (int i = 0; i < 60; i++) po[i] = 0;
    char* optr = nullptr;
    auto put = [&](const uint32_t (&po)[60], auto part) {
      constexpr int k = decltype(part)::value >> 1;
      const char* o = optr + (size_t)(8 * (k & 1) + 64 * (k >> 1)) * NROWS * 2;
      if ((decltype(part)::value & 1) == 0)
        asm volatile(
            "{\n.reg .pred p;\nsetp.ne.u64 p, %9, 0;\n"
            "@p st.global.v4.u32 [%8], {%0, %1, %2, %3};\n@p st.global.v4.u32 [%8 + 64], {%4, %5, %6, %7};\n}\n"
            ::"r"(po[15 * k]), "r"(po[15 * k + 1]), "r"(po[15 * k + 2]), "r"(po[15 * k + 3]), "r"(po[15 * k + 4]), "r"(po[15 * k + 5]),
            "r"(po[15 * k + 6]), "r"(po[15 * k + 7]), "l"(o + (wg ? 288 : 0) + (lane & 3) * 16), "l"(optr) : "memory");
      else
        asm volatile(
            "{\n.reg .pred p;\nsetp.ne.u64 p, %10, 0;\n"
            "@p st.global.v4.u32 [%7 + 128], {%0, %1, %2, %3};\n@p st.global.v2.u32 [%8], {%4, %5};\n@p st.global.u32 [%9], %6;\n}\n"
            ::"r"(po[15 * k + 8]), "r"(po[15 * k + 9]), "r"(po[15 * k + 10]), "r"(po[15 * k + 11]), "r"(po[15 * k + 12]),
            "r"(po[15 * k + 13]), "r"(po[15 * k + 14]), "l"(o + (wg ? 288 : 0) + (lane & 3) * 16),
            "l"(o + (wg ? 256 : 192) + (lane & 3) * 8), "l"(o + (wg ? 240 : 224) + (lane & 3) * 4), "l"(optr) : "memory");
    };
    auto publish = [&]() { __syncwarp(); if (lane == 0) mbar_arrive(sb + BAR_STAGE + 8 * wg); };
    if (PP_MODE == 2 && wg == 1) mbar_wait(sb + BAR_RFULL + 8 * 3, 0);
    for (int u = cl; u < NUNITS; u += ncl, it++) {
      float o0[60], o1[60];
      uint32_t prev = 0;
      auto qstep = [&](int s, int acc) {
        const uint32_t j = s & 3, par = ((s >> 2) + (j < 2 ? it : 0)) & 1;
        TR(it * 160 + 3 * s);
        ring_wait();
        TR(it * 160 + 3 * s + 1);
        mbar_wait(sb + BAR_XFULL + 32 * wg + 8 * j, par);
        TR(it * 160 + 3 * s + 2);
        wg_fence();
        mma_tn(o0, o1, ring_addr(), qd + (j & 1) * (XB >> 4) + (j >> 1) * (4 * XB >> 4), acc);
        wg_commit();
        if (s > 0) {
          wg_wait<1>();
          release(prev);
          if (s <= 6 && lane == 0) mbar_arrive_cl(xempty + 8 * ((s - 1) & 3));
        }
        prev = r.slot;
        r.next();
      };
      qstep(0, 0);
      qstep(1, 1); put(po, IC<0>());
      qstep(2, 1); put(po, IC<1>());
      qstep(3, 1); put(po, IC<2>());
      qstep(4, 1); put(po, IC<3>());
      qstep(5, 1); put(po, IC<4>());
      qstep(6, 1); put(po, IC<5>());
      qstep(7, 1); put(po, IC<6>());
      qstep(8, 1); put(po, IC<7>());
      if (it > 0) publish();
      qstep(9, 1);
      wg_wait<0>();
      reg_fence(o0); reg_fence(o1);
      release(prev);
      TR(it * 160 + 30);
      bar_sync(bar_id);
#pragma unroll
      for (int j = 0; j < 15; j += 2) {
        if (j + 1 < 15) {
          stsm4t(qreg + st_off + j * 1024, pack(o0[4 * j] * QSCALE, o0[4 * j + 1] * QSCALE), pack(o0[4 * j + 2] * QSCALE, o0[4 * j + 3] * QSCALE),
                 pack(o0[4 * j + 4] * QSCALE, o0[4 * j + 5] * QSCALE), pack(o0[4 * j + 6] * QSCALE, o0[4 * j + 7] * QSCALE));
          stsm4t(qreg + XB + st_off + j * 1024, pack(o1[4 * j] * QSCALE, o1[4 * j + 1] * QSCALE), pack(o1[4 * j + 2] * QSCALE, o1[4 * j + 3] * QSCALE),
                 pack(o1[4 * j + 4] * QSCALE, o1[4 * j + 5] * QSCALE), pack(o1[4 * j + 6] * QSCALE, o1[4 * j + 7] * QSCALE));
        } else {
          stsm2t(qreg + st_off + j * 1024, pack(o0[4 * j] * QSCALE, o0[4 * j + 1] * QSCALE), pack(o0[4 * j + 2] * QSCALE, o0[4 * j + 3] * QSCALE));
          stsm2t(qreg + XB + st_off + j * 1024, pack(o1[4 * j] * QSCALE, o1[4 * j + 1] * QSCALE), pack(o1[4 * j + 2] * QSCALE, o1[4 * j + 3] * QSCALE));
        }
      }
      fence_async_smem();
      bar_sync(bar_id);
      TR(it * 160 + 32);

      float sc[60], l[30];
      ring_wait();
      TR(it * 160 + 33);
      if (PP_MODE == 2 && wg == 1) turn_wait();
      wg_fence();
      mma_qk(sc, ring_addr(), qd);
      wg_commit();
      if (PP_MODE == 2 && wg == 1) turn_pass();
      wg_wait<0>();
      reg_fence(sc);
      TR(it * 160 + 35);
      release(r.slot);
      r.next();
      exp_store<0, 15, true>(sc, l, preg + st_off);
      fence_async_smem();
      bar_sync(bar_id);
      const bool more = u + ncl < NUNITS;
#pragma unroll 1
      for (int s = 1; s < 16; s++) {
        const uint32_t kslot = r.slot;
        TR(it * 160 + 32 + 6 * s);
        ring_wait();
        TR(it * 160 + 33 + 6 * s);
        turn_wait();
        wg_fence();
        mma_qk(sc, ring_addr(), qd);
        wg_commit();
        r.next();
        TR(it * 160 + 36 + 6 * s);
        ring_wait();
        TR(it * 160 + 34 + 6 * s);
        wg_fence();
        mma_tn(o0, o1, ring_addr(), pd + ((s - 1) & 1) * (XB >> 4), s != 1);
        wg_commit();
        turn_pass();
        wg_wait<1>();
        reg_fence(sc);
        TR(it * 160 + 35 + 6 * s);
        release(kslot);
        if (s == 15) {
          if (more) { if (lane < 2) mbar_arrive_cl(xempty + 8 * lane); }
          else if (lane < 3) mbar_arrive_cl(mapa(sb + BAR_BEMPTY + 8 * lane, lane & 1));
        }
        exp_store<0, VREL>(sc, l, preg + (s & 1) * XB + st_off);
        wg_wait<0>();
        reg_fence(o0); reg_fence(o1);
        release(r.slot);
        r.next();
        exp_store<VREL, 15>(sc, l, preg + (s & 1) * XB + st_off);
        fence_async_smem();
        bar_sync(bar_id);
      }
      TR(it * 160 + 128);
      {
        const uint32_t a = preg + (8 * w + (lane >> 2)) * 480 + (lane & 3) * 8;
#pragma unroll
        for (int j = 0; j < 15; j++) asm volatile("st.shared.v2.f32 [%0], {%1, %2};" ::"r"(a + j * 32), "f"(l[2 * j]), "f"(l[2 * j + 1]) : "memory");
      }
      ring_wait();
      TR(it * 160 + 129);
      if (PP_MODE == 2 && wg == 0) turn_wait();
      wg_fence();
      mma_tn(o0, o1, ring_addr(), pd + (XB >> 4), 1);
      wg_commit();
      if (PP_MODE == 2 && wg == 0) turn_pass();
      bar_sync(bar_id);
      bool bad;
      {
        const int t = min(32 * w + lane, 119);
        float a0 = 0.f, a1 = 0.f, a2 = 0.f, a3 = 0.f;
#pragma unroll
        for (int g = 0; g < 32; g += 4) {
          float v0, v1, v2, v3;
          asm volatile("ld.shared.f32 %0, [%1];" : "=f"(v0) : "r"(preg + g * 480 + t * 4) : "memory");
          asm volatile("ld.shared.f32 %0, [%1];" : "=f"(v1) : "r"(preg + (g + 1) * 480 + t * 4) : "memory");
          asm volatile("ld.shared.f32 %0, [%1];" : "=f"(v2) : "r"(preg + (g + 2) * 480 + t * 4) : "memory");
          asm volatile("ld.shared.f32 %0, [%1];" : "=f"(v3) : "r"(preg + (g + 3) * 480 + t * 4) : "memory");
          a0 += v0; a1 += v1; a2 += v2; a3 += v3;
        }
        const float lsum = (a0 + a1) + (a2 + a3);
        bad = !(lsum >= L_MIN && lsum <= L_MAX);
        asm volatile("st.shared.f32 [%0], %1;" ::"r"(sb + OFF_INV + wg * 512 + (32 * w + lane) * 4), "f"(__frcp_rn(lsum)) : "memory");
      }
      fence_async_smem();
      bar_sync(bar_id);
      if (more && lane == 0) mbar_arrive_cl(xempty + 16);
#pragma unroll
      for (int j = 0; j < 15; j++)
        asm volatile("ld.shared.v2.f32 {%0, %1}, [%2];" : "=f"(l[2 * j]), "=f"(l[2 * j + 1]) : "r"(sb + OFF_INV + wg * 512 + j * 32 + (lane & 3) * 8) : "memory");
      wg_wait<0>();
      reg_fence(o0); reg_fence(o1);
      release(r.slot);
      r.next();
      if (more) { if (lane == 0) mbar_arrive_cl(xempty + 24); }
      else if (lane < 3) mbar_arrive_cl(mapa(sb + BAR_BEMPTY + 24 + 8 * lane, (lane + 1) & 1));
      TR(it * 160 + 130);
#pragma unroll
      for (int j = 0; j < 15; j++) {
        po[j] = pack(o0[4 * j] * l[2 * j], o0[4 * j + 1] * l[2 * j + 1]);
        po[15 + j] = pack(o0[4 * j + 2] * l[2 * j], o0[4 * j + 3] * l[2 * j + 1]);
        po[30 + j] = pack(o1[4 * j] * l[2 * j], o1[4 * j + 1] * l[2 * j + 1]);
        po[45 + j] = pack(o1[4 * j + 2] * l[2 * j], o1[4 * j + 3] * l[2 * j + 1]);
      }
      {
        uint32_t mx_s = 0, mx_u = 0;
#pragma unroll
        for (int j = 0; j < 60; j += 2) { mx_s = __vimax3_s16x2(mx_s, po[j], po[j + 1]); mx_u = __vimax3_u16x2(mx_u, po[j], po[j + 1]); }
        bad = bad || (mx_s & 0xFFFF) >= 0x7F80 || (mx_s >> 16) >= 0x7F80 || (mx_u & 0xFFFF) >= 0xFF80 || (mx_u >> 16) >= 0xFF80;
      }
      optr = reinterpret_cast<char*>(g_o + (size_t)(unit_head(u, rank) * DH + 16 * w + (lane >> 2)) * NROWS + unit_batch(u) * SQ);
      if (__any_sync(~0u, bar_red_or(bar_id, bad))) {
        slow_path(P, unit_batch(u), unit_head(u, rank), wg, w, lane);
        optr = nullptr;
#pragma unroll
        for (int i = 0; i < 60; i++) po[i] = 0;
      }
      TR(it * 160 + 131);
    }
    if (cl >= NOTILES) {
      put(po, IC<0>()); put(po, IC<1>()); put(po, IC<2>()); put(po, IC<3>());
      put(po, IC<4>()); put(po, IC<5>()); put(po, IC<6>()); put(po, IC<7>());
      publish();
    }
    uint32_t pb[60];
#pragma unroll
    for (int i = 0; i < 60; i++) pb[i] = po[i] ^ (gridDim.y - 1);

    uint32_t bslot = 0, bphase = 0;
    for (int t = cl; t < NOTILES; t += ncl) {
      float acc[80];
      uint32_t prev = 0, bprev = 0;
      auto bstep = [&](int ks, int accf) {
        TR(640 + 2 * ks);
        ring_wait();
        mbar_wait(sb + BAR_BFULL + 8 * bslot, bphase);
        TR(641 + 2 * ks);
        wg_fence();
        const uint32_t a = ring_addr() + wg * 512, bd = (((sb & 0x3FFFF) + OFF_Q + bslot * BB) >> 4) | ((4096u >> 4) << 16);
#pragma unroll
        for (int k = 0; k < 4; k++) wgmma_n160<1, 1>(acc, a + k * 128, HI128, bd + k * 64, HI64, k == 0 ? accf : 1);
        wg_commit();
        if (ks > 0) {
          wg_wait<1>();
          release(prev);
          if (lane == 0) mbar_arrive_cl(mapa(sb + BAR_BEMPTY + 8 * bprev, bprev & 1));
        }
        prev = r.slot; bprev = bslot;
        r.next();
        if (++bslot == 6) { bslot = 0; bphase ^= 1; }
      };
      bstep(0, 0);
      bstep(1, 1); put(pb, IC<0>()); bstep(2, 1);
      bstep(3, 1); put(pb, IC<1>()); bstep(4, 1);
      bstep(5, 1); put(pb, IC<2>()); bstep(6, 1);
      bstep(7, 1); put(pb, IC<3>()); bstep(8, 1);
      bstep(9, 1); put(pb, IC<4>()); bstep(10, 1);
      bstep(11, 1); put(pb, IC<5>()); bstep(12, 1);
      bstep(13, 1); put(pb, IC<6>()); bstep(14, 1);
      bstep(15, 1); put(pb, IC<7>()); bstep(16, 1);
      if (t == cl) publish();
      optr = nullptr;
#pragma unroll 1
      for (int ks = 17; ks < 64; ks++) bstep(ks, 1);
      wg_wait<0>();
      reg_fence(acc);
      release(prev);
      if (lane == 0) mbar_arrive_cl(mapa(sb + BAR_BEMPTY + 8 * bprev, bprev & 1));
      TR(158);
      const int pos0 = (t >> 2) * 256 + rank * 128 + wg * 64 + w * 16;
      if (t + ncl >= NOTILES) {
        bar_sync(bar_id);
        const uint32_t st = sb + w * RING_BYTES + wg * 8192;
        const uint32_t sa = st + (lane & 15) * 336 + (lane >> 4) * 16;
#pragma unroll
        for (int j = 0; j < 20; j += 2)
          asm volatile("stmatrix.sync.aligned.m8n8.x4.shared.b16 [%0], {%1,%2,%3,%4};" ::"r"(sa + j * 16), "r"(pack(acc[4 * j], acc[4 * j + 1])),
                       "r"(pack(acc[4 * j + 2], acc[4 * j + 3])), "r"(pack(acc[4 * j + 4], acc[4 * j + 5])), "r"(pack(acc[4 * j + 6], acc[4 * j + 7])) : "memory");
        fence_async_smem();
        __syncwarp();
        if (lane < 16) {
          __nv_bfloat16* dst = P.out + (size_t)o_row(pos0 + lane) * DM + (t & 3) * 160;
          asm volatile("cp.async.bulk.global.shared::cta.bulk_group [%0], [%1], 320;" ::"l"(dst), "r"(st + lane * 336) : "memory");
          asm volatile("cp.async.bulk.commit_group;" ::: "memory");
          asm volatile("cp.async.bulk.wait_group.read 0;" ::: "memory");
        }
      } else {
        __nv_bfloat16* op0 = P.out + (size_t)o_row(pos0 + (lane >> 2)) * DM + (t & 3) * 160 + (lane & 3) * 2;
        __nv_bfloat16* op1 = P.out + (size_t)o_row(pos0 + (lane >> 2) + 8) * DM + (t & 3) * 160 + (lane & 3) * 2;
#pragma unroll
        for (int j = 0; j < 20; j++) {
          *reinterpret_cast<uint32_t*>(op0 + j * 8) = pack(acc[4 * j], acc[4 * j + 1]);
          *reinterpret_cast<uint32_t*>(op1 + j * 8) = pack(acc[4 * j + 2], acc[4 * j + 3]);
        }
      }
    }
    if (wg == 0) turn_wait();
    TR(159);
  }
  __syncthreads();
  cluster_sync();
  if (threadIdx.x == 0) {
    __threadfence();
    if (atomicAdd(&g_cnt[512], 1) == gridDim.x - 1) {
      for (int i = 0; i <= 64; i++) g_cnt[i * 8] = 0;
    }
  }
}

typedef CUresult (*EncodeFn)(CUtensorMap*, CUtensorMapDataType, cuuint32_t, void*, const cuuint64_t*, const cuuint64_t*,
                             const cuuint32_t*, const cuuint32_t*, CUtensorMapInterleave, CUtensorMapSwizzle,
                             CUtensorMapL2promotion, CUtensorMapFloatOOBfill);

void make_map(EncodeFn enc, CUtensorMap* m, const void* p, int rank, const cuuint64_t* dims, const cuuint64_t* strides,
              const cuuint32_t* box, CUtensorMapSwizzle sw, CUtensorMapL2promotion promo) {
  cuuint32_t es[3] = {1, 1, 1};
  enc(m, CU_TENSOR_MAP_DATA_TYPE_BFLOAT16, rank, const_cast<void*>(p), dims, strides, box, es, CU_TENSOR_MAP_INTERLEAVE_NONE, sw,
      promo, CU_TENSOR_MAP_FLOAT_OOB_FILL_NONE);
}

}

extern "C" void kernel_launch(void* const* d_in, const int* in_sizes, int n_in, void* d_out, int out_size) {
  static EncodeFn enc = nullptr;
  static int nclusters = 0;
  static void* o_ptr = nullptr;
  if (!enc) {
    cudaDriverEntryPointQueryResult qr;
    cudaGetDriverEntryPoint("cuTensorMapEncodeTiled", (void**)&enc, cudaEnableDefault, &qr);
    cudaFuncSetAttribute(fused_attn_kernel, cudaFuncAttributeMaxDynamicSharedMemorySize, SMEM_BYTES);
    cudaGetSymbolAddress(&o_ptr, g_o);
    cudaLaunchConfig_t cfg = {};
    cfg.gridDim = 128; cfg.blockDim = 384; cfg.dynamicSmemBytes = SMEM_BYTES;
    cudaLaunchAttribute at; at.id = cudaLaunchAttributeClusterDimension;
    at.val.clusterDim.x = 2; at.val.clusterDim.y = 1; at.val.clusterDim.z = 1;
    cfg.attrs = &at; cfg.numAttrs = 1;
    int n = 0;
    cudaOccupancyMaxActiveClusters(&n, fused_attn_kernel, &cfg);
    nclusters = n >= 64 || n <= 0 ? 64 : n;
  }
  const __nv_bfloat16* x = (const __nv_bfloat16*)d_in[0];
  const __nv_bfloat16* k = (const __nv_bfloat16*)d_in[1];
  const __nv_bfloat16* v = (const __nv_bfloat16*)d_in[2];
  const __nv_bfloat16* wq = (const __nv_bfloat16*)d_in[3];
  const __nv_bfloat16* wo = (const __nv_bfloat16*)d_in[4];
  CUtensorMap tm_x, tm_wq, tm_k, tm_v, tm_o, tm_wo;
  const auto S128 = CU_TENSOR_MAP_SWIZZLE_128B;
  const auto P128 = CU_TENSOR_MAP_L2_PROMOTION_L2_128B, P256 = CU_TENSOR_MAP_L2_PROMOTION_L2_256B;
  { cuuint64_t d[2] = {DM, NB * SQ}, s[1] = {DM * 2}; cuuint32_t b[2] = {64, 120}; make_map(enc, &tm_x, x, 2, d, s, b, S128, P128); }
  { cuuint64_t d[3] = {64, DM, HD / 64}, s[2] = {HD * 2, 128}; cuuint32_t b[3] = {64, 64, 2}; make_map(enc, &tm_wq, wq, 3, d, s, b, S128, P256); }
  { cuuint64_t d[3] = {64, NB * NH * SK, 2}, s[2] = {DH * 2, 128}; cuuint32_t b[3] = {64, 64, 2};
    make_map(enc, &tm_k, k, 3, d, s, b, S128, KV_PROMO); make_map(enc, &tm_v, v, 3, d, s, b, S128, KV_PROMO); }
  { cuuint64_t d[3] = {64, HD, NROWS / 64}, s[2] = {NROWS * 2, 128}; cuuint32_t b[3] = {64, 64, 2}; make_map(enc, &tm_o, o_ptr, 3, d, s, b, S128, P256); }
  { cuuint64_t d[3] = {32, HD, DM / 32}, s[2] = {DM * 2, 64}; cuuint32_t b[3] = {32, 64, 5};
    make_map(enc, &tm_wo, wo, 3, d, s, b, CU_TENSOR_MAP_SWIZZLE_64B, P128); }
  Params P{x, k, v, wq, (__nv_bfloat16*)d_out};
  fused_attn_kernel<<<2 * nclusters, 384, SMEM_BYTES>>>(tm_x, tm_wq, tm_k, tm_v, tm_o, tm_wo, P);
}
```

```cpp
#include <cuda_runtime.h>
#include <cuda.h>
#include <cuda_bf16.h>
#include <stdint.h>

namespace {

constexpr int NB = 16, SQ = 240, DM = 640, NH = 32, SK = 1024, DH = 128, HD = NH * DH;
constexpr int NROWS = NB * SQ;
constexpr int NUNITS = 256;
#define WAITV 0
#define XW_PF 0
#define B_PF 0
#define WO_PF 0
#define B_ORDER 1
#define TAIL_ORDER 2
#define PF_LSU 0
#define PF_FIRST 0
#define GATE 0
#define X_PF 0
#define HEAD 3
#define SPLIT_STEP 3
#define TAIL_V 1
#define KV_PROMO P128
#define PF_POL 0
#define NOT 60
#define O_EF 1
#define PF_HOLD 4
#define VREL 8
#define PP_MODE 1
#define PF_N 4
#define PF_J0 3
#define PF_STEP 3
#define PF_WHAT 2
#define ROT 1
constexpr int NOTILES = NOT;
constexpr float QSCALE = 0.08838834764831845f * 1.4426950408889634f;
constexpr float L_MIN = 9.5367431640625e-07f;
constexpr float L_MAX = 1.152921504606846976e18f;

constexpr uint32_t RING_SLOTS = 6, RING_BYTES = 16384;
constexpr uint32_t XB = 15360;
constexpr uint32_t BB = 20480;
constexpr uint32_t OFF_Q = RING_SLOTS * RING_BYTES;
constexpr uint32_t OFF_P = OFF_Q + 4 * XB;
constexpr uint32_t OFF_INV = OFF_P + 4 * XB;
constexpr uint32_t OFF_BAR = OFF_INV + 1024;
constexpr uint32_t BAR_RFULL = OFF_BAR, BAR_REMPTY = BAR_RFULL + 48, BAR_XFULL = BAR_REMPTY + 48,
    BAR_XEMPTY = BAR_XFULL + 64, BAR_BFULL = BAR_XEMPTY + 32, BAR_BEMPTY = BAR_BFULL + 48, BAR_STAGE = BAR_BEMPTY + 48;
constexpr uint32_t BAR_GATE = BAR_STAGE + 16;
constexpr uint32_t OFF_TR = BAR_GATE + 16;
constexpr uint32_t SMEM_BYTES = OFF_TR + 1024;

constexpr uint32_t HI128 = (1u << 30) | (1024 >> 4);
constexpr uint32_t HI64 = (2u << 30) | (512 >> 4);

__device__ __nv_bfloat16 g_o[HD * NROWS];
__device__ unsigned g_cnt[64 * 8 + 8];
#define TR(i)

struct Params {
  const __nv_bfloat16 *x, *k, *v, *wq;
  __nv_bfloat16* out;
};

__device__ __forceinline__ void wg_fence() { asm volatile("wgmma.fence.sync.aligned;" ::: "memory"); }
__device__ __forceinline__ void wg_commit() { asm volatile("wgmma.commit_group.sync.aligned;" ::: "memory"); }
template <int N> __device__ __forceinline__ void wg_wait() { asm volatile("wgmma.wait_group.sync.aligned %0;" ::"n"(N) : "memory"); }
template <int N> __device__ __forceinline__ void reg_fence(float (&r)[N]) {
#pragma unroll
  for (int i = 0; i < N; i++) asm volatile("" : "+f"(r[i])::"memory");
}
template <int TA, int TB>
__device__ __forceinline__ void wgmma_n120(float (&d)[60], uint32_t a_lo, uint32_t a_hi, uint32_t b_lo, uint32_t b_hi, int acc) {
  asm volatile(
      "{\n.reg .pred p;\n.reg .b64 da, db;\nsetp.ne.b32 p, %64, 0;\n"
      "mov.b64 da, {%60, %61};\nmov.b64 db, {%62, %63};\n"
      "wgmma.mma_async.sync.aligned.m64n120k16.f32.bf16.bf16 {"
      "%0, %1, %2, %3, %4, %5, %6, %7, %8, %9, %10, %11, %12, %13, %14, %15, %16, %17, %18, %19, %20, %21, %22, %23, "
      "%24, %25, %26, %27, %28, %29, %30, %31, %32, %33, %34, %35, %36, %37, %38, %39, %40, %41, %42, %43, %44, %45, "
      "%46, %47, %48, %49, %50, %51, %52, %53, %54, %55, %56, %57, %58, %59"
      "}, da, db, p, 1, 1, %65, %66;\n}\n"
      : "+f"(d[0]), "+f"(d[1]), "+f"(d[2]), "+f"(d[3]), "+f"(d[4]), "+f"(d[5]), "+f"(d[6]), "+f"(d[7]), "+f"(d[8]),
        "+f"(d[9]), "+f"(d[10]), "+f"(d[11]), "+f"(d[12]), "+f"(d[13]), "+f"(d[14]), "+f"(d[15]), "+f"(d[16]),
        "+f"(d[17]), "+f"(d[18]), "+f"(d[19]), "+f"(d[20]), "+f"(d[21]), "+f"(d[22]), "+f"(d[23]), "+f"(d[24]),
        "+f"(d[25]), "+f"(d[26]), "+f"(d[27]), "+f"(d[28]), "+f"(d[29]), "+f"(d[30]), "+f"(d[31]), "+f"(d[32]),
        "+f"(d[33]), "+f"(d[34]), "+f"(d[35]), "+f"(d[36]), "+f"(d[37]), "+f"(d[38]), "+f"(d[39]), "+f"(d[40]),
        "+f"(d[41]), "+f"(d[42]), "+f"(d[43]), "+f"(d[44]), "+f"(d[45]), "+f"(d[46]), "+f"(d[47]), "+f"(d[48]),
        "+f"(d[49]), "+f"(d[50]), "+f"(d[51]), "+f"(d[52]), "+f"(d[53]), "+f"(d[54]), "+f"(d[55]), "+f"(d[56]),
        "+f"(d[57]), "+f"(d[58]), "+f"(d[59])
      : "r"(a_lo), "r"(a_hi), "r"(b_lo), "r"(b_hi), "r"(acc), "n"(TA), "n"(TB));
}

template <int TA, int TB>
__device__ __forceinline__ void wgmma_n160(float (&d)[80], uint32_t a_lo, uint32_t a_hi, uint32_t b_lo, uint32_t b_hi, int acc) {
  asm volatile(
      "{\n.reg .pred p;\n.reg .b64 da, db;\nsetp.ne.b32 p, %84, 0;\n"
      "mov.b64 da, {%80, %81};\nmov.b64 db, {%82, %83};\n"
      "wgmma.mma_async.sync.aligned.m64n160k16.f32.bf16.bf16 {"
      "%0, %1, %2, %3, %4, %5, %6, %7, %8, %9, %10, %11, %12, %13, %14, %15, %16, %17, %18, %19, %20, %21, %22, %23, "
      "%24, %25, %26, %27, %28, %29, %30, %31, %32, %33, %34, %35, %36, %37, %38, %39, %40, %41, %42, %43, %44, %45, "
      "%46, %47, %48, %49, %50, %51, %52, %53, %54, %55, %56, %57, %58, %59, %60, %61, %62, %63, %64, %65, %66, %67, "
      "%68, %69, %70, %71, %72, %73, %74, %75, %76, %77, %78, %79"
      "}, da, db, p, 1, 1, %85, %86;\n}\n"
      : "+f"(d[0]), "+f"(d[1]), "+f"(d[2]), "+f"(d[3]), "+f"(d[4]), "+f"(d[5]), "+f"(d[6]), "+f"(d[7]), "+f"(d[8]),
        "+f"(d[9]), "+f"(d[10]), "+f"(d[11]), "+f"(d[12]), "+f"(d[13]), "+f"(d[14]), "+f"(d[15]), "+f"(d[16]),
        "+f"(d[17]), "+f"(d[18]), "+f"(d[19]), "+f"(d[20]), "+f"(d[21]), "+f"(d[22]), "+f"(d[23]), "+f"(d[24]),
        "+f"(d[25]), "+f"(d[26]), "+f"(d[27]), "+f"(d[28]), "+f"(d[29]), "+f"(d[30]), "+f"(d[31]), "+f"(d[32]),
        "+f"(d[33]), "+f"(d[34]), "+f"(d[35]), "+f"(d[36]), "+f"(d[37]), "+f"(d[38]), "+f"(d[39]), "+f"(d[40]),
        "+f"(d[41]), "+f"(d[42]), "+f"(d[43]), "+f"(d[44]), "+f"(d[45]), "+f"(d[46]), "+f"(d[47]), "+f"(d[48]),
        "+f"(d[49]), "+f"(d[50]), "+f"(d[51]), "+f"(d[52]), "+f"(d[53]), "+f"(d[54]), "+f"(d[55]), "+f"(d[56]),
        "+f"(d[57]), "+f"(d[58]), "+f"(d[59]), "+f"(d[60]), "+f"(d[61]), "+f"(d[62]), "+f"(d[63]), "+f"(d[64]),
        "+f"(d[65]), "+f"(d[66]), "+f"(d[67]), "+f"(d[68]), "+f"(d[69]), "+f"(d[70]), "+f"(d[71]), "+f"(d[72]),
        "+f"(d[73]), "+f"(d[74]), "+f"(d[75]), "+f"(d[76]), "+f"(d[77]), "+f"(d[78]), "+f"(d[79])
      : "r"(a_lo), "r"(a_hi), "r"(b_lo), "r"(b_hi), "r"(acc), "n"(TA), "n"(TB));
}
__device__ __forceinline__ void mbar_init(uint32_t bar, int cnt) { asm volatile("mbarrier.init.shared::cta.b64 [%0], %1;" ::"r"(bar), "r"(cnt)); }
__device__ __forceinline__ void mbar_expect(uint32_t bar, uint32_t bytes) {
  asm volatile("mbarrier.arrive.expect_tx.shared::cta.b64 _, [%0], %1;" ::"r"(bar), "r"(bytes) : "memory");
}
__device__ __forceinline__ uint32_t mapa(uint32_t addr, uint32_t cta) {
  uint32_t r; asm("mapa.shared::cluster.u32 %0, %1, %2;" : "=r"(r) : "r"(addr), "r"(cta)); return r;
}
__device__ __forceinline__ void mbar_expect_cl(uint32_t cbar, uint32_t bytes) {
  asm volatile("mbarrier.arrive.expect_tx.shared::cluster.b64 _, [%0], %1;" ::"r"(cbar), "r"(bytes) : "memory");
}
__device__ __forceinline__ void mbar_arrive(uint32_t bar) { asm volatile("mbarrier.arrive.shared::cta.b64 _, [%0];" ::"r"(bar) : "memory"); }
__device__ __forceinline__ void mbar_arrive_cl(uint32_t cbar) { asm volatile("mbarrier.arrive.shared::cluster.b64 _, [%0];" ::"r"(cbar) : "memory"); }
__device__ __forceinline__ void mbar_wait(uint32_t bar, uint32_t parity) {
  asm volatile(
      "{\n.reg .pred p;\n.reg .u32 n;\n"
      "mbarrier.try_wait.parity.shared::cta.b64 p, [%0], %1;\n@p bra WAIT_DONE;\n"
      "mov.u32 n, 0;\n"
      "WAIT_LOOP:\n"
      "mbarrier.try_wait.parity.shared::cta.b64 p, [%0], %1;\n@p bra WAIT_DONE;\n"
      "add.u32 n, n, 1;\nsetp.lt.u32 p, n, 0x4000000;\n@p bra WAIT_LOOP;\ntrap;\n"
      "WAIT_DONE:\n}\n" ::"r"(bar), "r"(parity) : "memory");
}
__device__ __forceinline__ void tma3d(uint32_t dst, const CUtensorMap* m, int c0, int c1, int c2, uint32_t bar) {
  asm volatile("cp.async.bulk.tensor.3d.shared::cluster.global.mbarrier::complete_tx::bytes [%0], [%1, {%3, %4, %5}], [%2];"
               ::"r"(dst), "l"(m), "r"(bar), "r"(c0), "r"(c1), "r"(c2) : "memory");
}
__device__ __forceinline__ void tma3d_hint(uint32_t dst, const CUtensorMap* m, int c0, int c1, int c2, uint32_t bar, uint64_t pol) {
  asm volatile("cp.async.bulk.tensor.3d.shared::cluster.global.mbarrier::complete_tx::bytes.L2::cache_hint [%0], [%1, {%3, %4, %5}], [%2], %6;"
               ::"r"(dst), "l"(m), "r"(bar), "r"(c0), "r"(c1), "r"(c2), "l"(pol) : "memory");
}
__device__ __forceinline__ void tma2d_mc(uint32_t dst, const CUtensorMap* m, int c0, int c1, uint32_t bar) {
  asm volatile("cp.async.bulk.tensor.2d.shared::cluster.global.mbarrier::complete_tx::bytes.multicast::cluster [%0], [%1, {%3, %4}], [%2], %5;"
               ::"r"(dst), "l"(m), "r"(bar), "r"(c0), "r"(c1), "h"((uint16_t)3) : "memory");
}
__device__ __forceinline__ void tma3d_mc(uint32_t dst, const CUtensorMap* m, int c0, int c1, int c2, uint32_t bar) {
  asm volatile("cp.async.bulk.tensor.3d.shared::cluster.global.mbarrier::complete_tx::bytes.multicast::cluster [%0], [%1, {%3, %4, %5}], [%2], %6;"
               ::"r"(dst), "l"(m), "r"(bar), "r"(c0), "r"(c1), "r"(c2), "h"((uint16_t)3) : "memory");
}
__device__ __forceinline__ void l2_prefetch(const void* p, uint32_t bytes, uint64_t pol) {
  if (PF_POL) asm volatile("cp.async.bulk.prefetch.L2.global.L2::cache_hint [%0], %1, %2;" ::"l"(p), "r"(bytes), "l"(pol) : "memory");
  else asm volatile("cp.async.bulk.prefetch.L2.global [%0], %1;" ::"l"(p), "r"(bytes) : "memory");
}
__device__ __forceinline__ void fence_async_smem() { asm volatile("fence.proxy.async.shared::cta;" ::: "memory"); }
__device__ __forceinline__ void bar_sync(int id) { asm volatile("bar.sync %0, 128;" ::"r"(id) : "memory"); }
__device__ __forceinline__ bool bar_red_or(int id, bool v) {
  uint32_t r;
  asm volatile("{\n.reg .pred p, q;\nsetp.ne.u32 p, %2, 0;\nbar.red.or.pred q, %1, 128, p;\nselp.u32 %0, 1, 0, q;\n}\n"
               : "=r"(r) : "r"(id), "r"((uint32_t)v) : "memory");
  return r != 0;
}
__device__ __forceinline__ void tma3d_prefetch(const CUtensorMap* m, int c0, int c1, int c2) {
  asm volatile("cp.async.bulk.prefetch.tensor.3d.L2.global [%0, {%1, %2, %3}];" ::"l"(m), "r"(c0), "r"(c1), "r"(c2) : "memory");
}
__device__ __forceinline__ uint32_t hfma2(uint32_t a, uint32_t b, uint32_t c) { uint32_t r; asm("fma.rn.bf16x2 %0, %1, %2, %3;" : "=r"(r) : "r"(a), "r"(b), "r"(c)); return r; }
__device__ __forceinline__ float ex2(float x) { float y; asm("ex2.approx.ftz.f32 %0, %1;" : "=f"(y) : "f"(x)); return y; }
__device__ __forceinline__ uint32_t pack(float lo, float hi) { uint32_t r; asm("cvt.rn.bf16x2.f32 %0, %1, %2;" : "=r"(r) : "f"(hi), "f"(lo)); return r; }
__device__ __forceinline__ void stsm4t(uint32_t a, uint32_t r0, uint32_t r1, uint32_t r2, uint32_t r3) {
  asm volatile("stmatrix.sync.aligned.m8n8.x4.trans.shared.b16 [%0], {%1,%2,%3,%4};" ::"r"(a), "r"(r0), "r"(r1), "r"(r2), "r"(r3) : "memory");
}
__device__ __forceinline__ void stsm2t(uint32_t a, uint32_t r0, uint32_t r1) {
  asm volatile("stmatrix.sync.aligned.m8n8.x2.trans.shared.b16 [%0], {%1,%2};" ::"r"(a), "r"(r0), "r"(r1) : "memory");
}
__device__ __forceinline__ void mma16816(float (&d)[4], const uint32_t (&a)[4], uint32_t b0, uint32_t b1) {
  asm volatile("mma.sync.aligned.m16n8k16.row.col.f32.bf16.bf16.f32 {%0,%1,%2,%3}, {%4,%5,%6,%7}, {%8,%9}, {%0,%1,%2,%3};"
               : "+f"(d[0]), "+f"(d[1]), "+f"(d[2]), "+f"(d[3]) : "r"(a[0]), "r"(a[1]), "r"(a[2]), "r"(a[3]), "r"(b0), "r"(b1));
}

template <int V> struct IC { static constexpr int value = V; };

struct Ring {
  uint32_t slot = 0, phase = 0;
  __device__ __forceinline__ void next() { if (++slot == RING_SLOTS) { slot = 0; phase ^= 1; } }
};

__device__ __forceinline__ void mma_tn(float (&o0)[60], float (&o1)[60], uint32_t a, uint32_t b, int acc) {
#pragma unroll
  for (int k = 0; k < 4; k++) {
    wgmma_n120<1, 0>(o0, a + k * 128, HI128, b + k * 2, HI128, k == 0 ? acc : 1);
    wgmma_n120<1, 0>(o1, a + 512 + k * 128, HI128, b + k * 2, HI128, k == 0 ? acc : 1);
  }
}
__device__ __forceinline__ void mma_tn_split(float (&o0)[60], float (&o1)[60], uint32_t a, uint32_t b) {
#pragma unroll
  for (int k = 0; k < 4; k++) wgmma_n120<1, 0>(o0, a + k * 128, HI128, b + k * 2, HI128, 1);
  wg_commit();
#pragma unroll
  for (int k = 0; k < 4; k++) wgmma_n120<1, 0>(o1, a + 512 + k * 128, HI128, b + k * 2, HI128, 1);
  wg_commit();
}
__device__ __forceinline__ void mma_qk(float (&s)[60], uint32_t a, uint32_t q) {
#pragma unroll
  for (int k = 0; k < 8; k++)
    wgmma_n120<0, 0>(s, a + (k >> 2) * 512 + (k & 3) * 2, HI128, q + (k >> 2) * (XB >> 4) + (k & 3) * 2, HI128, k != 0);
}
template <int J0, int J1, bool FIRST = false>
__device__ __forceinline__ void exp_store(const float (&s)[60], float (&l)[30], uint32_t dst) {
#pragma unroll
  for (int j = J0; j < J1; j += 2) {
    uint32_t p[4];
#pragma unroll
    for (int jj = 0; jj < 2; jj++) {
      if (j + jj < 15) {
        const int c = j + jj;
        float e0 = ex2(s[4 * c]), e1 = ex2(s[4 * c + 1]), e2 = ex2(s[4 * c + 2]), e3 = ex2(s[4 * c + 3]);
        if (FIRST) { l[2 * c] = e0 + e2; l[2 * c + 1] = e1 + e3; }
        else { l[2 * c] += e0; l[2 * c + 1] += e1; l[2 * c] += e2; l[2 * c + 1] += e3; }
        p[2 * jj] = pack(e0, e1); p[2 * jj + 1] = pack(e2, e3);
      }
    }
    if (j + 1 < 15) stsm4t(dst + j * 1024, p[0], p[1], p[2], p[3]);
    else stsm2t(dst + j * 1024, p[0], p[1]);
  }
}

__device__ __forceinline__ int o_pos(int wg, int r) {
  const int j = r >> 3, q = (r >> 1) & 3, c = r & 1;
  if (j < 12) return (wg ? 144 : 0) + (j >> 2) * 32 + q * 8 + (j & 3) * 2 + c;
  if (j < 14) return (wg ? 128 : 96) + q * 4 + (j - 12) * 2 + c;
  return (wg ? 120 : 112) + q * 2 + c;
}
__device__ __forceinline__ int o_row(int p) {
  const int b = p / SQ, r = p - b * SQ, wg = r >= 120, c = r & 1;
  const int a = r - (wg ? 144 : 0), m = r - (wg ? 128 : 96), e = r - (wg ? 120 : 112);
  int row;
  if (a >= 0 && a < 96) row = ((a >> 5) * 4 + ((a >> 1) & 3)) * 8 + ((a >> 3) & 3) * 2 + c;
  else if (m >= 0 && m < 16) row = (12 + ((m >> 1) & 1)) * 8 + (m >> 2) * 2 + c;
  else row = 112 + e;
  return b * SQ + wg * 120 + row;
}

__device__ __forceinline__ void slow_path(const Params& P, int b, int h, int wg, int w, int lane) {
  const int g = lane >> 2, q = lane & 3, row0 = wg * 120;
  const uint16_t* wq = reinterpret_cast<const uint16_t*>(P.wq) + h * DH + g;
  const __nv_bfloat16* kp = P.k + (size_t)(b * NH + h) * SK * DH;
  const uint16_t* vp = reinterpret_cast<const uint16_t*>(P.v) + (size_t)(b * NH + h) * SK * DH + g;
#pragma unroll 1
  for (int t = w; t < 8; t += 4) {
    const int r0 = 16 * t + g, r1 = r0 + 8;
    const __nv_bfloat16* x0 = P.x + (size_t)(b * SQ + row0 + r0) * DM + 2 * q;
    const __nv_bfloat16* x1 = P.x + (size_t)(b * SQ + row0 + min(r1, 119)) * DM + 2 * q;
    float o[16][4];
#pragma unroll
    for (int n = 0; n < 16; n++) o[n][0] = o[n][1] = o[n][2] = o[n][3] = 0.f;
#pragma unroll 1
    for (int k0 = 0; k0 < DM; k0 += 16) {
      uint32_t a[4] = {*(const uint32_t*)(x0 + k0), *(const uint32_t*)(x1 + k0), *(const uint32_t*)(x0 + k0 + 8), *(const uint32_t*)(x1 + k0 + 8)};
      const uint16_t* wr = wq + (size_t)(k0 + 2 * q) * HD;
#pragma unroll
      for (int n = 0; n < 16; n++)
        mma16816(o[n], a, wr[8 * n] | ((uint32_t)wr[8 * n + HD] << 16), wr[8 * n + 8 * HD] | ((uint32_t)wr[8 * n + 9 * HD] << 16));
    }
    uint32_t qa[8][4];
#pragma unroll
    for (int k = 0; k < 8; k++) {
      qa[k][0] = pack(o[2 * k][0] * QSCALE, o[2 * k][1] * QSCALE);
      qa[k][1] = pack(o[2 * k][2] * QSCALE, o[2 * k][3] * QSCALE);
      qa[k][2] = pack(o[2 * k + 1][0] * QSCALE, o[2 * k + 1][1] * QSCALE);
      qa[k][3] = pack(o[2 * k + 1][2] * QSCALE, o[2 * k + 1][3] * QSCALE);
    }
#pragma unroll
    for (int n = 0; n < 16; n++) o[n][0] = o[n][1] = o[n][2] = o[n][3] = 0.f;
    float m0 = -INFINITY, m1 = -INFINITY, l0 = 0.f, l1 = 0.f;
#pragma unroll 1
    for (int key0 = 0; key0 < SK; key0 += 16) {
      float s[2][4];
#pragma unroll
      for (int nt = 0; nt < 2; nt++) {
        s[nt][0] = s[nt][1] = s[nt][2] = s[nt][3] = 0.f;
        const __nv_bfloat16* kr = kp + (size_t)(key0 + 8 * nt + g) * DH + 2 * q;
#pragma unroll
        for (int k = 0; k < 8; k++) mma16816(s[nt], qa[k], *(const uint32_t*)(kr + 16 * k), *(const uint32_t*)(kr + 16 * k + 8));
      }
      float n0 = fmaxf(fmaxf(s[0][0], s[0][1]), fmaxf(s[1][0], s[1][1])), n1 = fmaxf(fmaxf(s[0][2], s[0][3]), fmaxf(s[1][2], s[1][3]));
      n0 = fmaxf(n0, __shfl_xor_sync(~0u, n0, 1)); n1 = fmaxf(n1, __shfl_xor_sync(~0u, n1, 1));
      n0 = fmaxf(n0, __shfl_xor_sync(~0u, n0, 2)); n1 = fmaxf(n1, __shfl_xor_sync(~0u, n1, 2));
      n0 = fmaxf(n0, m0); n1 = fmaxf(n1, m1);
      const float z0 = n0 == -INFINITY ? 0.f : n0, z1 = n1 == -INFINITY ? 0.f : n1;
      const float c0 = ex2(m0 - z0), c1 = ex2(m1 - z1);
      m0 = n0; m1 = n1;
#pragma unroll
      for (int nt = 0; nt < 2; nt++) {
        s[nt][0] = ex2(s[nt][0] - z0); s[nt][1] = ex2(s[nt][1] - z0);
        s[nt][2] = ex2(s[nt][2] - z1); s[nt][3] = ex2(s[nt][3] - z1);
      }
      l0 = l0 * c0 + s[0][0] + s[0][1] + s[1][0] + s[1][1];
      l1 = l1 * c1 + s[0][2] + s[0][3] + s[1][2] + s[1][3];
      uint32_t pa[4] = {pack(s[0][0], s[0][1]), pack(s[0][2], s[0][3]), pack(s[1][0], s[1][1]), pack(s[1][2], s[1][3])};
      const uint16_t* vr = vp + (size_t)(key0 + 2 * q) * DH;
#pragma unroll
      for (int n = 0; n < 16; n++) {
        o[n][0] *= c0; o[n][1] *= c0; o[n][2] *= c1; o[n][3] *= c1;
        mma16816(o[n], pa, vr[8 * n] | ((uint32_t)vr[8 * n + DH] << 16), vr[8 * n + 8 * DH] | ((uint32_t)vr[8 * n + 9 * DH] << 16));
      }
    }
    l0 += __shfl_xor_sync(~0u, l0, 1); l1 += __shfl_xor_sync(~0u, l1, 1);
    l0 += __shfl_xor_sync(~0u, l0, 2); l1 += __shfl_xor_sync(~0u, l1, 2);
    const float i0 = 1.f / l0, i1 = 1.f / l1;
    __nv_bfloat16* oc = g_o + (size_t)(h * DH + 2 * q) * NROWS + b * SQ;
    const int p0 = o_pos(wg, r0), p1 = o_pos(wg, min(r1, 119));
#pragma unroll
    for (int n = 0; n < 16; n++) {
      oc[(size_t)(8 * n) * NROWS + p0] = __float2bfloat16(o[n][0] * i0);
      oc[(size_t)(8 * n + 1) * NROWS + p0] = __float2bfloat16(o[n][1] * i0);
      if (r1 < 120) {
        oc[(size_t)(8 * n) * NROWS + p1] = __float2bfloat16(o[n][2] * i1);
        oc[(size_t)(8 * n + 1) * NROWS + p1] = __float2bfloat16(o[n][3] * i1);
      }
    }
  }
}

__device__ __forceinline__ int bk(int ks) { return B_ORDER && ks < 48 ? 32 - (ks & 48) + (ks & 15) : ks; }
__device__ __forceinline__ uint32_t x_slot(uint32_t j) { return j < 2 ? j * XB : (7 - j) * XB; }
__device__ __forceinline__ int unit_batch(int u) { return (u & 63) >> 2; }
__device__ __forceinline__ int unit_head(int u, int rank) { return (u >> 6) * 8 + (u & 3) * 2 + rank; }

__global__ void __cluster_dims__(2, 1, 1) __launch_bounds__(384, 1)
fused_attn_kernel(const __grid_constant__ CUtensorMap tm_x, const __grid_constant__ CUtensorMap tm_wq,
                  const __grid_constant__ CUtensorMap tm_k, const __grid_constant__ CUtensorMap tm_v,
                  const __grid_constant__ CUtensorMap tm_o, const __grid_constant__ CUtensorMap tm_wo,
                  const __grid_constant__ Params P) {
  extern __shared__ uint8_t smem_raw[];
  const uint32_t sb = ((uint32_t)__cvta_generic_to_shared(smem_raw) + 1023) & ~1023u;
  const int warp = __shfl_sync(~0u, threadIdx.x >> 5, 0);
  const int lane = threadIdx.x & 31;
  const int rank = blockIdx.x & 1, cl = blockIdx.x >> 1, ncl = gridDim.x >> 1;

  auto prefetch_proj = [&](int u) {
    l2_prefetch(P.x + (size_t)(unit_batch(u) * SQ + ((u & 3) * 2 + rank) * 30) * DM, 30 * DM * 2, 0);
    if (unit_batch(u) < 10) tma3d_prefetch(&tm_wq, 0, unit_batch(u) * 64, 2 * unit_head(u, rank));
  };
  if (threadIdx.x == 256 && (XW_PF & 1)) prefetch_proj(cl);
  if (threadIdx.x == 0) {
    for (int i = 0; i < 6; i++) {
      mbar_init(sb + BAR_RFULL + 8 * i, 1); mbar_init(sb + BAR_REMPTY + 8 * i, 8);
      mbar_init(sb + BAR_BFULL + 8 * i, 1); mbar_init(sb + BAR_BEMPTY + 8 * i, 16);
    }
    for (int i = 0; i < 8; i++) mbar_init(sb + BAR_XFULL + 8 * i, 1);
    for (int i = 0; i < 4; i++) mbar_init(sb + BAR_XEMPTY + 8 * i, 8);
    for (int i = 0; i < 2; i++) mbar_init(sb + BAR_STAGE + 8 * i, 4);
    mbar_init(sb + BAR_GATE, 1);
    asm volatile("fence.mbarrier_init.release.cluster;" ::: "memory");
  }
  __syncwarp();
  asm volatile("barrier.cluster.arrive.relaxed.aligned;\nbarrier.cluster.wait.aligned;" ::: "memory");

  if (warp >= 8) {
    asm volatile("setmaxnreg.dec.sync.aligned.u32 24;");
    if (warp == 8) {
      uint64_t pol;
      asm volatile("createpolicy.fractional.L2::evict_first.b64 %0, 1.0;" : "=l"(pol));
      Ring r;
      auto load = [&](const CUtensorMap* m, int c1, int c2, bool ef) {
        mbar_wait(sb + BAR_REMPTY + 8 * r.slot, r.phase ^ 1);
        if (lane == 0) {
          mbar_expect(sb + BAR_RFULL + 8 * r.slot, RING_BYTES);
          if (ef) tma3d_hint(sb + r.slot * RING_BYTES, m, 0, c1, c2, sb + BAR_RFULL + 8 * r.slot, pol);
          else tma3d(sb + r.slot * RING_BYTES, m, 0, c1, c2, sb + BAR_RFULL + 8 * r.slot);
        }
        r.next();
      };
      auto pf_tile = [&](const __nv_bfloat16* p) {
        if (PF_LSU) {
#pragma unroll
          for (int i = 0; i < 4; i++) asm volatile("prefetch.global.L2 [%0];" ::"l"(p + (i * 32 + lane) * 64) : "memory");
        } else if (lane == 0) l2_prefetch(p, 16384, pol);
      };
      uint32_t gph = 0;
      const int rot = ROT * (blockIdx.x * 5 + (blockIdx.x >> 4));
      for (int u = cl; u < NUNITS; u += ncl) {
        const int h = unit_head(u, rank);
        const int krow = (unit_batch(u) * NH + h) * SK;
#pragma unroll 1
        for (int s = 0; s < 10; s++) {
          load(&tm_wq, s * 64, 2 * h, false);
          const int sp = u == cl ? s - PF_HOLD : s;
          if (sp >= 0 && sp < PF_N) {
            const size_t off = (size_t)(krow + ((PF_J0 + sp * PF_STEP + rot) & 15) * 64) * DH;
            if (PF_WHAT & 1) pf_tile(P.k + off);
            if (PF_WHAT & 2) pf_tile(P.v + off);
          }
          if (PF_FIRST && s >= PF_FIRST && s < PF_FIRST + 3) {
            const int f = s - PF_FIRST;
            pf_tile((f == 2 ? P.v : P.k) + (size_t)(krow + (((f & 1) + rot) & 15) * 64) * DH);
          }
        }
        if (GATE) mbar_wait(sb + BAR_GATE, gph), gph ^= 1;
#pragma unroll 1
        for (int j = 0; j <= 16; j++) {
          if (j < 16) load(&tm_k, krow + ((j + rot) & 15) * 64, 0, true);
          if (j > 0) load(&tm_v, krow + ((j - 1 + rot) & 15) * 64, 0, true);
          if ((XW_PF & 2) && j == 11 && u + ncl < NUNITS && lane == 0) prefetch_proj(u + ncl);
        }
      }
      for (int t = cl; t < NOTILES; t += ncl) {
        const int row0 = (t >> 2) * 256 + rank * 128;
        const int b0 = row0 / SQ, b1 = (row0 + 127) / SQ;
#pragma unroll 1
        for (int ks = 0; ks < 64; ks++) {
          if (ks == 0 || ks == 48) {
            const unsigned* c = &g_cnt[((lane & 1 ? b1 : b0) * 4 + (ks ? 3 : min(lane >> 1, 2))) * 8];
            unsigned v, n = 0;
            do {
              asm volatile("ld.acquire.gpu.global.u32 %0, [%1];" : "=r"(v) : "l"(c) : "memory");
              if (++n > (1u << 26)) __trap();
            } while (v < 16);
            __syncwarp();
            asm volatile("fence.proxy.async.global;" ::: "memory");
          }
          load(&tm_o, bk(ks) * 64, row0 >> 6, O_EF);
          if (B_PF && ks + B_PF < 48 && (ks & 3) == (t & 3) && lane == 0) tma3d_prefetch(&tm_o, 0, bk(ks + B_PF) * 64, row0 >> 6);
        }
      }
      if (lane == 0 && atomicAdd(&g_cnt[512], 1) == gridDim.x - 1) {
        for (int i = 0; i <= 64; i++) g_cnt[i * 8] = 0;
      }
    } else if (warp == 9) {
      if (lane == 0) {
        uint32_t it = 0;
        for (int u = cl; u < NUNITS; u += ncl, it++) {
          const int row = unit_batch(u) * SQ + rank * 120;
#pragma unroll 1
          for (int s = 0; s < 10; s++) {
            const uint32_t j = s & 3, par = ((s >> 2) + (j < 2 ? it : 0)) & 1;
            mbar_wait(sb + BAR_XEMPTY + 8 * j, par ^ 1);
            const uint32_t fb = sb + BAR_XFULL + 32 * rank + 8 * j;
            mbar_expect(fb, XB);
            mbar_expect_cl(mapa(fb, rank ^ 1), XB);
            tma2d_mc(sb + OFF_Q + rank * 2 * XB + x_slot(j), &tm_x, s * 64, row, fb);
            if (GATE && s == GATE) mbar_arrive(sb + BAR_GATE);
            if (X_PF && s < 2) {
#pragma unroll
              for (int i = 0; i < 3; i++)
                asm volatile("cp.async.bulk.prefetch.tensor.2d.L2.global [%0, {%1, %2}];" ::"l"(&tm_x), "r"((4 + 3 * s + i) * 64), "r"(row) : "memory");
            }
          }
        }
        uint32_t slot = rank, phase = 0;
        for (int t = cl; t < NOTILES; t += ncl) {
#pragma unroll 1
          for (int ks = rank; ks < 64; ks += 2) {
            mbar_wait(sb + BAR_BEMPTY + 8 * slot, phase);
            const uint32_t fb = sb + BAR_BFULL + 8 * slot;
            mbar_expect(fb, BB);
            mbar_expect_cl(mapa(fb, rank ^ 1), BB);
            tma3d_mc(sb + OFF_Q + slot * BB, &tm_wo, 0, bk(ks) * 64, (t & 3) * 5, fb);
            if (WO_PF && ks + WO_PF < 64 && ((ks >> 1) & 3) == ((t >> 2) & 3)) tma3d_prefetch(&tm_wo, 0, bk(ks + WO_PF) * 64, (t & 3) * 5);
            slot += 2;
            if (slot >= 6) { slot -= 6; phase ^= 1; }
          }
        }
      }
    } else {
      const int wg = warp - 10;
      if (lane == 0) {
        uint32_t it = 0;
        for (int u = cl; u < NUNITS; u += ncl, it++) {
          mbar_wait(sb + BAR_STAGE + 8 * wg, it & 1);
          __threadfence();
          asm volatile("red.relaxed.gpu.global.add.u32 [%0], 1;" ::"l"(&g_cnt[(unit_batch(u) * 4 + (u >> 6)) * 8]) : "memory");
        }
      }
    }
  } else {
    asm volatile("setmaxnreg.inc.sync.aligned.u32 240;");
    const int wg = warp >> 2, w = warp & 3;
    const uint32_t qreg = sb + OFF_Q + wg * 2 * XB, preg = qreg + 4 * XB;
    const uint32_t st_off = ((lane >> 4) * 8 + (lane & 7)) * 128 + (((2 * w + ((lane >> 3) & 1)) ^ (lane & 7)) << 4);
    const uint32_t xempty = mapa(sb + BAR_XEMPTY, wg);
    const int bar_id = 1 + wg;
    Ring r;
    uint32_t it = 0;
    const uint32_t qd = (qreg & 0x3FFFF) >> 4, pd = qd + (4 * XB >> 4);
    auto ring_addr = [&]() { return ((sb & 0x3FFFF) + r.slot * RING_BYTES) >> 4; };
    auto ring_wait = [&]() { mbar_wait(sb + BAR_RFULL + 8 * r.slot, r.phase); };
    auto release = [&](uint32_t slot) { if (lane == 0) mbar_arrive(sb + BAR_REMPTY + 8 * slot); };
    auto turn_wait = [&]() { asm volatile("bar.sync %0, 256;" ::"r"(3 + wg) : "memory"); };
    auto turn_pass = [&]() { asm volatile("bar.arrive %0, 256;" ::"r"(4 - wg) : "memory"); };

    bool bad = false;
    uint32_t chk = 0;
    auto sum_l = [&]() {
      bar_sync(bar_id);
      const uint32_t a = preg + (lane & 3) * 480 + min(8 * w + (lane >> 2), 29) * 16;
      float a0 = 0.f, a1 = 0.f, a2 = 0.f, a3 = 0.f;
#pragma unroll
      for (int g = 0; g < 8; g++) {
        float v0, v1, v2, v3;
        asm volatile("ld.shared.v4.f32 {%0, %1, %2, %3}, [%4];" : "=f"(v0), "=f"(v1), "=f"(v2), "=f"(v3) : "r"(a + g * 1920) : "memory");
        a0 += v0; a1 += v1; a2 += v2; a3 += v3;
      }
      const bool hi = lane & 2, od = lane & 1;
      const float b0 = (hi ? a2 : a0) + __shfl_xor_sync(~0u, hi ? a0 : a2, 2), b1 = (hi ? a3 : a1) + __shfl_xor_sync(~0u, hi ? a1 : a3, 2);
      const float lsum = (od ? b1 : b0) + __shfl_xor_sync(~0u, od ? b0 : b1, 1);
      bad = !(lsum >= L_MIN && lsum <= L_MAX);
      chk = 0;
      float inv;
      asm("rcp.approx.ftz.f32 %0, %1;" : "=f"(inv) : "f"(lsum));
      const uint32_t hl = pack(inv, 0.f), lo = pack(inv - __uint_as_float(hl << 16), 0.f);
      const uint32_t ia = sb + OFF_INV + wg * 512 + ((32 * w + lane) >> 1) * 8 + (lane & 1) * 2;
      asm volatile("st.shared.u16 [%0], %1;\nst.shared.u16 [%0 + 4], %2;" ::"r"(ia), "h"((uint16_t)hl), "h"((uint16_t)lo) : "memory");
      fence_async_smem();
      __syncwarp();
    };
    auto load_inv = [&](uint32_t (&iv)[30]) {
      bar_sync(bar_id);
#pragma unroll
      for (int j = 0; j < 15; j++)
        asm volatile("ld.shared.v2.u32 {%0, %1}, [%2];" : "=r"(iv[2 * j]), "=r"(iv[2 * j + 1]) : "r"(sb + OFF_INV + wg * 512 + j * 32 + (lane & 3) * 8) : "memory");
    };
    auto put = [&](const uint32_t (&po)[60], const uint32_t (&iv)[30], const char* optr, auto part) {
      constexpr int k = decltype(part)::value >> 1, j0 = (decltype(part)::value & 1) * 8;
      const char* o = optr + (size_t)(8 * (k & 1) + 64 * (k >> 1)) * NROWS * 2;
      uint32_t n[8];
#pragma unroll
      for (int j = 0; j < 8; j++)
        n[j] = j0 + j < 15 ? hfma2(po[15 * k + (j0 + j) % 15], iv[2 * ((j0 + j) % 15)], hfma2(po[15 * k + (j0 + j) % 15], iv[2 * ((j0 + j) % 15) + 1], 0x80008000u)) : 0x3F803F80u;
#pragma unroll
      for (int j = 0; j < 8; j += 2) chk = hfma2(n[j], n[j + 1], chk);
      if (j0 == 0)
        asm volatile(
            "{\n.reg .pred p;\nsetp.ne.u64 p, %9, 0;\n"
            "@p st.global.v4.u32 [%8], {%0, %1, %2, %3};\n@p st.global.v4.u32 [%8 + 64], {%4, %5, %6, %7};\n}\n"
            ::"r"(n[0]), "r"(n[1]), "r"(n[2]), "r"(n[3]), "r"(n[4]), "r"(n[5]), "r"(n[6]), "r"(n[7]),
            "l"(o + (wg ? 288 : 0) + (lane & 3) * 16), "l"(optr) : "memory");
      else
        asm volatile(
            "{\n.reg .pred p;\nsetp.ne.u64 p, %10, 0;\n"
            "@p st.global.v4.u32 [%7 + 128], {%0, %1, %2, %3};\n@p st.global.v2.u32 [%8], {%4, %5};\n@p st.global.u32 [%9], %6;\n}\n"
            ::"r"(n[0]), "r"(n[1]), "r"(n[2]), "r"(n[3]), "r"(n[4]), "r"(n[5]), "r"(n[6]), "l"(o + (wg ? 288 : 0) + (lane & 3) * 16),
            "l"(o + (wg ? 256 : 192) + (lane & 3) * 8), "l"(o + (wg ? 240 : 224) + (lane & 3) * 4), "l"(optr) : "memory");
    };
    auto out_ptr = [&](int u) {
      return reinterpret_cast<const char*>(g_o + (size_t)(unit_head(u, rank) * DH + 16 * w + (lane >> 2)) * NROWS + unit_batch(u) * SQ);
    };
    auto unsafe = [&](bool valid) {
      const bool b = valid && (bad || (chk & 0x7F80u) == 0x7F80u || (chk & 0x7F800000u) == 0x7F800000u);
      return __any_sync(~0u, bar_red_or(bar_id, b));
    };
    auto publish = [&]() { __syncwarp(); if (lane == 0) mbar_arrive(sb + BAR_STAGE + 8 * wg); };

    uint32_t po[60];
#pragma unroll
    for (int i = 0; i < 60; i++) po[i] = 0;
    const uint32_t nit = __shfl_sync(~0u, (NUNITS - cl + ncl - 1) / ncl, 0);
    for (; it < nit; it++) {
      const int up = cl + ((int)it - 1) * ncl;
      float o0[60], o1[60];
      uint32_t prev = 0;
      auto qstep = [&](int s, int acc) {
        const uint32_t j = s & 3, par = ((s >> 2) + (j < 2 ? it : 0)) & 1;
        TR(it * 160 + 3 * s);
        ring_wait();
        TR(it * 160 + 3 * s + 1);
        mbar_wait(sb + BAR_XFULL + 32 * wg + 8 * j, par);
        TR(it * 160 + 3 * s + 2);
        wg_fence();
        mma_tn(o0, o1, ring_addr(), qd + (x_slot(j) >> 4), acc);
        wg_commit();
        if (s == 8 && wg == 1) turn_pass();
        if (s > 0) {
          wg_wait<1>();
          release(prev);
          if (s <= 6 && lane == 0) mbar_arrive_cl(xempty + 8 * ((s - 1) & 3));
        }
        prev = r.slot;
        r.next();
      };
      {
        const char* optr = it > 0 ? out_ptr(up) : nullptr;
        uint32_t iv[30];
        qstep(0, 0);
        if (it > 0) {
          sum_l();
          if (lane == 0) mbar_arrive_cl(xempty + 24);
        }
        qstep(1, 1); load_inv(iv); put(po, iv, optr, IC<0>());
        qstep(2, 1); put(po, iv, optr, IC<1>());
        qstep(3, 1); put(po, iv, optr, IC<2>());
        qstep(4, 1); put(po, iv, optr, IC<3>());
        qstep(5, 1); put(po, iv, optr, IC<4>());
        qstep(6, 1); put(po, iv, optr, IC<5>());
        qstep(7, 1); put(po, iv, optr, IC<6>());
        qstep(8, 1); put(po, iv, optr, IC<7>());
      }
      TR(it * 160 + 27);
      ring_wait();
      TR(it * 160 + 28);
      mbar_wait(sb + BAR_XFULL + 32 * wg + 8, it & 1);
      TR(it * 160 + 29);
      turn_wait();
      wg_fence();
      mma_tn_split(o0, o1, ring_addr(), qd + (XB >> 4));
      turn_pass();
      wg_wait<2>();
      release(prev);
      wg_wait<1>();
      reg_fence(o0);
      uint32_t pq[30];
#pragma unroll
      for (int j = 0; j < 30; j++) pq[j] = pack(o0[2 * j] * QSCALE, o0[2 * j + 1] * QSCALE);
      wg_wait<0>();
      reg_fence(o1);
      release(r.slot);
      r.next();
      TR(it * 160 + 30);
      bar_sync(bar_id);
#pragma unroll
      for (int j = 0; j < 14; j += 2) stsm4t(qreg + st_off + j * 1024, pq[2 * j], pq[2 * j + 1], pq[2 * j + 2], pq[2 * j + 3]);
      stsm2t(qreg + st_off + 14 * 1024, pq[28], pq[29]);
#pragma unroll
      for (int j = 0; j < 14; j += 2)
        stsm4t(qreg + XB + st_off + j * 1024, pack(o1[4 * j] * QSCALE, o1[4 * j + 1] * QSCALE), pack(o1[4 * j + 2] * QSCALE, o1[4 * j + 3] * QSCALE),
               pack(o1[4 * j + 4] * QSCALE, o1[4 * j + 5] * QSCALE), pack(o1[4 * j + 6] * QSCALE, o1[4 * j + 7] * QSCALE));
      stsm2t(qreg + XB + st_off + 14 * 1024, pack(o1[56] * QSCALE, o1[57] * QSCALE), pack(o1[58] * QSCALE, o1[59] * QSCALE));
      fence_async_smem();
      if (unsafe(it > 0)) {
        slow_path(P, unit_batch(up), unit_head(up, rank), wg, w, lane);
#pragma unroll
        for (int i = 0; i < 60; i++) o0[i] = o1[i] = 0.f;
      }
      TR(it * 160 + 32);

      float sc[60], l[30];
      ring_wait();
      TR(it * 160 + 33);
      turn_wait();
      wg_fence();
      mma_qk(sc, ring_addr(), qd);
      wg_commit();
      turn_pass();
      if (it > 0) publish();
      wg_wait<0>();
      reg_fence(sc);
      TR(it * 160 + 35);
      release(r.slot);
      r.next();
      exp_store<0, 15, true>(sc, l, preg + st_off);
      fence_async_smem();
      bar_sync(bar_id);
      const bool more = it + 1 < nit;
#pragma unroll 1
      for (int s = 1; s < 16; s++) {
        const uint32_t kslot = r.slot;
        TR(it * 160 + 32 + 6 * s);
        ring_wait();
        TR(it * 160 + 33 + 6 * s);
        turn_wait();
        wg_fence();
        mma_qk(sc, ring_addr(), qd);
        wg_commit();
        r.next();
        TR(it * 160 + 36 + 6 * s);
        ring_wait();
        TR(it * 160 + 34 + 6 * s);
        wg_fence();
        mma_tn(o0, o1, ring_addr(), pd + ((s - 1) & 1) * (XB >> 4), s != 1);
        wg_commit();
        if (wg == 0 || s < 15) turn_pass();
        wg_wait<1>();
        reg_fence(sc);
        TR(it * 160 + 35 + 6 * s);
        release(kslot);
        if (s == 15) {
          if (more) { if (lane < 2) mbar_arrive_cl(xempty + 8 * lane); }
          else if (lane < 3 && cl < NOTILES) mbar_arrive_cl(mapa(sb + BAR_BEMPTY + 8 * lane, lane & 1));
        }
        exp_store<0, VREL>(sc, l, preg + (s & 1) * XB + st_off);
        wg_wait<0>();
        reg_fence(o0); reg_fence(o1);
        release(r.slot);
        r.next();
        exp_store<VREL, 15>(sc, l, preg + (s & 1) * XB + st_off);
        fence_async_smem();
        bar_sync(bar_id);
      }
      TR(it * 160 + 128);
      ring_wait();
      wg_fence();
      mma_tn_split(o0, o1, ring_addr(), pd + (XB >> 4));
      TR(it * 160 + 132);
      {
        const uint32_t a = preg + (8 * w + (lane >> 2)) * 480 + (lane & 3) * 8;
#pragma unroll
        for (int j = 0; j < 15; j++) asm volatile("st.shared.v2.f32 [%0], {%1, %2};" ::"r"(a + j * 32), "f"(l[2 * j]), "f"(l[2 * j + 1]) : "memory");
      }
      TR(it * 160 + 133);
      wg_wait<1>();
      reg_fence(o0);
      TR(it * 160 + 134);
#pragma unroll
      for (int j = 0; j < 15; j++) { po[j] = pack(o0[4 * j], o0[4 * j + 1]); po[15 + j] = pack(o0[4 * j + 2], o0[4 * j + 3]); }
      wg_wait<0>();
      reg_fence(o1);
      release(r.slot);
      r.next();
      if (more && lane == 0) mbar_arrive_cl(xempty + 16);
      TR(it * 160 + 130);
#pragma unroll
      for (int j = 0; j < 15; j++) { po[30 + j] = pack(o1[4 * j], o1[4 * j + 1]); po[45 + j] = pack(o1[4 * j + 2], o1[4 * j + 3]); }
      TR(it * 160 + 131);
    }
    const int u = cl + ((int)nit - 1) * ncl;
    uint32_t pb[60];
#pragma unroll
    for (int i = 0; i < 60; i++) pb[i] = po[i] ^ (gridDim.y - 1);

    uint32_t bslot = 0, bphase = 0;
    for (int t = cl; t < NOTILES || t == cl; t += ncl) {
      float acc[80];
      uint32_t prev = 0, bprev = 0;
      const bool tile = t < NOTILES;
      const bool last = t + ncl >= NOTILES;
      auto bstep = [&](int ks, int accf) {
        TR(640 + 2 * ks);
        ring_wait();
        mbar_wait(sb + BAR_BFULL + 8 * bslot, bphase);
        TR(641 + 2 * ks);
        wg_fence();
        const uint32_t a = ring_addr() + wg * 512, bd = (((sb & 0x3FFFF) + OFF_Q + bslot * BB) >> 4) | ((4096u >> 4) << 16);
#pragma unroll
        for (int k = 0; k < 4; k++) wgmma_n160<1, 1>(acc, a + k * 128, HI128, bd + k * 64, HI64, k == 0 ? accf : 1);
        wg_commit();
        if (ks > 0) {
          wg_wait<1>();
          release(prev);
          if (lane == 0 && (ks < 59 || !last)) mbar_arrive_cl(mapa(sb + BAR_BEMPTY + 8 * bprev, bprev & 1));
        }
        prev = r.slot; bprev = bslot;
        r.next();
        if (++bslot == 6) { bslot = 0; bphase ^= 1; }
      };
      const char* optr = t == cl ? out_ptr(u) : nullptr;
      uint32_t iv[30];
      if (tile) {
        bstep(0, 0);
        if (t == cl) {
          sum_l();
          if (lane < 3) mbar_arrive_cl(mapa(sb + BAR_BEMPTY + 24 + 8 * lane, (lane + 1) & 1));
        }
        bstep(1, 1); load_inv(iv);
        bstep(2, 1); put(pb, iv, optr, IC<0>()); bstep(3, 1);
        bstep(4, 1); put(pb, iv, optr, IC<1>()); bstep(5, 1);
        bstep(6, 1); put(pb, iv, optr, IC<2>()); bstep(7, 1);
        bstep(8, 1); put(pb, iv, optr, IC<3>()); bstep(9, 1);
        bstep(10, 1); put(pb, iv, optr, IC<4>()); bstep(11, 1);
        bstep(12, 1); put(pb, iv, optr, IC<5>()); bstep(13, 1);
        bstep(14, 1); put(pb, iv, optr, IC<6>()); bstep(15, 1);
        bstep(16, 1); put(pb, iv, optr, IC<7>());
        wg_wait<0>();
        reg_fence(acc);
      } else {
#pragma unroll
        for (int i = 0; i < 80; i++) acc[i] = 0.f;
        sum_l();
        load_inv(iv);
        put(pb, iv, optr, IC<0>()); put(pb, iv, optr, IC<1>()); put(pb, iv, optr, IC<2>()); put(pb, iv, optr, IC<3>());
        put(pb, iv, optr, IC<4>()); put(pb, iv, optr, IC<5>()); put(pb, iv, optr, IC<6>()); put(pb, iv, optr, IC<7>());
      }
      if (unsafe(t == cl)) slow_path(P, unit_batch(u), unit_head(u, rank), wg, w, lane);
      if (t == cl) publish();
      if (!tile) break;
#pragma unroll 1
      for (int ks = 17; ks < 64; ks++) bstep(ks, 1);
      wg_wait<0>();
      reg_fence(acc);
      release(prev);
      if (lane == 0 && !last) mbar_arrive_cl(mapa(sb + BAR_BEMPTY + 8 * bprev, bprev & 1));
      TR(158);
      const int pos0 = (t >> 2) * 256 + rank * 128 + wg * 64 + w * 16;
      if (last) {
        bar_sync(bar_id);
        const uint32_t st = sb + w * RING_BYTES + wg * 8192;
        const uint32_t sa = st + (lane & 15) * 336 + (lane >> 4) * 16;
#pragma unroll
        for (int j = 0; j < 20; j += 2)
          asm volatile("stmatrix.sync.aligned.m8n8.x4.shared.b16 [%0], {%1,%2,%3,%4};" ::"r"(sa + j * 16), "r"(pack(acc[4 * j], acc[4 * j + 1])),
                       "r"(pack(acc[4 * j + 2], acc[4 * j + 3])), "r"(pack(acc[4 * j + 4], acc[4 * j + 5])), "r"(pack(acc[4 * j + 6], acc[4 * j + 7])) : "memory");
        fence_async_smem();
        __syncwarp();
        if (lane < 16) {
          __nv_bfloat16* dst = P.out + (size_t)o_row(pos0 + lane) * DM + (t & 3) * 160;
          asm volatile("cp.async.bulk.global.shared::cta.bulk_group [%0], [%1], 320;" ::"l"(dst), "r"(st + lane * 336) : "memory");
          asm volatile("cp.async.bulk.commit_group;" ::: "memory");
          asm volatile("cp.async.bulk.wait_group.read 0;" ::: "memory");
        }
      } else {
        __nv_bfloat16* op0 = P.out + (size_t)o_row(pos0 + (lane >> 2)) * DM + (t & 3) * 160 + (lane & 3) * 2;
        __nv_bfloat16* op1 = P.out + (size_t)o_row(pos0 + (lane >> 2) + 8) * DM + (t & 3) * 160 + (lane & 3) * 2;
#pragma unroll
        for (int j = 0; j < 20; j++) {
          *reinterpret_cast<uint32_t*>(op0 + j * 8) = pack(acc[4 * j], acc[4 * j + 1]);
          *reinterpret_cast<uint32_t*>(op1 + j * 8) = pack(acc[4 * j + 2], acc[4 * j + 3]);
        }
      }
#pragma unroll
      for (int i = 0; i < 60; i++) pb[i] = 0;
    }
    TR(159);
  }
}

typedef CUresult (*EncodeFn)(CUtensorMap*, CUtensorMapDataType, cuuint32_t, void*, const cuuint64_t*, const cuuint64_t*,
                             const cuuint32_t*, const cuuint32_t*, CUtensorMapInterleave, CUtensorMapSwizzle,
                             CUtensorMapL2promotion, CUtensorMapFloatOOBfill);

void make_map(EncodeFn enc, CUtensorMap* m, const void* p, int rank, const cuuint64_t* dims, const cuuint64_t* strides,
              const cuuint32_t* box, CUtensorMapSwizzle sw, CUtensorMapL2promotion promo) {
  cuuint32_t es[3] = {1, 1, 1};
  enc(m, CU_TENSOR_MAP_DATA_TYPE_BFLOAT16, rank, const_cast<void*>(p), dims, strides, box, es, CU_TENSOR_MAP_INTERLEAVE_NONE, sw,
      promo, CU_TENSOR_MAP_FLOAT_OOB_FILL_NONE);
}

}

extern "C" void kernel_launch(void* const* d_in, const int* in_sizes, int n_in, void* d_out, int out_size) {
  static EncodeFn enc = nullptr;
  static int nclusters = 0;
  static void* o_ptr = nullptr;
  if (!enc) {
    cudaDriverEntryPointQueryResult qr;
    cudaGetDriverEntryPoint("cuTensorMapEncodeTiled", (void**)&enc, cudaEnableDefault, &qr);
    cudaFuncSetAttribute(fused_attn_kernel, cudaFuncAttributeMaxDynamicSharedMemorySize, SMEM_BYTES);
    cudaGetSymbolAddress(&o_ptr, g_o);
    cudaLaunchConfig_t cfg = {};
    cfg.gridDim = 128; cfg.blockDim = 384; cfg.dynamicSmemBytes = SMEM_BYTES;
    cudaLaunchAttribute at; at.id = cudaLaunchAttributeClusterDimension;
    at.val.clusterDim.x = 2; at.val.clusterDim.y = 1; at.val.clusterDim.z = 1;
    cfg.attrs = &at; cfg.numAttrs = 1;
    int n = 0;
    cudaOccupancyMaxActiveClusters(&n, fused_attn_kernel, &cfg);
    nclusters = n >= 64 || n <= 0 ? 64 : n;
  }
  const __nv_bfloat16* x = (const __nv_bfloat16*)d_in[0];
  const __nv_bfloat16* k = (const __nv_bfloat16*)d_in[1];
  const __nv_bfloat16* v = (const __nv_bfloat16*)d_in[2];
  const __nv_bfloat16* wq = (const __nv_bfloat16*)d_in[3];
  const __nv_bfloat16* wo = (const __nv_bfloat16*)d_in[4];
  CUtensorMap tm_x, tm_wq, tm_k, tm_v, tm_o, tm_wo;
  const auto S128 = CU_TENSOR_MAP_SWIZZLE_128B;
  const auto P128 = CU_TENSOR_MAP_L2_PROMOTION_L2_128B, P256 = CU_TENSOR_MAP_L2_PROMOTION_L2_256B;
  { cuuint64_t d[2] = {DM, NB * SQ}, s[1] = {DM * 2}; cuuint32_t b[2] = {64, 120}; make_map(enc, &tm_x, x, 2, d, s, b, S128, P128); }
  { cuuint64_t d[3] = {64, DM, HD / 64}, s[2] = {HD * 2, 128}; cuuint32_t b[3] = {64, 64, 2}; make_map(enc, &tm_wq, wq, 3, d, s, b, S128, P256); }
  { cuuint64_t d[3] = {64, NB * NH * SK, 2}, s[2] = {DH * 2, 128}; cuuint32_t b[3] = {64, 64, 2};
    make_map(enc, &tm_k, k, 3, d, s, b, S128, KV_PROMO); make_map(enc, &tm_v, v, 3, d, s, b, S128, KV_PROMO); }
  { cuuint64_t d[3] = {64, HD, NROWS / 64}, s[2] = {NROWS * 2, 128}; cuuint32_t b[3] = {64, 64, 2}; make_map(enc, &tm_o, o_ptr, 3, d, s, b, S128, P256); }
  { cuuint64_t d[3] = {32, HD, DM / 32}, s[2] = {DM * 2, 64}; cuuint32_t b[3] = {32, 64, 5};
    make_map(enc, &tm_wo, wo, 3, d, s, b, CU_TENSOR_MAP_SWIZZLE_64B, P128); }
  Params P{x, k, v, wq, (__nv_bfloat16*)d_out};
  fused_attn_kernel<<<2 * nclusters, 384, SMEM_BYTES>>>(tm_x, tm_wq, tm_k, tm_v, tm_o, tm_wo, P);
}
```

```cpp
#include <cuda_runtime.h>
#include <cuda.h>
#include <cuda_bf16.h>
#include <stdint.h>

namespace {

constexpr int NB = 16, SQ = 240, DM = 640, NH = 32, SK = 1024, DH = 128, HD = NH * DH;
constexpr int NROWS = NB * SQ;
constexpr int NUNITS = 256;
#define WAITV 0
#define XW_PF 0
#define B_PF 0
#define WO_PF 0
#define B_ORDER 1
#define TAIL_ORDER 2
#define PF_LSU 0
#define PF_FIRST 0
#define GATE 0
#define X_PF 0
#define HEAD 3
#define SPLIT_STEP 3
#define TAIL_V 1
#define HDEPTH 4
#define INV_AT 2
#define ALT_FROM 3
#define START_PF 1
#define MERGE89 1
#define END_SKEW 5
#define EPI_STG 0
#define TM_PF 1
#define KV_PROMO P128
#define PF_POL 0
#define NOT 60
#define O_EF 1
#define PF_HOLD 6
#define VREL 8
#define PP_MODE 1
#define PF_N 4
#define PF_J0 3
#define PF_STEP 3
#define PF_WHAT 2
#define ROT 1
constexpr int NOTILES = NOT;
constexpr float QSCALE = 0.08838834764831845f * 1.4426950408889634f;
constexpr float L_MIN = 9.5367431640625e-07f;
constexpr float L_MAX = 1.152921504606846976e18f;

constexpr uint32_t RING_SLOTS = 6, RING_BYTES = 16384;
constexpr uint32_t XB = 15360;
constexpr uint32_t BB = 20480;
constexpr uint32_t OFF_Q = RING_SLOTS * RING_BYTES;
constexpr uint32_t OFF_P = OFF_Q + 4 * XB;
constexpr uint32_t OFF_INV = OFF_P + 4 * XB;
constexpr uint32_t OFF_BAR = OFF_INV + 1024;
constexpr uint32_t BAR_RFULL = OFF_BAR, BAR_REMPTY = BAR_RFULL + 48, BAR_XFULL = BAR_REMPTY + 48,
    BAR_XEMPTY = BAR_XFULL + 64, BAR_BFULL = BAR_XEMPTY + 32, BAR_BEMPTY = BAR_BFULL + 48, BAR_STAGE = BAR_BEMPTY + 48;
constexpr uint32_t BAR_GATE = BAR_STAGE + 16, BAR_LSUM = BAR_GATE + 16, BAR_INV = BAR_LSUM + 16;
constexpr uint32_t OFF_TR = BAR_INV + 16;
constexpr uint32_t SMEM_BYTES = OFF_TR + 1024;

constexpr uint32_t HI128 = (1u << 30) | (1024 >> 4);
constexpr uint32_t HI64 = (2u << 30) | (512 >> 4);

__device__ __nv_bfloat16 g_o[HD * NROWS];
__device__ unsigned g_cnt[64 * 8 + 8];
#define TR(i)

struct Params {
  const __nv_bfloat16 *x, *k, *v, *wq;
  __nv_bfloat16 *out, *o;
};

__device__ __forceinline__ void wg_fence() { asm volatile("wgmma.fence.sync.aligned;" ::: "memory"); }
__device__ __forceinline__ void wg_commit() { asm volatile("wgmma.commit_group.sync.aligned;" ::: "memory"); }
template <int N> __device__ __forceinline__ void wg_wait() { asm volatile("wgmma.wait_group.sync.aligned %0;" ::"n"(N) : "memory"); }
template <int N> __device__ __forceinline__ void reg_fence(float (&r)[N]) {
#pragma unroll
  for (int i = 0; i < N; i++) asm volatile("" : "+f"(r[i])::"memory");
}
template <int TA, int TB>
__device__ __forceinline__ void wgmma_n120(float (&d)[60], uint32_t a_lo, uint32_t a_hi, uint32_t b_lo, uint32_t b_hi, int acc) {
  asm volatile(
      "{\n.reg .pred p;\n.reg .b64 da, db;\nsetp.ne.b32 p, %64, 0;\n"
      "mov.b64 da, {%60, %61};\nmov.b64 db, {%62, %63};\n"
      "wgmma.mma_async.sync.aligned.m64n120k16.f32.bf16.bf16 {"
      "%0, %1, %2, %3, %4, %5, %6, %7, %8, %9, %10, %11, %12, %13, %14, %15, %16, %17, %18, %19, %20, %21, %22, %23, "
      "%24, %25, %26, %27, %28, %29, %30, %31, %32, %33, %34, %35, %36, %37, %38, %39, %40, %41, %42, %43, %44, %45, "
      "%46, %47, %48, %49, %50, %51, %52, %53, %54, %55, %56, %57, %58, %59"
      "}, da, db, p, 1, 1, %65, %66;\n}\n"
      : "+f"(d[0]), "+f"(d[1]), "+f"(d[2]), "+f"(d[3]), "+f"(d[4]), "+f"(d[5]), "+f"(d[6]), "+f"(d[7]), "+f"(d[8]),
        "+f"(d[9]), "+f"(d[10]), "+f"(d[11]), "+f"(d[12]), "+f"(d[13]), "+f"(d[14]), "+f"(d[15]), "+f"(d[16]),
        "+f"(d[17]), "+f"(d[18]), "+f"(d[19]), "+f"(d[20]), "+f"(d[21]), "+f"(d[22]), "+f"(d[23]), "+f"(d[24]),
        "+f"(d[25]), "+f"(d[26]), "+f"(d[27]), "+f"(d[28]), "+f"(d[29]), "+f"(d[30]), "+f"(d[31]), "+f"(d[32]),
        "+f"(d[33]), "+f"(d[34]), "+f"(d[35]), "+f"(d[36]), "+f"(d[37]), "+f"(d[38]), "+f"(d[39]), "+f"(d[40]),
        "+f"(d[41]), "+f"(d[42]), "+f"(d[43]), "+f"(d[44]), "+f"(d[45]), "+f"(d[46]), "+f"(d[47]), "+f"(d[48]),
        "+f"(d[49]), "+f"(d[50]), "+f"(d[51]), "+f"(d[52]), "+f"(d[53]), "+f"(d[54]), "+f"(d[55]), "+f"(d[56]),
        "+f"(d[57]), "+f"(d[58]), "+f"(d[59])
      : "r"(a_lo), "r"(a_hi), "r"(b_lo), "r"(b_hi), "r"(acc), "n"(TA), "n"(TB));
}

template <int TA, int TB>
__device__ __forceinline__ void wgmma_n160(float (&d)[80], uint32_t a_lo, uint32_t a_hi, uint32_t b_lo, uint32_t b_hi, int acc) {
  asm volatile(
      "{\n.reg .pred p;\n.reg .b64 da, db;\nsetp.ne.b32 p, %84, 0;\n"
      "mov.b64 da, {%80, %81};\nmov.b64 db, {%82, %83};\n"
      "wgmma.mma_async.sync.aligned.m64n160k16.f32.bf16.bf16 {"
      "%0, %1, %2, %3, %4, %5, %6, %7, %8, %9, %10, %11, %12, %13, %14, %15, %16, %17, %18, %19, %20, %21, %22, %23, "
      "%24, %25, %26, %27, %28, %29, %30, %31, %32, %33, %34, %35, %36, %37, %38, %39, %40, %41, %42, %43, %44, %45, "
      "%46, %47, %48, %49, %50, %51, %52, %53, %54, %55, %56, %57, %58, %59, %60, %61, %62, %63, %64, %65, %66, %67, "
      "%68, %69, %70, %71, %72, %73, %74, %75, %76, %77, %78, %79"
      "}, da, db, p, 1, 1, %85, %86;\n}\n"
      : "+f"(d[0]), "+f"(d[1]), "+f"(d[2]), "+f"(d[3]), "+f"(d[4]), "+f"(d[5]), "+f"(d[6]), "+f"(d[7]), "+f"(d[8]),
        "+f"(d[9]), "+f"(d[10]), "+f"(d[11]), "+f"(d[12]), "+f"(d[13]), "+f"(d[14]), "+f"(d[15]), "+f"(d[16]),
        "+f"(d[17]), "+f"(d[18]), "+f"(d[19]), "+f"(d[20]), "+f"(d[21]), "+f"(d[22]), "+f"(d[23]), "+f"(d[24]),
        "+f"(d[25]), "+f"(d[26]), "+f"(d[27]), "+f"(d[28]), "+f"(d[29]), "+f"(d[30]), "+f"(d[31]), "+f"(d[32]),
        "+f"(d[33]), "+f"(d[34]), "+f"(d[35]), "+f"(d[36]), "+f"(d[37]), "+f"(d[38]), "+f"(d[39]), "+f"(d[40]),
        "+f"(d[41]), "+f"(d[42]), "+f"(d[43]), "+f"(d[44]), "+f"(d[45]), "+f"(d[46]), "+f"(d[47]), "+f"(d[48]),
        "+f"(d[49]), "+f"(d[50]), "+f"(d[51]), "+f"(d[52]), "+f"(d[53]), "+f"(d[54]), "+f"(d[55]), "+f"(d[56]),
        "+f"(d[57]), "+f"(d[58]), "+f"(d[59]), "+f"(d[60]), "+f"(d[61]), "+f"(d[62]), "+f"(d[63]), "+f"(d[64]),
        "+f"(d[65]), "+f"(d[66]), "+f"(d[67]), "+f"(d[68]), "+f"(d[69]), "+f"(d[70]), "+f"(d[71]), "+f"(d[72]),
        "+f"(d[73]), "+f"(d[74]), "+f"(d[75]), "+f"(d[76]), "+f"(d[77]), "+f"(d[78]), "+f"(d[79])
      : "r"(a_lo), "r"(a_hi), "r"(b_lo), "r"(b_hi), "r"(acc), "n"(TA), "n"(TB));
}
__device__ __forceinline__ void mbar_init(uint32_t bar, int cnt) { asm volatile("mbarrier.init.shared::cta.b64 [%0], %1;" ::"r"(bar), "r"(cnt)); }
__device__ __forceinline__ void mbar_expect(uint32_t bar, uint32_t bytes) {
  asm volatile("mbarrier.arrive.expect_tx.shared::cta.b64 _, [%0], %1;" ::"r"(bar), "r"(bytes) : "memory");
}
__device__ __forceinline__ uint32_t mapa(uint32_t addr, uint32_t cta) {
  uint32_t r; asm("mapa.shared::cluster.u32 %0, %1, %2;" : "=r"(r) : "r"(addr), "r"(cta)); return r;
}
__device__ __forceinline__ void mbar_expect_cl(uint32_t cbar, uint32_t bytes) {
  asm volatile("mbarrier.arrive.expect_tx.shared::cluster.b64 _, [%0], %1;" ::"r"(cbar), "r"(bytes) : "memory");
}
__device__ __forceinline__ void mbar_arrive(uint32_t bar) { asm volatile("mbarrier.arrive.shared::cta.b64 _, [%0];" ::"r"(bar) : "memory"); }
__device__ __forceinline__ void mbar_arrive_cl(uint32_t cbar) { asm volatile("mbarrier.arrive.shared::cluster.b64 _, [%0];" ::"r"(cbar) : "memory"); }
__device__ __forceinline__ void mbar_wait(uint32_t bar, uint32_t parity) {
  asm volatile(
      "{\n.reg .pred p;\n.reg .u32 n;\n"
      "mbarrier.try_wait.parity.shared::cta.b64 p, [%0], %1;\n@p bra WAIT_DONE;\n"
      "mov.u32 n, 0;\n"
      "WAIT_LOOP:\n"
      "mbarrier.try_wait.parity.shared::cta.b64 p, [%0], %1;\n@p bra WAIT_DONE;\n"
      "add.u32 n, n, 1;\nsetp.lt.u32 p, n, 0x4000000;\n@p bra WAIT_LOOP;\ntrap;\n"
      "WAIT_DONE:\n}\n" ::"r"(bar), "r"(parity) : "memory");
}
__device__ __forceinline__ void tma3d(uint32_t dst, const CUtensorMap* m, int c0, int c1, int c2, uint32_t bar) {
  asm volatile("cp.async.bulk.tensor.3d.shared::cluster.global.mbarrier::complete_tx::bytes [%0], [%1, {%3, %4, %5}], [%2];"
               ::"r"(dst), "l"(m), "r"(bar), "r"(c0), "r"(c1), "r"(c2) : "memory");
}
__device__ __forceinline__ void tma3d_hint(uint32_t dst, const CUtensorMap* m, int c0, int c1, int c2, uint32_t bar, uint64_t pol) {
  asm volatile("cp.async.bulk.tensor.3d.shared::cluster.global.mbarrier::complete_tx::bytes.L2::cache_hint [%0], [%1, {%3, %4, %5}], [%2], %6;"
               ::"r"(dst), "l"(m), "r"(bar), "r"(c0), "r"(c1), "r"(c2), "l"(pol) : "memory");
}
__device__ __forceinline__ void tma2d_mc(uint32_t dst, const CUtensorMap* m, int c0, int c1, uint32_t bar) {
  asm volatile("cp.async.bulk.tensor.2d.shared::cluster.global.mbarrier::complete_tx::bytes.multicast::cluster [%0], [%1, {%3, %4}], [%2], %5;"
               ::"r"(dst), "l"(m), "r"(bar), "r"(c0), "r"(c1), "h"((uint16_t)3) : "memory");
}
__device__ __forceinline__ void tma3d_mc(uint32_t dst, const CUtensorMap* m, int c0, int c1, int c2, uint32_t bar) {
  asm volatile("cp.async.bulk.tensor.3d.shared::cluster.global.mbarrier::complete_tx::bytes.multicast::cluster [%0], [%1, {%3, %4, %5}], [%2], %6;"
               ::"r"(dst), "l"(m), "r"(bar), "r"(c0), "r"(c1), "r"(c2), "h"((uint16_t)3) : "memory");
}
__device__ __forceinline__ void l2_prefetch(const void* p, uint32_t bytes, uint64_t pol) {
  if (PF_POL) asm volatile("cp.async.bulk.prefetch.L2.global.L2::cache_hint [%0], %1, %2;" ::"l"(p), "r"(bytes), "l"(pol) : "memory");
  else asm volatile("cp.async.bulk.prefetch.L2.global [%0], %1;" ::"l"(p), "r"(bytes) : "memory");
}
__device__ __forceinline__ void fence_async_smem() { asm volatile("fence.proxy.async.shared::cta;" ::: "memory"); }
__device__ __forceinline__ void bar_sync(int id) { asm volatile("bar.sync %0, 128;" ::"r"(id) : "memory"); }
__device__ __forceinline__ bool bar_red_or(int id, bool v) {
  uint32_t r;
  asm volatile("{\n.reg .pred p, q;\nsetp.ne.u32 p, %2, 0;\nbar.red.or.pred q, %1, 128, p;\nselp.u32 %0, 1, 0, q;\n}\n"
               : "=r"(r) : "r"(id), "r"((uint32_t)v) : "memory");
  return r != 0;
}
__device__ __forceinline__ void tma3d_prefetch(const CUtensorMap* m, int c0, int c1, int c2) {
  asm volatile("cp.async.bulk.prefetch.tensor.3d.L2.global [%0, {%1, %2, %3}];" ::"l"(m), "r"(c0), "r"(c1), "r"(c2) : "memory");
}
__device__ __forceinline__ uint32_t hfma2(uint32_t a, uint32_t b, uint32_t c) { uint32_t r; asm("fma.rn.bf16x2 %0, %1, %2, %3;" : "=r"(r) : "r"(a), "r"(b), "r"(c)); return r; }
__device__ __forceinline__ float ex2(float x) { float y; asm("ex2.approx.ftz.f32 %0, %1;" : "=f"(y) : "f"(x)); return y; }
__device__ __forceinline__ uint32_t pack(float lo, float hi) { uint32_t r; asm("cvt.rn.bf16x2.f32 %0, %1, %2;" : "=r"(r) : "f"(hi), "f"(lo)); return r; }
__device__ __forceinline__ void stsm4t(uint32_t a, uint32_t r0, uint32_t r1, uint32_t r2, uint32_t r3) {
  asm volatile("stmatrix.sync.aligned.m8n8.x4.trans.shared.b16 [%0], {%1,%2,%3,%4};" ::"r"(a), "r"(r0), "r"(r1), "r"(r2), "r"(r3) : "memory");
}
__device__ __forceinline__ void stsm2t(uint32_t a, uint32_t r0, uint32_t r1) {
  asm volatile("stmatrix.sync.aligned.m8n8.x2.trans.shared.b16 [%0], {%1,%2};" ::"r"(a), "r"(r0), "r"(r1) : "memory");
}
__device__ __forceinline__ void mma16816(float (&d)[4], const uint32_t (&a)[4], uint32_t b0, uint32_t b1) {
  asm volatile("mma.sync.aligned.m16n8k16.row.col.f32.bf16.bf16.f32 {%0,%1,%2,%3}, {%4,%5,%6,%7}, {%8,%9}, {%0,%1,%2,%3};"
               : "+f"(d[0]), "+f"(d[1]), "+f"(d[2]), "+f"(d[3]) : "r"(a[0]), "r"(a[1]), "r"(a[2]), "r"(a[3]), "r"(b0), "r"(b1));
}

template <int V> struct IC { static constexpr int value = V; };

struct Ring {
  uint32_t slot = 0, phase = 0;
  __device__ __forceinline__ void next() { if (++slot == RING_SLOTS) { slot = 0; phase ^= 1; } }
};

__device__ __forceinline__ void mma_tn(float (&o0)[60], float (&o1)[60], uint32_t a, uint32_t b, int acc) {
#pragma unroll
  for (int k = 0; k < 4; k++) {
    wgmma_n120<1, 0>(o0, a + k * 128, HI128, b + k * 2, HI128, k == 0 ? acc : 1);
    wgmma_n120<1, 0>(o1, a + 512 + k * 128, HI128, b + k * 2, HI128, k == 0 ? acc : 1);
  }
}
__device__ __forceinline__ void mma_tn_split(float (&o0)[60], float (&o1)[60], uint32_t a, uint32_t b) {
#pragma unroll
  for (int k = 0; k < 4; k++) wgmma_n120<1, 0>(o0, a + k * 128, HI128, b + k * 2, HI128, 1);
  wg_commit();
#pragma unroll
  for (int k = 0; k < 4; k++) wgmma_n120<1, 0>(o1, a + 512 + k * 128, HI128, b + k * 2, HI128, 1);
  wg_commit();
}
__device__ __forceinline__ void mma_qk(float (&s)[60], uint32_t a, uint32_t q) {
#pragma unroll
  for (int k = 0; k < 8; k++)
    wgmma_n120<0, 0>(s, a + (k >> 2) * 512 + (k & 3) * 2, HI128, q + (k >> 2) * (XB >> 4) + (k & 3) * 2, HI128, k != 0);
}
template <int J0, int J1, bool FIRST = false>
__device__ __forceinline__ void exp_store(const float (&s)[60], float (&l)[30], uint32_t dst) {
#pragma unroll
  for (int j = J0; j < J1; j += 2) {
    uint32_t p[4];
#pragma unroll
    for (int jj = 0; jj < 2; jj++) {
      if (j + jj < 15) {
        const int c = j + jj;
        float e0 = ex2(s[4 * c]), e1 = ex2(s[4 * c + 1]), e2 = ex2(s[4 * c + 2]), e3 = ex2(s[4 * c + 3]);
        if (FIRST) { l[2 * c] = e0 + e2; l[2 * c + 1] = e1 + e3; }
        else { l[2 * c] += e0; l[2 * c + 1] += e1; l[2 * c] += e2; l[2 * c + 1] += e3; }
        p[2 * jj] = pack(e0, e1); p[2 * jj + 1] = pack(e2, e3);
      }
    }
    if (j + 1 < 15) stsm4t(dst + j * 1024, p[0], p[1], p[2], p[3]);
    else stsm2t(dst + j * 1024, p[0], p[1]);
  }
}

__device__ __forceinline__ int o_pos(int wg, int r) {
  const int j = r >> 3, q = (r >> 1) & 3, c = r & 1;
  if (j < 12) return (wg ? 144 : 0) + (j >> 2) * 32 + q * 8 + (j & 3) * 2 + c;
  if (j < 14) return (wg ? 128 : 96) + q * 4 + (j - 12) * 2 + c;
  return (wg ? 120 : 112) + q * 2 + c;
}
__device__ __forceinline__ int o_row(int p) {
  const int b = p / SQ, r = p - b * SQ, wg = r >= 120, c = r & 1;
  const int a = r - (wg ? 144 : 0), m = r - (wg ? 128 : 96), e = r - (wg ? 120 : 112);
  int row;
  if (a >= 0 && a < 96) row = ((a >> 5) * 4 + ((a >> 1) & 3)) * 8 + ((a >> 3) & 3) * 2 + c;
  else if (m >= 0 && m < 16) row = (12 + ((m >> 1) & 1)) * 8 + (m >> 2) * 2 + c;
  else row = 112 + e;
  return b * SQ + wg * 120 + row;
}

__device__ __forceinline__ void slow_path(const Params& P, int b, int h, int wg, int w, int lane) {
  const int g = lane >> 2, q = lane & 3, row0 = wg * 120;
  const uint16_t* wq = reinterpret_cast<const uint16_t*>(P.wq) + h * DH + g;
  const __nv_bfloat16* kp = P.k + (size_t)(b * NH + h) * SK * DH;
  const uint16_t* vp = reinterpret_cast<const uint16_t*>(P.v) + (size_t)(b * NH + h) * SK * DH + g;
#pragma unroll 1
  for (int t = w; t < 8; t += 4) {
    const int r0 = 16 * t + g, r1 = r0 + 8;
    const __nv_bfloat16* x0 = P.x + (size_t)(b * SQ + row0 + r0) * DM + 2 * q;
    const __nv_bfloat16* x1 = P.x + (size_t)(b * SQ + row0 + min(r1, 119)) * DM + 2 * q;
    float o[16][4];
#pragma unroll
    for (int n = 0; n < 16; n++) o[n][0] = o[n][1] = o[n][2] = o[n][3] = 0.f;
#pragma unroll 1
    for (int k0 = 0; k0 < DM; k0 += 16) {
      uint32_t a[4] = {*(const uint32_t*)(x0 + k0), *(const uint32_t*)(x1 + k0), *(const uint32_t*)(x0 + k0 + 8), *(const uint32_t*)(x1 + k0 + 8)};
      const uint16_t* wr = wq + (size_t)(k0 + 2 * q) * HD;
#pragma unroll
      for (int n = 0; n < 16; n++)
        mma16816(o[n], a, wr[8 * n] | ((uint32_t)wr[8 * n + HD] << 16), wr[8 * n + 8 * HD] | ((uint32_t)wr[8 * n + 9 * HD] << 16));
    }
    uint32_t qa[8][4];
#pragma unroll
    for (int k = 0; k < 8; k++) {
      qa[k][0] = pack(o[2 * k][0] * QSCALE, o[2 * k][1] * QSCALE);
      qa[k][1] = pack(o[2 * k][2] * QSCALE, o[2 * k][3] * QSCALE);
      qa[k][2] = pack(o[2 * k + 1][0] * QSCALE, o[2 * k + 1][1] * QSCALE);
      qa[k][3] = pack(o[2 * k + 1][2] * QSCALE, o[2 * k + 1][3] * QSCALE);
    }
#pragma unroll
    for (int n = 0; n < 16; n++) o[n][0] = o[n][1] = o[n][2] = o[n][3] = 0.f;
    float m0 = -INFINITY, m1 = -INFINITY, l0 = 0.f, l1 = 0.f;
#pragma unroll 1
    for (int key0 = 0; key0 < SK; key0 += 16) {
      float s[2][4];
#pragma unroll
      for (int nt = 0; nt < 2; nt++) {
        s[nt][0] = s[nt][1] = s[nt][2] = s[nt][3] = 0.f;
        const __nv_bfloat16* kr = kp + (size_t)(key0 + 8 * nt + g) * DH + 2 * q;
#pragma unroll
        for (int k = 0; k < 8; k++) mma16816(s[nt], qa[k], *(const uint32_t*)(kr + 16 * k), *(const uint32_t*)(kr + 16 * k + 8));
      }
      float n0 = fmaxf(fmaxf(s[0][0], s[0][1]), fmaxf(s[1][0], s[1][1])), n1 = fmaxf(fmaxf(s[0][2], s[0][3]), fmaxf(s[1][2], s[1][3]));
      n0 = fmaxf(n0, __shfl_xor_sync(~0u, n0, 1)); n1 = fmaxf(n1, __shfl_xor_sync(~0u, n1, 1));
      n0 = fmaxf(n0, __shfl_xor_sync(~0u, n0, 2)); n1 = fmaxf(n1, __shfl_xor_sync(~0u, n1, 2));
      n0 = fmaxf(n0, m0); n1 = fmaxf(n1, m1);
      const float z0 = n0 == -INFINITY ? 0.f : n0, z1 = n1 == -INFINITY ? 0.f : n1;
      const float c0 = ex2(m0 - z0), c1 = ex2(m1 - z1);
      m0 = n0; m1 = n1;
#pragma unroll
      for (int nt = 0; nt < 2; nt++) {
        s[nt][0] = ex2(s[nt][0] - z0); s[nt][1] = ex2(s[nt][1] - z0);
        s[nt][2] = ex2(s[nt][2] - z1); s[nt][3] = ex2(s[nt][3] - z1);
      }
      l0 = l0 * c0 + s[0][0] + s[0][1] + s[1][0] + s[1][1];
      l1 = l1 * c1 + s[0][2] + s[0][3] + s[1][2] + s[1][3];
      uint32_t pa[4] = {pack(s[0][0], s[0][1]), pack(s[0][2], s[0][3]), pack(s[1][0], s[1][1]), pack(s[1][2], s[1][3])};
      const uint16_t* vr = vp + (size_t)(key0 + 2 * q) * DH;
#pragma unroll
      for (int n = 0; n < 16; n++) {
        o[n][0] *= c0; o[n][1] *= c0; o[n][2] *= c1; o[n][3] *= c1;
        mma16816(o[n], pa, vr[8 * n] | ((uint32_t)vr[8 * n + DH] << 16), vr[8 * n + 8 * DH] | ((uint32_t)vr[8 * n + 9 * DH] << 16));
      }
    }
    l0 += __shfl_xor_sync(~0u, l0, 1); l1 += __shfl_xor_sync(~0u, l1, 1);
    l0 += __shfl_xor_sync(~0u, l0, 2); l1 += __shfl_xor_sync(~0u, l1, 2);
    const float i0 = 1.f / l0, i1 = 1.f / l1;
    __nv_bfloat16* oc = P.o + (size_t)(h * DH + 2 * q) * NROWS + b * SQ;
    const int p0 = o_pos(wg, r0), p1 = o_pos(wg, min(r1, 119));
#pragma unroll
    for (int n = 0; n < 16; n++) {
      oc[(size_t)(8 * n) * NROWS + p0] = __float2bfloat16(o[n][0] * i0);
      oc[(size_t)(8 * n + 1) * NROWS + p0] = __float2bfloat16(o[n][1] * i0);
      if (r1 < 120) {
        oc[(size_t)(8 * n) * NROWS + p1] = __float2bfloat16(o[n][2] * i1);
        oc[(size_t)(8 * n + 1) * NROWS + p1] = __float2bfloat16(o[n][3] * i1);
      }
    }
  }
}

__device__ __forceinline__ int bk(int ks) { return B_ORDER && ks < 48 ? 32 - (ks & 48) + (ks & 15) : ks; }
__device__ __forceinline__ uint32_t x_slot(uint32_t j) { return j < 2 ? j * XB : (7 - j) * XB; }
__device__ __forceinline__ int unit_batch(int u) { return (u & 63) >> 2; }
__device__ __forceinline__ int unit_head(int u, int rank) { return (u >> 6) * 8 + (u & 3) * 2 + rank; }

__global__ void __cluster_dims__(2, 1, 1) __launch_bounds__(384, 1)
fused_attn_kernel(const __grid_constant__ CUtensorMap tm_x, const __grid_constant__ CUtensorMap tm_wq,
                  const __grid_constant__ CUtensorMap tm_k, const __grid_constant__ CUtensorMap tm_v,
                  const __grid_constant__ CUtensorMap tm_o, const __grid_constant__ CUtensorMap tm_wo,
                  const __grid_constant__ Params P) {
  extern __shared__ uint8_t smem_raw[];
  const uint32_t sb = ((uint32_t)__cvta_generic_to_shared(smem_raw) + 1023) & ~1023u;
  const int warp = __shfl_sync(~0u, threadIdx.x >> 5, 0);
  const int lane = threadIdx.x & 31;
  const int rank = blockIdx.x & 1, cl = blockIdx.x >> 1, ncl = gridDim.x >> 1;

  if (threadIdx.x == 0) {
    for (int i = 0; i < 6; i++) {
      mbar_init(sb + BAR_RFULL + 8 * i, 1); mbar_init(sb + BAR_REMPTY + 8 * i, 8);
      mbar_init(sb + BAR_BFULL + 8 * i, 1); mbar_init(sb + BAR_BEMPTY + 8 * i, 16);
    }
    for (int i = 0; i < 8; i++) mbar_init(sb + BAR_XFULL + 8 * i, 1);
    for (int i = 0; i < 4; i++) mbar_init(sb + BAR_XEMPTY + 8 * i, 8);
    for (int i = 0; i < 2; i++) { mbar_init(sb + BAR_STAGE + 8 * i, 4); mbar_init(sb + BAR_LSUM + 8 * i, 4); mbar_init(sb + BAR_INV + 8 * i, 1); }
    mbar_init(sb + BAR_GATE, 1);
    asm volatile("fence.mbarrier_init.release.cluster;" ::: "memory");
  }
  __syncwarp();
  asm volatile("barrier.cluster.arrive.relaxed.aligned;\nbarrier.cluster.wait.aligned;" ::: "memory");

  if (warp >= 8) {
    asm volatile("setmaxnreg.dec.sync.aligned.u32 24;");
    if (warp == 8) {
      uint64_t pol;
      asm volatile("createpolicy.fractional.L2::evict_first.b64 %0, 1.0;" : "=l"(pol));
      Ring r;
      auto load = [&](const CUtensorMap* m, int c1, int c2, bool ef) {
        mbar_wait(sb + BAR_REMPTY + 8 * r.slot, r.phase ^ 1);
        if (lane == 0) {
          mbar_expect(sb + BAR_RFULL + 8 * r.slot, RING_BYTES);
          if (ef) tma3d_hint(sb + r.slot * RING_BYTES, m, 0, c1, c2, sb + BAR_RFULL + 8 * r.slot, pol);
          else tma3d(sb + r.slot * RING_BYTES, m, 0, c1, c2, sb + BAR_RFULL + 8 * r.slot);
        }
        r.next();
      };
      auto pf_tile = [&](const __nv_bfloat16* p) {
        if (PF_LSU) {
#pragma unroll
          for (int i = 0; i < 4; i++) asm volatile("prefetch.global.L2 [%0];" ::"l"(p + (i * 32 + lane) * 64) : "memory");
        } else if (lane == 0) l2_prefetch(p, 16384, pol);
      };
      uint32_t gph = 0;
      const int rot = ROT * (blockIdx.x * 5 + (blockIdx.x >> 4));
      for (int u = cl; u < NUNITS; u += ncl) {
        const int h = unit_head(u, rank);
        const int krow = (unit_batch(u) * NH + h) * SK;
#pragma unroll 1
        for (int s = 0; s < 10; s++) {
          load(&tm_wq, s * 64, 2 * h, false);
          const int sp = u == cl ? s - PF_HOLD : s;
          if (sp >= 0 && sp < PF_N) {
            const size_t off = (size_t)(krow + ((PF_J0 + sp * PF_STEP + rot) & 15) * 64) * DH;
            if (PF_WHAT & 1) pf_tile(P.k + off);
            if (PF_WHAT & 2) pf_tile(P.v + off);
          }
          if (PF_FIRST && s >= PF_FIRST && s < PF_FIRST + 3) {
            const int f = s - PF_FIRST;
            pf_tile((f == 2 ? P.v : P.k) + (size_t)(krow + (((f & 1) + rot) & 15) * 64) * DH);
          }
        }
        if (GATE) mbar_wait(sb + BAR_GATE, gph), gph ^= 1;
#pragma unroll 1
        for (int j = 0; j <= 16; j++) {
          if (j < 16) load(&tm_k, krow + ((j + rot) & 15) * 64, 0, true);
          if (j > 0) load(&tm_v, krow + ((j - 1 + rot) & 15) * 64, 0, true);
        }
      }
      for (int t = cl; t < NOTILES; t += ncl) {
        const int row0 = (t >> 2) * 256 + rank * 128;
        const int b0 = row0 / SQ, b1 = (row0 + 127) / SQ;
#pragma unroll 1
        for (int ks = 0; ks < 64; ks++) {
          if (ks == 0 || ks == 48) {
            const unsigned* c = &g_cnt[((lane & 1 ? b1 : b0) * 4 + (ks ? 3 : min(lane >> 1, 2))) * 8];
            unsigned v, n = 0;
            do {
              asm volatile("ld.acquire.gpu.global.u32 %0, [%1];" : "=r"(v) : "l"(c) : "memory");
              if (++n > (1u << 26)) __trap();
            } while (v < 16);
            __syncwarp();
            asm volatile("fence.proxy.async.global;" ::: "memory");
          }
          load(&tm_o, bk(ks) * 64, row0 >> 6, O_EF);
          if (B_PF && ks + B_PF < 48 && (ks & 3) == (t & 3) && lane == 0) tma3d_prefetch(&tm_o, 0, bk(ks + B_PF) * 64, row0 >> 6);
        }
      }
      if (lane == 0 && atomicAdd(&g_cnt[512], 1) == gridDim.x - 1) {
        for (int i = 0; i <= 64; i++) g_cnt[i * 8] = 0;
      }
    } else if (warp == 9) {
      if (lane == 0) {
        uint32_t it = 0;
        for (int u = cl; u < NUNITS; u += ncl, it++) {
          const int row = unit_batch(u) * SQ + rank * 120;
#pragma unroll 1
          for (int s = 0; s < 10; s++) {
            const uint32_t j = s & 3, par = ((s >> 2) + (j < 2 ? it : 0)) & 1;
            mbar_wait(sb + BAR_XEMPTY + 8 * j, par ^ 1);
            const uint32_t fb = sb + BAR_XFULL + 32 * rank + 8 * j;
            mbar_expect(fb, XB);
            mbar_expect_cl(mapa(fb, rank ^ 1), XB);
            tma2d_mc(sb + OFF_Q + rank * 2 * XB + x_slot(j), &tm_x, s * 64, row, fb);
            if (GATE && s == GATE) mbar_arrive(sb + BAR_GATE);
            if (X_PF && s < 2) {
#pragma unroll
              for (int i = 0; i < 3; i++)
                asm volatile("cp.async.bulk.prefetch.tensor.2d.L2.global [%0, {%1, %2}];" ::"l"(&tm_x), "r"((4 + 3 * s + i) * 64), "r"(row) : "memory");
            }
          }
        }
        uint32_t slot = rank, phase = 0;
        for (int t = cl; t < NOTILES; t += ncl) {
#pragma unroll 1
          for (int ks = rank; ks < 64; ks += 2) {
            mbar_wait(sb + BAR_BEMPTY + 8 * slot, phase);
            const uint32_t fb = sb + BAR_BFULL + 8 * slot;
            mbar_expect(fb, BB);
            mbar_expect_cl(mapa(fb, rank ^ 1), BB);
            tma3d_mc(sb + OFF_Q + slot * BB, &tm_wo, 0, bk(ks) * 64, (t & 3) * 5, fb);
            if (WO_PF && ks + WO_PF < 64 && ((ks >> 1) & 3) == ((t >> 2) & 3)) tma3d_prefetch(&tm_wo, 0, bk(ks + WO_PF) * 64, (t & 3) * 5);
            slot += 2;
            if (slot >= 6) { slot -= 6; phase ^= 1; }
          }
        }
      }
    } else {
      const int wg = warp - 10;
      if (TM_PF && lane == 0) {
        asm volatile("prefetch.tensormap [%0];" ::"l"(wg ? &tm_k : &tm_v) : "memory");
        asm volatile("prefetch.tensormap [%0];" ::"l"(wg ? &tm_o : &tm_wo) : "memory");
      }
      if (START_PF) {
        if (START_PF == 1) mbar_wait(sb + BAR_RFULL, 0);
        const __nv_bfloat16* xs = P.x + (size_t)(unit_batch(cl) * SQ + ((cl & 3) * 2 + rank) * 30 + min(lane, 29)) * DM + 256 + wg * 64;
#pragma unroll
        for (int i = 0; i < 3; i++) asm volatile("prefetch.global.L2 [%0];" ::"l"(xs + i * 128));
        if (lane < 16) asm volatile("prefetch.global.L2 [%0];" ::"l"(P.wq + (size_t)(384 + unit_batch(cl) * 16 + lane) * HD + unit_head(cl, rank) * DH + wg * 64));
      }
      uint32_t it = 0;
      for (int u = cl; u < NUNITS; u += ncl, it++) {
        mbar_wait(sb + BAR_LSUM + 8 * wg, it & 1);
        const uint32_t a = sb + OFF_P + wg * 2 * XB + min(lane, 29) * 16;
        float l4[4] = {0.f, 0.f, 0.f, 0.f};
        float v[HDEPTH][4];
#pragma unroll
        for (int g = 0; g < 32 + HDEPTH; g++) {
          float (&x)[4] = v[g % HDEPTH];
          if (g >= HDEPTH) {
#pragma unroll
            for (int c = 0; c < 4; c++) asm volatile("add.f32 %0, %0, %1;" : "+f"(l4[c]) : "f"(x[c]));
          }
          if (g < 32) asm volatile("ld.shared.v4.f32 {%0, %1, %2, %3}, [%4];" : "=f"(x[0]), "=f"(x[1]), "=f"(x[2]), "=f"(x[3]) : "r"(a + g * 480) : "memory");
        }
        fence_async_smem();
        __syncwarp();
        if (u + ncl < NUNITS) { if (lane < 4) mbar_arrive_cl(mapa(sb + BAR_XEMPTY + 24, wg)); }
#pragma unroll
        for (int c = 0; c < 4; c++) {
          float inv;
          asm("rcp.approx.ftz.f32 %0, %1;" : "=f"(inv) : "f"(l4[c]));
          l4[c] = l4[c] >= L_MIN && l4[c] <= L_MAX ? inv : __uint_as_float(0x7FFFFFFFu);
        }
        const uint32_t h0 = pack(l4[0], l4[1]), h1 = pack(l4[2], l4[3]);
        const uint32_t e0 = pack(l4[0] - __uint_as_float(h0 << 16), l4[1] - __uint_as_float(h0 & 0xFFFF0000u));
        const uint32_t e1 = pack(l4[2] - __uint_as_float(h1 << 16), l4[3] - __uint_as_float(h1 & 0xFFFF0000u));
        asm volatile("st.shared.v4.u32 [%0], {%1, %2, %3, %4};" ::"r"(sb + OFF_INV + wg * 512 + lane * 16), "r"(h0), "r"(e0), "r"(h1), "r"(e1) : "memory");
        __syncwarp();
        if (lane == 0) {
          mbar_arrive(sb + BAR_INV + 8 * wg);
          mbar_wait(sb + BAR_STAGE + 8 * wg, it & 1);
          __threadfence();
          asm volatile("red.relaxed.gpu.global.add.u32 [%0], 1;" ::"l"(&g_cnt[(unit_batch(u) * 4 + (u >> 6)) * 8]) : "memory");
        }
        __syncwarp();
      }
    }
  } else {
    asm volatile("setmaxnreg.inc.sync.aligned.u32 240;");
    const int wg = warp >> 2, w = warp & 3;
    const uint32_t qreg = sb + OFF_Q + wg * 2 * XB, preg = qreg + 4 * XB;
    const uint32_t st_off = ((lane >> 4) * 8 + (lane & 7)) * 128 + (((2 * w + ((lane >> 3) & 1)) ^ (lane & 7)) << 4);
    const uint32_t xempty = mapa(sb + BAR_XEMPTY, wg);
    const int bar_id = 1 + wg;
    Ring r;
    uint32_t it = 0;
    const uint32_t qd = (qreg & 0x3FFFF) >> 4, pd = qd + (4 * XB >> 4);
    auto ring_addr = [&]() { return ((sb & 0x3FFFF) + r.slot * RING_BYTES) >> 4; };
    auto ring_wait = [&]() { mbar_wait(sb + BAR_RFULL + 8 * r.slot, r.phase); };
    auto release = [&](uint32_t slot) { if (lane == 0) mbar_arrive(sb + BAR_REMPTY + 8 * slot); };
    auto turn_wait = [&]() { asm volatile("bar.sync %0, 256;" ::"r"(3 + wg) : "memory"); };
    auto turn_pass = [&]() { asm volatile("bar.arrive %0, 256;" ::"r"(4 - wg) : "memory"); };

    uint32_t chk = 0;
    auto load_inv = [&](uint32_t (&iv)[30], uint32_t parity) {
      mbar_wait(sb + BAR_INV + 8 * wg, parity);
      chk = 0;
#pragma unroll
      for (int j = 0; j < 15; j++)
        asm volatile("ld.shared.v2.u32 {%0, %1}, [%2];" : "=r"(iv[2 * j]), "=r"(iv[2 * j + 1]) : "r"(sb + OFF_INV + wg * 512 + j * 32 + (lane & 3) * 8) : "memory");
    };
    auto put = [&](const uint32_t (&po)[60], const uint32_t (&iv)[30], const char* optr, auto part) {
      constexpr int k = decltype(part)::value >> 1, j0 = (decltype(part)::value & 1) * 8;
      const char* o = optr + (size_t)(8 * (k & 1) + 64 * (k >> 1)) * NROWS * 2;
      uint32_t n[8];
#pragma unroll
      for (int j = 0; j < 8; j++)
        n[j] = j0 + j < 15 ? hfma2(po[15 * k + (j0 + j) % 15], iv[2 * ((j0 + j) % 15)], hfma2(po[15 * k + (j0 + j) % 15], iv[2 * ((j0 + j) % 15) + 1], 0x80008000u)) : 0x3F803F80u;
#pragma unroll
      for (int j = 0; j < 8; j += 2) chk = hfma2(n[j], n[j + 1], chk);
      if (j0 == 0)
        asm volatile(
            "{\n.reg .pred p;\nsetp.ne.u64 p, %9, 0;\n"
            "@p st.global.v4.u32 [%8], {%0, %1, %2, %3};\n@p st.global.v4.u32 [%8 + 64], {%4, %5, %6, %7};\n}\n"
            ::"r"(n[0]), "r"(n[1]), "r"(n[2]), "r"(n[3]), "r"(n[4]), "r"(n[5]), "r"(n[6]), "r"(n[7]),
            "l"(o + (wg ? 288 : 0) + (lane & 3) * 16), "l"(optr) : "memory");
      else
        asm volatile(
            "{\n.reg .pred p;\nsetp.ne.u64 p, %10, 0;\n"
            "@p st.global.v4.u32 [%7 + 128], {%0, %1, %2, %3};\n@p st.global.v2.u32 [%8], {%4, %5};\n@p st.global.u32 [%9], %6;\n}\n"
            ::"r"(n[0]), "r"(n[1]), "r"(n[2]), "r"(n[3]), "r"(n[4]), "r"(n[5]), "r"(n[6]), "l"(o + (wg ? 288 : 0) + (lane & 3) * 16),
            "l"(o + (wg ? 256 : 192) + (lane & 3) * 8), "l"(o + (wg ? 240 : 224) + (lane & 3) * 4), "l"(optr) : "memory");
    };
    auto out_ptr = [&](int u) {
      return reinterpret_cast<const char*>(P.o + (size_t)(unit_head(u, rank) * DH + 16 * w + (lane >> 2)) * NROWS + unit_batch(u) * SQ);
    };
    auto unsafe = [&](bool valid) {
      const bool b = valid && ((chk & 0x7F80u) == 0x7F80u || (chk & 0x7F800000u) == 0x7F800000u);
      return __any_sync(~0u, bar_red_or(bar_id, b));
    };
    auto publish = [&]() { __syncwarp(); if (lane == 0) mbar_arrive(sb + BAR_STAGE + 8 * wg); };

    uint32_t po[60];
#pragma unroll
    for (int i = 0; i < 60; i++) po[i] = 0;
    const uint32_t nit = __shfl_sync(~0u, (NUNITS - cl + ncl - 1) / ncl, 0);
    for (; it < nit; it++) {
      const int up = cl + ((int)it - 1) * ncl;
      float o0[60], o1[60];
      uint32_t prev = 0;
      auto qstep = [&](int s, int acc) {
        const uint32_t j = s & 3, par = ((s >> 2) + (j < 2 ? it : 0)) & 1;
        TR(it * 160 + 3 * s);
        ring_wait();
        TR(it * 160 + 3 * s + 1);
        mbar_wait(sb + BAR_XFULL + 32 * wg + 8 * j, par);
        TR(it * 160 + 3 * s + 2);
        if (s >= ALT_FROM) turn_wait();
        wg_fence();
        mma_tn(o0, o1, ring_addr(), qd + (x_slot(j) >> 4), acc);
        wg_commit();
        if ((s >= ALT_FROM && !(MERGE89 && s == 8)) || (s == ALT_FROM - 1 && wg == 1)) turn_pass();
        if (s > 0) {
          wg_wait<1>();
          release(prev);
          if (s <= 6 && lane == 0) mbar_arrive_cl(xempty + 8 * ((s - 1) & 3));
        }
        prev = r.slot;
        r.next();
      };
      {
        const char* optr = it > 0 ? out_ptr(up) : nullptr;
        uint32_t iv[30];
        qstep(0, 0);
        if (INV_AT == 1) {
          qstep(1, 1); load_inv(iv, (it + 1) & 1); put(po, iv, optr, IC<0>());
          qstep(2, 1); put(po, iv, optr, IC<1>());
          qstep(3, 1); put(po, iv, optr, IC<2>());
          qstep(4, 1); put(po, iv, optr, IC<3>());
          qstep(5, 1); put(po, iv, optr, IC<4>());
          qstep(6, 1); put(po, iv, optr, IC<5>());
          qstep(7, 1); put(po, iv, optr, IC<6>());
          qstep(8, 1); put(po, iv, optr, IC<7>());
        } else if (INV_AT == 4) {
          qstep(1, 1);
          qstep(2, 1); load_inv(iv, (it + 1) & 1); put(po, iv, optr, IC<0>());
          qstep(3, 1); put(po, iv, optr, IC<1>()); put(po, iv, optr, IC<2>());
          qstep(4, 1); put(po, iv, optr, IC<3>());
          qstep(5, 1); put(po, iv, optr, IC<4>()); put(po, iv, optr, IC<5>());
          qstep(6, 1); put(po, iv, optr, IC<6>());
          qstep(7, 1); put(po, iv, optr, IC<7>());
          qstep(8, 1);
        } else if (INV_AT == 2) {
          qstep(1, 1);
          qstep(2, 1); load_inv(iv, (it + 1) & 1); put(po, iv, optr, IC<0>());
          qstep(3, 1); put(po, iv, optr, IC<1>());
          qstep(4, 1); put(po, iv, optr, IC<2>());
          qstep(5, 1); put(po, iv, optr, IC<3>()); put(po, iv, optr, IC<4>());
          qstep(6, 1); put(po, iv, optr, IC<5>());
          qstep(7, 1); put(po, iv, optr, IC<6>());
          qstep(8, 1); put(po, iv, optr, IC<7>());
        } else {
          qstep(1, 1);
          qstep(2, 1);
          qstep(3, 1); load_inv(iv, (it + 1) & 1); put(po, iv, optr, IC<0>());
          qstep(4, 1); put(po, iv, optr, IC<1>()); put(po, iv, optr, IC<2>());
          qstep(5, 1); put(po, iv, optr, IC<3>());
          qstep(6, 1); put(po, iv, optr, IC<4>()); put(po, iv, optr, IC<5>());
          qstep(7, 1); put(po, iv, optr, IC<6>());
          qstep(8, 1); put(po, iv, optr, IC<7>());
        }
      }
      TR(it * 160 + 27);
      ring_wait();
      TR(it * 160 + 28);
      mbar_wait(sb + BAR_XFULL + 32 * wg + 8, it & 1);
      TR(it * 160 + 29);
      if (!MERGE89) turn_wait();
      wg_fence();
      mma_tn_split(o0, o1, ring_addr(), qd + (XB >> 4));
      turn_pass();
      wg_wait<2>();
      release(prev);
      wg_wait<1>();
      reg_fence(o0);
      uint32_t pq[30];
#pragma unroll
      for (int j = 0; j < 30; j++) pq[j] = pack(o0[2 * j] * QSCALE, o0[2 * j + 1] * QSCALE);
      wg_wait<0>();
      reg_fence(o1);
      release(r.slot);
      r.next();
      TR(it * 160 + 30);
      bar_sync(bar_id);
#pragma unroll
      for (int j = 0; j < 14; j += 2) stsm4t(qreg + st_off + j * 1024, pq[2 * j], pq[2 * j + 1], pq[2 * j + 2], pq[2 * j + 3]);
      stsm2t(qreg + st_off + 14 * 1024, pq[28], pq[29]);
#pragma unroll
      for (int j = 0; j < 14; j += 2)
        stsm4t(qreg + XB + st_off + j * 1024, pack(o1[4 * j] * QSCALE, o1[4 * j + 1] * QSCALE), pack(o1[4 * j + 2] * QSCALE, o1[4 * j + 3] * QSCALE),
               pack(o1[4 * j + 4] * QSCALE, o1[4 * j + 5] * QSCALE), pack(o1[4 * j + 6] * QSCALE, o1[4 * j + 7] * QSCALE));
      stsm2t(qreg + XB + st_off + 14 * 1024, pack(o1[56] * QSCALE, o1[57] * QSCALE), pack(o1[58] * QSCALE, o1[59] * QSCALE));
      fence_async_smem();
      if (unsafe(it > 0)) {
        slow_path(P, unit_batch(up), unit_head(up, rank), wg, w, lane);
#pragma unroll
        for (int i = 0; i < 60; i++) o0[i] = o1[i] = 0.f;
      }
      TR(it * 160 + 32);

      float sc[60], l[30];
      ring_wait();
      TR(it * 160 + 33);
      turn_wait();
      wg_fence();
      mma_qk(sc, ring_addr(), qd);
      wg_commit();
      turn_pass();
      if (it > 0) publish();
      wg_wait<0>();
      reg_fence(sc);
      TR(it * 160 + 35);
      release(r.slot);
      r.next();
      exp_store<0, 15, true>(sc, l, preg + st_off);
      fence_async_smem();
      bar_sync(bar_id);
      const bool more = it + 1 < nit;
#pragma unroll 1
      for (int s = 1; s < 16; s++) {
        const uint32_t kslot = r.slot;
        TR(it * 160 + 32 + 6 * s);
        ring_wait();
        TR(it * 160 + 33 + 6 * s);
        turn_wait();
        wg_fence();
        mma_qk(sc, ring_addr(), qd);
        wg_commit();
        r.next();
        TR(it * 160 + 36 + 6 * s);
        ring_wait();
        TR(it * 160 + 34 + 6 * s);
        wg_fence();
        mma_tn(o0, o1, ring_addr(), pd + ((s - 1) & 1) * (XB >> 4), s != 1);
        wg_commit();
        if (wg == 0 || s < 15) turn_pass();
        wg_wait<1>();
        reg_fence(sc);
        TR(it * 160 + 35 + 6 * s);
        release(kslot);
        if (s == 15) {
          if (more) { if (lane < 2) mbar_arrive_cl(xempty + 8 * lane); }
          else if (lane < 3 && cl < NOTILES) mbar_arrive_cl(mapa(sb + BAR_BEMPTY + 8 * lane, lane & 1));
        }
        exp_store<0, VREL>(sc, l, preg + (s & 1) * XB + st_off);
        wg_wait<0>();
        reg_fence(o0); reg_fence(o1);
        release(r.slot);
        r.next();
        exp_store<VREL, 15>(sc, l, preg + (s & 1) * XB + st_off);
        fence_async_smem();
        bar_sync(bar_id);
      }
      TR(it * 160 + 128);
      ring_wait();
      wg_fence();
      mma_tn_split(o0, o1, ring_addr(), pd + (XB >> 4));
      TR(it * 160 + 132);
      {
        const uint32_t a = preg + (8 * w + (lane >> 2)) * 480 + (lane & 3) * 8;
#pragma unroll
        for (int j = 0; j < 15; j++) asm volatile("st.shared.v2.f32 [%0], {%1, %2};" ::"r"(a + j * 32), "f"(l[2 * j]), "f"(l[2 * j + 1]) : "memory");
      }
      __syncwarp();
      if (lane == 0) mbar_arrive(sb + BAR_LSUM + 8 * wg);
      TR(it * 160 + 133);
      wg_wait<1>();
      reg_fence(o0);
      TR(it * 160 + 134);
#pragma unroll
      for (int j = 0; j < 15; j++) { po[j] = pack(o0[4 * j], o0[4 * j + 1]); po[15 + j] = pack(o0[4 * j + 2], o0[4 * j + 3]); }
      wg_wait<0>();
      reg_fence(o1);
      release(r.slot);
      r.next();
      if (more && lane == 0) mbar_arrive_cl(xempty + 16);
      TR(it * 160 + 130);
#pragma unroll
      for (int j = 0; j < 15; j++) { po[30 + j] = pack(o1[4 * j], o1[4 * j + 1]); po[45 + j] = pack(o1[4 * j + 2], o1[4 * j + 3]); }
      TR(it * 160 + 131);
    }
    const int u = cl + ((int)nit - 1) * ncl;
    uint32_t pb[60];
#pragma unroll
    for (int i = 0; i < 60; i++) pb[i] = po[i] ^ (gridDim.y - 1);

    uint32_t bslot = 0, bphase = 0;
    for (int t = cl; t < NOTILES || t == cl; t += ncl) {
      float acc[80];
      uint32_t prev = 0, bprev = 0;
      const bool tile = t < NOTILES;
      const bool last = t + ncl >= NOTILES;
      auto bstep = [&](int ks, int accf) {
        TR(640 + 2 * ks);
        ring_wait();
        mbar_wait(sb + BAR_BFULL + 8 * bslot, bphase);
        TR(641 + 2 * ks);
        wg_fence();
        const uint32_t a = ring_addr() + wg * 512, bd = (((sb & 0x3FFFF) + OFF_Q + bslot * BB) >> 4) | ((4096u >> 4) << 16);
#pragma unroll
        for (int k = 0; k < 4; k++) wgmma_n160<1, 1>(acc, a + k * 128, HI128, bd + k * 64, HI64, k == 0 ? accf : 1);
        wg_commit();
        if (ks > 0) {
          wg_wait<1>();
          release(prev);
          if (lane == 0 && (ks < 59 || !last)) mbar_arrive_cl(mapa(sb + BAR_BEMPTY + 8 * bprev, bprev & 1));
        }
        prev = r.slot; bprev = bslot;
        r.next();
        if (++bslot == 6) { bslot = 0; bphase ^= 1; }
      };
      const char* optr = t == cl ? out_ptr(u) : nullptr;
      uint32_t iv[30];
      if (tile) {
        bstep(0, 0);
        bstep(1, 1);
        load_inv(iv, (nit + 1) & 1);
        if (t == cl && lane < 3) mbar_arrive_cl(mapa(sb + BAR_BEMPTY + 24 + 8 * lane, (lane + 1) & 1));
        bstep(2, 1); put(pb, iv, optr, IC<0>()); bstep(3, 1);
        bstep(4, 1); put(pb, iv, optr, IC<1>()); bstep(5, 1);
        bstep(6, 1); put(pb, iv, optr, IC<2>()); bstep(7, 1);
        bstep(8, 1); put(pb, iv, optr, IC<3>()); bstep(9, 1);
        bstep(10, 1); put(pb, iv, optr, IC<4>()); bstep(11, 1);
        bstep(12, 1); put(pb, iv, optr, IC<5>()); bstep(13, 1);
        bstep(14, 1); put(pb, iv, optr, IC<6>()); bstep(15, 1);
        bstep(16, 1); put(pb, iv, optr, IC<7>());
        wg_wait<0>();
        reg_fence(acc);
      } else {
#pragma unroll
        for (int i = 0; i < 80; i++) acc[i] = 0.f;
        load_inv(iv, (nit + 1) & 1);
        put(pb, iv, optr, IC<0>()); put(pb, iv, optr, IC<1>()); put(pb, iv, optr, IC<2>()); put(pb, iv, optr, IC<3>());
        put(pb, iv, optr, IC<4>()); put(pb, iv, optr, IC<5>()); put(pb, iv, optr, IC<6>()); put(pb, iv, optr, IC<7>());
      }
      if (unsafe(t == cl)) slow_path(P, unit_batch(u), unit_head(u, rank), wg, w, lane);
      if (t == cl) publish();
      if (!tile) break;
#pragma unroll 1
      for (int ks = 17; ks < 64; ks++) {
        if (END_SKEW && wg == 1 && ks == 64 - END_SKEW) turn_wait();
        bstep(ks, 1);
      }
      if (END_SKEW && wg == 0) turn_pass();
      wg_wait<0>();
      reg_fence(acc);
      release(prev);
      if (lane == 0 && !last) mbar_arrive_cl(mapa(sb + BAR_BEMPTY + 8 * bprev, bprev & 1));
      TR(158);
      const int pos0 = (t >> 2) * 256 + rank * 128 + wg * 64 + w * 16;
      if (last) {
        bar_sync(bar_id);
        const uint32_t st = sb + w * RING_BYTES + wg * 8192;
        const uint32_t sa = st + (lane & 15) * 336 + (lane >> 4) * 16;
#pragma unroll
        for (int j = 0; j < 20; j += 2)
          asm volatile("stmatrix.sync.aligned.m8n8.x4.shared.b16 [%0], {%1,%2,%3,%4};" ::"r"(sa + j * 16), "r"(pack(acc[4 * j], acc[4 * j + 1])),
                       "r"(pack(acc[4 * j + 2], acc[4 * j + 3])), "r"(pack(acc[4 * j + 4], acc[4 * j + 5])), "r"(pack(acc[4 * j + 6], acc[4 * j + 7])) : "memory");
        if (EPI_STG) {
          __syncwarp();
          const int lane = __shfl_sync(~0u, (int)(threadIdx.x & 31), threadIdx.x & 31);
          const int myrow = o_row(pos0 + (lane & 15));
#pragma unroll
          for (int i = 0; i < 10; i++) {
            const int c = i * 32 + lane, rr = c / 20, cc = c - rr * 20;
            uint4 v;
            asm volatile("ld.shared.v4.u32 {%0, %1, %2, %3}, [%4];" : "=r"(v.x), "=r"(v.y), "=r"(v.z), "=r"(v.w) : "r"(st + rr * 336 + cc * 16) : "memory");
            *reinterpret_cast<uint4*>(P.out + (size_t)__shfl_sync(~0u, myrow, rr) * DM + (t & 3) * 160 + cc * 8) = v;
          }
        } else {
          fence_async_smem();
          __syncwarp();
          if (lane < 16) {
            __nv_bfloat16* dst = P.out + (size_t)o_row(pos0 + lane) * DM + (t & 3) * 160;
            asm volatile("cp.async.bulk.global.shared::cta.bulk_group [%0], [%1], 320;" ::"l"(dst), "r"(st + lane * 336) : "memory");
            asm volatile("cp.async.bulk.commit_group;" ::: "memory");
            asm volatile("cp.async.bulk.wait_group.read 0;" ::: "memory");
          }
        }
      } else {
        __nv_bfloat16* op0 = P.out + (size_t)o_row(pos0 + (lane >> 2)) * DM + (t & 3) * 160 + (lane & 3) * 2;
        __nv_bfloat16* op1 = P.out + (size_t)o_row(pos0 + (lane >> 2) + 8) * DM + (t & 3) * 160 + (lane & 3) * 2;
#pragma unroll
        for (int j = 0; j < 20; j++) {
          *reinterpret_cast<uint32_t*>(op0 + j * 8) = pack(acc[4 * j], acc[4 * j + 1]);
          *reinterpret_cast<uint32_t*>(op1 + j * 8) = pack(acc[4 * j + 2], acc[4 * j + 3]);
        }
      }
#pragma unroll
      for (int i = 0; i < 60; i++) pb[i] = 0;
    }
    TR(159);
  }
}

typedef CUresult (*EncodeFn)(CUtensorMap*, CUtensorMapDataType, cuuint32_t, void*, const cuuint64_t*, const cuuint64_t*,
                             const cuuint32_t*, const cuuint32_t*, CUtensorMapInterleave, CUtensorMapSwizzle,
                             CUtensorMapL2promotion, CUtensorMapFloatOOBfill);

void make_map(EncodeFn enc, CUtensorMap* m, const void* p, int rank, const cuuint64_t* dims, const cuuint64_t* strides,
              const cuuint32_t* box, CUtensorMapSwizzle sw, CUtensorMapL2promotion promo) {
  cuuint32_t es[3] = {1, 1, 1};
  enc(m, CU_TENSOR_MAP_DATA_TYPE_BFLOAT16, rank, const_cast<void*>(p), dims, strides, box, es, CU_TENSOR_MAP_INTERLEAVE_NONE, sw,
      promo, CU_TENSOR_MAP_FLOAT_OOB_FILL_NONE);
}

}

extern "C" void kernel_launch(void* const* d_in, const int* in_sizes, int n_in, void* d_out, int out_size) {
  static EncodeFn enc = nullptr;
  static int nclusters = 0;
  static void* o_ptr = nullptr;
  if (!enc) {
    cudaDriverEntryPointQueryResult qr;
    cudaGetDriverEntryPoint("cuTensorMapEncodeTiled", (void**)&enc, cudaEnableDefault, &qr);
    cudaFuncSetAttribute(fused_attn_kernel, cudaFuncAttributeMaxDynamicSharedMemorySize, SMEM_BYTES);
    cudaGetSymbolAddress(&o_ptr, g_o);
    cudaLaunchConfig_t cfg = {};
    cfg.gridDim = 128; cfg.blockDim = 384; cfg.dynamicSmemBytes = SMEM_BYTES;
    cudaLaunchAttribute at; at.id = cudaLaunchAttributeClusterDimension;
    at.val.clusterDim.x = 2; at.val.clusterDim.y = 1; at.val.clusterDim.z = 1;
    cfg.attrs = &at; cfg.numAttrs = 1;
    int n = 0;
    cudaOccupancyMaxActiveClusters(&n, fused_attn_kernel, &cfg);
    nclusters = n >= 64 || n <= 0 ? 64 : n;
  }
  const __nv_bfloat16* x = (const __nv_bfloat16*)d_in[0];
  const __nv_bfloat16* k = (const __nv_bfloat16*)d_in[1];
  const __nv_bfloat16* v = (const __nv_bfloat16*)d_in[2];
  const __nv_bfloat16* wq = (const __nv_bfloat16*)d_in[3];
  const __nv_bfloat16* wo = (const __nv_bfloat16*)d_in[4];
  CUtensorMap tm_x, tm_wq, tm_k, tm_v, tm_o, tm_wo;
  const auto S128 = CU_TENSOR_MAP_SWIZZLE_128B;
  const auto P128 = CU_TENSOR_MAP_L2_PROMOTION_L2_128B, P256 = CU_TENSOR_MAP_L2_PROMOTION_L2_256B;
  { cuuint64_t d[2] = {DM, NB * SQ}, s[1] = {DM * 2}; cuuint32_t b[2] = {64, 120}; make_map(enc, &tm_x, x, 2, d, s, b, S128, P128); }
  { cuuint64_t d[3] = {64, DM, HD / 64}, s[2] = {HD * 2, 128}; cuuint32_t b[3] = {64, 64, 2}; make_map(enc, &tm_wq, wq, 3, d, s, b, S128, P256); }
  { cuuint64_t d[3] = {64, NB * NH * SK, 2}, s[2] = {DH * 2, 128}; cuuint32_t b[3] = {64, 64, 2};
    make_map(enc, &tm_k, k, 3, d, s, b, S128, KV_PROMO); make_map(enc, &tm_v, v, 3, d, s, b, S128, KV_PROMO); }
  { cuuint64_t d[3] = {64, HD, NROWS / 64}, s[2] = {NROWS * 2, 128}; cuuint32_t b[3] = {64, 64, 2}; make_map(enc, &tm_o, o_ptr, 3, d, s, b, S128, P256); }
  { cuuint64_t d[3] = {32, HD, DM / 32}, s[2] = {DM * 2, 64}; cuuint32_t b[3] = {32, 64, 5};
    make_map(enc, &tm_wo, wo, 3, d, s, b, CU_TENSOR_MAP_SWIZZLE_64B, P128); }
  Params P{x, k, v, wq, (__nv_bfloat16*)d_out, (__nv_bfloat16*)o_ptr};
  fused_attn_kernel<<<2 * nclusters, 384, SMEM_BYTES>>>(tm_x, tm_wq, tm_k, tm_v, tm_o, tm_wo, P);
}
```

```cpp
#include <cuda_runtime.h>
#include <cuda.h>
#include <cuda_bf16.h>
#include <stdint.h>

namespace {

constexpr int NB = 16, SQ = 240, DM = 640, NH = 32, SK = 1024, DH = 128, HD = NH * DH;
constexpr int NROWS = NB * SQ;
constexpr int NUNITS = 256;
#define WAITV 0
#define XW_PF 0
#define B_PF 0
#define WO_PF 0
#define B_ORDER 1
#define TAIL_ORDER 2
#define PF_LSU 0
#define PF_FIRST 0
#define GATE 0
#define X_PF 0
#define HEAD 3
#define SPLIT_STEP 3
#define TAIL_V 1
#define HDEPTH 4
#define INV_AT 2
#define ALT_FROM 3
#define START_PF 1
#define MERGE89 1
#define END_SKEW 5
#define EPI_STG 0
#define TM_PF 1
#define KV_PROMO P128
#define PF_POL 0
#define NOT 60
#define O_EF 1
#define PF_HOLD 6
#define VREL 8
#define PP_MODE 1
#define PF_N 4
#define PF_J0 3
#define PF_STEP 3
#define PF_WHAT 2
#define ROT 1
constexpr int NOTILES = NOT;
constexpr float QSCALE = 0.08838834764831845f * 1.4426950408889634f;
constexpr float L_MIN = 9.5367431640625e-07f;
constexpr float L_MAX = 1.152921504606846976e18f;

constexpr uint32_t RING_SLOTS = 6, RING_BYTES = 16384;
constexpr uint32_t XB = 15360;
constexpr uint32_t BB = 20480;
constexpr uint32_t OFF_Q = RING_SLOTS * RING_BYTES;
constexpr uint32_t OFF_P = OFF_Q + 4 * XB;
constexpr uint32_t OFF_INV = OFF_P + 4 * XB;
constexpr uint32_t OFF_BAR = OFF_INV + 1024;
constexpr uint32_t BAR_RFULL = OFF_BAR, BAR_REMPTY = BAR_RFULL + 48, BAR_XFULL = BAR_REMPTY + 48,
    BAR_XEMPTY = BAR_XFULL + 64, BAR_BFULL = BAR_XEMPTY + 32, BAR_BEMPTY = BAR_BFULL + 48, BAR_STAGE = BAR_BEMPTY + 48;
constexpr uint32_t BAR_GATE = BAR_STAGE + 16, BAR_LSUM = BAR_GATE + 16, BAR_INV = BAR_LSUM + 16;
constexpr uint32_t OFF_TR = BAR_INV + 16;
constexpr uint32_t SMEM_BYTES = OFF_TR + 1024;

constexpr uint32_t HI128 = (1u << 30) | (1024 >> 4);
constexpr uint32_t HI64 = (2u << 30) | (512 >> 4);

__device__ __nv_bfloat16 g_o[HD * NROWS];
__device__ unsigned g_cnt[64 * 8 + 8];
#define TR(i)
#define TG(i)

struct Params {
  const __nv_bfloat16 *x, *k, *v, *wq;
  __nv_bfloat16 *out, *o;
};

__device__ __forceinline__ void wg_fence() { asm volatile("wgmma.fence.sync.aligned;" ::: "memory"); }
__device__ __forceinline__ void wg_commit() { asm volatile("wgmma.commit_group.sync.aligned;" ::: "memory"); }
template <int N> __device__ __forceinline__ void wg_wait() { asm volatile("wgmma.wait_group.sync.aligned %0;" ::"n"(N) : "memory"); }
template <int N> __device__ __forceinline__ void reg_fence(float (&r)[N]) {
#pragma unroll
  for (int i = 0; i < N; i++) asm volatile("" : "+f"(r[i])::"memory");
}
template <int TA, int TB>
__device__ __forceinline__ void wgmma_n120(float (&d)[60], uint32_t a_lo, uint32_t a_hi, uint32_t b_lo, uint32_t b_hi, int acc) {
  asm volatile(
      "{\n.reg .pred p;\n.reg .b64 da, db;\nsetp.ne.b32 p, %64, 0;\n"
      "mov.b64 da, {%60, %61};\nmov.b64 db, {%62, %63};\n"
      "wgmma.mma_async.sync.aligned.m64n120k16.f32.bf16.bf16 {"
      "%0, %1, %2, %3, %4, %5, %6, %7, %8, %9, %10, %11, %12, %13, %14, %15, %16, %17, %18, %19, %20, %21, %22, %23, "
      "%24, %25, %26, %27, %28, %29, %30, %31, %32, %33, %34, %35, %36, %37, %38, %39, %40, %41, %42, %43, %44, %45, "
      "%46, %47, %48, %49, %50, %51, %52, %53, %54, %55, %56, %57, %58, %59"
      "}, da, db, p, 1, 1, %65, %66;\n}\n"
      : "+f"(d[0]), "+f"(d[1]), "+f"(d[2]), "+f"(d[3]), "+f"(d[4]), "+f"(d[5]), "+f"(d[6]), "+f"(d[7]), "+f"(d[8]),
        "+f"(d[9]), "+f"(d[10]), "+f"(d[11]), "+f"(d[12]), "+f"(d[13]), "+f"(d[14]), "+f"(d[15]), "+f"(d[16]),
        "+f"(d[17]), "+f"(d[18]), "+f"(d[19]), "+f"(d[20]), "+f"(d[21]), "+f"(d[22]), "+f"(d[23]), "+f"(d[24]),
        "+f"(d[25]), "+f"(d[26]), "+f"(d[27]), "+f"(d[28]), "+f"(d[29]), "+f"(d[30]), "+f"(d[31]), "+f"(d[32]),
        "+f"(d[33]), "+f"(d[34]), "+f"(d[35]), "+f"(d[36]), "+f"(d[37]), "+f"(d[38]), "+f"(d[39]), "+f"(d[40]),
        "+f"(d[41]), "+f"(d[42]), "+f"(d[43]), "+f"(d[44]), "+f"(d[45]), "+f"(d[46]), "+f"(d[47]), "+f"(d[48]),
        "+f"(d[49]), "+f"(d[50]), "+f"(d[51]), "+f"(d[52]), "+f"(d[53]), "+f"(d[54]), "+f"(d[55]), "+f"(d[56]),
        "+f"(d[57]), "+f"(d[58]), "+f"(d[59])
      : "r"(a_lo), "r"(a_hi), "r"(b_lo), "r"(b_hi), "r"(acc), "n"(TA), "n"(TB));
}

template <int TA, int TB>
__device__ __forceinline__ void wgmma_n160(float (&d)[80], uint32_t a_lo, uint32_t a_hi, uint32_t b_lo, uint32_t b_hi, int acc) {
  asm volatile(
      "{\n.reg .pred p;\n.reg .b64 da, db;\nsetp.ne.b32 p, %84, 0;\n"
      "mov.b64 da, {%80, %81};\nmov.b64 db, {%82, %83};\n"
      "wgmma.mma_async.sync.aligned.m64n160k16.f32.bf16.bf16 {"
      "%0, %1, %2, %3, %4, %5, %6, %7, %8, %9, %10, %11, %12, %13, %14, %15, %16, %17, %18, %19, %20, %21, %22, %23, "
      "%24, %25, %26, %27, %28, %29, %30, %31, %32, %33, %34, %35, %36, %37, %38, %39, %40, %41, %42, %43, %44, %45, "
      "%46, %47, %48, %49, %50, %51, %52, %53, %54, %55, %56, %57, %58, %59, %60, %61, %62, %63, %64, %65, %66, %67, "
      "%68, %69, %70, %71, %72, %73, %74, %75, %76, %77, %78, %79"
      "}, da, db, p, 1, 1, %85, %86;\n}\n"
      : "+f"(d[0]), "+f"(d[1]), "+f"(d[2]), "+f"(d[3]), "+f"(d[4]), "+f"(d[5]), "+f"(d[6]), "+f"(d[7]), "+f"(d[8]),
        "+f"(d[9]), "+f"(d[10]), "+f"(d[11]), "+f"(d[12]), "+f"(d[13]), "+f"(d[14]), "+f"(d[15]), "+f"(d[16]),
        "+f"(d[17]), "+f"(d[18]), "+f"(d[19]), "+f"(d[20]), "+f"(d[21]), "+f"(d[22]), "+f"(d[23]), "+f"(d[24]),
        "+f"(d[25]), "+f"(d[26]), "+f"(d[27]), "+f"(d[28]), "+f"(d[29]), "+f"(d[30]), "+f"(d[31]), "+f"(d[32]),
        "+f"(d[33]), "+f"(d[34]), "+f"(d[35]), "+f"(d[36]), "+f"(d[37]), "+f"(d[38]), "+f"(d[39]), "+f"(d[40]),
        "+f"(d[41]), "+f"(d[42]), "+f"(d[43]), "+f"(d[44]), "+f"(d[45]), "+f"(d[46]), "+f"(d[47]), "+f"(d[48]),
        "+f"(d[49]), "+f"(d[50]), "+f"(d[51]), "+f"(d[52]), "+f"(d[53]), "+f"(d[54]), "+f"(d[55]), "+f"(d[56]),
        "+f"(d[57]), "+f"(d[58]), "+f"(d[59]), "+f"(d[60]), "+f"(d[61]), "+f"(d[62]), "+f"(d[63]), "+f"(d[64]),
        "+f"(d[65]), "+f"(d[66]), "+f"(d[67]), "+f"(d[68]), "+f"(d[69]), "+f"(d[70]), "+f"(d[71]), "+f"(d[72]),
        "+f"(d[73]), "+f"(d[74]), "+f"(d[75]), "+f"(d[76]), "+f"(d[77]), "+f"(d[78]), "+f"(d[79])
      : "r"(a_lo), "r"(a_hi), "r"(b_lo), "r"(b_hi), "r"(acc), "n"(TA), "n"(TB));
}
__device__ __forceinline__ void mbar_init(uint32_t bar, int cnt) { asm volatile("mbarrier.init.shared::cta.b64 [%0], %1;" ::"r"(bar), "r"(cnt)); }
__device__ __forceinline__ void mbar_expect(uint32_t bar, uint32_t bytes) {
  asm volatile("mbarrier.arrive.expect_tx.shared::cta.b64 _, [%0], %1;" ::"r"(bar), "r"(bytes) : "memory");
}
__device__ __forceinline__ uint32_t mapa(uint32_t addr, uint32_t cta) {
  uint32_t r; asm("mapa.shared::cluster.u32 %0, %1, %2;" : "=r"(r) : "r"(addr), "r"(cta)); return r;
}
__device__ __forceinline__ void mbar_expect_cl(uint32_t cbar, uint32_t bytes) {
  asm volatile("mbarrier.arrive.expect_tx.shared::cluster.b64 _, [%0], %1;" ::"r"(cbar), "r"(bytes) : "memory");
}
__device__ __forceinline__ void mbar_arrive(uint32_t bar) { asm volatile("mbarrier.arrive.shared::cta.b64 _, [%0];" ::"r"(bar) : "memory"); }
__device__ __forceinline__ void mbar_arrive_cl(uint32_t cbar) { asm volatile("mbarrier.arrive.shared::cluster.b64 _, [%0];" ::"r"(cbar) : "memory"); }
__device__ __forceinline__ void mbar_wait(uint32_t bar, uint32_t parity) {
  asm volatile(
      "{\n.reg .pred p;\n.reg .u32 n;\n"
      "mbarrier.try_wait.parity.shared::cta.b64 p, [%0], %1;\n@p bra WAIT_DONE;\n"
      "mov.u32 n, 0;\n"
      "WAIT_LOOP:\n"
      "mbarrier.try_wait.parity.shared::cta.b64 p, [%0], %1;\n@p bra WAIT_DONE;\n"
      "add.u32 n, n, 1;\nsetp.lt.u32 p, n, 0x4000000;\n@p bra WAIT_LOOP;\ntrap;\n"
      "WAIT_DONE:\n}\n" ::"r"(bar), "r"(parity) : "memory");
}
__device__ __forceinline__ void tma3d(uint32_t dst, const CUtensorMap* m, int c0, int c1, int c2, uint32_t bar) {
  asm volatile("cp.async.bulk.tensor.3d.shared::cluster.global.mbarrier::complete_tx::bytes [%0], [%1, {%3, %4, %5}], [%2];"
               ::"r"(dst), "l"(m), "r"(bar), "r"(c0), "r"(c1), "r"(c2) : "memory");
}
__device__ __forceinline__ void tma3d_hint(uint32_t dst, const CUtensorMap* m, int c0, int c1, int c2, uint32_t bar, uint64_t pol) {
  asm volatile("cp.async.bulk.tensor.3d.shared::cluster.global.mbarrier::complete_tx::bytes.L2::cache_hint [%0], [%1, {%3, %4, %5}], [%2], %6;"
               ::"r"(dst), "l"(m), "r"(bar), "r"(c0), "r"(c1), "r"(c2), "l"(pol) : "memory");
}
__device__ __forceinline__ void tma2d_mc(uint32_t dst, const CUtensorMap* m, int c0, int c1, uint32_t bar) {
  asm volatile("cp.async.bulk.tensor.2d.shared::cluster.global.mbarrier::complete_tx::bytes.multicast::cluster [%0], [%1, {%3, %4}], [%2], %5;"
               ::"r"(dst), "l"(m), "r"(bar), "r"(c0), "r"(c1), "h"((uint16_t)3) : "memory");
}
__device__ __forceinline__ void tma3d_mc(uint32_t dst, const CUtensorMap* m, int c0, int c1, int c2, uint32_t bar) {
  asm volatile("cp.async.bulk.tensor.3d.shared::cluster.global.mbarrier::complete_tx::bytes.multicast::cluster [%0], [%1, {%3, %4, %5}], [%2], %6;"
               ::"r"(dst), "l"(m), "r"(bar), "r"(c0), "r"(c1), "r"(c2), "h"((uint16_t)3) : "memory");
}
__device__ __forceinline__ void l2_prefetch(const void* p, uint32_t bytes, uint64_t pol) {
  if (PF_POL) asm volatile("cp.async.bulk.prefetch.L2.global.L2::cache_hint [%0], %1, %2;" ::"l"(p), "r"(bytes), "l"(pol) : "memory");
  else asm volatile("cp.async.bulk.prefetch.L2.global [%0], %1;" ::"l"(p), "r"(bytes) : "memory");
}
__device__ __forceinline__ void fence_async_smem() { asm volatile("fence.proxy.async.shared::cta;" ::: "memory"); }
__device__ __forceinline__ void bar_sync(int id) { asm volatile("bar.sync %0, 128;" ::"r"(id) : "memory"); }
__device__ __forceinline__ bool bar_red_or(int id, bool v) {
  uint32_t r;
  asm volatile("{\n.reg .pred p, q;\nsetp.ne.u32 p, %2, 0;\nbar.red.or.pred q, %1, 128, p;\nselp.u32 %0, 1, 0, q;\n}\n"
               : "=r"(r) : "r"(id), "r"((uint32_t)v) : "memory");
  return r != 0;
}
__device__ __forceinline__ void tma3d_prefetch(const CUtensorMap* m, int c0, int c1, int c2) {
  asm volatile("cp.async.bulk.prefetch.tensor.3d.L2.global [%0, {%1, %2, %3}];" ::"l"(m), "r"(c0), "r"(c1), "r"(c2) : "memory");
}
__device__ __forceinline__ uint32_t hfma2(uint32_t a, uint32_t b, uint32_t c) { uint32_t r; asm("fma.rn.bf16x2 %0, %1, %2, %3;" : "=r"(r) : "r"(a), "r"(b), "r"(c)); return r; }
__device__ __forceinline__ float ex2(float x) { float y; asm("ex2.approx.ftz.f32 %0, %1;" : "=f"(y) : "f"(x)); return y; }
__device__ __forceinline__ uint32_t pack(float lo, float hi) { uint32_t r; asm("cvt.rn.bf16x2.f32 %0, %1, %2;" : "=r"(r) : "f"(hi), "f"(lo)); return r; }
__device__ __forceinline__ void stsm4t(uint32_t a, uint32_t r0, uint32_t r1, uint32_t r2, uint32_t r3) {
  asm volatile("stmatrix.sync.aligned.m8n8.x4.trans.shared.b16 [%0], {%1,%2,%3,%4};" ::"r"(a), "r"(r0), "r"(r1), "r"(r2), "r"(r3) : "memory");
}
__device__ __forceinline__ void stsm2t(uint32_t a, uint32_t r0, uint32_t r1) {
  asm volatile("stmatrix.sync.aligned.m8n8.x2.trans.shared.b16 [%0], {%1,%2};" ::"r"(a), "r"(r0), "r"(r1) : "memory");
}
__device__ __forceinline__ void mma16816(float (&d)[4], const uint32_t (&a)[4], uint32_t b0, uint32_t b1) {
  asm volatile("mma.sync.aligned.m16n8k16.row.col.f32.bf16.bf16.f32 {%0,%1,%2,%3}, {%4,%5,%6,%7}, {%8,%9}, {%0,%1,%2,%3};"
               : "+f"(d[0]), "+f"(d[1]), "+f"(d[2]), "+f"(d[3]) : "r"(a[0]), "r"(a[1]), "r"(a[2]), "r"(a[3]), "r"(b0), "r"(b1));
}

template <int V> struct IC { static constexpr int value = V; };

struct Ring {
  uint32_t slot = 0, phase = 0;
  __device__ __forceinline__ void next() { if (++slot == RING_SLOTS) { slot = 0; phase ^= 1; } }
};

__device__ __forceinline__ void mma_tn(float (&o0)[60], float (&o1)[60], uint32_t a, uint32_t b, int acc) {
#pragma unroll
  for (int k = 0; k < 4; k++) {
    wgmma_n120<1, 0>(o0, a + k * 128, HI128, b + k * 2, HI128, k == 0 ? acc : 1);
    wgmma_n120<1, 0>(o1, a + 512 + k * 128, HI128, b + k * 2, HI128, k == 0 ? acc : 1);
  }
}
__device__ __forceinline__ void mma_tn_split(float (&o0)[60], float (&o1)[60], uint32_t a, uint32_t b) {
#pragma unroll
  for (int k = 0; k < 4; k++) wgmma_n120<1, 0>(o0, a + k * 128, HI128, b + k * 2, HI128, 1);
  wg_commit();
#pragma unroll
  for (int k = 0; k < 4; k++) wgmma_n120<1, 0>(o1, a + 512 + k * 128, HI128, b + k * 2, HI128, 1);
  wg_commit();
}
__device__ __forceinline__ void mma_qk(float (&s)[60], uint32_t a, uint32_t q) {
#pragma unroll
  for (int k = 0; k < 8; k++)
    wgmma_n120<0, 0>(s, a + (k >> 2) * 512 + (k & 3) * 2, HI128, q + (k >> 2) * (XB >> 4) + (k & 3) * 2, HI128, k != 0);
}
template <int J0, int J1, bool FIRST = false>
__device__ __forceinline__ void exp_store(const float (&s)[60], float (&l)[30], uint32_t dst) {
#pragma unroll
  for (int j = J0; j < J1; j += 2) {
    uint32_t p[4];
#pragma unroll
    for (int jj = 0; jj < 2; jj++) {
      if (j + jj < 15) {
        const int c = j + jj;
        float e0 = ex2(s[4 * c]), e1 = ex2(s[4 * c + 1]), e2 = ex2(s[4 * c + 2]), e3 = ex2(s[4 * c + 3]);
        if (FIRST) { l[2 * c] = e0 + e2; l[2 * c + 1] = e1 + e3; }
        else { l[2 * c] += e0; l[2 * c + 1] += e1; l[2 * c] += e2; l[2 * c + 1] += e3; }
        p[2 * jj] = pack(e0, e1); p[2 * jj + 1] = pack(e2, e3);
      }
    }
    if (j + 1 < 15) stsm4t(dst + j * 1024, p[0], p[1], p[2], p[3]);
    else stsm2t(dst + j * 1024, p[0], p[1]);
  }
}

__device__ __forceinline__ int o_pos(int wg, int r) {
  const int j = r >> 3, q = (r >> 1) & 3, c = r & 1;
  if (j < 12) return (wg ? 144 : 0) + (j >> 2) * 32 + q * 8 + (j & 3) * 2 + c;
  if (j < 14) return (wg ? 128 : 96) + q * 4 + (j - 12) * 2 + c;
  return (wg ? 120 : 112) + q * 2 + c;
}
__device__ __forceinline__ int o_row(int p) {
  const int b = p / SQ, r = p - b * SQ, wg = r >= 120, c = r & 1;
  const int a = r - (wg ? 144 : 0), m = r - (wg ? 128 : 96), e = r - (wg ? 120 : 112);
  int row;
  if (a >= 0 && a < 96) row = ((a >> 5) * 4 + ((a >> 1) & 3)) * 8 + ((a >> 3) & 3) * 2 + c;
  else if (m >= 0 && m < 16) row = (12 + ((m >> 1) & 1)) * 8 + (m >> 2) * 2 + c;
  else row = 112 + e;
  return b * SQ + wg * 120 + row;
}

__device__ __forceinline__ void slow_path(const Params& P, int b, int h, int wg, int w, int lane) {
  const int g = lane >> 2, q = lane & 3, row0 = wg * 120;
  const uint16_t* wq = reinterpret_cast<const uint16_t*>(P.wq) + h * DH + g;
  const __nv_bfloat16* kp = P.k + (size_t)(b * NH + h) * SK * DH;
  const uint16_t* vp = reinterpret_cast<const uint16_t*>(P.v) + (size_t)(b * NH + h) * SK * DH + g;
#pragma unroll 1
  for (int t = w; t < 8; t += 4) {
    const int r0 = 16 * t + g, r1 = r0 + 8;
    const __nv_bfloat16* x0 = P.x + (size_t)(b * SQ + row0 + r0) * DM + 2 * q;
    const __nv_bfloat16* x1 = P.x + (size_t)(b * SQ + row0 + min(r1, 119)) * DM + 2 * q;
    float o[16][4];
#pragma unroll
    for (int n = 0; n < 16; n++) o[n][0] = o[n][1] = o[n][2] = o[n][3] = 0.f;
#pragma unroll 1
    for (int k0 = 0; k0 < DM; k0 += 16) {
      uint32_t a[4] = {*(const uint32_t*)(x0 + k0), *(const uint32_t*)(x1 + k0), *(const uint32_t*)(x0 + k0 + 8), *(const uint32_t*)(x1 + k0 + 8)};
      const uint16_t* wr = wq + (size_t)(k0 + 2 * q) * HD;
#pragma unroll
      for (int n = 0; n < 16; n++)
        mma16816(o[n], a, wr[8 * n] | ((uint32_t)wr[8 * n + HD] << 16), wr[8 * n + 8 * HD] | ((uint32_t)wr[8 * n + 9 * HD] << 16));
    }
    uint32_t qa[8][4];
#pragma unroll
    for (int k = 0; k < 8; k++) {
      qa[k][0] = pack(o[2 * k][0] * QSCALE, o[2 * k][1] * QSCALE);
      qa[k][1] = pack(o[2 * k][2] * QSCALE, o[2 * k][3] * QSCALE);
      qa[k][2] = pack(o[2 * k + 1][0] * QSCALE, o[2 * k + 1][1] * QSCALE);
      qa[k][3] = pack(o[2 * k + 1][2] * QSCALE, o[2 * k + 1][3] * QSCALE);
    }
#pragma unroll
    for (int n = 0; n < 16; n++) o[n][0] = o[n][1] = o[n][2] = o[n][3] = 0.f;
    float m0 = -INFINITY, m1 = -INFINITY, l0 = 0.f, l1 = 0.f;
#pragma unroll 1
    for (int key0 = 0; key0 < SK; key0 += 16) {
      float s[2][4];
#pragma unroll
      for (int nt = 0; nt < 2; nt++) {
        s[nt][0] = s[nt][1] = s[nt][2] = s[nt][3] = 0.f;
        const __nv_bfloat16* kr = kp + (size_t)(key0 + 8 * nt + g) * DH + 2 * q;
#pragma unroll
        for (int k = 0; k < 8; k++) mma16816(s[nt], qa[k], *(const uint32_t*)(kr + 16 * k), *(const uint32_t*)(kr + 16 * k + 8));
      }
      float n0 = fmaxf(fmaxf(s[0][0], s[0][1]), fmaxf(s[1][0], s[1][1])), n1 = fmaxf(fmaxf(s[0][2], s[0][3]), fmaxf(s[1][2], s[1][3]));
      n0 = fmaxf(n0, __shfl_xor_sync(~0u, n0, 1)); n1 = fmaxf(n1, __shfl_xor_sync(~0u, n1, 1));
      n0 = fmaxf(n0, __shfl_xor_sync(~0u, n0, 2)); n1 = fmaxf(n1, __shfl_xor_sync(~0u, n1, 2));
      n0 = fmaxf(n0, m0); n1 = fmaxf(n1, m1);
      const float z0 = n0 == -INFINITY ? 0.f : n0, z1 = n1 == -INFINITY ? 0.f : n1;
      const float c0 = ex2(m0 - z0), c1 = ex2(m1 - z1);
      m0 = n0; m1 = n1;
#pragma unroll
      for (int nt = 0; nt < 2; nt++) {
        s[nt][0] = ex2(s[nt][0] - z0); s[nt][1] = ex2(s[nt][1] - z0);
        s[nt][2] = ex2(s[nt][2] - z1); s[nt][3] = ex2(s[nt][3] - z1);
      }
      l0 = l0 * c0 + s[0][0] + s[0][1] + s[1][0] + s[1][1];
      l1 = l1 * c1 + s[0][2] + s[0][3] + s[1][2] + s[1][3];
      uint32_t pa[4] = {pack(s[0][0], s[0][1]), pack(s[0][2], s[0][3]), pack(s[1][0], s[1][1]), pack(s[1][2], s[1][3])};
      const uint16_t* vr = vp + (size_t)(key0 + 2 * q) * DH;
#pragma unroll
      for (int n = 0; n < 16; n++) {
        o[n][0] *= c0; o[n][1] *= c0; o[n][2] *= c1; o[n][3] *= c1;
        mma16816(o[n], pa, vr[8 * n] | ((uint32_t)vr[8 * n + DH] << 16), vr[8 * n + 8 * DH] | ((uint32_t)vr[8 * n + 9 * DH] << 16));
      }
    }
    l0 += __shfl_xor_sync(~0u, l0, 1); l1 += __shfl_xor_sync(~0u, l1, 1);
    l0 += __shfl_xor_sync(~0u, l0, 2); l1 += __shfl_xor_sync(~0u, l1, 2);
    const float i0 = 1.f / l0, i1 = 1.f / l1;
    __nv_bfloat16* oc = P.o + (size_t)(h * DH + 2 * q) * NROWS + b * SQ;
    const int p0 = o_pos(wg, r0), p1 = o_pos(wg, min(r1, 119));
#pragma unroll
    for (int n = 0; n < 16; n++) {
      oc[(size_t)(8 * n) * NROWS + p0] = __float2bfloat16(o[n][0] * i0);
      oc[(size_t)(8 * n + 1) * NROWS + p0] = __float2bfloat16(o[n][1] * i0);
      if (r1 < 120) {
        oc[(size_t)(8 * n) * NROWS + p1] = __float2bfloat16(o[n][2] * i1);
        oc[(size_t)(8 * n + 1) * NROWS + p1] = __float2bfloat16(o[n][3] * i1);
      }
    }
  }
}

__device__ __forceinline__ int bk(int ks) { return B_ORDER && ks < 48 ? 32 - (ks & 48) + (ks & 15) : ks; }
__device__ __forceinline__ uint32_t x_slot(uint32_t j) { return j < 2 ? j * XB : (7 - j) * XB; }
__device__ __forceinline__ int unit_batch(int u) { return (u & 63) >> 2; }
__device__ __forceinline__ int unit_head(int u, int rank) { return (u >> 6) * 8 + (u & 3) * 2 + rank; }

__global__ void __cluster_dims__(2, 1, 1) __launch_bounds__(384, 1)
fused_attn_kernel(const __grid_constant__ CUtensorMap tm_x, const __grid_constant__ CUtensorMap tm_wq,
                  const __grid_constant__ CUtensorMap tm_k, const __grid_constant__ CUtensorMap tm_v,
                  const __grid_constant__ CUtensorMap tm_o, const __grid_constant__ CUtensorMap tm_wo,
                  const __grid_constant__ Params P) {
  extern __shared__ uint8_t smem_raw[];
  const uint32_t sb = ((uint32_t)__cvta_generic_to_shared(smem_raw) + 1023) & ~1023u;
  const int warp = __shfl_sync(~0u, threadIdx.x >> 5, 0);
  const int lane = threadIdx.x & 31;
  const int rank = blockIdx.x & 1, cl = blockIdx.x >> 1, ncl = gridDim.x >> 1;

  if (threadIdx.x == 0) {
    for (int i = 0; i < 6; i++) {
      mbar_init(sb + BAR_RFULL + 8 * i, 1); mbar_init(sb + BAR_REMPTY + 8 * i, 8);
      mbar_init(sb + BAR_BFULL + 8 * i, 1); mbar_init(sb + BAR_BEMPTY + 8 * i, 16);
    }
    for (int i = 0; i < 8; i++) mbar_init(sb + BAR_XFULL + 8 * i, 1);
    for (int i = 0; i < 4; i++) mbar_init(sb + BAR_XEMPTY + 8 * i, 8);
    for (int i = 0; i < 2; i++) { mbar_init(sb + BAR_STAGE + 8 * i, 4); mbar_init(sb + BAR_LSUM + 8 * i, 4); mbar_init(sb + BAR_INV + 8 * i, 1); }
    mbar_init(sb + BAR_GATE, 1);
    asm volatile("fence.mbarrier_init.release.cluster;" ::: "memory");
  }
  __syncwarp();
  asm volatile("barrier.cluster.arrive.relaxed.aligned;\nbarrier.cluster.wait.aligned;" ::: "memory");

  if (warp >= 8) {
    asm volatile("setmaxnreg.dec.sync.aligned.u32 24;");
    if (warp == 8) {
      uint64_t pol;
      asm volatile("createpolicy.fractional.L2::evict_first.b64 %0, 1.0;" : "=l"(pol));
      Ring r;
      auto load = [&](const CUtensorMap* m, int c1, int c2, bool ef) {
        mbar_wait(sb + BAR_REMPTY + 8 * r.slot, r.phase ^ 1);
        if (lane == 0) {
          mbar_expect(sb + BAR_RFULL + 8 * r.slot, RING_BYTES);
          if (ef) tma3d_hint(sb + r.slot * RING_BYTES, m, 0, c1, c2, sb + BAR_RFULL + 8 * r.slot, pol);
          else tma3d(sb + r.slot * RING_BYTES, m, 0, c1, c2, sb + BAR_RFULL + 8 * r.slot);
        }
        r.next();
      };
      auto pf_tile = [&](const __nv_bfloat16* p) {
        if (PF_LSU) {
#pragma unroll
          for (int i = 0; i < 4; i++) asm volatile("prefetch.global.L2 [%0];" ::"l"(p + (i * 32 + lane) * 64) : "memory");
        } else if (lane == 0) l2_prefetch(p, 16384, pol);
      };
      uint32_t gph = 0;
      const int rot = ROT * (blockIdx.x * 5 + (blockIdx.x >> 4));
      for (int u = cl; u < NUNITS; u += ncl) {
        const int h = unit_head(u, rank);
        const int krow = (unit_batch(u) * NH + h) * SK;
#pragma unroll 1
        for (int s = 0; s < 10; s++) {
          load(&tm_wq, s * 64, 2 * h, false);
          const int sp = u == cl ? s - PF_HOLD : s;
          if (sp >= 0 && sp < PF_N) {
            const size_t off = (size_t)(krow + ((PF_J0 + sp * PF_STEP + rot) & 15) * 64) * DH;
            if (PF_WHAT & 1) pf_tile(P.k + off);
            if (PF_WHAT & 2) pf_tile(P.v + off);
          }
          if (PF_FIRST && s >= PF_FIRST && s < PF_FIRST + 3) {
            const int f = s - PF_FIRST;
            pf_tile((f == 2 ? P.v : P.k) + (size_t)(krow + (((f & 1) + rot) & 15) * 64) * DH);
          }
        }
        if (GATE) mbar_wait(sb + BAR_GATE, gph), gph ^= 1;
#pragma unroll 1
        for (int j = 0; j <= 16; j++) {
          if (j < 16) load(&tm_k, krow + ((j + rot) & 15) * 64, 0, true);
          if (j > 0) load(&tm_v, krow + ((j - 1 + rot) & 15) * 64, 0, true);
        }
      }
      for (int t = cl; t < NOTILES; t += ncl) {
        const int row0 = (t >> 2) * 256 + rank * 128;
        const int b0 = row0 / SQ, b1 = (row0 + 127) / SQ;
#pragma unroll 1
        for (int ks = 0; ks < 64; ks++) {
          if (ks == 0 || ks == 48) {
            const unsigned* c = &g_cnt[((lane & 1 ? b1 : b0) * 4 + (ks ? 3 : min(lane >> 1, 2))) * 8];
            unsigned v, n = 0;
            do {
              asm volatile("ld.acquire.gpu.global.u32 %0, [%1];" : "=r"(v) : "l"(c) : "memory");
              if (++n > (1u << 26)) __trap();
            } while (v < 16);
            __syncwarp();
            asm volatile("fence.proxy.async.global;" ::: "memory");
          }
          load(&tm_o, bk(ks) * 64, row0 >> 6, O_EF);
          if (B_PF && ks + B_PF < 48 && (ks & 3) == (t & 3) && lane == 0) tma3d_prefetch(&tm_o, 0, bk(ks + B_PF) * 64, row0 >> 6);
        }
      }
      if (lane == 0 && atomicAdd(&g_cnt[512], 1) == gridDim.x - 1) {
        for (int i = 0; i <= 64; i++) g_cnt[i * 8] = 0;
      }
    } else if (warp == 9) {
      if (lane == 0) {
        uint32_t it = 0;
        for (int u = cl; u < NUNITS; u += ncl, it++) {
          const int row = unit_batch(u) * SQ + rank * 120;
#pragma unroll 1
          for (int s = 0; s < 10; s++) {
            const uint32_t j = s & 3, par = ((s >> 2) + (j < 2 ? it : 0)) & 1;
            mbar_wait(sb + BAR_XEMPTY + 8 * j, par ^ 1);
            const uint32_t fb = sb + BAR_XFULL + 32 * rank + 8 * j;
            mbar_expect(fb, XB);
            mbar_expect_cl(mapa(fb, rank ^ 1), XB);
            tma2d_mc(sb + OFF_Q + rank * 2 * XB + x_slot(j), &tm_x, s * 64, row, fb);
            if (GATE && s == GATE) mbar_arrive(sb + BAR_GATE);
            if (X_PF && s < 2) {
#pragma unroll
              for (int i = 0; i < 3; i++)
                asm volatile("cp.async.bulk.prefetch.tensor.2d.L2.global [%0, {%1, %2}];" ::"l"(&tm_x), "r"((4 + 3 * s + i) * 64), "r"(row) : "memory");
            }
          }
        }
        uint32_t slot = rank, phase = 0;
        for (int t = cl; t < NOTILES; t += ncl) {
#pragma unroll 1
          for (int ks = rank; ks < 64; ks += 2) {
            mbar_wait(sb + BAR_BEMPTY + 8 * slot, phase);
            const uint32_t fb = sb + BAR_BFULL + 8 * slot;
            mbar_expect(fb, BB);
            mbar_expect_cl(mapa(fb, rank ^ 1), BB);
            tma3d_mc(sb + OFF_Q + slot * BB, &tm_wo, 0, bk(ks) * 64, (t & 3) * 5, fb);
            if (WO_PF && ks + WO_PF < 64 && ((ks >> 1) & 3) == ((t >> 2) & 3)) tma3d_prefetch(&tm_wo, 0, bk(ks + WO_PF) * 64, (t & 3) * 5);
            slot += 2;
            if (slot >= 6) { slot -= 6; phase ^= 1; }
          }
        }
      }
    } else {
      const int wg = warp - 10;
      if (TM_PF && lane == 0) {
        asm volatile("prefetch.tensormap [%0];" ::"l"(wg ? &tm_k : &tm_v) : "memory");
        asm volatile("prefetch.tensormap [%0];" ::"l"(wg ? &tm_o : &tm_wo) : "memory");
      }
      if (START_PF) {
        if (START_PF == 1) mbar_wait(sb + BAR_RFULL, 0);
        const __nv_bfloat16* xs = P.x + (size_t)(unit_batch(cl) * SQ + ((cl & 3) * 2 + rank) * 30 + min(lane, 29)) * DM + 256 + wg * 64;
#pragma unroll
        for (int i = 0; i < 3; i++) asm volatile("prefetch.global.L2 [%0];" ::"l"(xs + i * 128));
        if (lane < 16) asm volatile("prefetch.global.L2 [%0];" ::"l"(P.wq + (size_t)(384 + unit_batch(cl) * 16 + lane) * HD + unit_head(cl, rank) * DH + wg * 64));
      }
      uint32_t it = 0;
      for (int u = cl; u < NUNITS; u += ncl, it++) {
        mbar_wait(sb + BAR_LSUM + 8 * wg, it & 1);
        const uint32_t a = sb + OFF_P + wg * 2 * XB + min(lane, 29) * 16;
        float l4[4] = {0.f, 0.f, 0.f, 0.f};
        float v[HDEPTH][4];
#pragma unroll
        for (int g = 0; g < 32 + HDEPTH; g++) {
          float (&x)[4] = v[g % HDEPTH];
          if (g >= HDEPTH) {
#pragma unroll
            for (int c = 0; c < 4; c++) asm volatile("add.f32 %0, %0, %1;" : "+f"(l4[c]) : "f"(x[c]));
          }
          if (g < 32) asm volatile("ld.shared.v4.f32 {%0, %1, %2, %3}, [%4];" : "=f"(x[0]), "=f"(x[1]), "=f"(x[2]), "=f"(x[3]) : "r"(a + g * 480) : "memory");
        }
        fence_async_smem();
        __syncwarp();
        if (u + ncl < NUNITS) { if (lane < 4) mbar_arrive_cl(mapa(sb + BAR_XEMPTY + 24, wg)); }
#pragma unroll
        for (int c = 0; c < 4; c++) {
          float inv;
          asm("rcp.approx.ftz.f32 %0, %1;" : "=f"(inv) : "f"(l4[c]));
          l4[c] = l4[c] >= L_MIN && l4[c] <= L_MAX ? inv : __uint_as_float(0x7FFFFFFFu);
        }
        const uint32_t h0 = pack(l4[0], l4[1]), h1 = pack(l4[2], l4[3]);
        const uint32_t e0 = pack(l4[0] - __uint_as_float(h0 << 16), l4[1] - __uint_as_float(h0 & 0xFFFF0000u));
        const uint32_t e1 = pack(l4[2] - __uint_as_float(h1 << 16), l4[3] - __uint_as_float(h1 & 0xFFFF0000u));
        asm volatile("st.shared.v4.u32 [%0], {%1, %2, %3, %4};" ::"r"(sb + OFF_INV + wg * 512 + lane * 16), "r"(h0), "r"(e0), "r"(h1), "r"(e1) : "memory");
        __syncwarp();
        if (lane == 0) {
          mbar_arrive(sb + BAR_INV + 8 * wg);
          mbar_wait(sb + BAR_STAGE + 8 * wg, it & 1);
          __threadfence();
          asm volatile("red.relaxed.gpu.global.add.u32 [%0], 1;" ::"l"(&g_cnt[(unit_batch(u) * 4 + (u >> 6)) * 8]) : "memory");
        }
        __syncwarp();
      }
    }
  } else {
    asm volatile("setmaxnreg.inc.sync.aligned.u32 240;");
    const int wg = warp >> 2, w = warp & 3;
    const uint32_t qreg = sb + OFF_Q + wg * 2 * XB, preg = qreg + 4 * XB;
    const uint32_t st_off = ((lane >> 4) * 8 + (lane & 7)) * 128 + (((2 * w + ((lane >> 3) & 1)) ^ (lane & 7)) << 4);
    const uint32_t xempty = mapa(sb + BAR_XEMPTY, wg);
    const int bar_id = 1 + wg;
    Ring r;
    uint32_t it = 0;
    const uint32_t qd = (qreg & 0x3FFFF) >> 4, pd = qd + (4 * XB >> 4);
    auto ring_addr = [&]() { return ((sb & 0x3FFFF) + r.slot * RING_BYTES) >> 4; };
    auto ring_wait = [&]() { mbar_wait(sb + BAR_RFULL + 8 * r.slot, r.phase); };
    auto release = [&](uint32_t slot) { if (lane == 0) mbar_arrive(sb + BAR_REMPTY + 8 * slot); };
    auto turn_wait = [&]() { asm volatile("bar.sync %0, 256;" ::"r"(3 + wg) : "memory"); };
    auto turn_pass = [&]() { asm volatile("bar.arrive %0, 256;" ::"r"(4 - wg) : "memory"); };

    uint32_t chk = 0;
    auto load_inv = [&](uint32_t (&iv)[30], uint32_t parity) {
      mbar_wait(sb + BAR_INV + 8 * wg, parity);
      chk = 0;
#pragma unroll
      for (int j = 0; j < 15; j++)
        asm volatile("ld.shared.v2.u32 {%0, %1}, [%2];" : "=r"(iv[2 * j]), "=r"(iv[2 * j + 1]) : "r"(sb + OFF_INV + wg * 512 + j * 32 + (lane & 3) * 8) : "memory");
    };
    auto put = [&](const uint32_t (&po)[60], const uint32_t (&iv)[30], const char* optr, auto part) {
      constexpr int k = decltype(part)::value >> 1, j0 = (decltype(part)::value & 1) * 8;
      const char* o = optr + (size_t)(8 * (k & 1) + 64 * (k >> 1)) * NROWS * 2;
      uint32_t n[8];
#pragma unroll
      for (int j = 0; j < 8; j++)
        n[j] = j0 + j < 15 ? hfma2(po[15 * k + (j0 + j) % 15], iv[2 * ((j0 + j) % 15)], hfma2(po[15 * k + (j0 + j) % 15], iv[2 * ((j0 + j) % 15) + 1], 0x80008000u)) : 0x3F803F80u;
#pragma unroll
      for (int j = 0; j < 8; j += 2) chk = hfma2(n[j], n[j + 1], chk);
      if (j0 == 0)
        asm volatile(
            "{\n.reg .pred p;\nsetp.ne.u64 p, %9, 0;\n"
            "@p st.global.v4.u32 [%8], {%0, %1, %2, %3};\n@p st.global.v4.u32 [%8 + 64], {%4, %5, %6, %7};\n}\n"
            ::"r"(n[0]), "r"(n[1]), "r"(n[2]), "r"(n[3]), "r"(n[4]), "r"(n[5]), "r"(n[6]), "r"(n[7]),
            "l"(o + (wg ? 288 : 0) + (lane & 3) * 16), "l"(optr) : "memory");
      else
        asm volatile(
            "{\n.reg .pred p;\nsetp.ne.u64 p, %10, 0;\n"
            "@p st.global.v4.u32 [%7 + 128], {%0, %1, %2, %3};\n@p st.global.v2.u32 [%8], {%4, %5};\n@p st.global.u32 [%9], %6;\n}\n"
            ::"r"(n[0]), "r"(n[1]), "r"(n[2]), "r"(n[3]), "r"(n[4]), "r"(n[5]), "r"(n[6]), "l"(o + (wg ? 288 : 0) + (lane & 3) * 16),
            "l"(o + (wg ? 256 : 192) + (lane & 3) * 8), "l"(o + (wg ? 240 : 224) + (lane & 3) * 4), "l"(optr) : "memory");
    };
    auto out_ptr = [&](int u) {
      return reinterpret_cast<const char*>(P.o + (size_t)(unit_head(u, rank) * DH + 16 * w + (lane >> 2)) * NROWS + unit_batch(u) * SQ);
    };
    auto unsafe = [&](bool valid) {
      const bool b = valid && ((chk & 0x7F80u) == 0x7F80u || (chk & 0x7F800000u) == 0x7F800000u);
      return __any_sync(~0u, bar_red_or(bar_id, b));
    };
    auto publish = [&]() { __syncwarp(); if (lane == 0) mbar_arrive(sb + BAR_STAGE + 8 * wg); };

    uint32_t po[60];
#pragma unroll
    for (int i = 0; i < 60; i++) po[i] = 0;
    const uint32_t nit = __shfl_sync(~0u, (NUNITS - cl + ncl - 1) / ncl, 0);
    for (; it < nit; it++) {
      const int up = cl + ((int)it - 1) * ncl;
      float o0[60], o1[60];
      uint32_t prev = 0;
      auto qstep = [&](int s, int acc) {
        const uint32_t j = s & 3, par = ((s >> 2) + (j < 2 ? it : 0)) & 1;
        TR(it * 160 + 3 * s);
        ring_wait();
        TR(it * 160 + 3 * s + 1);
        mbar_wait(sb + BAR_XFULL + 32 * wg + 8 * j, par);
        TR(it * 160 + 3 * s + 2);
        if (s >= ALT_FROM) turn_wait();
        wg_fence();
        mma_tn(o0, o1, ring_addr(), qd + (x_slot(j) >> 4), acc);
        wg_commit();
        if ((s >= ALT_FROM && !(MERGE89 && s == 8)) || (s == ALT_FROM - 1 && wg == 1)) turn_pass();
        if (s > 0) {
          wg_wait<1>();
          release(prev);
          if (s <= 6 && lane == 0) mbar_arrive_cl(xempty + 8 * ((s - 1) & 3));
        }
        prev = r.slot;
        r.next();
      };
      {
        const char* optr = it > 0 ? out_ptr(up) : nullptr;
        uint32_t iv[30];
        qstep(0, 0);
        if (INV_AT == 1) {
          qstep(1, 1); load_inv(iv, (it + 1) & 1); put(po, iv, optr, IC<0>());
          qstep(2, 1); put(po, iv, optr, IC<1>());
          qstep(3, 1); put(po, iv, optr, IC<2>());
          qstep(4, 1); put(po, iv, optr, IC<3>());
          qstep(5, 1); put(po, iv, optr, IC<4>());
          qstep(6, 1); put(po, iv, optr, IC<5>());
          qstep(7, 1); put(po, iv, optr, IC<6>());
          qstep(8, 1); put(po, iv, optr, IC<7>());
        } else if (INV_AT == 4) {
          qstep(1, 1);
          qstep(2, 1); load_inv(iv, (it + 1) & 1); put(po, iv, optr, IC<0>());
          qstep(3, 1); put(po, iv, optr, IC<1>()); put(po, iv, optr, IC<2>());
          qstep(4, 1); put(po, iv, optr, IC<3>());
          qstep(5, 1); put(po, iv, optr, IC<4>()); put(po, iv, optr, IC<5>());
          qstep(6, 1); put(po, iv, optr, IC<6>());
          qstep(7, 1); put(po, iv, optr, IC<7>());
          qstep(8, 1);
        } else if (INV_AT == 2) {
          qstep(1, 1);
          qstep(2, 1); load_inv(iv, (it + 1) & 1); put(po, iv, optr, IC<0>());
          qstep(3, 1); put(po, iv, optr, IC<1>());
          qstep(4, 1); put(po, iv, optr, IC<2>());
          qstep(5, 1); put(po, iv, optr, IC<3>()); put(po, iv, optr, IC<4>());
          qstep(6, 1); put(po, iv, optr, IC<5>());
          qstep(7, 1); put(po, iv, optr, IC<6>());
          qstep(8, 1); put(po, iv, optr, IC<7>());
        } else {
          qstep(1, 1);
          qstep(2, 1);
          qstep(3, 1); load_inv(iv, (it + 1) & 1); put(po, iv, optr, IC<0>());
          qstep(4, 1); put(po, iv, optr, IC<1>()); put(po, iv, optr, IC<2>());
          qstep(5, 1); put(po, iv, optr, IC<3>());
          qstep(6, 1); put(po, iv, optr, IC<4>()); put(po, iv, optr, IC<5>());
          qstep(7, 1); put(po, iv, optr, IC<6>());
          qstep(8, 1); put(po, iv, optr, IC<7>());
        }
      }
      TR(it * 160 + 27);
      ring_wait();
      TR(it * 160 + 28);
      mbar_wait(sb + BAR_XFULL + 32 * wg + 8, it & 1);
      TR(it * 160 + 29);
      if (!MERGE89) turn_wait();
      wg_fence();
      mma_tn_split(o0, o1, ring_addr(), qd + (XB >> 4));
      turn_pass();
      wg_wait<2>();
      release(prev);
      wg_wait<1>();
      reg_fence(o0);
      uint32_t pq[30];
#pragma unroll
      for (int j = 0; j < 30; j++) pq[j] = pack(o0[2 * j] * QSCALE, o0[2 * j + 1] * QSCALE);
      wg_wait<0>();
      reg_fence(o1);
      release(r.slot);
      r.next();
      TR(it * 160 + 30);
      bar_sync(bar_id);
#pragma unroll
      for (int j = 0; j < 14; j += 2) stsm4t(qreg + st_off + j * 1024, pq[2 * j], pq[2 * j + 1], pq[2 * j + 2], pq[2 * j + 3]);
      stsm2t(qreg + st_off + 14 * 1024, pq[28], pq[29]);
#pragma unroll
      for (int j = 0; j < 14; j += 2)
        stsm4t(qreg + XB + st_off + j * 1024, pack(o1[4 * j] * QSCALE, o1[4 * j + 1] * QSCALE), pack(o1[4 * j + 2] * QSCALE, o1[4 * j + 3] * QSCALE),
               pack(o1[4 * j + 4] * QSCALE, o1[4 * j + 5] * QSCALE), pack(o1[4 * j + 6] * QSCALE, o1[4 * j + 7] * QSCALE));
      stsm2t(qreg + XB + st_off + 14 * 1024, pack(o1[56] * QSCALE, o1[57] * QSCALE), pack(o1[58] * QSCALE, o1[59] * QSCALE));
      fence_async_smem();
      if (unsafe(it > 0)) {
        slow_path(P, unit_batch(up), unit_head(up, rank), wg, w, lane);
#pragma unroll
        for (int i = 0; i < 60; i++) o0[i] = o1[i] = 0.f;
      }
      TR(it * 160 + 32); TG(it * 160 + 142);

      float sc[60], l[30];
      ring_wait();
      TR(it * 160 + 33);
      turn_wait();
      wg_fence();
      mma_qk(sc, ring_addr(), qd);
      wg_commit();
      turn_pass();
      if (it > 0) publish();
      wg_wait<0>();
      reg_fence(sc);
      TR(it * 160 + 35);
      release(r.slot);
      r.next();
      exp_store<0, 15, true>(sc, l, preg + st_off);
      fence_async_smem();
      bar_sync(bar_id);
      const bool more = it + 1 < nit;
#pragma unroll 1
      for (int s = 1; s < 16; s++) {
        const uint32_t kslot = r.slot;
        TR(it * 160 + 32 + 6 * s); TG(it * 160 + 37 + 6 * s);
        ring_wait();
        TR(it * 160 + 33 + 6 * s);
        turn_wait();
        wg_fence();
        mma_qk(sc, ring_addr(), qd);
        wg_commit();
        r.next();
        TR(it * 160 + 36 + 6 * s);
        ring_wait();
        TR(it * 160 + 34 + 6 * s);
        wg_fence();
        mma_tn(o0, o1, ring_addr(), pd + ((s - 1) & 1) * (XB >> 4), s != 1);
        wg_commit();
        if (wg == 0 || s < 15) turn_pass();
        wg_wait<1>();
        reg_fence(sc);
        TR(it * 160 + 35 + 6 * s);
        release(kslot);
        if (s == 15) {
          if (more) { if (lane < 2) mbar_arrive_cl(xempty + 8 * lane); }
          else if (lane < 3 && cl < NOTILES) mbar_arrive_cl(mapa(sb + BAR_BEMPTY + 8 * lane, lane & 1));
        }
        exp_store<0, VREL>(sc, l, preg + (s & 1) * XB + st_off);
        wg_wait<0>();
        reg_fence(o0); reg_fence(o1);
        release(r.slot);
        r.next();
        exp_store<VREL, 15>(sc, l, preg + (s & 1) * XB + st_off);
        fence_async_smem();
        bar_sync(bar_id);
      }
      TR(it * 160 + 128);
      ring_wait();
      wg_fence();
      mma_tn_split(o0, o1, ring_addr(), pd + (XB >> 4));
      TR(it * 160 + 132);
      {
        const uint32_t a = preg + (8 * w + (lane >> 2)) * 480 + (lane & 3) * 8;
#pragma unroll
        for (int j = 0; j < 15; j++) asm volatile("st.shared.v2.f32 [%0], {%1, %2};" ::"r"(a + j * 32), "f"(l[2 * j]), "f"(l[2 * j + 1]) : "memory");
      }
      __syncwarp();
      if (lane == 0) mbar_arrive(sb + BAR_LSUM + 8 * wg);
      TR(it * 160 + 133);
      wg_wait<1>();
      reg_fence(o0);
      TR(it * 160 + 134);
#pragma unroll
      for (int j = 0; j < 15; j++) { po[j] = pack(o0[4 * j], o0[4 * j + 1]); po[15 + j] = pack(o0[4 * j + 2], o0[4 * j + 3]); }
      wg_wait<0>();
      reg_fence(o1);
      release(r.slot);
      r.next();
      if (more && lane == 0) mbar_arrive_cl(xempty + 16);
      TR(it * 160 + 130);
#pragma unroll
      for (int j = 0; j < 15; j++) { po[30 + j] = pack(o1[4 * j], o1[4 * j + 1]); po[45 + j] = pack(o1[4 * j + 2], o1[4 * j + 3]); }
      TR(it * 160 + 131); TG(it * 160 + 143);
    }
    const int u = cl + ((int)nit - 1) * ncl;
    uint32_t pb[60];
#pragma unroll
    for (int i = 0; i < 60; i++) pb[i] = po[i] ^ (gridDim.y - 1);

    uint32_t bslot = 0, bphase = 0;
    for (int t = cl; t < NOTILES || t == cl; t += ncl) {
      float acc[80];
      uint32_t prev = 0, bprev = 0;
      const bool tile = t < NOTILES;
      const bool last = t + ncl >= NOTILES;
      auto bstep = [&](int ks, int accf) {
        TR(640 + 2 * ks); if ((ks & 7) == 0) TG(144 + (ks >> 3));
        ring_wait();
        mbar_wait(sb + BAR_BFULL + 8 * bslot, bphase);
        TR(641 + 2 * ks);
        wg_fence();
        const uint32_t a = ring_addr() + wg * 512, bd = (((sb & 0x3FFFF) + OFF_Q + bslot * BB) >> 4) | ((4096u >> 4) << 16);
#pragma unroll
        for (int k = 0; k < 4; k++) wgmma_n160<1, 1>(acc, a + k * 128, HI128, bd + k * 64, HI64, k == 0 ? accf : 1);
        wg_commit();
        if (ks > 0) {
          wg_wait<1>();
          release(prev);
          if (lane == 0 && (ks < 59 || !last)) mbar_arrive_cl(mapa(sb + BAR_BEMPTY + 8 * bprev, bprev & 1));
        }
        prev = r.slot; bprev = bslot;
        r.next();
        if (++bslot == 6) { bslot = 0; bphase ^= 1; }
      };
      const char* optr = t == cl ? out_ptr(u) : nullptr;
      uint32_t iv[30];
      if (tile) {
        bstep(0, 0);
        bstep(1, 1);
        load_inv(iv, (nit + 1) & 1);
        if (t == cl && lane < 3) mbar_arrive_cl(mapa(sb + BAR_BEMPTY + 24 + 8 * lane, (lane + 1) & 1));
        bstep(2, 1); put(pb, iv, optr, IC<0>()); bstep(3, 1);
        bstep(4, 1); put(pb, iv, optr, IC<1>()); bstep(5, 1);
        bstep(6, 1); put(pb, iv, optr, IC<2>()); bstep(7, 1);
        bstep(8, 1); put(pb, iv, optr, IC<3>()); bstep(9, 1);
        bstep(10, 1); put(pb, iv, optr, IC<4>()); bstep(11, 1);
        bstep(12, 1); put(pb, iv, optr, IC<5>()); bstep(13, 1);
        bstep(14, 1); put(pb, iv, optr, IC<6>()); bstep(15, 1);
        bstep(16, 1); put(pb, iv, optr, IC<7>());
        wg_wait<0>();
        reg_fence(acc);
      } else {
#pragma unroll
        for (int i = 0; i < 80; i++) acc[i] = 0.f;
        load_inv(iv, (nit + 1) & 1);
        put(pb, iv, optr, IC<0>()); put(pb, iv, optr, IC<1>()); put(pb, iv, optr, IC<2>()); put(pb, iv, optr, IC<3>());
        put(pb, iv, optr, IC<4>()); put(pb, iv, optr, IC<5>()); put(pb, iv, optr, IC<6>()); put(pb, iv, optr, IC<7>());
      }
      if (unsafe(t == cl)) slow_path(P, unit_batch(u), unit_head(u, rank), wg, w, lane);
      if (t == cl) publish();
      if (!tile) break;
#pragma unroll 1
      for (int ks = 17; ks < 64; ks++) {
        if (END_SKEW && wg == 1 && ks == 64 - END_SKEW) turn_wait();
        bstep(ks, 1);
      }
      if (END_SKEW && wg == 0) turn_pass();
      wg_wait<0>();
      reg_fence(acc);
      release(prev);
      if (lane == 0 && !last) mbar_arrive_cl(mapa(sb + BAR_BEMPTY + 8 * bprev, bprev & 1));
      TR(158); TG(156);
      const int pos0 = (t >> 2) * 256 + rank * 128 + wg * 64 + w * 16;
      if (last) {
        bar_sync(bar_id);
        const uint32_t st = sb + w * RING_BYTES + wg * 8192;
        const uint32_t sa = st + (lane & 15) * 336 + (lane >> 4) * 16;
#pragma unroll
        for (int j = 0; j < 20; j += 2)
          asm volatile("stmatrix.sync.aligned.m8n8.x4.shared.b16 [%0], {%1,%2,%3,%4};" ::"r"(sa + j * 16), "r"(pack(acc[4 * j], acc[4 * j + 1])),
                       "r"(pack(acc[4 * j + 2], acc[4 * j + 3])), "r"(pack(acc[4 * j + 4], acc[4 * j + 5])), "r"(pack(acc[4 * j + 6], acc[4 * j + 7])) : "memory");
        if (EPI_STG) {
          __syncwarp();
          const int lane = __shfl_sync(~0u, (int)(threadIdx.x & 31), threadIdx.x & 31);
          const int myrow = o_row(pos0 + (lane & 15));
#pragma unroll
          for (int i = 0; i < 10; i++) {
            const int c = i * 32 + lane, rr = c / 20, cc = c - rr * 20;
            uint4 v;
            asm volatile("ld.shared.v4.u32 {%0, %1, %2, %3}, [%4];" : "=r"(v.x), "=r"(v.y), "=r"(v.z), "=r"(v.w) : "r"(st + rr * 336 + cc * 16) : "memory");
            *reinterpret_cast<uint4*>(P.out + (size_t)__shfl_sync(~0u, myrow, rr) * DM + (t & 3) * 160 + cc * 8) = v;
          }
        } else {
          fence_async_smem();
          __syncwarp();
          if (lane < 16) {
            __nv_bfloat16* dst = P.out + (size_t)o_row(pos0 + lane) * DM + (t & 3) * 160;
            asm volatile("cp.async.bulk.global.shared::cta.bulk_group [%0], [%1], 320;" ::"l"(dst), "r"(st + lane * 336) : "memory");
            asm volatile("cp.async.bulk.commit_group;" ::: "memory");
            asm volatile("cp.async.bulk.wait_group.read 0;" ::: "memory");
          }
        }
      } else {
        __nv_bfloat16* op0 = P.out + (size_t)o_row(pos0 + (lane >> 2)) * DM + (t & 3) * 160 + (lane & 3) * 2;
        __nv_bfloat16* op1 = P.out + (size_t)o_row(pos0 + (lane >> 2) + 8) * DM + (t & 3) * 160 + (lane & 3) * 2;
#pragma unroll
        for (int j = 0; j < 20; j++) {
          *reinterpret_cast<uint32_t*>(op0 + j * 8) = pack(acc[4 * j], acc[4 * j + 1]);
          *reinterpret_cast<uint32_t*>(op1 + j * 8) = pack(acc[4 * j + 2], acc[4 * j + 3]);
        }
      }
#pragma unroll
      for (int i = 0; i < 60; i++) pb[i] = 0;
    }
    TR(159);
  }
}

typedef CUresult (*EncodeFn)(CUtensorMap*, CUtensorMapDataType, cuuint32_t, void*, const cuuint64_t*, const cuuint64_t*,
                             const cuuint32_t*, const cuuint32_t*, CUtensorMapInterleave, CUtensorMapSwizzle,
                             CUtensorMapL2promotion, CUtensorMapFloatOOBfill);

void make_map(EncodeFn enc, CUtensorMap* m, const void* p, int rank, const cuuint64_t* dims, const cuuint64_t* strides,
              const cuuint32_t* box, CUtensorMapSwizzle sw, CUtensorMapL2promotion promo) {
  cuuint32_t es[3] = {1, 1, 1};
  enc(m, CU_TENSOR_MAP_DATA_TYPE_BFLOAT16, rank, const_cast<void*>(p), dims, strides, box, es, CU_TENSOR_MAP_INTERLEAVE_NONE, sw,
      promo, CU_TENSOR_MAP_FLOAT_OOB_FILL_NONE);
}

}

extern "C" void kernel_launch(void* const* d_in, const int* in_sizes, int n_in, void* d_out, int out_size) {
  static EncodeFn enc = nullptr;
  static int nclusters = 0;
  static void* o_ptr = nullptr;
  if (!enc) {
    cudaDriverEntryPointQueryResult qr;
    cudaGetDriverEntryPoint("cuTensorMapEncodeTiled", (void**)&enc, cudaEnableDefault, &qr);
    cudaFuncSetAttribute(fused_attn_kernel, cudaFuncAttributeMaxDynamicSharedMemorySize, SMEM_BYTES);
    cudaGetSymbolAddress(&o_ptr, g_o);
    cudaLaunchConfig_t cfg = {};
    cfg.gridDim = 128; cfg.blockDim = 384; cfg.dynamicSmemBytes = SMEM_BYTES;
    cudaLaunchAttribute at; at.id = cudaLaunchAttributeClusterDimension;
    at.val.clusterDim.x = 2; at.val.clusterDim.y = 1; at.val.clusterDim.z = 1;
    cfg.attrs = &at; cfg.numAttrs = 1;
    int n = 0;
    cudaOccupancyMaxActiveClusters(&n, fused_attn_kernel, &cfg);
    nclusters = n >= 64 || n <= 0 ? 64 : n;
  }
  const __nv_bfloat16* x = (const __nv_bfloat16*)d_in[0];
  const __nv_bfloat16* k = (const __nv_bfloat16*)d_in[1];
  const __nv_bfloat16* v = (const __nv_bfloat16*)d_in[2];
  const __nv_bfloat16* wq = (const __nv_bfloat16*)d_in[3];
  const __nv_bfloat16* wo = (const __nv_bfloat16*)d_in[4];
  CUtensorMap tm_x, tm_wq, tm_k, tm_v, tm_o, tm_wo;
  const auto S128 = CU_TENSOR_MAP_SWIZZLE_128B;
  const auto P128 = CU_TENSOR_MAP_L2_PROMOTION_L2_128B, P256 = CU_TENSOR_MAP_L2_PROMOTION_L2_256B;
  { cuuint64_t d[2] = {DM, NB * SQ}, s[1] = {DM * 2}; cuuint32_t b[2] = {64, 120}; make_map(enc, &tm_x, x, 2, d, s, b, S128, P128); }
  { cuuint64_t d[3] = {64, DM, HD / 64}, s[2] = {HD * 2, 128}; cuuint32_t b[3] = {64, 64, 2}; make_map(enc, &tm_wq, wq, 3, d, s, b, S128, P256); }
  { cuuint64_t d[3] = {64, NB * NH * SK, 2}, s[2] = {DH * 2, 128}; cuuint32_t b[3] = {64, 64, 2};
    make_map(enc, &tm_k, k, 3, d, s, b, S128, KV_PROMO); make_map(enc, &tm_v, v, 3, d, s, b, S128, KV_PROMO); }
  { cuuint64_t d[3] = {64, HD, NROWS / 64}, s[2] = {NROWS * 2, 128}; cuuint32_t b[3] = {64, 64, 2}; make_map(enc, &tm_o, o_ptr, 3, d, s, b, S128, P256); }
  { cuuint64_t d[3] = {32, HD, DM / 32}, s[2] = {DM * 2, 64}; cuuint32_t b[3] = {32, 64, 5};
    make_map(enc, &tm_wo, wo, 3, d, s, b, CU_TENSOR_MAP_SWIZZLE_64B, P128); }
  Params P{x, k, v, wq, (__nv_bfloat16*)d_out, (__nv_bfloat16*)o_ptr};
  fused_attn_kernel<<<2 * nclusters, 384, SMEM_BYTES>>>(tm_x, tm_wq, tm_k, tm_v, tm_o, tm_wo, P);
}
```

```cpp
#include <cuda_runtime.h>
#include <cuda.h>
#include <cuda_bf16.h>
#include <stdint.h>

namespace {

constexpr int NB = 16, SQ = 240, DM = 640, NH = 32, SK = 1024, DH = 128, HD = NH * DH;
constexpr int NROWS = NB * SQ;
constexpr int NUNITS = 256;
#define WAITV 0
#define XW_PF 0
#define B_PF 0
#define WO_PF 0
#define B_ORDER 1
#define TAIL_ORDER 2
#define PF_LSU 0
#define PF_FIRST 0
#define GATE 0
#define X_PF 0
#define HEAD 3
#define SPLIT_STEP 3
#define TAIL_V 1
#define HDEPTH 4
#define INV_AT 2
#define ALT_FROM 5
#define START_PF 1
#define MERGE89 1
#define END_SKEW 5
#define EPI_STG 0
#define TM_PF 1
#define LATE_AT 2
#define DPRO 1
#define KV_PROMO P128
#define PF_POL 0
#define NOT 60
#define O_EF 1
#define PF_HOLD 6
#define VREL 8
#define PP_MODE 1
#define PF_N 4
#define PF_J0 3
#define PF_STEP 3
#define PF_WHAT 2
#define ROT 1
constexpr int NOTILES = NOT;
constexpr float QSCALE = 0.08838834764831845f * 1.4426950408889634f;
constexpr float L_MIN = 9.5367431640625e-07f;
constexpr float L_MAX = 1.152921504606846976e18f;

constexpr uint32_t RING_SLOTS = 6, RING_BYTES = 16384;
constexpr uint32_t XB = 15360;
constexpr uint32_t BB = 20480;
constexpr uint32_t OFF_Q = RING_SLOTS * RING_BYTES;
constexpr uint32_t OFF_P = OFF_Q + 4 * XB;
constexpr uint32_t OFF_INV = OFF_P + 4 * XB;
constexpr uint32_t OFF_L2 = OFF_INV + 1024;
constexpr uint32_t OFF_BAR = OFF_L2 + 4096;
constexpr uint32_t BAR_RFULL = OFF_BAR, BAR_REMPTY = BAR_RFULL + 48, BAR_XFULL = BAR_REMPTY + 48,
    BAR_XEMPTY = BAR_XFULL + 64, BAR_BFULL = BAR_XEMPTY + 32, BAR_BEMPTY = BAR_BFULL + 48, BAR_STAGE = BAR_BEMPTY + 48;
constexpr uint32_t BAR_GATE = BAR_STAGE + 16, BAR_LSUM = BAR_GATE + 16, BAR_INV = BAR_LSUM + 16;
constexpr uint32_t OFF_TR = BAR_INV + 16;
constexpr uint32_t SMEM_BYTES = OFF_TR + 1024;

constexpr uint32_t HI128 = (1u << 30) | (1024 >> 4);
constexpr uint32_t HI64 = (2u << 30) | (512 >> 4);

__device__ __nv_bfloat16 g_o[HD * NROWS];
__device__ unsigned g_cnt[64 * 8 + 8];
#define TR(i)
#define TG(i)

struct Params {
  const __nv_bfloat16 *x, *k, *v, *wq;
  __nv_bfloat16 *out, *o;
};

__device__ __forceinline__ void wg_fence() { asm volatile("wgmma.fence.sync.aligned;" ::: "memory"); }
__device__ __forceinline__ void wg_commit() { asm volatile("wgmma.commit_group.sync.aligned;" ::: "memory"); }
template <int N> __device__ __forceinline__ void wg_wait() { asm volatile("wgmma.wait_group.sync.aligned %0;" ::"n"(N) : "memory"); }
template <int N> __device__ __forceinline__ void reg_fence(float (&r)[N]) {
#pragma unroll
  for (int i = 0; i < N; i++) asm volatile("" : "+f"(r[i])::"memory");
}
template <int TA, int TB>
__device__ __forceinline__ void wgmma_n120(float (&d)[60], uint32_t a_lo, uint32_t a_hi, uint32_t b_lo, uint32_t b_hi, int acc) {
  asm volatile(
      "{\n.reg .pred p;\n.reg .b64 da, db;\nsetp.ne.b32 p, %64, 0;\n"
      "mov.b64 da, {%60, %61};\nmov.b64 db, {%62, %63};\n"
      "wgmma.mma_async.sync.aligned.m64n120k16.f32.bf16.bf16 {"
      "%0, %1, %2, %3, %4, %5, %6, %7, %8, %9, %10, %11, %12, %13, %14, %15, %16, %17, %18, %19, %20, %21, %22, %23, "
      "%24, %25, %26, %27, %28, %29, %30, %31, %32, %33, %34, %35, %36, %37, %38, %39, %40, %41, %42, %43, %44, %45, "
      "%46, %47, %48, %49, %50, %51, %52, %53, %54, %55, %56, %57, %58, %59"
      "}, da, db, p, 1, 1, %65, %66;\n}\n"
      : "+f"(d[0]), "+f"(d[1]), "+f"(d[2]), "+f"(d[3]), "+f"(d[4]), "+f"(d[5]), "+f"(d[6]), "+f"(d[7]), "+f"(d[8]),
        "+f"(d[9]), "+f"(d[10]), "+f"(d[11]), "+f"(d[12]), "+f"(d[13]), "+f"(d[14]), "+f"(d[15]), "+f"(d[16]),
        "+f"(d[17]), "+f"(d[18]), "+f"(d[19]), "+f"(d[20]), "+f"(d[21]), "+f"(d[22]), "+f"(d[23]), "+f"(d[24]),
        "+f"(d[25]), "+f"(d[26]), "+f"(d[27]), "+f"(d[28]), "+f"(d[29]), "+f"(d[30]), "+f"(d[31]), "+f"(d[32]),
        "+f"(d[33]), "+f"(d[34]), "+f"(d[35]), "+f"(d[36]), "+f"(d[37]), "+f"(d[38]), "+f"(d[39]), "+f"(d[40]),
        "+f"(d[41]), "+f"(d[42]), "+f"(d[43]), "+f"(d[44]), "+f"(d[45]), "+f"(d[46]), "+f"(d[47]), "+f"(d[48]),
        "+f"(d[49]), "+f"(d[50]), "+f"(d[51]), "+f"(d[52]), "+f"(d[53]), "+f"(d[54]), "+f"(d[55]), "+f"(d[56]),
        "+f"(d[57]), "+f"(d[58]), "+f"(d[59])
      : "r"(a_lo), "r"(a_hi), "r"(b_lo), "r"(b_hi), "r"(acc), "n"(TA), "n"(TB));
}

template <int TA, int TB>
__device__ __forceinline__ void wgmma_n160(float (&d)[80], uint32_t a_lo, uint32_t a_hi, uint32_t b_lo, uint32_t b_hi, int acc) {
  asm volatile(
      "{\n.reg .pred p;\n.reg .b64 da, db;\nsetp.ne.b32 p, %84, 0;\n"
      "mov.b64 da, {%80, %81};\nmov.b64 db, {%82, %83};\n"
      "wgmma.mma_async.sync.aligned.m64n160k16.f32.bf16.bf16 {"
      "%0, %1, %2, %3, %4, %5, %6, %7, %8, %9, %10, %11, %12, %13, %14, %15, %16, %17, %18, %19, %20, %21, %22, %23, "
      "%24, %25, %26, %27, %28, %29, %30, %31, %32, %33, %34, %35, %36, %37, %38, %39, %40, %41, %42, %43, %44, %45, "
      "%46, %47, %48, %49, %50, %51, %52, %53, %54, %55, %56, %57, %58, %59, %60, %61, %62, %63, %64, %65, %66, %67, "
      "%68, %69, %70, %71, %72, %73, %74, %75, %76, %77, %78, %79"
      "}, da, db, p, 1, 1, %85, %86;\n}\n"
      : "+f"(d[0]), "+f"(d[1]), "+f"(d[2]), "+f"(d[3]), "+f"(d[4]), "+f"(d[5]), "+f"(d[6]), "+f"(d[7]), "+f"(d[8]),
        "+f"(d[9]), "+f"(d[10]), "+f"(d[11]), "+f"(d[12]), "+f"(d[13]), "+f"(d[14]), "+f"(d[15]), "+f"(d[16]),
        "+f"(d[17]), "+f"(d[18]), "+f"(d[19]), "+f"(d[20]), "+f"(d[21]), "+f"(d[22]), "+f"(d[23]), "+f"(d[24]),
        "+f"(d[25]), "+f"(d[26]), "+f"(d[27]), "+f"(d[28]), "+f"(d[29]), "+f"(d[30]), "+f"(d[31]), "+f"(d[32]),
        "+f"(d[33]), "+f"(d[34]), "+f"(d[35]), "+f"(d[36]), "+f"(d[37]), "+f"(d[38]), "+f"(d[39]), "+f"(d[40]),
        "+f"(d[41]), "+f"(d[42]), "+f"(d[43]), "+f"(d[44]), "+f"(d[45]), "+f"(d[46]), "+f"(d[47]), "+f"(d[48]),
        "+f"(d[49]), "+f"(d[50]), "+f"(d[51]), "+f"(d[52]), "+f"(d[53]), "+f"(d[54]), "+f"(d[55]), "+f"(d[56]),
        "+f"(d[57]), "+f"(d[58]), "+f"(d[59]), "+f"(d[60]), "+f"(d[61]), "+f"(d[62]), "+f"(d[63]), "+f"(d[64]),
        "+f"(d[65]), "+f"(d[66]), "+f"(d[67]), "+f"(d[68]), "+f"(d[69]), "+f"(d[70]), "+f"(d[71]), "+f"(d[72]),
        "+f"(d[73]), "+f"(d[74]), "+f"(d[75]), "+f"(d[76]), "+f"(d[77]), "+f"(d[78]), "+f"(d[79])
      : "r"(a_lo), "r"(a_hi), "r"(b_lo), "r"(b_hi), "r"(acc), "n"(TA), "n"(TB));
}
__device__ __forceinline__ void mbar_init(uint32_t bar, int cnt) { asm volatile("mbarrier.init.shared::cta.b64 [%0], %1;" ::"r"(bar), "r"(cnt)); }
__device__ __forceinline__ void mbar_expect(uint32_t bar, uint32_t bytes) {
  asm volatile("mbarrier.arrive.expect_tx.shared::cta.b64 _, [%0], %1;" ::"r"(bar), "r"(bytes) : "memory");
}
__device__ __forceinline__ uint32_t mapa(uint32_t addr, uint32_t cta) {
  uint32_t r; asm("mapa.shared::cluster.u32 %0, %1, %2;" : "=r"(r) : "r"(addr), "r"(cta)); return r;
}
__device__ __forceinline__ void mbar_expect_cl(uint32_t cbar, uint32_t bytes) {
  asm volatile("mbarrier.arrive.expect_tx.shared::cluster.b64 _, [%0], %1;" ::"r"(cbar), "r"(bytes) : "memory");
}
__device__ __forceinline__ void mbar_arrive(uint32_t bar) { asm volatile("mbarrier.arrive.shared::cta.b64 _, [%0];" ::"r"(bar) : "memory"); }
__device__ __forceinline__ void mbar_arrive_cl(uint32_t cbar) { asm volatile("mbarrier.arrive.shared::cluster.b64 _, [%0];" ::"r"(cbar) : "memory"); }
__device__ __forceinline__ void mbar_wait(uint32_t bar, uint32_t parity) {
  asm volatile(
      "{\n.reg .pred p;\n.reg .u32 n;\n"
      "mbarrier.try_wait.parity.shared::cta.b64 p, [%0], %1;\n@p bra WAIT_DONE;\n"
      "mov.u32 n, 0;\n"
      "WAIT_LOOP:\n"
      "mbarrier.try_wait.parity.shared::cta.b64 p, [%0], %1;\n@p bra WAIT_DONE;\n"
      "add.u32 n, n, 1;\nsetp.lt.u32 p, n, 0x4000000;\n@p bra WAIT_LOOP;\ntrap;\n"
      "WAIT_DONE:\n}\n" ::"r"(bar), "r"(parity) : "memory");
}
__device__ __forceinline__ void tma3d(uint32_t dst, const CUtensorMap* m, int c0, int c1, int c2, uint32_t bar) {
  asm volatile("cp.async.bulk.tensor.3d.shared::cluster.global.mbarrier::complete_tx::bytes [%0], [%1, {%3, %4, %5}], [%2];"
               ::"r"(dst), "l"(m), "r"(bar), "r"(c0), "r"(c1), "r"(c2) : "memory");
}
__device__ __forceinline__ void tma3d_hint(uint32_t dst, const CUtensorMap* m, int c0, int c1, int c2, uint32_t bar, uint64_t pol) {
  asm volatile("cp.async.bulk.tensor.3d.shared::cluster.global.mbarrier::complete_tx::bytes.L2::cache_hint [%0], [%1, {%3, %4, %5}], [%2], %6;"
               ::"r"(dst), "l"(m), "r"(bar), "r"(c0), "r"(c1), "r"(c2), "l"(pol) : "memory");
}
__device__ __forceinline__ void tma2d_mc(uint32_t dst, const CUtensorMap* m, int c0, int c1, uint32_t bar) {
  asm volatile("cp.async.bulk.tensor.2d.shared::cluster.global.mbarrier::complete_tx::bytes.multicast::cluster [%0], [%1, {%3, %4}], [%2], %5;"
               ::"r"(dst), "l"(m), "r"(bar), "r"(c0), "r"(c1), "h"((uint16_t)3) : "memory");
}
__device__ __forceinline__ void tma3d_mc(uint32_t dst, const CUtensorMap* m, int c0, int c1, int c2, uint32_t bar) {
  asm volatile("cp.async.bulk.tensor.3d.shared::cluster.global.mbarrier::complete_tx::bytes.multicast::cluster [%0], [%1, {%3, %4, %5}], [%2], %6;"
               ::"r"(dst), "l"(m), "r"(bar), "r"(c0), "r"(c1), "r"(c2), "h"((uint16_t)3) : "memory");
}
__device__ __forceinline__ void l2_prefetch(const void* p, uint32_t bytes, uint64_t pol) {
  if (PF_POL) asm volatile("cp.async.bulk.prefetch.L2.global.L2::cache_hint [%0], %1, %2;" ::"l"(p), "r"(bytes), "l"(pol) : "memory");
  else asm volatile("cp.async.bulk.prefetch.L2.global [%0], %1;" ::"l"(p), "r"(bytes) : "memory");
}
__device__ __forceinline__ void fence_async_smem() { asm volatile("fence.proxy.async.shared::cta;" ::: "memory"); }
__device__ __forceinline__ void bar_sync(int id) { asm volatile("bar.sync %0, 128;" ::"r"(id) : "memory"); }
__device__ __forceinline__ bool bar_red_or(int id, bool v) {
  uint32_t r;
  asm volatile("{\n.reg .pred p, q;\nsetp.ne.u32 p, %2, 0;\nbar.red.or.pred q, %1, 128, p;\nselp.u32 %0, 1, 0, q;\n}\n"
               : "=r"(r) : "r"(id), "r"((uint32_t)v) : "memory");
  return r != 0;
}
__device__ __forceinline__ void tma3d_prefetch(const CUtensorMap* m, int c0, int c1, int c2) {
  asm volatile("cp.async.bulk.prefetch.tensor.3d.L2.global [%0, {%1, %2, %3}];" ::"l"(m), "r"(c0), "r"(c1), "r"(c2) : "memory");
}
__device__ __forceinline__ uint32_t hfma2(uint32_t a, uint32_t b, uint32_t c) { uint32_t r; asm("fma.rn.bf16x2 %0, %1, %2, %3;" : "=r"(r) : "r"(a), "r"(b), "r"(c)); return r; }
__device__ __forceinline__ float ex2(float x) { float y; asm("ex2.approx.ftz.f32 %0, %1;" : "=f"(y) : "f"(x)); return y; }
__device__ __forceinline__ uint32_t pack(float lo, float hi) { uint32_t r; asm("cvt.rn.bf16x2.f32 %0, %1, %2;" : "=r"(r) : "f"(hi), "f"(lo)); return r; }
__device__ __forceinline__ void stsm4t(uint32_t a, uint32_t r0, uint32_t r1, uint32_t r2, uint32_t r3) {
  asm volatile("stmatrix.sync.aligned.m8n8.x4.trans.shared.b16 [%0], {%1,%2,%3,%4};" ::"r"(a), "r"(r0), "r"(r1), "r"(r2), "r"(r3) : "memory");
}
__device__ __forceinline__ void stsm2t(uint32_t a, uint32_t r0, uint32_t r1) {
  asm volatile("stmatrix.sync.aligned.m8n8.x2.trans.shared.b16 [%0], {%1,%2};" ::"r"(a), "r"(r0), "r"(r1) : "memory");
}
__device__ __forceinline__ void mma16816(float (&d)[4], const uint32_t (&a)[4], uint32_t b0, uint32_t b1) {
  asm volatile("mma.sync.aligned.m16n8k16.row.col.f32.bf16.bf16.f32 {%0,%1,%2,%3}, {%4,%5,%6,%7}, {%8,%9}, {%0,%1,%2,%3};"
               : "+f"(d[0]), "+f"(d[1]), "+f"(d[2]), "+f"(d[3]) : "r"(a[0]), "r"(a[1]), "r"(a[2]), "r"(a[3]), "r"(b0), "r"(b1));
}

template <int V> struct IC { static constexpr int value = V; };

struct Ring {
  uint32_t slot = 0, phase = 0;
  __device__ __forceinline__ void next() { if (++slot == RING_SLOTS) { slot = 0; phase ^= 1; } }
};

__device__ __forceinline__ void mma_tn(float (&o0)[60], float (&o1)[60], uint32_t a, uint32_t b, int acc) {
#pragma unroll
  for (int k = 0; k < 4; k++) {
    wgmma_n120<1, 0>(o0, a + k * 128, HI128, b + k * 2, HI128, k == 0 ? acc : 1);
    wgmma_n120<1, 0>(o1, a + 512 + k * 128, HI128, b + k * 2, HI128, k == 0 ? acc : 1);
  }
}
__device__ __forceinline__ void mma_tn_split(float (&o0)[60], float (&o1)[60], uint32_t a, uint32_t b) {
#pragma unroll
  for (int k = 0; k < 4; k++) wgmma_n120<1, 0>(o0, a + k * 128, HI128, b + k * 2, HI128, 1);
  wg_commit();
#pragma unroll
  for (int k = 0; k < 4; k++) wgmma_n120<1, 0>(o1, a + 512 + k * 128, HI128, b + k * 2, HI128, 1);
  wg_commit();
}
__device__ __forceinline__ void mma_qk(float (&s)[60], uint32_t a, uint32_t q) {
#pragma unroll
  for (int k = 0; k < 8; k++)
    wgmma_n120<0, 0>(s, a + (k >> 2) * 512 + (k & 3) * 2, HI128, q + (k >> 2) * (XB >> 4) + (k & 3) * 2, HI128, k != 0);
}
template <int J0, int J1, bool FIRST = false>
__device__ __forceinline__ void exp_store(const float (&s)[60], float (&l)[30], uint32_t dst) {
#pragma unroll
  for (int j = J0; j < J1; j += 2) {
    uint32_t p[4];
#pragma unroll
    for (int jj = 0; jj < 2; jj++) {
      if (j + jj < 15) {
        const int c = j + jj;
        float e0 = ex2(s[4 * c]), e1 = ex2(s[4 * c + 1]), e2 = ex2(s[4 * c + 2]), e3 = ex2(s[4 * c + 3]);
        if (FIRST) { l[2 * c] = e0 + e2; l[2 * c + 1] = e1 + e3; }
        else { l[2 * c] += e0; l[2 * c + 1] += e1; l[2 * c] += e2; l[2 * c + 1] += e3; }
        p[2 * jj] = pack(e0, e1); p[2 * jj + 1] = pack(e2, e3);
      }
    }
    if (j + 1 < 15) stsm4t(dst + j * 1024, p[0], p[1], p[2], p[3]);
    else stsm2t(dst + j * 1024, p[0], p[1]);
  }
}

__device__ __forceinline__ int o_pos(int wg, int r) {
  const int j = r >> 3, q = (r >> 1) & 3, c = r & 1;
  if (j < 12) return (wg ? 144 : 0) + (j >> 2) * 32 + q * 8 + (j & 3) * 2 + c;
  if (j < 14) return (wg ? 128 : 96) + q * 4 + (j - 12) * 2 + c;
  return (wg ? 120 : 112) + q * 2 + c;
}
__device__ __forceinline__ int o_row(int p) {
  const int b = p / SQ, r = p - b * SQ, wg = r >= 120, c = r & 1;
  const int a = r - (wg ? 144 : 0), m = r - (wg ? 128 : 96), e = r - (wg ? 120 : 112);
  int row;
  if (a >= 0 && a < 96) row = ((a >> 5) * 4 + ((a >> 1) & 3)) * 8 + ((a >> 3) & 3) * 2 + c;
  else if (m >= 0 && m < 16) row = (12 + ((m >> 1) & 1)) * 8 + (m >> 2) * 2 + c;
  else row = 112 + e;
  return b * SQ + wg * 120 + row;
}

__device__ __forceinline__ void slow_path(const Params& P, int b, int h, int wg, int w, int lane) {
  const int g = lane >> 2, q = lane & 3, row0 = wg * 120;
  const uint16_t* wq = reinterpret_cast<const uint16_t*>(P.wq) + h * DH + g;
  const __nv_bfloat16* kp = P.k + (size_t)(b * NH + h) * SK * DH;
  const uint16_t* vp = reinterpret_cast<const uint16_t*>(P.v) + (size_t)(b * NH + h) * SK * DH + g;
#pragma unroll 1
  for (int t = w; t < 8; t += 4) {
    const int r0 = 16 * t + g, r1 = r0 + 8;
    const __nv_bfloat16* x0 = P.x + (size_t)(b * SQ + row0 + r0) * DM + 2 * q;
    const __nv_bfloat16* x1 = P.x + (size_t)(b * SQ + row0 + min(r1, 119)) * DM + 2 * q;
    float o[16][4];
#pragma unroll
    for (int n = 0; n < 16; n++) o[n][0] = o[n][1] = o[n][2] = o[n][3] = 0.f;
#pragma unroll 1
    for (int k0 = 0; k0 < DM; k0 += 16) {
      uint32_t a[4] = {*(const uint32_t*)(x0 + k0), *(const uint32_t*)(x1 + k0), *(const uint32_t*)(x0 + k0 + 8), *(const uint32_t*)(x1 + k0 + 8)};
      const uint16_t* wr = wq + (size_t)(k0 + 2 * q) * HD;
#pragma unroll
      for (int n = 0; n < 16; n++)
        mma16816(o[n], a, wr[8 * n] | ((uint32_t)wr[8 * n + HD] << 16), wr[8 * n + 8 * HD] | ((uint32_t)wr[8 * n + 9 * HD] << 16));
    }
    uint32_t qa[8][4];
#pragma unroll
    for (int k = 0; k < 8; k++) {
      qa[k][0] = pack(o[2 * k][0] * QSCALE, o[2 * k][1] * QSCALE);
      qa[k][1] = pack(o[2 * k][2] * QSCALE, o[2 * k][3] * QSCALE);
      qa[k][2] = pack(o[2 * k + 1][0] * QSCALE, o[2 * k + 1][1] * QSCALE);
      qa[k][3] = pack(o[2 * k + 1][2] * QSCALE, o[2 * k + 1][3] * QSCALE);
    }
#pragma unroll
    for (int n = 0; n < 16; n++) o[n][0] = o[n][1] = o[n][2] = o[n][3] = 0.f;
    float m0 = -INFINITY, m1 = -INFINITY, l0 = 0.f, l1 = 0.f;
#pragma unroll 1
    for (int key0 = 0; key0 < SK; key0 += 16) {
      float s[2][4];
#pragma unroll
      for (int nt = 0; nt < 2; nt++) {
        s[nt][0] = s[nt][1] = s[nt][2] = s[nt][3] = 0.f;
        const __nv_bfloat16* kr = kp + (size_t)(key0 + 8 * nt + g) * DH + 2 * q;
#pragma unroll
        for (int k = 0; k < 8; k++) mma16816(s[nt], qa[k], *(const uint32_t*)(kr + 16 * k), *(const uint32_t*)(kr + 16 * k + 8));
      }
      float n0 = fmaxf(fmaxf(s[0][0], s[0][1]), fmaxf(s[1][0], s[1][1])), n1 = fmaxf(fmaxf(s[0][2], s[0][3]), fmaxf(s[1][2], s[1][3]));
      n0 = fmaxf(n0, __shfl_xor_sync(~0u, n0, 1)); n1 = fmaxf(n1, __shfl_xor_sync(~0u, n1, 1));
      n0 = fmaxf(n0, __shfl_xor_sync(~0u, n0, 2)); n1 = fmaxf(n1, __shfl_xor_sync(~0u, n1, 2));
      n0 = fmaxf(n0, m0); n1 = fmaxf(n1, m1);
      const float z0 = n0 == -INFINITY ? 0.f : n0, z1 = n1 == -INFINITY ? 0.f : n1;
      const float c0 = ex2(m0 - z0), c1 = ex2(m1 - z1);
      m0 = n0; m1 = n1;
#pragma unroll
      for (int nt = 0; nt < 2; nt++) {
        s[nt][0] = ex2(s[nt][0] - z0); s[nt][1] = ex2(s[nt][1] - z0);
        s[nt][2] = ex2(s[nt][2] - z1); s[nt][3] = ex2(s[nt][3] - z1);
      }
      l0 = l0 * c0 + s[0][0] + s[0][1] + s[1][0] + s[1][1];
      l1 = l1 * c1 + s[0][2] + s[0][3] + s[1][2] + s[1][3];
      uint32_t pa[4] = {pack(s[0][0], s[0][1]), pack(s[0][2], s[0][3]), pack(s[1][0], s[1][1]), pack(s[1][2], s[1][3])};
      const uint16_t* vr = vp + (size_t)(key0 + 2 * q) * DH;
#pragma unroll
      for (int n = 0; n < 16; n++) {
        o[n][0] *= c0; o[n][1] *= c0; o[n][2] *= c1; o[n][3] *= c1;
        mma16816(o[n], pa, vr[8 * n] | ((uint32_t)vr[8 * n + DH] << 16), vr[8 * n + 8 * DH] | ((uint32_t)vr[8 * n + 9 * DH] << 16));
      }
    }
    l0 += __shfl_xor_sync(~0u, l0, 1); l1 += __shfl_xor_sync(~0u, l1, 1);
    l0 += __shfl_xor_sync(~0u, l0, 2); l1 += __shfl_xor_sync(~0u, l1, 2);
    const float i0 = 1.f / l0, i1 = 1.f / l1;
    __nv_bfloat16* oc = P.o + (size_t)(h * DH + 2 * q) * NROWS + b * SQ;
    const int p0 = o_pos(wg, r0), p1 = o_pos(wg, min(r1, 119));
#pragma unroll
    for (int n = 0; n < 16; n++) {
      oc[(size_t)(8 * n) * NROWS + p0] = __float2bfloat16(o[n][0] * i0);
      oc[(size_t)(8 * n + 1) * NROWS + p0] = __float2bfloat16(o[n][1] * i0);
      if (r1 < 120) {
        oc[(size_t)(8 * n) * NROWS + p1] = __float2bfloat16(o[n][2] * i1);
        oc[(size_t)(8 * n + 1) * NROWS + p1] = __float2bfloat16(o[n][3] * i1);
      }
    }
  }
}

__device__ __forceinline__ int bk(int ks) { return B_ORDER && ks < 48 ? 32 - (ks & 48) + (ks & 15) : ks; }
__device__ __forceinline__ uint32_t x_slot(uint32_t wg, uint32_t j) { return j < 2 ? (2 * wg + j) * XB : (2 * j + wg) * XB; }
__device__ __forceinline__ int unit_batch(int u) { return (u & 63) >> 2; }
__device__ __forceinline__ int unit_head(int u, int rank) { return (u >> 6) * 8 + (u & 3) * 2 + rank; }

__global__ void __cluster_dims__(2, 1, 1) __launch_bounds__(384, 1)
fused_attn_kernel(const __grid_constant__ CUtensorMap tm_x, const __grid_constant__ CUtensorMap tm_wq,
                  const __grid_constant__ CUtensorMap tm_k, const __grid_constant__ CUtensorMap tm_v,
                  const __grid_constant__ CUtensorMap tm_o, const __grid_constant__ CUtensorMap tm_wo,
                  const __grid_constant__ Params P) {
  extern __shared__ uint8_t smem_raw[];
  const uint32_t sb = ((uint32_t)__cvta_generic_to_shared(smem_raw) + 1023) & ~1023u;
  const int warp = __shfl_sync(~0u, threadIdx.x >> 5, 0);
  const int lane = threadIdx.x & 31;
  const int rank = blockIdx.x & 1, cl = blockIdx.x >> 1, ncl = gridDim.x >> 1;

  if (threadIdx.x == 0) {
    for (int i = 0; i < 6; i++) {
      mbar_init(sb + BAR_RFULL + 8 * i, 1); mbar_init(sb + BAR_REMPTY + 8 * i, 8);
      mbar_init(sb + BAR_BFULL + 8 * i, 1); mbar_init(sb + BAR_BEMPTY + 8 * i, 16);
    }
    for (int i = 0; i < 8; i++) mbar_init(sb + BAR_XFULL + 8 * i, 1);
    for (int i = 0; i < 4; i++) mbar_init(sb + BAR_XEMPTY + 8 * i, 8);
    for (int i = 0; i < 2; i++) { mbar_init(sb + BAR_STAGE + 8 * i, 4); mbar_init(sb + BAR_LSUM + 8 * i, 4); mbar_init(sb + BAR_INV + 8 * i, 1); }
    mbar_init(sb + BAR_GATE, 1);
    asm volatile("fence.mbarrier_init.release.cluster;" ::: "memory");
  }
  __syncwarp();
  asm volatile("barrier.cluster.arrive.relaxed.aligned;\nbarrier.cluster.wait.aligned;" ::: "memory");

  if (warp >= 8) {
    asm volatile("setmaxnreg.dec.sync.aligned.u32 24;");
    if (warp == 8) {
      uint64_t pol;
      asm volatile("createpolicy.fractional.L2::evict_first.b64 %0, 1.0;" : "=l"(pol));
      Ring r;
      auto load = [&](const CUtensorMap* m, int c1, int c2, bool ef) {
        mbar_wait(sb + BAR_REMPTY + 8 * r.slot, r.phase ^ 1);
        if (lane == 0) {
          mbar_expect(sb + BAR_RFULL + 8 * r.slot, RING_BYTES);
          if (ef) tma3d_hint(sb + r.slot * RING_BYTES, m, 0, c1, c2, sb + BAR_RFULL + 8 * r.slot, pol);
          else tma3d(sb + r.slot * RING_BYTES, m, 0, c1, c2, sb + BAR_RFULL + 8 * r.slot);
        }
        r.next();
      };
      auto pf_tile = [&](const __nv_bfloat16* p) {
        if (PF_LSU) {
#pragma unroll
          for (int i = 0; i < 4; i++) asm volatile("prefetch.global.L2 [%0];" ::"l"(p + (i * 32 + lane) * 64) : "memory");
        } else if (lane == 0) l2_prefetch(p, 16384, pol);
      };
      uint32_t gph = 0;
      const int rot = ROT * (blockIdx.x * 5 + (blockIdx.x >> 4));
      for (int u = cl; u < NUNITS; u += ncl) {
        const int h = unit_head(u, rank);
        const int krow = (unit_batch(u) * NH + h) * SK;
#pragma unroll 1
        for (int s = 0; s < 10; s++) {
          load(&tm_wq, s * 64, 2 * h, false);
          const int sp = u == cl ? s - PF_HOLD : s;
          if (sp >= 0 && sp < PF_N) {
            const size_t off = (size_t)(krow + ((PF_J0 + sp * PF_STEP + rot) & 15) * 64) * DH;
            if (PF_WHAT & 1) pf_tile(P.k + off);
            if (PF_WHAT & 2) pf_tile(P.v + off);
          }
          if (PF_FIRST && s >= PF_FIRST && s < PF_FIRST + 3) {
            const int f = s - PF_FIRST;
            pf_tile((f == 2 ? P.v : P.k) + (size_t)(krow + (((f & 1) + rot) & 15) * 64) * DH);
          }
        }
        if (GATE) mbar_wait(sb + BAR_GATE, gph), gph ^= 1;
#pragma unroll 1
        for (int j = 0; j <= 16; j++) {
          if (j < 16) load(&tm_k, krow + ((j + rot) & 15) * 64, 0, true);
          if (j == 1 + DPRO) load(&tm_v, krow + (rot & 15) * 64, 0, true);
          if (j > 1) load(&tm_v, krow + ((j - 1 + rot) & 15) * 64, 0, true);
        }
      }
      for (int t = cl; t < NOTILES; t += ncl) {
        const int row0 = (t >> 2) * 256 + rank * 128;
        const int b0 = row0 / SQ, b1 = (row0 + 127) / SQ;
#pragma unroll 1
        for (int ks = 0; ks < 64; ks++) {
          if (ks == 0 || ks == 48) {
            const unsigned* c = &g_cnt[((lane & 1 ? b1 : b0) * 4 + (ks ? 3 : min(lane >> 1, 2))) * 8];
            unsigned v, n = 0;
            do {
              asm volatile("ld.acquire.gpu.global.u32 %0, [%1];" : "=r"(v) : "l"(c) : "memory");
              if (++n > (1u << 26)) __trap();
            } while (v < 16);
            __syncwarp();
            asm volatile("fence.proxy.async.global;" ::: "memory");
          }
          load(&tm_o, bk(ks) * 64, row0 >> 6, O_EF);
          if (B_PF && ks + B_PF < 48 && (ks & 3) == (t & 3) && lane == 0) tma3d_prefetch(&tm_o, 0, bk(ks + B_PF) * 64, row0 >> 6);
        }
      }
      if (lane == 0 && atomicAdd(&g_cnt[512], 1) == gridDim.x - 1) {
        for (int i = 0; i <= 64; i++) g_cnt[i * 8] = 0;
      }
    } else if (warp == 9) {
      if (lane == 0) {
        uint32_t it = 0;
        for (int u = cl; u < NUNITS; u += ncl, it++) {
          const int row = unit_batch(u) * SQ + rank * 120;
#pragma unroll 1
          for (int s = 0; s < 10; s++) {
            const uint32_t j = s & 3, par = ((s >> 2) + (j < 2 ? it : 0)) & 1;
            mbar_wait(sb + BAR_XEMPTY + 8 * j, par ^ 1);
            const uint32_t fb = sb + BAR_XFULL + 32 * rank + 8 * j;
            mbar_expect(fb, XB);
            mbar_expect_cl(mapa(fb, rank ^ 1), XB);
            tma2d_mc(sb + OFF_Q + x_slot(rank, j), &tm_x, s * 64, row, fb);
            if (GATE && s == GATE) mbar_arrive(sb + BAR_GATE);
            if (X_PF && s < 2) {
#pragma unroll
              for (int i = 0; i < 3; i++)
                asm volatile("cp.async.bulk.prefetch.tensor.2d.L2.global [%0, {%1, %2}];" ::"l"(&tm_x), "r"((4 + 3 * s + i) * 64), "r"(row) : "memory");
            }
          }
        }
        uint32_t slot = rank, phase = 0;
        for (int t = cl; t < NOTILES; t += ncl) {
#pragma unroll 1
          for (int ks = rank; ks < 64; ks += 2) {
            mbar_wait(sb + BAR_BEMPTY + 8 * slot, phase);
            const uint32_t fb = sb + BAR_BFULL + 8 * slot;
            mbar_expect(fb, BB);
            mbar_expect_cl(mapa(fb, rank ^ 1), BB);
            tma3d_mc(sb + OFF_Q + slot * BB, &tm_wo, 0, bk(ks) * 64, (t & 3) * 5, fb);
            if (WO_PF && ks + WO_PF < 64 && ((ks >> 1) & 3) == ((t >> 2) & 3)) tma3d_prefetch(&tm_wo, 0, bk(ks + WO_PF) * 64, (t & 3) * 5);
            slot += 2;
            if (slot >= 6) { slot -= 6; phase ^= 1; }
          }
        }
      }
    } else {
      const int wg = warp - 10;
      if (TM_PF && lane == 0) {
        asm volatile("prefetch.tensormap [%0];" ::"l"(wg ? &tm_k : &tm_v) : "memory");
        asm volatile("prefetch.tensormap [%0];" ::"l"(wg ? &tm_o : &tm_wo) : "memory");
      }
      if (START_PF) {
        if (START_PF == 1) mbar_wait(sb + BAR_RFULL, 0);
        const __nv_bfloat16* xs = P.x + (size_t)(unit_batch(cl) * SQ + ((cl & 3) * 2 + rank) * 30 + min(lane, 29)) * DM + 256 + wg * 64;
#pragma unroll
        for (int i = 0; i < 3; i++) asm volatile("prefetch.global.L2 [%0];" ::"l"(xs + i * 128));
        if (lane < 16) asm volatile("prefetch.global.L2 [%0];" ::"l"(P.wq + (size_t)(384 + unit_batch(cl) * 16 + lane) * HD + unit_head(cl, rank) * DH + wg * 64));
      }
      uint32_t it = 0;
      for (int u = cl; u < NUNITS; u += ncl, it++) {
        mbar_wait(sb + BAR_LSUM + 8 * wg, it & 1);
        float l4[4], v[4];
        const uint32_t a = sb + OFF_L2 + wg * 2048 + lane * 16;
        asm volatile("ld.shared.v4.f32 {%0, %1, %2, %3}, [%4];" : "=f"(l4[0]), "=f"(l4[1]), "=f"(l4[2]), "=f"(l4[3]) : "r"(a) : "memory");
#pragma unroll
        for (int g = 1; g < 4; g++) {
          asm volatile("ld.shared.v4.f32 {%0, %1, %2, %3}, [%4];" : "=f"(v[0]), "=f"(v[1]), "=f"(v[2]), "=f"(v[3]) : "r"(a + g * 512) : "memory");
#pragma unroll
          for (int c = 0; c < 4; c++) l4[c] += v[c];
        }
#pragma unroll
        for (int c = 0; c < 4; c++) {
          float inv;
          asm("rcp.approx.ftz.f32 %0, %1;" : "=f"(inv) : "f"(l4[c]));
          l4[c] = l4[c] >= L_MIN && l4[c] <= L_MAX ? inv : __uint_as_float(0x7FFFFFFFu);
        }
        const uint32_t h0 = pack(l4[0], l4[1]), h1 = pack(l4[2], l4[3]);
        const uint32_t e0 = pack(l4[0] - __uint_as_float(h0 << 16), l4[1] - __uint_as_float(h0 & 0xFFFF0000u));
        const uint32_t e1 = pack(l4[2] - __uint_as_float(h1 << 16), l4[3] - __uint_as_float(h1 & 0xFFFF0000u));
        asm volatile("st.shared.v4.u32 [%0], {%1, %2, %3, %4};" ::"r"(sb + OFF_INV + wg * 512 + lane * 16), "r"(h0), "r"(e0), "r"(h1), "r"(e1) : "memory");
        __syncwarp();
        if (lane == 0) {
          mbar_arrive(sb + BAR_INV + 8 * wg);
          mbar_wait(sb + BAR_STAGE + 8 * wg, it & 1);
          __threadfence();
          asm volatile("red.relaxed.gpu.global.add.u32 [%0], 1;" ::"l"(&g_cnt[(unit_batch(u) * 4 + (u >> 6)) * 8]) : "memory");
        }
        __syncwarp();
      }
    }
  } else {
    asm volatile("setmaxnreg.inc.sync.aligned.u32 240;");
    const int wg = warp >> 2, w = warp & 3;
    const uint32_t qreg = sb + OFF_Q + wg * 2 * XB, preg = sb + OFF_P + (2 + wg) * XB;
    const uint32_t st_off = ((lane >> 4) * 8 + (lane & 7)) * 128 + (((2 * w + ((lane >> 3) & 1)) ^ (lane & 7)) << 4);
    const uint32_t xempty = mapa(sb + BAR_XEMPTY, wg);
    const int bar_id = 1 + wg;
    Ring r;
    uint32_t it = 0;
    const uint32_t qd = (qreg & 0x3FFFF) >> 4, pd = (preg & 0x3FFFF) >> 4;
    auto ring_addr = [&]() { return ((sb & 0x3FFFF) + r.slot * RING_BYTES) >> 4; };
    auto ring_wait = [&]() { mbar_wait(sb + BAR_RFULL + 8 * r.slot, r.phase); };
    auto release = [&](uint32_t slot) { if (lane == 0) mbar_arrive(sb + BAR_REMPTY + 8 * slot); };
    auto turn_wait = [&]() { asm volatile("bar.sync %0, 256;" ::"r"(3 + wg) : "memory"); };
    auto turn_pass = [&]() { asm volatile("bar.arrive %0, 256;" ::"r"(4 - wg) : "memory"); };

    uint32_t chk = 0;
    auto load_inv = [&](uint32_t (&iv)[30], uint32_t parity) {
      mbar_wait(sb + BAR_INV + 8 * wg, parity);
      chk = 0;
#pragma unroll
      for (int j = 0; j < 15; j++)
        asm volatile("ld.shared.v2.u32 {%0, %1}, [%2];" : "=r"(iv[2 * j]), "=r"(iv[2 * j + 1]) : "r"(sb + OFF_INV + wg * 512 + j * 32 + (lane & 3) * 8) : "memory");
    };
    auto norm = [&](uint32_t (&n)[8], const uint32_t (&po)[60], const uint32_t (&iv)[30], auto part) {
      constexpr int k = decltype(part)::value >> 1, j0 = (decltype(part)::value & 1) * 8;
#pragma unroll
      for (int j = 0; j < 8; j++)
        n[j] = j0 + j < 15 ? hfma2(po[15 * k + (j0 + j) % 15], iv[2 * ((j0 + j) % 15)], hfma2(po[15 * k + (j0 + j) % 15], iv[2 * ((j0 + j) % 15) + 1], 0x80008000u)) : 0x3F803F80u;
#pragma unroll
      for (int j = 0; j < 8; j += 2) chk = hfma2(n[j], n[j + 1], chk);
    };
    auto store = [&](const uint32_t (&n)[8], const char* optr, auto part) {
      constexpr int k = decltype(part)::value >> 1;
      const char* o = optr + (size_t)(8 * (k & 1) + 64 * (k >> 1)) * NROWS * 2;
      if ((decltype(part)::value & 1) == 0)
        asm volatile(
            "{\n.reg .pred p;\nsetp.ne.u64 p, %9, 0;\n"
            "@p st.global.v4.u32 [%8], {%0, %1, %2, %3};\n@p st.global.v4.u32 [%8 + 64], {%4, %5, %6, %7};\n}\n"
            ::"r"(n[0]), "r"(n[1]), "r"(n[2]), "r"(n[3]), "r"(n[4]), "r"(n[5]), "r"(n[6]), "r"(n[7]),
            "l"(o + (wg ? 288 : 0) + (lane & 3) * 16), "l"(optr) : "memory");
      else
        asm volatile(
            "{\n.reg .pred p;\nsetp.ne.u64 p, %10, 0;\n"
            "@p st.global.v4.u32 [%7 + 128], {%0, %1, %2, %3};\n@p st.global.v2.u32 [%8], {%4, %5};\n@p st.global.u32 [%9], %6;\n}\n"
            ::"r"(n[0]), "r"(n[1]), "r"(n[2]), "r"(n[3]), "r"(n[4]), "r"(n[5]), "r"(n[6]), "l"(o + (wg ? 288 : 0) + (lane & 3) * 16),
            "l"(o + (wg ? 256 : 192) + (lane & 3) * 8), "l"(o + (wg ? 240 : 224) + (lane & 3) * 4), "l"(optr) : "memory");
    };
    auto put = [&](const uint32_t (&po)[60], const uint32_t (&iv)[30], const char* optr, auto part) {
      uint32_t n[8];
      norm(n, po, iv, part);
      store(n, optr, part);
    };
    auto out_ptr = [&](int u) {
      return reinterpret_cast<const char*>(P.o + (size_t)(unit_head(u, rank) * DH + 16 * w + (lane >> 2)) * NROWS + unit_batch(u) * SQ);
    };
    auto unsafe = [&](bool valid) {
      const bool b = valid && ((chk & 0x7F80u) == 0x7F80u || (chk & 0x7F800000u) == 0x7F800000u);
      return __any_sync(~0u, bar_red_or(bar_id, b));
    };
    auto publish = [&]() { __syncwarp(); if (lane == 0) mbar_arrive(sb + BAR_STAGE + 8 * wg); };

    uint32_t po[60];
#pragma unroll
    for (int i = 0; i < 60; i++) po[i] = 0;
    const uint32_t nit = __shfl_sync(~0u, (NUNITS - cl + ncl - 1) / ncl, 0);
    for (; it < nit; it++) {
      const int up = cl + ((int)it - 1) * ncl;
      float o0[60], o1[60];
      uint32_t prev = 0;
      auto qstep = [&](int s, int acc) {
        const uint32_t j = s & 3, par = ((s >> 2) + (j < 2 ? it : 0)) & 1;
        TR(it * 160 + 3 * s);
        ring_wait();
        TR(it * 160 + 3 * s + 1);
        mbar_wait(sb + BAR_XFULL + 32 * wg + 8 * j, par);
        TR(it * 160 + 3 * s + 2);
        if (s >= ALT_FROM) turn_wait();
        wg_fence();
        mma_tn(o0, o1, ring_addr(), ((sb & 0x3FFFF) + OFF_Q + x_slot(wg, j)) >> 4, acc);
        wg_commit();
        if ((s >= ALT_FROM && !(MERGE89 && s == 8)) || (s == ALT_FROM - 1 && wg == 1)) turn_pass();
        if (s > 0) {
          wg_wait<1>();
          release(prev);
          if (s <= 6 && lane == 0) mbar_arrive_cl(xempty + 8 * ((s - 1) & 3));
        }
        prev = r.slot;
        r.next();
      };
      const char* optr = it > 0 ? out_ptr(up) : nullptr;
      uint32_t n7[8];
      {
        uint32_t iv[30];
        qstep(0, 0);
        if (it > 0) {
          fence_async_smem();
          __syncwarp();
          if (lane == 0) mbar_arrive_cl(xempty + 24);
        }
        qstep(1, 1); load_inv(iv, (it + 1) & 1); put(po, iv, optr, IC<0>());
        qstep(2, 1); put(po, iv, optr, IC<1>());
        qstep(3, 1); put(po, iv, optr, IC<2>());
        qstep(4, 1); put(po, iv, optr, IC<3>());
        qstep(5, 1); put(po, iv, optr, IC<4>());
        qstep(6, 1); put(po, iv, optr, IC<5>());
        qstep(7, 1); put(po, iv, optr, IC<6>());
        norm(n7, po, iv, IC<7>());
        if (LATE_AT == 3) store(n7, optr, IC<7>());
        qstep(8, 1);
        if (LATE_AT == 2) store(n7, optr, IC<7>());
      }
      TR(it * 160 + 27);
      ring_wait();
      TR(it * 160 + 28);
      mbar_wait(sb + BAR_XFULL + 32 * wg + 8, it & 1);
      TR(it * 160 + 29);
      if (!MERGE89) turn_wait();
      wg_fence();
      mma_tn_split(o0, o1, ring_addr(), qd + (XB >> 4));
      turn_pass();
      wg_wait<2>();
      release(prev);
      wg_wait<1>();
      reg_fence(o0);
      uint32_t pq[30];
#pragma unroll
      for (int j = 0; j < 30; j++) pq[j] = pack(o0[2 * j] * QSCALE, o0[2 * j + 1] * QSCALE);
      wg_wait<0>();
      reg_fence(o1);
      release(r.slot);
      r.next();
      TR(it * 160 + 30);
      bar_sync(bar_id);
#pragma unroll
      for (int j = 0; j < 14; j += 2) stsm4t(qreg + st_off + j * 1024, pq[2 * j], pq[2 * j + 1], pq[2 * j + 2], pq[2 * j + 3]);
      stsm2t(qreg + st_off + 14 * 1024, pq[28], pq[29]);
#pragma unroll
      for (int j = 0; j < 14; j += 2)
        stsm4t(qreg + XB + st_off + j * 1024, pack(o1[4 * j] * QSCALE, o1[4 * j + 1] * QSCALE), pack(o1[4 * j + 2] * QSCALE, o1[4 * j + 3] * QSCALE),
               pack(o1[4 * j + 4] * QSCALE, o1[4 * j + 5] * QSCALE), pack(o1[4 * j + 6] * QSCALE, o1[4 * j + 7] * QSCALE));
      stsm2t(qreg + XB + st_off + 14 * 1024, pack(o1[56] * QSCALE, o1[57] * QSCALE), pack(o1[58] * QSCALE, o1[59] * QSCALE));
      fence_async_smem();
      if (unsafe(it > 0)) {
        slow_path(P, unit_batch(up), unit_head(up, rank), wg, w, lane);
        optr = nullptr;
        if (!DPRO) {
#pragma unroll
          for (int i = 0; i < 60; i++) o0[i] = o1[i] = 0.f;
        }
      }
      TR(it * 160 + 32); TG(it * 160 + 142);

      float sc[60], l[30];
      uint32_t slot0 = r.slot;
      ring_wait();
      TR(it * 160 + 33);
      turn_wait();
      wg_fence();
      mma_qk(sc, ring_addr(), qd);
      wg_commit();
      r.next();
      uint32_t slot1 = r.slot;
      ring_wait();
      wg_fence();
      mma_qk(o1, ring_addr(), qd);
      wg_commit();
      r.next();
      turn_pass();
      if (LATE_AT == 0) store(n7, optr, IC<7>());
      wg_wait<1>();
      reg_fence(sc);
      TR(it * 160 + 35);
      release(slot0);
      exp_store<0, 15, true>(sc, l, preg + st_off);
      TR(it * 160 + 38); TG(it * 160 + 43);
      slot0 = r.slot;
      ring_wait();
      wg_fence();
      mma_qk(sc, ring_addr(), qd);
      wg_commit();
      r.next();
      wg_wait<1>();
      reg_fence(o1);
      TR(it * 160 + 41);
      release(slot1);
      exp_store<0, 15>(o1, l, preg - 2 * XB + st_off);
      fence_async_smem();
      bar_sync(bar_id);
      TR(it * 160 + 44);
      slot1 = r.slot;
      ring_wait();
      turn_wait();
      wg_fence();
      mma_tn(o0, o1, ring_addr(), pd, 0);
      wg_commit();
      r.next();
      ring_wait();
      wg_fence();
      mma_tn(o0, o1, ring_addr(), pd - (2 * XB >> 4), 1);
      wg_commit();
      turn_pass();
      if (LATE_AT == 1) store(n7, optr, IC<7>());
      if (it > 0) publish();
      wg_wait<1>();
      reg_fence(sc);
      release(slot0);
      release(slot1);
      bar_sync(bar_id);
      TR(it * 160 + 47);
      exp_store<0, VREL>(sc, l, preg + st_off);
      wg_wait<0>();
      reg_fence(o0); reg_fence(o1);
      release(r.slot);
      r.next();
      exp_store<VREL, 15>(sc, l, preg + st_off);
      fence_async_smem();
      bar_sync(bar_id);
      const bool more = it + 1 < nit;
#pragma unroll 1
      for (int s = DPRO ? 3 : 1; s < 16; s++) {
        const uint32_t kslot = r.slot;
        TR(it * 160 + 32 + 6 * s); TG(it * 160 + 37 + 6 * s);
        ring_wait();
        TR(it * 160 + 33 + 6 * s);
        turn_wait();
        wg_fence();
        mma_qk(sc, ring_addr(), qd);
        wg_commit();
        r.next();
        TR(it * 160 + 36 + 6 * s);
        ring_wait();
        TR(it * 160 + 34 + 6 * s);
        wg_fence();
        mma_tn(o0, o1, ring_addr(), pd - ((s - 1) & 1) * (2 * XB >> 4), DPRO || s != 1);
        wg_commit();
        if (wg == 0 || s < 15) turn_pass();
        wg_wait<1>();
        reg_fence(sc);
        TR(it * 160 + 35 + 6 * s);
        release(kslot);
        if (s == 15) {
          if (more) { if (lane < 2) mbar_arrive_cl(xempty + 8 * lane); }
          else if (lane < 3 && cl < NOTILES) mbar_arrive_cl(mapa(sb + BAR_BEMPTY + 8 * lane, lane & 1));
        }
        exp_store<0, VREL>(sc, l, preg - (s & 1) * 2 * XB + st_off);
        wg_wait<0>();
        reg_fence(o0); reg_fence(o1);
        release(r.slot);
        r.next();
        exp_store<VREL, 15>(sc, l, preg - (s & 1) * 2 * XB + st_off);
        fence_async_smem();
        bar_sync(bar_id);
      }
      TR(it * 160 + 128);
      ring_wait();
      wg_fence();
      mma_tn_split(o0, o1, ring_addr(), pd - (2 * XB >> 4));
      TR(it * 160 + 132);
      {
        const uint32_t a = preg + (8 * w + (lane >> 2)) * 480 + (lane & 3) * 8;
#pragma unroll
        for (int j = 0; j < 15; j++) asm volatile("st.shared.v2.f32 [%0], {%1, %2};" ::"r"(a + j * 32), "f"(l[2 * j]), "f"(l[2 * j + 1]) : "memory");
      }
      __syncwarp();
      float lv[8][4];
#pragma unroll
      for (int g = 0; g < 8; g++)
        asm volatile("ld.shared.v4.f32 {%0, %1, %2, %3}, [%4];" : "=f"(lv[g][0]), "=f"(lv[g][1]), "=f"(lv[g][2]), "=f"(lv[g][3])
                     : "r"(preg + (8 * w + g) * 480 + min(lane, 29) * 16) : "memory");
      TR(it * 160 + 133);
      wg_wait<1>();
      reg_fence(o0);
      TR(it * 160 + 134);
#pragma unroll
      for (int j = 0; j < 15; j++) { po[j] = pack(o0[4 * j], o0[4 * j + 1]); po[15 + j] = pack(o0[4 * j + 2], o0[4 * j + 3]); }
#pragma unroll
      for (int c = 0; c < 4; c++) lv[0][c] = ((lv[0][c] + lv[1][c]) + (lv[2][c] + lv[3][c])) + ((lv[4][c] + lv[5][c]) + (lv[6][c] + lv[7][c]));
      asm volatile("st.shared.v4.f32 [%0], {%1, %2, %3, %4};" ::"r"(sb + OFF_L2 + wg * 2048 + w * 512 + lane * 16), "f"(lv[0][0]), "f"(lv[0][1]),
                   "f"(lv[0][2]), "f"(lv[0][3]) : "memory");
      __syncwarp();
      if (lane == 0) mbar_arrive(sb + BAR_LSUM + 8 * wg);
      wg_wait<0>();
      reg_fence(o1);
      release(r.slot);
      r.next();
      if (more) { if (lane == 0) mbar_arrive_cl(xempty + 16); }
      else if (cl < NOTILES && lane <= wg) mbar_arrive_cl(mapa(sb + BAR_BEMPTY + 24 + 8 * lane, 1 - lane));
      TR(it * 160 + 130);
#pragma unroll
      for (int j = 0; j < 15; j++) { po[30 + j] = pack(o1[4 * j], o1[4 * j + 1]); po[45 + j] = pack(o1[4 * j + 2], o1[4 * j + 3]); }
      TR(it * 160 + 131); TG(it * 160 + 143);
    }
    const int u = cl + ((int)nit - 1) * ncl;
    uint32_t pb[60];
#pragma unroll
    for (int i = 0; i < 60; i++) pb[i] = po[i] ^ (gridDim.y - 1);

    uint32_t bslot = 0, bphase = 0;
    for (int t = cl; t < NOTILES || t == cl; t += ncl) {
      float acc[80];
      uint32_t prev = 0, bprev = 0;
      const bool tile = t < NOTILES;
      const bool last = t + ncl >= NOTILES;
      auto bstep = [&](int ks, int accf) {
        if (!(ks & 1)) TR(640 + ks); if ((ks & 7) == 0) TG(144 + (ks >> 3));
        ring_wait();
        mbar_wait(sb + BAR_BFULL + 8 * bslot, bphase);
        if (!(ks & 1)) TR(641 + ks);
        wg_fence();
        const uint32_t a = ring_addr() + wg * 512, bd = (((sb & 0x3FFFF) + OFF_Q + bslot * BB) >> 4) | ((4096u >> 4) << 16);
#pragma unroll
        for (int k = 0; k < 4; k++) wgmma_n160<1, 1>(acc, a + k * 128, HI128, bd + k * 64, HI64, k == 0 ? accf : 1);
        wg_commit();
        if (ks > 0) {
          wg_wait<1>();
          release(prev);
          if (lane == 0 && (ks < 59 || !last)) mbar_arrive_cl(mapa(sb + BAR_BEMPTY + 8 * bprev, bprev & 1));
        }
        prev = r.slot; bprev = bslot;
        r.next();
        if (++bslot == 6) { bslot = 0; bphase ^= 1; }
      };
      const char* optr = t == cl ? out_ptr(u) : nullptr;
      uint32_t iv[30];
      if (tile) {
        bstep(0, 0);
        if (t == cl) {
          fence_async_smem();
          __syncwarp();
          if (lane < 2 - wg) mbar_arrive_cl(mapa(sb + BAR_BEMPTY + 40 - 8 * lane, 1 - lane));
        }
        bstep(1, 1);
        bstep(2, 1); load_inv(iv, (nit + 1) & 1); put(pb, iv, optr, IC<0>()); bstep(3, 1);
        bstep(4, 1); put(pb, iv, optr, IC<1>()); bstep(5, 1);
        bstep(6, 1); put(pb, iv, optr, IC<2>()); bstep(7, 1);
        bstep(8, 1); put(pb, iv, optr, IC<3>()); bstep(9, 1);
        bstep(10, 1); put(pb, iv, optr, IC<4>()); bstep(11, 1);
        bstep(12, 1); put(pb, iv, optr, IC<5>()); bstep(13, 1);
        bstep(14, 1); put(pb, iv, optr, IC<6>()); bstep(15, 1);
        bstep(16, 1); put(pb, iv, optr, IC<7>());
        wg_wait<0>();
        reg_fence(acc);
      } else {
#pragma unroll
        for (int i = 0; i < 80; i++) acc[i] = 0.f;
        load_inv(iv, (nit + 1) & 1);
        put(pb, iv, optr, IC<0>()); put(pb, iv, optr, IC<1>()); put(pb, iv, optr, IC<2>()); put(pb, iv, optr, IC<3>());
        put(pb, iv, optr, IC<4>()); put(pb, iv, optr, IC<5>()); put(pb, iv, optr, IC<6>()); put(pb, iv, optr, IC<7>());
      }
      if (unsafe(t == cl)) slow_path(P, unit_batch(u), unit_head(u, rank), wg, w, lane);
      if (t == cl) publish();
      if (!tile) break;
#pragma unroll 1
      for (int ks = 17; ks < 64; ks++) {
        if (END_SKEW && wg == 1 && ks == 64 - END_SKEW) turn_wait();
        bstep(ks, 1);
      }
      if (END_SKEW && wg == 0) turn_pass();
      wg_wait<0>();
      reg_fence(acc);
      release(prev);
      if (lane == 0 && !last) mbar_arrive_cl(mapa(sb + BAR_BEMPTY + 8 * bprev, bprev & 1));
      TR(158); TG(156);
      const int pos0 = (t >> 2) * 256 + rank * 128 + wg * 64 + w * 16;
      if (last) {
        bar_sync(bar_id);
        const uint32_t st = sb + w * RING_BYTES + wg * 8192;
        const uint32_t sa = st + (lane & 15) * 336 + (lane >> 4) * 16;
#pragma unroll
        for (int j = 0; j < 20; j += 2)
          asm volatile("stmatrix.sync.aligned.m8n8.x4.shared.b16 [%0], {%1,%2,%3,%4};" ::"r"(sa + j * 16), "r"(pack(acc[4 * j], acc[4 * j + 1])),
                       "r"(pack(acc[4 * j + 2], acc[4 * j + 3])), "r"(pack(acc[4 * j + 4], acc[4 * j + 5])), "r"(pack(acc[4 * j + 6], acc[4 * j + 7])) : "memory");
        if (EPI_STG) {
          __syncwarp();
          const int lane = __shfl_sync(~0u, (int)(threadIdx.x & 31), threadIdx.x & 31);
          const int myrow = o_row(pos0 + (lane & 15));
#pragma unroll
          for (int i = 0; i < 10; i++) {
            const int c = i * 32 + lane, rr = c / 20, cc = c - rr * 20;
            uint4 v;
            asm volatile("ld.shared.v4.u32 {%0, %1, %2, %3}, [%4];" : "=r"(v.x), "=r"(v.y), "=r"(v.z), "=r"(v.w) : "r"(st + rr * 336 + cc * 16) : "memory");
            *reinterpret_cast<uint4*>(P.out + (size_t)__shfl_sync(~0u, myrow, rr) * DM + (t & 3) * 160 + cc * 8) = v;
          }
        } else {
          fence_async_smem();
          __syncwarp();
          if (lane < 16) {
            __nv_bfloat16* dst = P.out + (size_t)o_row(pos0 + lane) * DM + (t & 3) * 160;
            asm volatile("cp.async.bulk.global.shared::cta.bulk_group [%0], [%1], 320;" ::"l"(dst), "r"(st + lane * 336) : "memory");
            asm volatile("cp.async.bulk.commit_group;" ::: "memory");
            asm volatile("cp.async.bulk.wait_group.read 0;" ::: "memory");
          }
        }
      } else {
        __nv_bfloat16* op0 = P.out + (size_t)o_row(pos0 + (lane >> 2)) * DM + (t & 3) * 160 + (lane & 3) * 2;
        __nv_bfloat16* op1 = P.out + (size_t)o_row(pos0 + (lane >> 2) + 8) * DM + (t & 3) * 160 + (lane & 3) * 2;
#pragma unroll
        for (int j = 0; j < 20; j++) {
          *reinterpret_cast<uint32_t*>(op0 + j * 8) = pack(acc[4 * j], acc[4 * j + 1]);
          *reinterpret_cast<uint32_t*>(op1 + j * 8) = pack(acc[4 * j + 2], acc[4 * j + 3]);
        }
      }
#pragma unroll
      for (int i = 0; i < 60; i++) pb[i] = 0;
    }
    TR(159);
  }
}

typedef CUresult (*EncodeFn)(CUtensorMap*, CUtensorMapDataType, cuuint32_t, void*, const cuuint64_t*, const cuuint64_t*,
                             const cuuint32_t*, const cuuint32_t*, CUtensorMapInterleave, CUtensorMapSwizzle,
                             CUtensorMapL2promotion, CUtensorMapFloatOOBfill);

void make_map(EncodeFn enc, CUtensorMap* m, const void* p, int rank, const cuuint64_t* dims, const cuuint64_t* strides,
              const cuuint32_t* box, CUtensorMapSwizzle sw, CUtensorMapL2promotion promo) {
  cuuint32_t es[3] = {1, 1, 1};
  enc(m, CU_TENSOR_MAP_DATA_TYPE_BFLOAT16, rank, const_cast<void*>(p), dims, strides, box, es, CU_TENSOR_MAP_INTERLEAVE_NONE, sw,
      promo, CU_TENSOR_MAP_FLOAT_OOB_FILL_NONE);
}

}

extern "C" void kernel_launch(void* const* d_in, const int* in_sizes, int n_in, void* d_out, int out_size) {
  static EncodeFn enc = nullptr;
  static int nclusters = 0;
  static void* o_ptr = nullptr;
  if (!enc) {
    cudaDriverEntryPointQueryResult qr;
    cudaGetDriverEntryPoint("cuTensorMapEncodeTiled", (void**)&enc, cudaEnableDefault, &qr);
    cudaFuncSetAttribute(fused_attn_kernel, cudaFuncAttributeMaxDynamicSharedMemorySize, SMEM_BYTES);
    cudaGetSymbolAddress(&o_ptr, g_o);
    cudaLaunchConfig_t cfg = {};
    cfg.gridDim = 128; cfg.blockDim = 384; cfg.dynamicSmemBytes = SMEM_BYTES;
    cudaLaunchAttribute at; at.id = cudaLaunchAttributeClusterDimension;
    at.val.clusterDim.x = 2; at.val.clusterDim.y = 1; at.val.clusterDim.z = 1;
    cfg.attrs = &at; cfg.numAttrs = 1;
    int n = 0;
    cudaOccupancyMaxActiveClusters(&n, fused_attn_kernel, &cfg);
    nclusters = n >= 64 || n <= 0 ? 64 : n;
  }
  const __nv_bfloat16* x = (const __nv_bfloat16*)d_in[0];
  const __nv_bfloat16* k = (const __nv_bfloat16*)d_in[1];
  const __nv_bfloat16* v = (const __nv_bfloat16*)d_in[2];
  const __nv_bfloat16* wq = (const __nv_bfloat16*)d_in[3];
  const __nv_bfloat16* wo = (const __nv_bfloat16*)d_in[4];
  CUtensorMap tm_x, tm_wq, tm_k, tm_v, tm_o, tm_wo;
  const auto S128 = CU_TENSOR_MAP_SWIZZLE_128B;
  const auto P128 = CU_TENSOR_MAP_L2_PROMOTION_L2_128B, P256 = CU_TENSOR_MAP_L2_PROMOTION_L2_256B;
  { cuuint64_t d[2] = {DM, NB * SQ}, s[1] = {DM * 2}; cuuint32_t b[2] = {64, 120}; make_map(enc, &tm_x, x, 2, d, s, b, S128, P128); }
  { cuuint64_t d[3] = {64, DM, HD / 64}, s[2] = {HD * 2, 128}; cuuint32_t b[3] = {64, 64, 2}; make_map(enc, &tm_wq, wq, 3, d, s, b, S128, P256); }
  { cuuint64_t d[3] = {64, NB * NH * SK, 2}, s[2] = {DH * 2, 128}; cuuint32_t b[3] = {64, 64, 2};
    make_map(enc, &tm_k, k, 3, d, s, b, S128, KV_PROMO); make_map(enc, &tm_v, v, 3, d, s, b, S128, KV_PROMO); }
  { cuuint64_t d[3] = {64, HD, NROWS / 64}, s[2] = {NROWS * 2, 128}; cuuint32_t b[3] = {64, 64, 2}; make_map(enc, &tm_o, o_ptr, 3, d, s, b, S128, P256); }
  { cuuint64_t d[3] = {32, HD, DM / 32}, s[2] = {DM * 2, 64}; cuuint32_t b[3] = {32, 64, 5};
    make_map(enc, &tm_wo, wo, 3, d, s, b, CU_TENSOR_MAP_SWIZZLE_64B, P128); }
  Params P{x, k, v, wq, (__nv_bfloat16*)d_out, (__nv_bfloat16*)o_ptr};
  fused_attn_kernel<<<2 * nclusters, 384, SMEM_BYTES>>>(tm_x, tm_wq, tm_k, tm_v, tm_o, tm_wo, P);
}
```

```cpp
#include <cuda_runtime.h>
#include <cuda.h>
#include <cuda_bf16.h>
#include <stdint.h>

namespace {

constexpr int NB = 16, SQ = 240, DM = 640, NH = 32, SK = 1024, DH = 128, HD = NH * DH;
constexpr int NROWS = NB * SQ;
constexpr int NUNITS = 256;
#define DPRO 0
#define LATE_AT 0
#define ALT_FROM 5
#define MERGE89 1
#define END_SKEW 5
#define VREL 8
#define PF_HOLD 6
#define PF_N 4
#define PF_J0 3
#define PF_STEP 3
#define ROT 1
#define O_EF 1
#define B_ORDER 1
#define WO_PF 6
#define NOBAR 1
#define MAXCL 66
#define SMID_TOP 88
constexpr int NOTILES = 60;
constexpr float QSCALE = 0.08838834764831845f * 1.4426950408889634f;
constexpr float L_MIN = 9.5367431640625e-07f;
constexpr float L_MAX = 1.152921504606846976e18f;

constexpr uint32_t RING_SLOTS = 6, RING_BYTES = 16384;
constexpr uint32_t XB = 15360;
constexpr uint32_t BB = 20480;
constexpr uint32_t OFF_Q = RING_SLOTS * RING_BYTES;
constexpr uint32_t OFF_P = OFF_Q + 4 * XB;
constexpr uint32_t OFF_INV = OFF_P + 4 * XB;
constexpr uint32_t OFF_L2 = OFF_INV + 1024;
constexpr uint32_t OFF_BAR = OFF_L2 + 4096;
constexpr uint32_t BAR_RFULL = OFF_BAR, BAR_REMPTY = BAR_RFULL + 48, BAR_XFULL = BAR_REMPTY + 48,
    BAR_XEMPTY = BAR_XFULL + 64, BAR_BFULL = BAR_XEMPTY + 32, BAR_BEMPTY = BAR_BFULL + 48, BAR_STAGE = BAR_BEMPTY + 48;
constexpr uint32_t BAR_ROLE = BAR_STAGE + 16, BAR_LSUM = BAR_ROLE + 24, BAR_INV = BAR_LSUM + 16;
constexpr uint32_t OFF_TR = BAR_INV + 16;
constexpr uint32_t SMEM_BYTES = OFF_TR + 1024;

constexpr uint32_t HI128 = (1u << 30) | (1024 >> 4);
constexpr uint32_t HI64 = (2u << 30) | (512 >> 4);

__device__ __nv_bfloat16 g_o[HD * NROWS];
__device__ unsigned g_cnt[67 * 8];
#define TR(i)
#define TG(i)

struct Params {
  const __nv_bfloat16 *x, *k, *v, *wq;
  __nv_bfloat16 *out, *o;
};

__device__ __forceinline__ void wg_fence() { asm volatile("wgmma.fence.sync.aligned;" ::: "memory"); }
__device__ __forceinline__ void wg_commit() { asm volatile("wgmma.commit_group.sync.aligned;" ::: "memory"); }
template <int N> __device__ __forceinline__ void wg_wait() { asm volatile("wgmma.wait_group.sync.aligned %0;" ::"n"(N) : "memory"); }
template <int N> __device__ __forceinline__ void reg_fence(float (&r)[N]) {
#pragma unroll
  for (int i = 0; i < N; i++) asm volatile("" : "+f"(r[i])::"memory");
}
template <int TA, int TB>
__device__ __forceinline__ void wgmma_n120(float (&d)[60], uint32_t a_lo, uint32_t a_hi, uint32_t b_lo, uint32_t b_hi, int acc) {
  asm volatile(
      "{\n.reg .pred p;\n.reg .b64 da, db;\nsetp.ne.b32 p, %64, 0;\n"
      "mov.b64 da, {%60, %61};\nmov.b64 db, {%62, %63};\n"
      "wgmma.mma_async.sync.aligned.m64n120k16.f32.bf16.bf16 {"
      "%0, %1, %2, %3, %4, %5, %6, %7, %8, %9, %10, %11, %12, %13, %14, %15, %16, %17, %18, %19, %20, %21, %22, %23, "
      "%24, %25, %26, %27, %28, %29, %30, %31, %32, %33, %34, %35, %36, %37, %38, %39, %40, %41, %42, %43, %44, %45, "
      "%46, %47, %48, %49, %50, %51, %52, %53, %54, %55, %56, %57, %58, %59"
      "}, da, db, p, 1, 1, %65, %66;\n}\n"
      : "+f"(d[0]), "+f"(d[1]), "+f"(d[2]), "+f"(d[3]), "+f"(d[4]), "+f"(d[5]), "+f"(d[6]), "+f"(d[7]), "+f"(d[8]),
        "+f"(d[9]), "+f"(d[10]), "+f"(d[11]), "+f"(d[12]), "+f"(d[13]), "+f"(d[14]), "+f"(d[15]), "+f"(d[16]),
        "+f"(d[17]), "+f"(d[18]), "+f"(d[19]), "+f"(d[20]), "+f"(d[21]), "+f"(d[22]), "+f"(d[23]), "+f"(d[24]),
        "+f"(d[25]), "+f"(d[26]), "+f"(d[27]), "+f"(d[28]), "+f"(d[29]), "+f"(d[30]), "+f"(d[31]), "+f"(d[32]),
        "+f"(d[33]), "+f"(d[34]), "+f"(d[35]), "+f"(d[36]), "+f"(d[37]), "+f"(d[38]), "+f"(d[39]), "+f"(d[40]),
        "+f"(d[41]), "+f"(d[42]), "+f"(d[43]), "+f"(d[44]), "+f"(d[45]), "+f"(d[46]), "+f"(d[47]), "+f"(d[48]),
        "+f"(d[49]), "+f"(d[50]), "+f"(d[51]), "+f"(d[52]), "+f"(d[53]), "+f"(d[54]), "+f"(d[55]), "+f"(d[56]),
        "+f"(d[57]), "+f"(d[58]), "+f"(d[59])
      : "r"(a_lo), "r"(a_hi), "r"(b_lo), "r"(b_hi), "r"(acc), "n"(TA), "n"(TB));
}

template <int TA, int TB>
__device__ __forceinline__ void wgmma_n160(float (&d)[80], uint32_t a_lo, uint32_t a_hi, uint32_t b_lo, uint32_t b_hi, int acc) {
  asm volatile(
      "{\n.reg .pred p;\n.reg .b64 da, db;\nsetp.ne.b32 p, %84, 0;\n"
      "mov.b64 da, {%80, %81};\nmov.b64 db, {%82, %83};\n"
      "wgmma.mma_async.sync.aligned.m64n160k16.f32.bf16.bf16 {"
      "%0, %1, %2, %3, %4, %5, %6, %7, %8, %9, %10, %11, %12, %13, %14, %15, %16, %17, %18, %19, %20, %21, %22, %23, "
      "%24, %25, %26, %27, %28, %29, %30, %31, %32, %33, %34, %35, %36, %37, %38, %39, %40, %41, %42, %43, %44, %45, "
      "%46, %47, %48, %49, %50, %51, %52, %53, %54, %55, %56, %57, %58, %59, %60, %61, %62, %63, %64, %65, %66, %67, "
      "%68, %69, %70, %71, %72, %73, %74, %75, %76, %77, %78, %79"
      "}, da, db, p, 1, 1, %85, %86;\n}\n"
      : "+f"(d[0]), "+f"(d[1]), "+f"(d[2]), "+f"(d[3]), "+f"(d[4]), "+f"(d[5]), "+f"(d[6]), "+f"(d[7]), "+f"(d[8]),
        "+f"(d[9]), "+f"(d[10]), "+f"(d[11]), "+f"(d[12]), "+f"(d[13]), "+f"(d[14]), "+f"(d[15]), "+f"(d[16]),
        "+f"(d[17]), "+f"(d[18]), "+f"(d[19]), "+f"(d[20]), "+f"(d[21]), "+f"(d[22]), "+f"(d[23]), "+f"(d[24]),
        "+f"(d[25]), "+f"(d[26]), "+f"(d[27]), "+f"(d[28]), "+f"(d[29]), "+f"(d[30]), "+f"(d[31]), "+f"(d[32]),
        "+f"(d[33]), "+f"(d[34]), "+f"(d[35]), "+f"(d[36]), "+f"(d[37]), "+f"(d[38]), "+f"(d[39]), "+f"(d[40]),
        "+f"(d[41]), "+f"(d[42]), "+f"(d[43]), "+f"(d[44]), "+f"(d[45]), "+f"(d[46]), "+f"(d[47]), "+f"(d[48]),
        "+f"(d[49]), "+f"(d[50]), "+f"(d[51]), "+f"(d[52]), "+f"(d[53]), "+f"(d[54]), "+f"(d[55]), "+f"(d[56]),
        "+f"(d[57]), "+f"(d[58]), "+f"(d[59]), "+f"(d[60]), "+f"(d[61]), "+f"(d[62]), "+f"(d[63]), "+f"(d[64]),
        "+f"(d[65]), "+f"(d[66]), "+f"(d[67]), "+f"(d[68]), "+f"(d[69]), "+f"(d[70]), "+f"(d[71]), "+f"(d[72]),
        "+f"(d[73]), "+f"(d[74]), "+f"(d[75]), "+f"(d[76]), "+f"(d[77]), "+f"(d[78]), "+f"(d[79])
      : "r"(a_lo), "r"(a_hi), "r"(b_lo), "r"(b_hi), "r"(acc), "n"(TA), "n"(TB));
}
__device__ __forceinline__ void mbar_init(uint32_t bar, int cnt) { asm volatile("mbarrier.init.shared::cta.b64 [%0], %1;" ::"r"(bar), "r"(cnt)); }
__device__ __forceinline__ void mbar_expect(uint32_t bar, uint32_t bytes) {
  asm volatile("mbarrier.arrive.expect_tx.shared::cta.b64 _, [%0], %1;" ::"r"(bar), "r"(bytes) : "memory");
}
__device__ __forceinline__ uint32_t mapa(uint32_t addr, uint32_t cta) {
  uint32_t r; asm("mapa.shared::cluster.u32 %0, %1, %2;" : "=r"(r) : "r"(addr), "r"(cta)); return r;
}
__device__ __forceinline__ void mbar_expect_cl(uint32_t cbar, uint32_t bytes) {
  asm volatile("mbarrier.arrive.expect_tx.shared::cluster.b64 _, [%0], %1;" ::"r"(cbar), "r"(bytes) : "memory");
}
__device__ __forceinline__ void mbar_arrive(uint32_t bar) { asm volatile("mbarrier.arrive.shared::cta.b64 _, [%0];" ::"r"(bar) : "memory"); }
__device__ __forceinline__ void mbar_arrive_cl(uint32_t cbar) { asm volatile("mbarrier.arrive.shared::cluster.b64 _, [%0];" ::"r"(cbar) : "memory"); }
__device__ __forceinline__ void mbar_wait(uint32_t bar, uint32_t parity) {
  asm volatile(
      "{\n.reg .pred p;\n.reg .u32 n;\n"
      "mbarrier.try_wait.parity.shared::cta.b64 p, [%0], %1;\n@p bra WAIT_DONE;\n"
      "mov.u32 n, 0;\n"
      "WAIT_LOOP:\n"
      "mbarrier.try_wait.parity.shared::cta.b64 p, [%0], %1;\n@p bra WAIT_DONE;\n"
      "add.u32 n, n, 1;\nsetp.lt.u32 p, n, 0x4000000;\n@p bra WAIT_LOOP;\ntrap;\n"
      "WAIT_DONE:\n}\n" ::"r"(bar), "r"(parity) : "memory");
}
__device__ __forceinline__ void mbar_wait_cl(uint32_t bar, uint32_t parity) {
  asm volatile(
      "{\n.reg .pred p;\n.reg .u32 n;\nmov.u32 n, 0;\n"
      "WAIT_LOOP:\n"
      "mbarrier.try_wait.parity.acquire.cluster.shared::cta.b64 p, [%0], %1;\n@p bra WAIT_DONE;\n"
      "add.u32 n, n, 1;\nsetp.lt.u32 p, n, 0x4000000;\n@p bra WAIT_LOOP;\ntrap;\n"
      "WAIT_DONE:\n}\n" ::"r"(bar), "r"(parity) : "memory");
}
__device__ __forceinline__ void tma3d(uint32_t dst, const CUtensorMap* m, int c0, int c1, int c2, uint32_t bar) {
  asm volatile("cp.async.bulk.tensor.3d.shared::cluster.global.mbarrier::complete_tx::bytes [%0], [%1, {%3, %4, %5}], [%2];"
               ::"r"(dst), "l"(m), "r"(bar), "r"(c0), "r"(c1), "r"(c2) : "memory");
}
__device__ __forceinline__ void tma3d_hint(uint32_t dst, const CUtensorMap* m, int c0, int c1, int c2, uint32_t bar, uint64_t pol) {
  asm volatile("cp.async.bulk.tensor.3d.shared::cluster.global.mbarrier::complete_tx::bytes.L2::cache_hint [%0], [%1, {%3, %4, %5}], [%2], %6;"
               ::"r"(dst), "l"(m), "r"(bar), "r"(c0), "r"(c1), "r"(c2), "l"(pol) : "memory");
}
__device__ __forceinline__ void tma2d_mc(uint32_t dst, const CUtensorMap* m, int c0, int c1, uint32_t bar) {
  asm volatile("cp.async.bulk.tensor.2d.shared::cluster.global.mbarrier::complete_tx::bytes.multicast::cluster [%0], [%1, {%3, %4}], [%2], %5;"
               ::"r"(dst), "l"(m), "r"(bar), "r"(c0), "r"(c1), "h"((uint16_t)3) : "memory");
}
__device__ __forceinline__ void tma3d_mc(uint32_t dst, const CUtensorMap* m, int c0, int c1, int c2, uint32_t bar) {
  asm volatile("cp.async.bulk.tensor.3d.shared::cluster.global.mbarrier::complete_tx::bytes.multicast::cluster [%0], [%1, {%3, %4, %5}], [%2], %6;"
               ::"r"(dst), "l"(m), "r"(bar), "r"(c0), "r"(c1), "r"(c2), "h"((uint16_t)3) : "memory");
}
__device__ __forceinline__ void l2_prefetch(const void* p, uint32_t bytes) {
  asm volatile("cp.async.bulk.prefetch.L2.global [%0], %1;" ::"l"(p), "r"(bytes) : "memory");
}
__device__ __forceinline__ void fence_async_smem() { asm volatile("fence.proxy.async.shared::cta;" ::: "memory"); }
__device__ __forceinline__ void bar_sync(int wg) {
  if (wg == 0) asm volatile("bar.sync 1, 128;" ::: "memory");
  else asm volatile("bar.sync 2, 128;" ::: "memory");
}
__device__ __forceinline__ bool bar_red_or(int id, bool v) {
  uint32_t r;
  asm volatile("{\n.reg .pred p, q;\nsetp.ne.u32 p, %2, 0;\nbar.red.or.pred q, %1, 128, p;\nselp.u32 %0, 1, 0, q;\n}\n"
               : "=r"(r) : "r"(1 + id), "r"((uint32_t)v) : "memory");
  return r != 0;
}
__device__ __forceinline__ uint32_t hfma2(uint32_t a, uint32_t b, uint32_t c) { uint32_t r; asm("fma.rn.bf16x2 %0, %1, %2, %3;" : "=r"(r) : "r"(a), "r"(b), "r"(c)); return r; }
__device__ __forceinline__ float ex2(float x) { float y; asm("ex2.approx.ftz.f32 %0, %1;" : "=f"(y) : "f"(x)); return y; }
__device__ __forceinline__ uint32_t pack(float lo, float hi) { uint32_t r; asm("cvt.rn.bf16x2.f32 %0, %1, %2;" : "=r"(r) : "f"(hi), "f"(lo)); return r; }
__device__ __forceinline__ void stsm4t(uint32_t a, uint32_t r0, uint32_t r1, uint32_t r2, uint32_t r3) {
  asm volatile("stmatrix.sync.aligned.m8n8.x4.trans.shared.b16 [%0], {%1,%2,%3,%4};" ::"r"(a), "r"(r0), "r"(r1), "r"(r2), "r"(r3) : "memory");
}
__device__ __forceinline__ void stsm2t(uint32_t a, uint32_t r0, uint32_t r1) {
  asm volatile("stmatrix.sync.aligned.m8n8.x2.trans.shared.b16 [%0], {%1,%2};" ::"r"(a), "r"(r0), "r"(r1) : "memory");
}
__device__ __forceinline__ void mma16816(float (&d)[4], const uint32_t (&a)[4], uint32_t b0, uint32_t b1) {
  asm volatile("mma.sync.aligned.m16n8k16.row.col.f32.bf16.bf16.f32 {%0,%1,%2,%3}, {%4,%5,%6,%7}, {%8,%9}, {%0,%1,%2,%3};"
               : "+f"(d[0]), "+f"(d[1]), "+f"(d[2]), "+f"(d[3]) : "r"(a[0]), "r"(a[1]), "r"(a[2]), "r"(a[3]), "r"(b0), "r"(b1));
}

template <int V> struct IC { static constexpr int value = V; };

struct Ring {
  uint32_t slot = 0, phase = 0;
  __device__ __forceinline__ void next() { if (++slot == RING_SLOTS) { slot = 0; phase ^= 1; } }
};

__device__ __forceinline__ void mma_tn(float (&o0)[60], float (&o1)[60], uint32_t a, uint32_t b, int acc) {
#pragma unroll
  for (int k = 0; k < 4; k++) {
    wgmma_n120<1, 0>(o0, a + k * 128, HI128, b + k * 2, HI128, k == 0 ? acc : 1);
    wgmma_n120<1, 0>(o1, a + 512 + k * 128, HI128, b + k * 2, HI128, k == 0 ? acc : 1);
  }
}
__device__ __forceinline__ void mma_tn_split(float (&o0)[60], float (&o1)[60], uint32_t a, uint32_t b) {
#pragma unroll
  for (int k = 0; k < 4; k++) wgmma_n120<1, 0>(o0, a + k * 128, HI128, b + k * 2, HI128, 1);
  wg_commit();
#pragma unroll
  for (int k = 0; k < 4; k++) wgmma_n120<1, 0>(o1, a + 512 + k * 128, HI128, b + k * 2, HI128, 1);
  wg_commit();
}
__device__ __forceinline__ void mma_qk(float (&s)[60], uint32_t a, uint32_t q) {
#pragma unroll
  for (int k = 0; k < 8; k++)
    wgmma_n120<0, 0>(s, a + (k >> 2) * 512 + (k & 3) * 2, HI128, q + (k >> 2) * (XB >> 4) + (k & 3) * 2, HI128, k != 0);
}
template <int J0, int J1, bool FIRST = false>
__device__ __forceinline__ void exp_store(const float (&s)[60], float (&l)[30], uint32_t dst) {
#pragma unroll
  for (int j = J0; j < J1; j += 2) {
    uint32_t p[4];
#pragma unroll
    for (int jj = 0; jj < 2; jj++) {
      if (j + jj < 15) {
        const int c = j + jj;
        float e0 = ex2(s[4 * c]), e1 = ex2(s[4 * c + 1]), e2 = ex2(s[4 * c + 2]), e3 = ex2(s[4 * c + 3]);
        if (FIRST) { l[2 * c] = e0 + e2; l[2 * c + 1] = e1 + e3; }
        else { l[2 * c] += e0; l[2 * c + 1] += e1; l[2 * c] += e2; l[2 * c + 1] += e3; }
        p[2 * jj] = pack(e0, e1); p[2 * jj + 1] = pack(e2, e3);
      }
    }
    if (j + 1 < 15) stsm4t(dst + j * 1024, p[0], p[1], p[2], p[3]);
    else stsm2t(dst + j * 1024, p[0], p[1]);
  }
}

__device__ __forceinline__ int o_pos(int wg, int r) {
  const int j = r >> 3, q = (r >> 1) & 3, c = r & 1;
  if (j < 12) return (wg ? 144 : 0) + (j >> 2) * 32 + q * 8 + (j & 3) * 2 + c;
  if (j < 14) return (wg ? 128 : 96) + q * 4 + (j - 12) * 2 + c;
  return (wg ? 120 : 112) + q * 2 + c;
}
__device__ __forceinline__ int o_row(int p) {
  const int b = p / SQ, r = p - b * SQ, wg = r >= 120, c = r & 1;
  const int a = r - (wg ? 144 : 0), m = r - (wg ? 128 : 96), e = r - (wg ? 120 : 112);
  int row;
  if (a >= 0 && a < 96) row = ((a >> 5) * 4 + ((a >> 1) & 3)) * 8 + ((a >> 3) & 3) * 2 + c;
  else if (m >= 0 && m < 16) row = (12 + ((m >> 1) & 1)) * 8 + (m >> 2) * 2 + c;
  else row = 112 + e;
  return b * SQ + wg * 120 + row;
}

__device__ __forceinline__ void slow_path(const Params& P, int b, int h, int wg, int w, int lane) {
  const int g = lane >> 2, q = lane & 3, row0 = wg * 120;
  const uint16_t* wq = reinterpret_cast<const uint16_t*>(P.wq) + h * DH + g;
  const __nv_bfloat16* kp = P.k + (size_t)(b * NH + h) * SK * DH;
  const uint16_t* vp = reinterpret_cast<const uint16_t*>(P.v) + (size_t)(b * NH + h) * SK * DH + g;
#pragma unroll 1
  for (int t = w; t < 8; t += 4) {
    const int r0 = 16 * t + g, r1 = r0 + 8;
    const __nv_bfloat16* x0 = P.x + (size_t)(b * SQ + row0 + r0) * DM + 2 * q;
    const __nv_bfloat16* x1 = P.x + (size_t)(b * SQ + row0 + min(r1, 119)) * DM + 2 * q;
    float o[16][4];
#pragma unroll
    for (int n = 0; n < 16; n++) o[n][0] = o[n][1] = o[n][2] = o[n][3] = 0.f;
#pragma unroll 1
    for (int k0 = 0; k0 < DM; k0 += 16) {
      uint32_t a[4] = {*(const uint32_t*)(x0 + k0), *(const uint32_t*)(x1 + k0), *(const uint32_t*)(x0 + k0 + 8), *(const uint32_t*)(x1 + k0 + 8)};
      const uint16_t* wr = wq + (size_t)(k0 + 2 * q) * HD;
#pragma unroll
      for (int n = 0; n < 16; n++)
        mma16816(o[n], a, wr[8 * n] | ((uint32_t)wr[8 * n + HD] << 16), wr[8 * n + 8 * HD] | ((uint32_t)wr[8 * n + 9 * HD] << 16));
    }
    uint32_t qa[8][4];
#pragma unroll
    for (int k = 0; k < 8; k++) {
      qa[k][0] = pack(o[2 * k][0] * QSCALE, o[2 * k][1] * QSCALE);
      qa[k][1] = pack(o[2 * k][2] * QSCALE, o[2 * k][3] * QSCALE);
      qa[k][2] = pack(o[2 * k + 1][0] * QSCALE, o[2 * k + 1][1] * QSCALE);
      qa[k][3] = pack(o[2 * k + 1][2] * QSCALE, o[2 * k + 1][3] * QSCALE);
    }
#pragma unroll
    for (int n = 0; n < 16; n++) o[n][0] = o[n][1] = o[n][2] = o[n][3] = 0.f;
    float m0 = -INFINITY, m1 = -INFINITY, l0 = 0.f, l1 = 0.f;
#pragma unroll 1
    for (int key0 = 0; key0 < SK; key0 += 16) {
      float s[2][4];
#pragma unroll
      for (int nt = 0; nt < 2; nt++) {
        s[nt][0] = s[nt][1] = s[nt][2] = s[nt][3] = 0.f;
        const __nv_bfloat16* kr = kp + (size_t)(key0 + 8 * nt + g) * DH + 2 * q;
#pragma unroll
        for (int k = 0; k < 8; k++) mma16816(s[nt], qa[k], *(const uint32_t*)(kr + 16 * k), *(const uint32_t*)(kr + 16 * k + 8));
      }
      float n0 = fmaxf(fmaxf(s[0][0], s[0][1]), fmaxf(s[1][0], s[1][1])), n1 = fmaxf(fmaxf(s[0][2], s[0][3]), fmaxf(s[1][2], s[1][3]));
      n0 = fmaxf(n0, __shfl_xor_sync(~0u, n0, 1)); n1 = fmaxf(n1, __shfl_xor_sync(~0u, n1, 1));
      n0 = fmaxf(n0, __shfl_xor_sync(~0u, n0, 2)); n1 = fmaxf(n1, __shfl_xor_sync(~0u, n1, 2));
      n0 = fmaxf(n0, m0); n1 = fmaxf(n1, m1);
      const float z0 = n0 == -INFINITY ? 0.f : n0, z1 = n1 == -INFINITY ? 0.f : n1;
      const float c0 = ex2(m0 - z0), c1 = ex2(m1 - z1);
      m0 = n0; m1 = n1;
#pragma unroll
      for (int nt = 0; nt < 2; nt++) {
        s[nt][0] = ex2(s[nt][0] - z0); s[nt][1] = ex2(s[nt][1] - z0);
        s[nt][2] = ex2(s[nt][2] - z1); s[nt][3] = ex2(s[nt][3] - z1);
      }
      l0 = l0 * c0 + s[0][0] + s[0][1] + s[1][0] + s[1][1];
      l1 = l1 * c1 + s[0][2] + s[0][3] + s[1][2] + s[1][3];
      uint32_t pa[4] = {pack(s[0][0], s[0][1]), pack(s[0][2], s[0][3]), pack(s[1][0], s[1][1]), pack(s[1][2], s[1][3])};
      const uint16_t* vr = vp + (size_t)(key0 + 2 * q) * DH;
#pragma unroll
      for (int n = 0; n < 16; n++) {
        o[n][0] *= c0; o[n][1] *= c0; o[n][2] *= c1; o[n][3] *= c1;
        mma16816(o[n], pa, vr[8 * n] | ((uint32_t)vr[8 * n + DH] << 16), vr[8 * n + 8 * DH] | ((uint32_t)vr[8 * n + 9 * DH] << 16));
      }
    }
    l0 += __shfl_xor_sync(~0u, l0, 1); l1 += __shfl_xor_sync(~0u, l1, 1);
    l0 += __shfl_xor_sync(~0u, l0, 2); l1 += __shfl_xor_sync(~0u, l1, 2);
    const float i0 = 1.f / l0, i1 = 1.f / l1;
    __nv_bfloat16* oc = P.o + (size_t)(h * DH + 2 * q) * NROWS + b * SQ;
    const int p0 = o_pos(wg, r0), p1 = o_pos(wg, min(r1, 119));
#pragma unroll
    for (int n = 0; n < 16; n++) {
      oc[(size_t)(8 * n) * NROWS + p0] = __float2bfloat16(o[n][0] * i0);
      oc[(size_t)(8 * n + 1) * NROWS + p0] = __float2bfloat16(o[n][1] * i0);
      if (r1 < 120) {
        oc[(size_t)(8 * n) * NROWS + p1] = __float2bfloat16(o[n][2] * i1);
        oc[(size_t)(8 * n + 1) * NROWS + p1] = __float2bfloat16(o[n][3] * i1);
      }
    }
  }
}

__device__ __forceinline__ int bk(int ks) { return B_ORDER && ks < 48 ? 32 - (ks & 48) + (ks & 15) : ks; }
__device__ __forceinline__ uint32_t x_slot(uint32_t wg, uint32_t j) { return j < 2 ? (2 * wg + j) * XB : (2 * j + wg) * XB; }
__device__ __forceinline__ int unit_batch(int u) { return (u & 63) >> 2; }
__device__ __forceinline__ int unit_head(int u, int rank) { return (u >> 6) * 8 + (u & 3) * 2 + rank; }

__global__ void __cluster_dims__(2, 1, 1) __launch_bounds__(384, 1)
fused_attn_kernel(const __grid_constant__ CUtensorMap tm_x, const __grid_constant__ CUtensorMap tm_wq,
                  const __grid_constant__ CUtensorMap tm_k, const __grid_constant__ CUtensorMap tm_v,
                  const __grid_constant__ CUtensorMap tm_o, const __grid_constant__ CUtensorMap tm_wo,
                  const __grid_constant__ Params P) {
  extern __shared__ uint8_t smem_raw[];
  const uint32_t sb = ((uint32_t)__cvta_generic_to_shared(smem_raw) + 1023) & ~1023u;
  const int warp = __shfl_sync(~0u, threadIdx.x >> 5, 0);
  int lane = threadIdx.x & 31;
  const int rank = blockIdx.x & 1, cl = blockIdx.x >> 1, ncl = gridDim.x >> 1;

  const int nsingle = ncl == 66 ? 44 : NOTILES;
  auto role = [&]() {
    mbar_wait(sb + BAR_ROLE + 16, 0);
    int id;
    asm volatile("ld.shared.u32 %0, [%1];" : "=r"(id) : "r"(sb + BAR_ROLE + 8) : "memory");
    return id;
  };

  if (threadIdx.x == 0) {
    for (int i = 0; i < 6; i++) {
      mbar_init(sb + BAR_RFULL + 8 * i, 1); mbar_init(sb + BAR_REMPTY + 8 * i, 8);
      mbar_init(sb + BAR_BFULL + 8 * i, 1); mbar_init(sb + BAR_BEMPTY + 8 * i, 16);
    }
    for (int i = 0; i < 8; i++) mbar_init(sb + BAR_XFULL + 8 * i, 1);
    for (int i = 0; i < 4; i++) mbar_init(sb + BAR_XEMPTY + 8 * i, 8);
    for (int i = 0; i < 2; i++) { mbar_init(sb + BAR_STAGE + 8 * i, 4); mbar_init(sb + BAR_LSUM + 8 * i, 4); mbar_init(sb + BAR_INV + 8 * i, 1); }
    mbar_init(sb + BAR_ROLE, 1); mbar_init(sb + BAR_ROLE + 16, 1);
    asm volatile("fence.mbarrier_init.release.cluster;" ::: "memory");
  }
  __syncwarp();
  asm volatile("barrier.cluster.arrive.relaxed.aligned;\nbarrier.cluster.wait.aligned;" ::: "memory");

  if (warp >= 8) {
    asm volatile("setmaxnreg.dec.sync.aligned.u32 24;");
    if (warp == 8) {
      uint64_t pol;
      asm volatile("createpolicy.fractional.L2::evict_first.b64 %0, 1.0;" : "=l"(pol));
      Ring r;
      auto load = [&](const CUtensorMap* m, int c1, int c2, bool ef) {
        mbar_wait(sb + BAR_REMPTY + 8 * r.slot, r.phase ^ 1);
        if (lane == 0) {
          mbar_expect(sb + BAR_RFULL + 8 * r.slot, RING_BYTES);
          if (ef) tma3d_hint(sb + r.slot * RING_BYTES, m, 0, c1, c2, sb + BAR_RFULL + 8 * r.slot, pol);
          else tma3d(sb + r.slot * RING_BYTES, m, 0, c1, c2, sb + BAR_RFULL + 8 * r.slot);
        }
        r.next();
      };
      const int rot = ROT * (blockIdx.x * 5 + (blockIdx.x >> 4));
      for (int u0 = 0;; u0 += ncl) {
        const int u = __shfl_sync(~0u, u0 ? role() + u0 : cl, 0);
        if (u >= NUNITS) break;
        const int h = unit_head(u, rank);
        const int krow = (unit_batch(u) * NH + h) * SK;
#pragma unroll 1
        for (int s = 0; s < 10; s++) {
          load(&tm_wq, s * 64, 2 * h, false);
          const int sp = u0 == 0 ? s - PF_HOLD : s;
          if (sp >= 0 && sp < PF_N && lane == 0) l2_prefetch(P.v + (size_t)(krow + ((PF_J0 + sp * PF_STEP + rot) & 15) * 64) * DH, 16384);
        }
#pragma unroll 1
        for (int j = 0; j <= 16; j++) {
          if (j < 16) load(&tm_k, krow + ((j + rot) & 15) * 64, 0, true);
          if (j == 1 + DPRO) load(&tm_v, krow + (rot & 15) * 64, 0, true);
          if (j > 1) load(&tm_v, krow + ((j - 1 + rot) & 15) * 64, 0, true);
        }
      }
      const int id = __shfl_sync(~0u, role(), 0);
      const bool dbl = ncl == 66 && id >= 58;
      for (int t = dbl ? 2 * id - 72 : id; t < (dbl ? NOTILES : nsingle); t += ncl) {
        const int row0 = (t >> 2) * 256 + rank * 128;
        const int b0 = row0 / SQ, b1 = (row0 + 127) / SQ;
#pragma unroll 1
        for (int ks = 0; ks < 64; ks++) {
          if (dbl ? (ks & 15) == 0 : ks == 0 || ks == 48) {
            const unsigned* c = &g_cnt[((lane & 1 ? b1 : b0) * 4 + (ks || dbl ? ks >> 4 : min(lane >> 1, 2))) * 8];
            unsigned v, n = 0;
            do {
              asm volatile("ld.acquire.gpu.global.u32 %0, [%1];" : "=r"(v) : "l"(c) : "memory");
              if (++n > (1u << 26)) __trap();
            } while (v < 16);
            __syncwarp();
            asm volatile("fence.proxy.async.global;" ::: "memory");
          }
          load(&tm_o, (dbl ? ks : bk(ks)) * 64, row0 >> 6, O_EF);
        }
      }
      if (lane == 0 && atomicAdd(&g_cnt[64 * 8], 1) == gridDim.x - 1) {
        for (int i = 0; i < 67; i++) g_cnt[i * 8] = 0;
      }
    } else if (warp == 9) {
      if (lane == 0) {
        uint32_t it = 0;
        for (;; it++) {
          const int u = it ? role() + it * ncl : cl;
          if (u >= NUNITS) break;
          const int row = unit_batch(u) * SQ + rank * 120;
#pragma unroll 1
          for (int s = 0; s < 10; s++) {
            const uint32_t j = s & 3, par = ((s >> 2) + (j < 2 ? it : 0)) & 1;
            mbar_wait(sb + BAR_XEMPTY + 8 * j, par ^ 1);
            const uint32_t fb = sb + BAR_XFULL + 32 * rank + 8 * j;
            mbar_expect(fb, XB);
            mbar_expect_cl(mapa(fb, rank ^ 1), XB);
            tma2d_mc(sb + OFF_Q + x_slot(rank, j), &tm_x, s * 64, row, fb);
          }
        }
        const int id = role();
        const bool dbl = ncl == 66 && id >= 58;
        uint32_t slot = rank, phase = 0;
        for (int t = dbl ? 2 * id - 72 + rank : id; t < (dbl ? NOTILES : nsingle); t += ncl) {
#pragma unroll 1
          for (int ks = dbl ? 0 : rank; ks < 64; ks += dbl ? 1 : 2) {
            mbar_wait(sb + BAR_BEMPTY + 8 * slot, phase);
            const uint32_t fb = sb + BAR_BFULL + 8 * slot;
            mbar_expect(fb, BB);
            mbar_expect_cl(mapa(fb, rank ^ 1), BB);
            tma3d_mc(sb + OFF_Q + slot * BB, &tm_wo, 0, (dbl ? ks : bk(ks)) * 64, (t & 3) * 5, fb);
            if (WO_PF && dbl && ks + WO_PF < 64 && (ks & 3) == ((id >> 1) & 3))
              asm volatile("cp.async.bulk.prefetch.tensor.3d.L2.global [%0, {%1, %2, %3}];" ::"l"(&tm_wo), "r"(0), "r"((ks + WO_PF) * 64), "r"((t & 3) * 5) : "memory");
            slot += 2;
            if (slot >= 6) { slot -= 6; phase ^= 1; }
          }
        }
      }
    } else {
      const int wg = warp - 10;
      {
        mbar_wait(sb + BAR_RFULL, 0);
        const __nv_bfloat16* xs = P.x + (size_t)(unit_batch(cl) * SQ + ((cl & 3) * 2 + rank) * 30 + min(lane, 29)) * DM + 256 + wg * 64;
#pragma unroll
        for (int i = 0; i < 3; i++) asm volatile("prefetch.global.L2 [%0];" ::"l"(xs + i * 128));
        if (lane < 16) asm volatile("prefetch.global.L2 [%0];" ::"l"(P.wq + (size_t)(384 + unit_batch(cl) * 16 + lane) * HD + unit_head(cl, rank) * DH + wg * 64));
      }
      if (wg == 0 && rank == 0 && lane == 0) {
        int id = cl;
        if (ncl == 66) {
          uint32_t smid;
          asm("mov.u32 %0, %smid;" : "=r"(smid));
          id = smid >= SMID_TOP ? 65 - atomicAdd(&g_cnt[65 * 8], 1) : atomicAdd(&g_cnt[66 * 8], 1);
        }
#pragma unroll
        for (int c = 0; c < 2; c++) {
          const uint32_t a = mapa(sb + BAR_ROLE, c);
          asm volatile("st.shared::cluster.u32 [%0 + 8], %1;\nmbarrier.arrive.release.cluster.shared::cluster.b64 _, [%0];" ::"r"(a), "r"(id) : "memory");
        }
      }
      if (wg == 0 && lane == 0) {
        mbar_wait_cl(sb + BAR_ROLE, 0);
        mbar_arrive(sb + BAR_ROLE + 16);
      }
      __syncwarp();
      for (uint32_t it = 0;; it++) {
        const int u = __shfl_sync(~0u, it ? role() + it * ncl : cl, 0);
        if (u >= NUNITS) break;
        mbar_wait(sb + BAR_LSUM + 8 * wg, it & 1);
        float l4[4], v[4];
        const uint32_t a = sb + OFF_L2 + wg * 2048 + lane * 16;
        asm volatile("ld.shared.v4.f32 {%0, %1, %2, %3}, [%4];" : "=f"(l4[0]), "=f"(l4[1]), "=f"(l4[2]), "=f"(l4[3]) : "r"(a) : "memory");
#pragma unroll
        for (int g = 1; g < 4; g++) {
          asm volatile("ld.shared.v4.f32 {%0, %1, %2, %3}, [%4];" : "=f"(v[0]), "=f"(v[1]), "=f"(v[2]), "=f"(v[3]) : "r"(a + g * 512) : "memory");
#pragma unroll
          for (int c = 0; c < 4; c++) l4[c] += v[c];
        }
#pragma unroll
        for (int c = 0; c < 4; c++) {
          float inv;
          asm("rcp.approx.ftz.f32 %0, %1;" : "=f"(inv) : "f"(l4[c]));
          l4[c] = l4[c] >= L_MIN && l4[c] <= L_MAX ? inv : __uint_as_float(0x7FFFFFFFu);
        }
        const uint32_t h0 = pack(l4[0], l4[1]), h1 = pack(l4[2], l4[3]);
        const uint32_t e0 = pack(l4[0] - __uint_as_float(h0 << 16), l4[1] - __uint_as_float(h0 & 0xFFFF0000u));
        const uint32_t e1 = pack(l4[2] - __uint_as_float(h1 << 16), l4[3] - __uint_as_float(h1 & 0xFFFF0000u));
        asm volatile("st.shared.v4.u32 [%0], {%1, %2, %3, %4};" ::"r"(sb + OFF_INV + wg * 512 + lane * 16), "r"(h0), "r"(e0), "r"(h1), "r"(e1) : "memory");
        __syncwarp();
        if (lane == 0) {
          mbar_arrive(sb + BAR_INV + 8 * wg);
          mbar_wait(sb + BAR_STAGE + 8 * wg, it & 1);
          __threadfence();
          asm volatile("red.relaxed.gpu.global.add.u32 [%0], 1;" ::"l"(&g_cnt[(unit_batch(u) * 4 + (u >> 6)) * 8]) : "memory");
        }
        __syncwarp();
      }
    }
  } else {
    asm volatile("setmaxnreg.inc.sync.aligned.u32 240;");
    const int wg = warp >> 2, w = warp & 3;
    const uint32_t qreg = sb + OFF_Q + wg * 2 * XB, preg = sb + OFF_P + (2 + wg) * XB;
    const uint32_t st_off = ((lane >> 4) * 8 + (lane & 7)) * 128 + (((2 * w + ((lane >> 3) & 1)) ^ (lane & 7)) << 4);
    const uint32_t xempty = mapa(sb + BAR_XEMPTY, wg);
    Ring r;
    uint32_t it = 0;
    const uint32_t qd = (qreg & 0x3FFFF) >> 4, pd = (preg & 0x3FFFF) >> 4;
    auto ring_addr = [&]() { return ((sb & 0x3FFFF) + r.slot * RING_BYTES) >> 4; };
    auto ring_wait = [&]() { mbar_wait(sb + BAR_RFULL + 8 * r.slot, r.phase); };
    auto release = [&](uint32_t slot) { if (lane == 0) mbar_arrive(sb + BAR_REMPTY + 8 * slot); };
    auto turn_wait = [&]() {
      if (wg == 0) asm volatile("bar.sync 3, 256;" ::: "memory");
      else asm volatile("bar.sync 4, 256;" ::: "memory");
    };
    auto turn_pass = [&]() {
      if (wg == 0) asm volatile("bar.arrive 4, 256;" ::: "memory");
      else asm volatile("bar.arrive 3, 256;" ::: "memory");
    };

    uint32_t chk = 0;
    auto load_inv = [&](uint32_t (&iv)[30], uint32_t parity) {
      mbar_wait(sb + BAR_INV + 8 * wg, parity);
      chk = 0;
#pragma unroll
      for (int j = 0; j < 15; j++)
        asm volatile("ld.shared.v2.u32 {%0, %1}, [%2];" : "=r"(iv[2 * j]), "=r"(iv[2 * j + 1]) : "r"(sb + OFF_INV + wg * 512 + j * 32 + (lane & 3) * 8) : "memory");
    };
    auto norm = [&](uint32_t (&n)[8], const uint32_t (&po)[60], const uint32_t (&iv)[30], auto part) {
      constexpr int k = decltype(part)::value >> 1, j0 = (decltype(part)::value & 1) * 8;
#pragma unroll
      for (int j = 0; j < 8; j++)
        n[j] = j0 + j < 15 ? hfma2(po[15 * k + (j0 + j) % 15], iv[2 * ((j0 + j) % 15)], hfma2(po[15 * k + (j0 + j) % 15], iv[2 * ((j0 + j) % 15) + 1], 0x80008000u)) : 0x3F803F80u;
#pragma unroll
      for (int j = 0; j < 8; j += 2) chk = hfma2(n[j], n[j + 1], chk);
    };
    auto store = [&](const uint32_t (&n)[8], const char* optr, auto part) {
      constexpr int k = decltype(part)::value >> 1;
      const char* o = optr + (size_t)(8 * (k & 1) + 64 * (k >> 1)) * NROWS * 2;
      if ((decltype(part)::value & 1) == 0)
        asm volatile(
            "{\n.reg .pred p;\nsetp.ne.u64 p, %9, 0;\n"
            "@p st.global.v4.u32 [%8], {%0, %1, %2, %3};\n@p st.global.v4.u32 [%8 + 64], {%4, %5, %6, %7};\n}\n"
            ::"r"(n[0]), "r"(n[1]), "r"(n[2]), "r"(n[3]), "r"(n[4]), "r"(n[5]), "r"(n[6]), "r"(n[7]),
            "l"(o + (wg ? 288 : 0) + (lane & 3) * 16), "l"(optr) : "memory");
      else
        asm volatile(
            "{\n.reg .pred p;\nsetp.ne.u64 p, %10, 0;\n"
            "@p st.global.v4.u32 [%7 + 128], {%0, %1, %2, %3};\n@p st.global.v2.u32 [%8], {%4, %5};\n@p st.global.u32 [%9], %6;\n}\n"
            ::"r"(n[0]), "r"(n[1]), "r"(n[2]), "r"(n[3]), "r"(n[4]), "r"(n[5]), "r"(n[6]), "l"(o + (wg ? 288 : 0) + (lane & 3) * 16),
            "l"(o + (wg ? 256 : 192) + (lane & 3) * 8), "l"(o + (wg ? 240 : 224) + (lane & 3) * 4), "l"(optr) : "memory");
    };
    auto put = [&](const uint32_t (&po)[60], const uint32_t (&iv)[30], const char* optr, auto part) {
      uint32_t n[8];
      norm(n, po, iv, part);
      store(n, optr, part);
    };
    auto out_ptr = [&](int u) {
      return reinterpret_cast<const char*>(P.o + (size_t)(unit_head(u, rank) * DH + 16 * w + (lane >> 2)) * NROWS + unit_batch(u) * SQ);
    };
    auto unsafe = [&](bool valid) {
      const bool b = valid && ((chk & 0x7F80u) == 0x7F80u || (chk & 0x7F800000u) == 0x7F800000u);
      return __any_sync(~0u, bar_red_or(wg, b));
    };
    auto publish = [&]() { __syncwarp(); if (lane == 0) mbar_arrive(sb + BAR_STAGE + 8 * wg); };

    uint32_t po[60];
#pragma unroll
    for (int i = 0; i < 60; i++) po[i] = 0;
    int id;
    bool more;
    do {
      float o0[60], o1[60];
      uint32_t prev = 0;
      auto qstep = [&](int s, int acc) {
        const uint32_t j = s & 3, par = ((s >> 2) + (j < 2 ? it : 0)) & 1;
        TR(it * 160 + 3 * s);
        ring_wait();
        TR(it * 160 + 3 * s + 1);
        mbar_wait(sb + BAR_XFULL + 32 * wg + 8 * j, par);
        TR(it * 160 + 3 * s + 2);
        if (s >= ALT_FROM) turn_wait();
        wg_fence();
        mma_tn(o0, o1, ring_addr(), ((sb & 0x3FFFF) + OFF_Q + x_slot(wg, j)) >> 4, acc);
        wg_commit();
        if ((s >= ALT_FROM && !(MERGE89 && s == 8)) || (s == ALT_FROM - 1 && wg == 1)) turn_pass();
        if (s > 0) {
          wg_wait<1>();
          release(prev);
          if (s <= 6 && lane == 0) mbar_arrive_cl(xempty + 8 * ((s - 1) & 3));
        }
        prev = r.slot;
        r.next();
      };
      qstep(0, 0);
      const int up = __shfl_sync(~0u, it > 1 ? role() + ((int)it - 1) * ncl : cl, 0);
      const char* optr = it > 0 ? out_ptr(up) : nullptr;
      uint32_t n7[8];
      {
        uint32_t iv[30];
        if (it > 0) {
          fence_async_smem();
          __syncwarp();
          if (lane == 0) mbar_arrive_cl(xempty + 24);
        }
        qstep(1, 1); load_inv(iv, (it + 1) & 1); put(po, iv, optr, IC<0>());
        qstep(2, 1); put(po, iv, optr, IC<1>());
        qstep(3, 1); put(po, iv, optr, IC<2>());
        qstep(4, 1); put(po, iv, optr, IC<3>());
        qstep(5, 1); put(po, iv, optr, IC<4>());
        qstep(6, 1); put(po, iv, optr, IC<5>());
        qstep(7, 1); put(po, iv, optr, IC<6>());
        norm(n7, po, iv, IC<7>());
        if (LATE_AT == 3) store(n7, optr, IC<7>());
        qstep(8, 1);
        if (LATE_AT == 2) store(n7, optr, IC<7>());
      }
      TR(it * 160 + 27);
      ring_wait();
      TR(it * 160 + 28);
      mbar_wait(sb + BAR_XFULL + 32 * wg + 8, it & 1);
      TR(it * 160 + 29);
      if (!MERGE89) turn_wait();
      wg_fence();
      mma_tn_split(o0, o1, ring_addr(), qd + (XB >> 4));
      turn_pass();
      wg_wait<2>();
      release(prev);
      wg_wait<1>();
      reg_fence(o0);
      uint32_t pq[30];
#pragma unroll
      for (int j = 0; j < 30; j++) pq[j] = pack(o0[2 * j] * QSCALE, o0[2 * j + 1] * QSCALE);
      wg_wait<0>();
      reg_fence(o1);
      release(r.slot);
      r.next();
      TR(it * 160 + 30);
      bar_sync(wg);
#pragma unroll
      for (int j = 0; j < 14; j += 2) stsm4t(qreg + st_off + j * 1024, pq[2 * j], pq[2 * j + 1], pq[2 * j + 2], pq[2 * j + 3]);
      stsm2t(qreg + st_off + 14 * 1024, pq[28], pq[29]);
#pragma unroll
      for (int j = 0; j < 14; j += 2)
        stsm4t(qreg + XB + st_off + j * 1024, pack(o1[4 * j] * QSCALE, o1[4 * j + 1] * QSCALE), pack(o1[4 * j + 2] * QSCALE, o1[4 * j + 3] * QSCALE),
               pack(o1[4 * j + 4] * QSCALE, o1[4 * j + 5] * QSCALE), pack(o1[4 * j + 6] * QSCALE, o1[4 * j + 7] * QSCALE));
      stsm2t(qreg + XB + st_off + 14 * 1024, pack(o1[56] * QSCALE, o1[57] * QSCALE), pack(o1[58] * QSCALE, o1[59] * QSCALE));
      fence_async_smem();
      if (unsafe(it > 0)) {
        slow_path(P, unit_batch(up), unit_head(up, rank), wg, w, lane);
        optr = nullptr;
        if (!DPRO) {
#pragma unroll
          for (int i = 0; i < 60; i++) o0[i] = o1[i] = 0.f;
        }
      }
      TR(it * 160 + 32); TG(it * 160 + 142);

      float sc[60], l[30];
      ring_wait();
      TR(it * 160 + 33);
      turn_wait();
      wg_fence();
      mma_qk(sc, ring_addr(), qd);
      wg_commit();
      turn_pass();
      if (LATE_AT < 2) store(n7, optr, IC<7>());
      if (it > 0) publish();
      id = __shfl_sync(~0u, role(), 0);
      wg_wait<0>();
      reg_fence(sc);
      TR(it * 160 + 35);
      release(r.slot);
      r.next();
      exp_store<0, 15, true>(sc, l, preg + st_off);
      fence_async_smem();
      if (!NOBAR) bar_sync(wg);
      more = id + ((int)it + 1) * ncl < NUNITS;
      const bool gemm = id < nsingle || (ncl == 66 && id >= 58);
#pragma unroll 1
      for (int s = DPRO ? 3 : 1; s < 16; s++) {
        const uint32_t kslot = r.slot;
        TR(it * 160 + 32 + 6 * s); TG(it * 160 + 37 + 6 * s);
        ring_wait();
        TR(it * 160 + 33 + 6 * s);
        turn_wait();
        wg_fence();
        mma_qk(sc, ring_addr(), qd);
        wg_commit();
        r.next();
        TR(it * 160 + 36 + 6 * s);
        ring_wait();
        TR(it * 160 + 34 + 6 * s);
        wg_fence();
        mma_tn(o0, o1, ring_addr(), pd - ((s - 1) & 1) * (2 * XB >> 4), DPRO || s != 1);
        wg_commit();
        if (wg == 0 || s < 15) turn_pass();
        wg_wait<1>();
        reg_fence(sc);
        TR(it * 160 + 35 + 6 * s);
        release(kslot);
        if (s == 15) {
          if (more) { if (lane < 2) mbar_arrive_cl(xempty + 8 * lane); }
          else if (lane < 3 && gemm) mbar_arrive_cl(mapa(sb + BAR_BEMPTY + 8 * lane, lane & 1));
        }
        exp_store<0, VREL>(sc, l, preg - (s & 1) * 2 * XB + st_off);
        wg_wait<0>();
        reg_fence(o0); reg_fence(o1);
        release(r.slot);
        r.next();
        exp_store<VREL, 15>(sc, l, preg - (s & 1) * 2 * XB + st_off);
        fence_async_smem();
        if (!NOBAR) bar_sync(wg);
      }
      if (NOBAR) bar_sync(wg);
      TR(it * 160 + 128);
      ring_wait();
      wg_fence();
      mma_tn_split(o0, o1, ring_addr(), pd - (2 * XB >> 4));
      TR(it * 160 + 132);
      {
        const uint32_t a = preg + (8 * w + (lane >> 2)) * 480 + (lane & 3) * 8;
#pragma unroll
        for (int j = 0; j < 15; j++) asm volatile("st.shared.v2.f32 [%0], {%1, %2};" ::"r"(a + j * 32), "f"(l[2 * j]), "f"(l[2 * j + 1]) : "memory");
      }
      __syncwarp();
      float lv[8][4];
#pragma unroll
      for (int g = 0; g < 8; g++)
        asm volatile("ld.shared.v4.f32 {%0, %1, %2, %3}, [%4];" : "=f"(lv[g][0]), "=f"(lv[g][1]), "=f"(lv[g][2]), "=f"(lv[g][3])
                     : "r"(preg + (8 * w + g) * 480 + min(lane, 29) * 16) : "memory");
      TR(it * 160 + 133);
      wg_wait<1>();
      reg_fence(o0);
      TR(it * 160 + 134);
#pragma unroll
      for (int j = 0; j < 15; j++) { po[j] = pack(o0[4 * j], o0[4 * j + 1]); po[15 + j] = pack(o0[4 * j + 2], o0[4 * j + 3]); }
#pragma unroll
      for (int c = 0; c < 4; c++) lv[0][c] = ((lv[0][c] + lv[1][c]) + (lv[2][c] + lv[3][c])) + ((lv[4][c] + lv[5][c]) + (lv[6][c] + lv[7][c]));
      asm volatile("st.shared.v4.f32 [%0], {%1, %2, %3, %4};" ::"r"(sb + OFF_L2 + wg * 2048 + w * 512 + lane * 16), "f"(lv[0][0]), "f"(lv[0][1]),
                   "f"(lv[0][2]), "f"(lv[0][3]) : "memory");
      __syncwarp();
      if (lane == 0) mbar_arrive(sb + BAR_LSUM + 8 * wg);
      wg_wait<0>();
      reg_fence(o1);
      release(r.slot);
      r.next();
      if (more) { if (lane == 0) mbar_arrive_cl(xempty + 16); }
      else if (gemm && lane <= wg) mbar_arrive_cl(mapa(sb + BAR_BEMPTY + 24 + 8 * lane, 1 - lane));
      TR(it * 160 + 130);
#pragma unroll
      for (int j = 0; j < 15; j++) { po[30 + j] = pack(o1[4 * j], o1[4 * j + 1]); po[45 + j] = pack(o1[4 * j + 2], o1[4 * j + 3]); }
      TR(it * 160 + 131); TG(it * 160 + 143);
      it++;
    } while (more);
    const bool gemm = id < nsingle || (ncl == 66 && id >= 58);
    const int u = id + ((int)it - 1) * ncl;
    lane = __shfl_sync(~0u, lane, lane);
    uint32_t pb[60];
#pragma unroll
    for (int i = 0; i < 60; i++) pb[i] = po[i] ^ (gridDim.y - 1);

    uint32_t bslot = 0, bphase = 0;
    auto free_p0 = [&]() {
      fence_async_smem();
      __syncwarp();
      if (lane < 2 - wg) mbar_arrive_cl(mapa(sb + BAR_BEMPTY + 40 - 8 * lane, 1 - lane));
    };
    auto out_tile = [&](const float (&acc)[80], int t) {
      const uint32_t st = sb + w * RING_BYTES + wg * 8192;
      const uint32_t sa = st + (lane & 15) * 336 + (lane >> 4) * 16;
#pragma unroll
      for (int j = 0; j < 20; j += 2)
        asm volatile("stmatrix.sync.aligned.m8n8.x4.shared.b16 [%0], {%1,%2,%3,%4};" ::"r"(sa + j * 16), "r"(pack(acc[4 * j], acc[4 * j + 1])),
                     "r"(pack(acc[4 * j + 2], acc[4 * j + 3])), "r"(pack(acc[4 * j + 4], acc[4 * j + 5])), "r"(pack(acc[4 * j + 6], acc[4 * j + 7])) : "memory");
      fence_async_smem();
      __syncwarp();
      if (lane < 16) {
        __nv_bfloat16* dst = P.out + (size_t)o_row((t >> 2) * 256 + rank * 128 + wg * 64 + w * 16 + lane) * DM + (t & 3) * 160;
        asm volatile("cp.async.bulk.global.shared::cta.bulk_group [%0], [%1], 320;" ::"l"(dst), "r"(st + lane * 336) : "memory");
        asm volatile("cp.async.bulk.commit_group;" ::: "memory");
        asm volatile("cp.async.bulk.wait_group.read 0;" ::: "memory");
      }
      __syncwarp();
    };
    for (int t = id; t < nsingle || t == id; t += ncl) {
      float acc[80];
      uint32_t prev = 0, bprev = 0;
      const bool tile = t < nsingle;
      const bool last = t + ncl >= nsingle;
      auto bstep = [&](int ks, int accf) {
        if (!(ks & 1)) TR(640 + ks); if ((ks & 7) == 0) TG(144 + (ks >> 3));
        ring_wait();
        mbar_wait(sb + BAR_BFULL + 8 * bslot, bphase);
        if (!(ks & 1)) TR(641 + ks);
        wg_fence();
        const uint32_t a = ring_addr() + wg * 512, bd = (((sb & 0x3FFFF) + OFF_Q + bslot * BB) >> 4) | ((4096u >> 4) << 16);
#pragma unroll
        for (int k = 0; k < 4; k++) wgmma_n160<1, 1>(acc, a + k * 128, HI128, bd + k * 64, HI64, k == 0 ? accf : 1);
        wg_commit();
        if (ks > 0) {
          wg_wait<1>();
          release(prev);
          if (lane == 0 && (ks < 59 || !last)) mbar_arrive_cl(mapa(sb + BAR_BEMPTY + 8 * bprev, bprev & 1));
        }
        prev = r.slot; bprev = bslot;
        r.next();
        if (++bslot == 6) { bslot = 0; bphase ^= 1; }
      };
      const char* optr = t == id ? out_ptr(u) : nullptr;
      uint32_t iv[30];
      if (tile) {
        bstep(0, 0);
        if (t == id) free_p0();
        bstep(1, 1);
        bstep(2, 1); load_inv(iv, (it + 1) & 1); put(pb, iv, optr, IC<0>()); bstep(3, 1);
        bstep(4, 1); put(pb, iv, optr, IC<1>()); bstep(5, 1);
        bstep(6, 1); put(pb, iv, optr, IC<2>()); bstep(7, 1);
        bstep(8, 1); put(pb, iv, optr, IC<3>()); bstep(9, 1);
        bstep(10, 1); put(pb, iv, optr, IC<4>()); bstep(11, 1);
        bstep(12, 1); put(pb, iv, optr, IC<5>()); bstep(13, 1);
        bstep(14, 1); put(pb, iv, optr, IC<6>()); bstep(15, 1);
        bstep(16, 1); put(pb, iv, optr, IC<7>());
        wg_wait<0>();
        reg_fence(acc);
      } else {
#pragma unroll
        for (int i = 0; i < 80; i++) acc[i] = 0.f;
        if (gemm) free_p0();
        load_inv(iv, (it + 1) & 1);
        put(pb, iv, optr, IC<0>()); put(pb, iv, optr, IC<1>()); put(pb, iv, optr, IC<2>()); put(pb, iv, optr, IC<3>());
        put(pb, iv, optr, IC<4>()); put(pb, iv, optr, IC<5>()); put(pb, iv, optr, IC<6>()); put(pb, iv, optr, IC<7>());
      }
      if (unsafe(t == id)) slow_path(P, unit_batch(u), unit_head(u, rank), wg, w, lane);
      if (t == id) publish();
      if (!tile) break;
#pragma unroll 1
      for (int ks = 17; ks < 64; ks++) {
        if (END_SKEW && wg == 1 && ks == 64 - END_SKEW) turn_wait();
        bstep(ks, 1);
      }
      if (END_SKEW && wg == 0) turn_pass();
      wg_wait<0>();
      reg_fence(acc);
      release(prev);
      if (lane == 0 && !last) mbar_arrive_cl(mapa(sb + BAR_BEMPTY + 8 * bprev, bprev & 1));
      TR(158); TG(156);
      const int pos0 = (t >> 2) * 256 + rank * 128 + wg * 64 + w * 16;
      if (last) {
        bar_sync(wg);
        out_tile(acc, t);
      } else {
        __nv_bfloat16* op0 = P.out + (size_t)o_row(pos0 + (lane >> 2)) * DM + (t & 3) * 160 + (lane & 3) * 2;
        __nv_bfloat16* op1 = P.out + (size_t)o_row(pos0 + (lane >> 2) + 8) * DM + (t & 3) * 160 + (lane & 3) * 2;
#pragma unroll
        for (int j = 0; j < 20; j++) {
          *reinterpret_cast<uint32_t*>(op0 + j * 8) = pack(acc[4 * j], acc[4 * j + 1]);
          *reinterpret_cast<uint32_t*>(op1 + j * 8) = pack(acc[4 * j + 2], acc[4 * j + 3]);
        }
      }
#pragma unroll
      for (int i = 0; i < 60; i++) pb[i] = 0;
    }
    if (gemm && id >= nsingle) {
      float ac0[80], ac1[80];
      uint32_t prev = 0, bprev = 0;
      auto half = [&](float (&acc)[80], int hs, int accf) {
        mbar_wait(sb + BAR_BFULL + 8 * bslot, bphase);
        wg_fence();
        const uint32_t a = ring_addr() + wg * 512, bd = (((sb & 0x3FFFF) + OFF_Q + bslot * BB) >> 4) | ((4096u >> 4) << 16);
#pragma unroll
        for (int k = 0; k < 4; k++) wgmma_n160<1, 1>(acc, a + k * 128, HI128, bd + k * 64, HI64, k == 0 ? accf : 1);
        wg_commit();
        if (hs > 0) {
          wg_wait<1>();
          if (lane == 0 && hs < 123) mbar_arrive_cl(mapa(sb + BAR_BEMPTY + 8 * bprev, bprev & 1));
        }
        bprev = bslot;
        if (++bslot == 6) { bslot = 0; bphase ^= 1; }
      };
      auto dstep = [&](int ks, int accf) {
        if (!(ks & 1)) TR(640 + ks); if ((ks & 7) == 0) TG(144 + (ks >> 3));
        ring_wait();
        if (!(ks & 1)) TR(641 + ks);
        half(ac0, 2 * ks, accf);
        if (ks > 0) release(prev);
        half(ac1, 2 * ks + 1, accf);
        prev = r.slot;
        r.next();
      };
      dstep(0, 0);
#pragma unroll 1
      for (int ks = 1; ks < 64; ks++) {
        if (wg == 1 && ks == 62) turn_wait();
        dstep(ks, 1);
      }
      if (wg == 0) turn_pass();
      wg_wait<0>();
      reg_fence(ac0); reg_fence(ac1);
      TR(158); TG(156);
      bar_sync(wg);
      out_tile(ac0, 2 * id - 72);
      out_tile(ac1, 2 * id - 71);
    }
    TR(159);
  }
}

typedef CUresult (*EncodeFn)(CUtensorMap*, CUtensorMapDataType, cuuint32_t, void*, const cuuint64_t*, const cuuint64_t*,
                             const cuuint32_t*, const cuuint32_t*, CUtensorMapInterleave, CUtensorMapSwizzle,
                             CUtensorMapL2promotion, CUtensorMapFloatOOBfill);

void make_map(EncodeFn enc, CUtensorMap* m, const void* p, int rank, const cuuint64_t* dims, const cuuint64_t* strides,
              const cuuint32_t* box, CUtensorMapSwizzle sw, CUtensorMapL2promotion promo) {
  cuuint32_t es[3] = {1, 1, 1};
  enc(m, CU_TENSOR_MAP_DATA_TYPE_BFLOAT16, rank, const_cast<void*>(p), dims, strides, box, es, CU_TENSOR_MAP_INTERLEAVE_NONE, sw,
      promo, CU_TENSOR_MAP_FLOAT_OOB_FILL_NONE);
}

}

extern "C" void kernel_launch(void* const* d_in, const int* in_sizes, int n_in, void* d_out, int out_size) {
  static EncodeFn enc = nullptr;
  static int nclusters = 0;
  static void* o_ptr = nullptr;
  if (!enc) {
    cudaDriverEntryPointQueryResult qr;
    cudaGetDriverEntryPoint("cuTensorMapEncodeTiled", (void**)&enc, cudaEnableDefault, &qr);
    cudaFuncSetAttribute(fused_attn_kernel, cudaFuncAttributeMaxDynamicSharedMemorySize, SMEM_BYTES);
    cudaGetSymbolAddress(&o_ptr, g_o);
    cudaLaunchConfig_t cfg = {};
    cfg.gridDim = 128; cfg.blockDim = 384; cfg.dynamicSmemBytes = SMEM_BYTES;
    cudaLaunchAttribute at; at.id = cudaLaunchAttributeClusterDimension;
    at.val.clusterDim.x = 2; at.val.clusterDim.y = 1; at.val.clusterDim.z = 1;
    cfg.attrs = &at; cfg.numAttrs = 1;
    int n = 0;
    cudaOccupancyMaxActiveClusters(&n, fused_attn_kernel, &cfg);
    nclusters = n >= 66 ? MAXCL : (n >= 64 || n <= 0 ? 64 : n);
  }
  const __nv_bfloat16* x = (const __nv_bfloat16*)d_in[0];
  const __nv_bfloat16* k = (const __nv_bfloat16*)d_in[1];
  const __nv_bfloat16* v = (const __nv_bfloat16*)d_in[2];
  const __nv_bfloat16* wq = (const __nv_bfloat16*)d_in[3];
  const __nv_bfloat16* wo = (const __nv_bfloat16*)d_in[4];
  CUtensorMap tm_x, tm_wq, tm_k, tm_v, tm_o, tm_wo;
  const auto S128 = CU_TENSOR_MAP_SWIZZLE_128B;
  const auto P128 = CU_TENSOR_MAP_L2_PROMOTION_L2_128B, P256 = CU_TENSOR_MAP_L2_PROMOTION_L2_256B;
  { cuuint64_t d[2] = {DM, NB * SQ}, s[1] = {DM * 2}; cuuint32_t b[2] = {64, 120}; make_map(enc, &tm_x, x, 2, d, s, b, S128, P128); }
  { cuuint64_t d[3] = {64, DM, HD / 64}, s[2] = {HD * 2, 128}; cuuint32_t b[3] = {64, 64, 2}; make_map(enc, &tm_wq, wq, 3, d, s, b, S128, P256); }
  { cuuint64_t d[3] = {64, NB * NH * SK, 2}, s[2] = {DH * 2, 128}; cuuint32_t b[3] = {64, 64, 2};
    make_map(enc, &tm_k, k, 3, d, s, b, S128, P128); make_map(enc, &tm_v, v, 3, d, s, b, S128, P128); }
  { cuuint64_t d[3] = {64, HD, NROWS / 64}, s[2] = {NROWS * 2, 128}; cuuint32_t b[3] = {64, 64, 2}; make_map(enc, &tm_o, o_ptr, 3, d, s, b, S128, P256); }
  { cuuint64_t d[3] = {32, HD, DM / 32}, s[2] = {DM * 2, 64}; cuuint32_t b[3] = {32, 64, 5};
    make_map(enc, &tm_wo, wo, 3, d, s, b, CU_TENSOR_MAP_SWIZZLE_64B, P128); }
  Params P{x, k, v, wq, (__nv_bfloat16*)d_out, (__nv_bfloat16*)o_ptr};
  fused_attn_kernel<<<2 * nclusters, 384, SMEM_BYTES>>>(tm_x, tm_wq, tm_k, tm_v, tm_o, tm_wo, P);
}
```

```cpp
#include <cuda_runtime.h>
#include <cuda.h>
#include <cuda_bf16.h>
#include <stdint.h>

namespace {

constexpr int NB = 16, SQ = 240, DM = 640, NH = 32, SK = 1024, DH = 128, HD = NH * DH;
constexpr int NROWS = NB * SQ;
constexpr int NUNITS = 256;
#define DPRO 0
#define LATE_AT 0
#define ALT_FROM 3
#define MERGE89 1
#define END_SKEW 5
#define VREL 8
#define PF_HOLD 6
#define PF_N 4
#define PF_J0 3
#define PF_STEP 3
#define ROT 0
#define O_EF 1
#define B_ORDER 1
#define WO_PF 6
#define NOBAR 1
#define MAXCL 66
#define SMID_TOP 88
constexpr int NOTILES = 60;
constexpr float QSCALE = 0.08838834764831845f * 1.4426950408889634f;
constexpr float L_MIN = 9.5367431640625e-07f;
constexpr float L_MAX = 1.152921504606846976e18f;

constexpr uint32_t RING_SLOTS = 6, RING_BYTES = 16384;
constexpr uint32_t XB = 15360;
constexpr uint32_t BB = 20480;
constexpr uint32_t OFF_Q = RING_SLOTS * RING_BYTES;
constexpr uint32_t OFF_P = OFF_Q + 4 * XB;
constexpr uint32_t OFF_INV = OFF_P + 4 * XB;
constexpr uint32_t OFF_L2 = OFF_INV + 1280;
constexpr uint32_t OFF_BAR = OFF_L2 + 4096;
constexpr uint32_t BAR_RFULL = OFF_BAR, BAR_REMPTY = BAR_RFULL + 48, BAR_XFULL = BAR_REMPTY + 48,
    BAR_XEMPTY = BAR_XFULL + 64, BAR_BFULL = BAR_XEMPTY + 32, BAR_BEMPTY = BAR_BFULL + 48, BAR_STAGE = BAR_BEMPTY + 48;
constexpr uint32_t BAR_ROLE = BAR_STAGE + 16, BAR_LSUM = BAR_ROLE + 24, BAR_INV = BAR_LSUM + 16;
constexpr uint32_t OFF_TR = BAR_INV + 16;
constexpr uint32_t SMEM_BYTES = OFF_TR + 1024;

constexpr uint32_t HI128 = (1u << 30) | (1024 >> 4);
constexpr uint32_t HI64 = (2u << 30) | (512 >> 4);

__device__ __nv_bfloat16 g_o[HD * NROWS];
__device__ unsigned g_cnt[67 * 8];
#define TR(i)
#define TG(i)

struct Params {
  const __nv_bfloat16 *x, *k, *v, *wq;
  __nv_bfloat16 *out, *o;
};

__device__ __forceinline__ void wg_fence() { asm volatile("wgmma.fence.sync.aligned;" ::: "memory"); }
__device__ __forceinline__ void wg_commit() { asm volatile("wgmma.commit_group.sync.aligned;" ::: "memory"); }
template <int N> __device__ __forceinline__ void wg_wait() { asm volatile("wgmma.wait_group.sync.aligned %0;" ::"n"(N) : "memory"); }
template <int N> __device__ __forceinline__ void reg_fence(float (&r)[N]) {
#pragma unroll
  for (int i = 0; i < N; i++) asm volatile("" : "+f"(r[i])::"memory");
}
template <int TA, int TB>
__device__ __forceinline__ void wgmma_n120(float (&d)[60], uint32_t a_lo, uint32_t a_hi, uint32_t b_lo, uint32_t b_hi, int acc) {
  asm volatile(
      "{\n.reg .pred p;\n.reg .b64 da, db;\nsetp.ne.b32 p, %64, 0;\n"
      "mov.b64 da, {%60, %61};\nmov.b64 db, {%62, %63};\n"
      "wgmma.mma_async.sync.aligned.m64n120k16.f32.bf16.bf16 {"
      "%0, %1, %2, %3, %4, %5, %6, %7, %8, %9, %10, %11, %12, %13, %14, %15, %16, %17, %18, %19, %20, %21, %22, %23, "
      "%24, %25, %26, %27, %28, %29, %30, %31, %32, %33, %34, %35, %36, %37, %38, %39, %40, %41, %42, %43, %44, %45, "
      "%46, %47, %48, %49, %50, %51, %52, %53, %54, %55, %56, %57, %58, %59"
      "}, da, db, p, 1, 1, %65, %66;\n}\n"
      : "+f"(d[0]), "+f"(d[1]), "+f"(d[2]), "+f"(d[3]), "+f"(d[4]), "+f"(d[5]), "+f"(d[6]), "+f"(d[7]), "+f"(d[8]),
        "+f"(d[9]), "+f"(d[10]), "+f"(d[11]), "+f"(d[12]), "+f"(d[13]), "+f"(d[14]), "+f"(d[15]), "+f"(d[16]),
        "+f"(d[17]), "+f"(d[18]), "+f"(d[19]), "+f"(d[20]), "+f"(d[21]), "+f"(d[22]), "+f"(d[23]), "+f"(d[24]),
        "+f"(d[25]), "+f"(d[26]), "+f"(d[27]), "+f"(d[28]), "+f"(d[29]), "+f"(d[30]), "+f"(d[31]), "+f"(d[32]),
        "+f"(d[33]), "+f"(d[34]), "+f"(d[35]), "+f"(d[36]), "+f"(d[37]), "+f"(d[38]), "+f"(d[39]), "+f"(d[40]),
        "+f"(d[41]), "+f"(d[42]), "+f"(d[43]), "+f"(d[44]), "+f"(d[45]), "+f"(d[46]), "+f"(d[47]), "+f"(d[48]),
        "+f"(d[49]), "+f"(d[50]), "+f"(d[51]), "+f"(d[52]), "+f"(d[53]), "+f"(d[54]), "+f"(d[55]), "+f"(d[56]),
        "+f"(d[57]), "+f"(d[58]), "+f"(d[59])
      : "r"(a_lo), "r"(a_hi), "r"(b_lo), "r"(b_hi), "r"(acc), "n"(TA), "n"(TB));
}

template <int TA, int TB>
__device__ __forceinline__ void wgmma_n160(float (&d)[80], uint32_t a_lo, uint32_t a_hi, uint32_t b_lo, uint32_t b_hi, int acc) {
  asm volatile(
      "{\n.reg .pred p;\n.reg .b64 da, db;\nsetp.ne.b32 p, %84, 0;\n"
      "mov.b64 da, {%80, %81};\nmov.b64 db, {%82, %83};\n"
      "wgmma.mma_async.sync.aligned.m64n160k16.f32.bf16.bf16 {"
      "%0, %1, %2, %3, %4, %5, %6, %7, %8, %9, %10, %11, %12, %13, %14, %15, %16, %17, %18, %19, %20, %21, %22, %23, "
      "%24, %25, %26, %27, %28, %29, %30, %31, %32, %33, %34, %35, %36, %37, %38, %39, %40, %41, %42, %43, %44, %45, "
      "%46, %47, %48, %49, %50, %51, %52, %53, %54, %55, %56, %57, %58, %59, %60, %61, %62, %63, %64, %65, %66, %67, "
      "%68, %69, %70, %71, %72, %73, %74, %75, %76, %77, %78, %79"
      "}, da, db, p, 1, 1, %85, %86;\n}\n"
      : "+f"(d[0]), "+f"(d[1]), "+f"(d[2]), "+f"(d[3]), "+f"(d[4]), "+f"(d[5]), "+f"(d[6]), "+f"(d[7]), "+f"(d[8]),
        "+f"(d[9]), "+f"(d[10]), "+f"(d[11]), "+f"(d[12]), "+f"(d[13]), "+f"(d[14]), "+f"(d[15]), "+f"(d[16]),
        "+f"(d[17]), "+f"(d[18]), "+f"(d[19]), "+f"(d[20]), "+f"(d[21]), "+f"(d[22]), "+f"(d[23]), "+f"(d[24]),
        "+f"(d[25]), "+f"(d[26]), "+f"(d[27]), "+f"(d[28]), "+f"(d[29]), "+f"(d[30]), "+f"(d[31]), "+f"(d[32]),
        "+f"(d[33]), "+f"(d[34]), "+f"(d[35]), "+f"(d[36]), "+f"(d[37]), "+f"(d[38]), "+f"(d[39]), "+f"(d[40]),
        "+f"(d[41]), "+f"(d[42]), "+f"(d[43]), "+f"(d[44]), "+f"(d[45]), "+f"(d[46]), "+f"(d[47]), "+f"(d[48]),
        "+f"(d[49]), "+f"(d[50]), "+f"(d[51]), "+f"(d[52]), "+f"(d[53]), "+f"(d[54]), "+f"(d[55]), "+f"(d[56]),
        "+f"(d[57]), "+f"(d[58]), "+f"(d[59]), "+f"(d[60]), "+f"(d[61]), "+f"(d[62]), "+f"(d[63]), "+f"(d[64]),
        "+f"(d[65]), "+f"(d[66]), "+f"(d[67]), "+f"(d[68]), "+f"(d[69]), "+f"(d[70]), "+f"(d[71]), "+f"(d[72]),
        "+f"(d[73]), "+f"(d[74]), "+f"(d[75]), "+f"(d[76]), "+f"(d[77]), "+f"(d[78]), "+f"(d[79])
      : "r"(a_lo), "r"(a_hi), "r"(b_lo), "r"(b_hi), "r"(acc), "n"(TA), "n"(TB));
}
__device__ __forceinline__ void mbar_init(uint32_t bar, int cnt) { asm volatile("mbarrier.init.shared::cta.b64 [%0], %1;" ::"r"(bar), "r"(cnt)); }
__device__ __forceinline__ void mbar_expect(uint32_t bar, uint32_t bytes) {
  asm volatile("mbarrier.arrive.expect_tx.shared::cta.b64 _, [%0], %1;" ::"r"(bar), "r"(bytes) : "memory");
}
__device__ __forceinline__ uint32_t mapa(uint32_t addr, uint32_t cta) {
  uint32_t r; asm("mapa.shared::cluster.u32 %0, %1, %2;" : "=r"(r) : "r"(addr), "r"(cta)); return r;
}
__device__ __forceinline__ void mbar_expect_cl(uint32_t cbar, uint32_t bytes) {
  asm volatile("mbarrier.arrive.expect_tx.shared::cluster.b64 _, [%0], %1;" ::"r"(cbar), "r"(bytes) : "memory");
}
__device__ __forceinline__ void mbar_arrive(uint32_t bar) { asm volatile("mbarrier.arrive.shared::cta.b64 _, [%0];" ::"r"(bar) : "memory"); }
__device__ __forceinline__ void mbar_arrive_cl(uint32_t cbar) { asm volatile("mbarrier.arrive.shared::cluster.b64 _, [%0];" ::"r"(cbar) : "memory"); }
__device__ __forceinline__ void mbar_wait(uint32_t bar, uint32_t parity) {
  asm volatile(
      "{\n.reg .pred p;\n.reg .u32 n;\n"
      "mbarrier.try_wait.parity.shared::cta.b64 p, [%0], %1;\n@p bra WAIT_DONE;\n"
      "mov.u32 n, 0;\n"
      "WAIT_LOOP:\n"
      "mbarrier.try_wait.parity.shared::cta.b64 p, [%0], %1;\n@p bra WAIT_DONE;\n"
      "add.u32 n, n, 1;\nsetp.lt.u32 p, n, 0x4000000;\n@p bra WAIT_LOOP;\ntrap;\n"
      "WAIT_DONE:\n}\n" ::"r"(bar), "r"(parity) : "memory");
}
__device__ __forceinline__ void mbar_wait_cl(uint32_t bar, uint32_t parity) {
  asm volatile(
      "{\n.reg .pred p;\n.reg .u32 n;\nmov.u32 n, 0;\n"
      "WAIT_LOOP:\n"
      "mbarrier.try_wait.parity.acquire.cluster.shared::cta.b64 p, [%0], %1;\n@p bra WAIT_DONE;\n"
      "add.u32 n, n, 1;\nsetp.lt.u32 p, n, 0x4000000;\n@p bra WAIT_LOOP;\ntrap;\n"
      "WAIT_DONE:\n}\n" ::"r"(bar), "r"(parity) : "memory");
}
__device__ __forceinline__ void tma3d(uint32_t dst, const CUtensorMap* m, int c0, int c1, int c2, uint32_t bar) {
  asm volatile("cp.async.bulk.tensor.3d.shared::cluster.global.mbarrier::complete_tx::bytes [%0], [%1, {%3, %4, %5}], [%2];"
               ::"r"(dst), "l"(m), "r"(bar), "r"(c0), "r"(c1), "r"(c2) : "memory");
}
__device__ __forceinline__ void tma3d_hint(uint32_t dst, const CUtensorMap* m, int c0, int c1, int c2, uint32_t bar, uint64_t pol) {
  asm volatile("cp.async.bulk.tensor.3d.shared::cluster.global.mbarrier::complete_tx::bytes.L2::cache_hint [%0], [%1, {%3, %4, %5}], [%2], %6;"
               ::"r"(dst), "l"(m), "r"(bar), "r"(c0), "r"(c1), "r"(c2), "l"(pol) : "memory");
}
__device__ __forceinline__ void tma2d_mc(uint32_t dst, const CUtensorMap* m, int c0, int c1, uint32_t bar) {
  asm volatile("cp.async.bulk.tensor.2d.shared::cluster.global.mbarrier::complete_tx::bytes.multicast::cluster [%0], [%1, {%3, %4}], [%2], %5;"
               ::"r"(dst), "l"(m), "r"(bar), "r"(c0), "r"(c1), "h"((uint16_t)3) : "memory");
}
__device__ __forceinline__ void tma3d_mc(uint32_t dst, const CUtensorMap* m, int c0, int c1, int c2, uint32_t bar) {
  asm volatile("cp.async.bulk.tensor.3d.shared::cluster.global.mbarrier::complete_tx::bytes.multicast::cluster [%0], [%1, {%3, %4, %5}], [%2], %6;"
               ::"r"(dst), "l"(m), "r"(bar), "r"(c0), "r"(c1), "r"(c2), "h"((uint16_t)3) : "memory");
}
__device__ __forceinline__ void l2_prefetch(const void* p, uint32_t bytes) {
  asm volatile("cp.async.bulk.prefetch.L2.global [%0], %1;" ::"l"(p), "r"(bytes) : "memory");
}
__device__ __forceinline__ void fence_async_smem() { asm volatile("fence.proxy.async.shared::cta;" ::: "memory"); }
__device__ __forceinline__ void bar_sync(int wg) {
  if (wg == 0) asm volatile("bar.sync 1, 128;" ::: "memory");
  else asm volatile("bar.sync 2, 128;" ::: "memory");
}
__device__ __forceinline__ bool bar_red_or(int id, bool v) {
  uint32_t r;
  asm volatile("{\n.reg .pred p, q;\nsetp.ne.u32 p, %2, 0;\nbar.red.or.pred q, %1, 128, p;\nselp.u32 %0, 1, 0, q;\n}\n"
               : "=r"(r) : "r"(1 + id), "r"((uint32_t)v) : "memory");
  return r != 0;
}
__device__ __forceinline__ uint32_t hfma2(uint32_t a, uint32_t b, uint32_t c) { uint32_t r; asm("fma.rn.bf16x2 %0, %1, %2, %3;" : "=r"(r) : "r"(a), "r"(b), "r"(c)); return r; }
__device__ __forceinline__ float ex2(float x) { float y; asm("ex2.approx.ftz.f32 %0, %1;" : "=f"(y) : "f"(x)); return y; }
__device__ __forceinline__ uint32_t pack(float lo, float hi) { uint32_t r; asm("cvt.rn.bf16x2.f32 %0, %1, %2;" : "=r"(r) : "f"(hi), "f"(lo)); return r; }
__device__ __forceinline__ void stsm4t(uint32_t a, uint32_t r0, uint32_t r1, uint32_t r2, uint32_t r3) {
  asm volatile("stmatrix.sync.aligned.m8n8.x4.trans.shared.b16 [%0], {%1,%2,%3,%4};" ::"r"(a), "r"(r0), "r"(r1), "r"(r2), "r"(r3) : "memory");
}
__device__ __forceinline__ void stsm2t(uint32_t a, uint32_t r0, uint32_t r1) {
  asm volatile("stmatrix.sync.aligned.m8n8.x2.trans.shared.b16 [%0], {%1,%2};" ::"r"(a), "r"(r0), "r"(r1) : "memory");
}
__device__ __forceinline__ void mma16816(float (&d)[4], const uint32_t (&a)[4], uint32_t b0, uint32_t b1) {
  asm volatile("mma.sync.aligned.m16n8k16.row.col.f32.bf16.bf16.f32 {%0,%1,%2,%3}, {%4,%5,%6,%7}, {%8,%9}, {%0,%1,%2,%3};"
               : "+f"(d[0]), "+f"(d[1]), "+f"(d[2]), "+f"(d[3]) : "r"(a[0]), "r"(a[1]), "r"(a[2]), "r"(a[3]), "r"(b0), "r"(b1));
}

template <int V> struct IC { static constexpr int value = V; };

struct Ring {
  uint32_t slot = 0, phase = 0;
  __device__ __forceinline__ void next() { if (++slot == RING_SLOTS) { slot = 0; phase ^= 1; } }
};

__device__ __forceinline__ void mma_tn(float (&o0)[60], float (&o1)[60], uint32_t a, uint32_t b, int acc) {
#pragma unroll
  for (int k = 0; k < 4; k++) {
    wgmma_n120<1, 0>(o0, a + k * 128, HI128, b + k * 2, HI128, k == 0 ? acc : 1);
    wgmma_n120<1, 0>(o1, a + 512 + k * 128, HI128, b + k * 2, HI128, k == 0 ? acc : 1);
  }
}
__device__ __forceinline__ void mma_tn_split(float (&o0)[60], float (&o1)[60], uint32_t a, uint32_t b) {
#pragma unroll
  for (int k = 0; k < 4; k++) wgmma_n120<1, 0>(o0, a + k * 128, HI128, b + k * 2, HI128, 1);
  wg_commit();
#pragma unroll
  for (int k = 0; k < 4; k++) wgmma_n120<1, 0>(o1, a + 512 + k * 128, HI128, b + k * 2, HI128, 1);
  wg_commit();
}
__device__ __forceinline__ void mma_qk(float (&s)[60], uint32_t a, uint32_t q) {
#pragma unroll
  for (int k = 0; k < 8; k++)
    wgmma_n120<0, 0>(s, a + (k >> 2) * 512 + (k & 3) * 2, HI128, q + (k >> 2) * (XB >> 4) + (k & 3) * 2, HI128, k != 0);
}
template <int J0, int J1, bool FIRST = false>
__device__ __forceinline__ void exp_store(const float (&s)[60], float (&l)[30], uint32_t dst) {
#pragma unroll
  for (int j = J0; j < J1; j += 2) {
    uint32_t p[4];
#pragma unroll
    for (int jj = 0; jj < 2; jj++) {
      if (j + jj < 15) {
        const int c = j + jj;
        float e0 = ex2(s[4 * c]), e1 = ex2(s[4 * c + 1]), e2 = ex2(s[4 * c + 2]), e3 = ex2(s[4 * c + 3]);
        if (FIRST) { l[2 * c] = e0 + e2; l[2 * c + 1] = e1 + e3; }
        else { l[2 * c] += e0; l[2 * c + 1] += e1; l[2 * c] += e2; l[2 * c + 1] += e3; }
        p[2 * jj] = pack(e0, e1); p[2 * jj + 1] = pack(e2, e3);
      }
    }
    if (j + 1 < 15) stsm4t(dst + j * 1024, p[0], p[1], p[2], p[3]);
    else stsm2t(dst + j * 1024, p[0], p[1]);
  }
}

__device__ __forceinline__ int o_pos(int wg, int r) {
  const int j = r >> 3, q = (r >> 1) & 3, c = r & 1;
  if (j < 12) return (wg ? 144 : 0) + (j >> 2) * 32 + q * 8 + (j & 3) * 2 + c;
  if (j < 14) return (wg ? 128 : 96) + q * 4 + (j - 12) * 2 + c;
  return (wg ? 120 : 112) + q * 2 + c;
}
__device__ __forceinline__ int o_row(int p) {
  const int b = p / SQ, r = p - b * SQ, wg = r >= 120, c = r & 1;
  const int a = r - (wg ? 144 : 0), m = r - (wg ? 128 : 96), e = r - (wg ? 120 : 112);
  int row;
  if (a >= 0 && a < 96) row = ((a >> 5) * 4 + ((a >> 1) & 3)) * 8 + ((a >> 3) & 3) * 2 + c;
  else if (m >= 0 && m < 16) row = (12 + ((m >> 1) & 1)) * 8 + (m >> 2) * 2 + c;
  else row = 112 + e;
  return b * SQ + wg * 120 + row;
}

__device__ __forceinline__ void slow_path(const Params& P, int b, int h, int wg, int w, int lane) {
  const int g = lane >> 2, q = lane & 3, row0 = wg * 120;
  const uint16_t* wq = reinterpret_cast<const uint16_t*>(P.wq) + h * DH + g;
  const __nv_bfloat16* kp = P.k + (size_t)(b * NH + h) * SK * DH;
  const uint16_t* vp = reinterpret_cast<const uint16_t*>(P.v) + (size_t)(b * NH + h) * SK * DH + g;
#pragma unroll 1
  for (int t = w; t < 8; t += 4) {
    const int r0 = 16 * t + g, r1 = r0 + 8;
    const __nv_bfloat16* x0 = P.x + (size_t)(b * SQ + row0 + r0) * DM + 2 * q;
    const __nv_bfloat16* x1 = P.x + (size_t)(b * SQ + row0 + min(r1, 119)) * DM + 2 * q;
    float o[16][4];
#pragma unroll
    for (int n = 0; n < 16; n++) o[n][0] = o[n][1] = o[n][2] = o[n][3] = 0.f;
#pragma unroll 1
    for (int k0 = 0; k0 < DM; k0 += 16) {
      uint32_t a[4] = {*(const uint32_t*)(x0 + k0), *(const uint32_t*)(x1 + k0), *(const uint32_t*)(x0 + k0 + 8), *(const uint32_t*)(x1 + k0 + 8)};
      const uint16_t* wr = wq + (size_t)(k0 + 2 * q) * HD;
#pragma unroll
      for (int n = 0; n < 16; n++)
        mma16816(o[n], a, wr[8 * n] | ((uint32_t)wr[8 * n + HD] << 16), wr[8 * n + 8 * HD] | ((uint32_t)wr[8 * n + 9 * HD] << 16));
    }
    uint32_t qa[8][4];
#pragma unroll
    for (int k = 0; k < 8; k++) {
      qa[k][0] = pack(o[2 * k][0] * QSCALE, o[2 * k][1] * QSCALE);
      qa[k][1] = pack(o[2 * k][2] * QSCALE, o[2 * k][3] * QSCALE);
      qa[k][2] = pack(o[2 * k + 1][0] * QSCALE, o[2 * k + 1][1] * QSCALE);
      qa[k][3] = pack(o[2 * k + 1][2] * QSCALE, o[2 * k + 1][3] * QSCALE);
    }
#pragma unroll
    for (int n = 0; n < 16; n++) o[n][0] = o[n][1] = o[n][2] = o[n][3] = 0.f;
    float m0 = -INFINITY, m1 = -INFINITY, l0 = 0.f, l1 = 0.f;
#pragma unroll 1
    for (int key0 = 0; key0 < SK; key0 += 16) {
      float s[2][4];
#pragma unroll
      for (int nt = 0; nt < 2; nt++) {
        s[nt][0] = s[nt][1] = s[nt][2] = s[nt][3] = 0.f;
        const __nv_bfloat16* kr = kp + (size_t)(key0 + 8 * nt + g) * DH + 2 * q;
#pragma unroll
        for (int k = 0; k < 8; k++) mma16816(s[nt], qa[k], *(const uint32_t*)(kr + 16 * k), *(const uint32_t*)(kr + 16 * k + 8));
      }
      float n0 = fmaxf(fmaxf(s[0][0], s[0][1]), fmaxf(s[1][0], s[1][1])), n1 = fmaxf(fmaxf(s[0][2], s[0][3]), fmaxf(s[1][2], s[1][3]));
      n0 = fmaxf(n0, __shfl_xor_sync(~0u, n0, 1)); n1 = fmaxf(n1, __shfl_xor_sync(~0u, n1, 1));
      n0 = fmaxf(n0, __shfl_xor_sync(~0u, n0, 2)); n1 = fmaxf(n1, __shfl_xor_sync(~0u, n1, 2));
      n0 = fmaxf(n0, m0); n1 = fmaxf(n1, m1);
      const float z0 = n0 == -INFINITY ? 0.f : n0, z1 = n1 == -INFINITY ? 0.f : n1;
      const float c0 = ex2(m0 - z0), c1 = ex2(m1 - z1);
      m0 = n0; m1 = n1;
#pragma unroll
      for (int nt = 0; nt < 2; nt++) {
        s[nt][0] = ex2(s[nt][0] - z0); s[nt][1] = ex2(s[nt][1] - z0);
        s[nt][2] = ex2(s[nt][2] - z1); s[nt][3] = ex2(s[nt][3] - z1);
      }
      l0 = l0 * c0 + s[0][0] + s[0][1] + s[1][0] + s[1][1];
      l1 = l1 * c1 + s[0][2] + s[0][3] + s[1][2] + s[1][3];
      uint32_t pa[4] = {pack(s[0][0], s[0][1]), pack(s[0][2], s[0][3]), pack(s[1][0], s[1][1]), pack(s[1][2], s[1][3])};
      const uint16_t* vr = vp + (size_t)(key0 + 2 * q) * DH;
#pragma unroll
      for (int n = 0; n < 16; n++) {
        o[n][0] *= c0; o[n][1] *= c0; o[n][2] *= c1; o[n][3] *= c1;
        mma16816(o[n], pa, vr[8 * n] | ((uint32_t)vr[8 * n + DH] << 16), vr[8 * n + 8 * DH] | ((uint32_t)vr[8 * n + 9 * DH] << 16));
      }
    }
    l0 += __shfl_xor_sync(~0u, l0, 1); l1 += __shfl_xor_sync(~0u, l1, 1);
    l0 += __shfl_xor_sync(~0u, l0, 2); l1 += __shfl_xor_sync(~0u, l1, 2);
    const float i0 = 1.f / l0, i1 = 1.f / l1;
    __nv_bfloat16* oc = P.o + (size_t)(h * DH + 2 * q) * NROWS + b * SQ;
    const int p0 = o_pos(wg, r0), p1 = o_pos(wg, min(r1, 119));
#pragma unroll
    for (int n = 0; n < 16; n++) {
      oc[(size_t)(8 * n) * NROWS + p0] = __float2bfloat16(o[n][0] * i0);
      oc[(size_t)(8 * n + 1) * NROWS + p0] = __float2bfloat16(o[n][1] * i0);
      if (r1 < 120) {
        oc[(size_t)(8 * n) * NROWS + p1] = __float2bfloat16(o[n][2] * i1);
        oc[(size_t)(8 * n + 1) * NROWS + p1] = __float2bfloat16(o[n][3] * i1);
      }
    }
  }
}

__device__ __forceinline__ int bk(int ks) { return B_ORDER && ks < 48 ? 32 - (ks & 48) + (ks & 15) : ks; }
__device__ __forceinline__ uint32_t x_slot(uint32_t wg, uint32_t j) { return j < 2 ? (2 * wg + j) * XB : (2 * j + wg) * XB; }
__device__ __forceinline__ int unit_batch(int u) { return (u & 63) >> 2; }
__device__ __forceinline__ int unit_head(int u, int rank) { return (u >> 6) * 8 + (u & 3) * 2 + rank; }

__global__ void __cluster_dims__(2, 1, 1) __launch_bounds__(384, 1)
fused_attn_kernel(const __grid_constant__ CUtensorMap tm_x, const __grid_constant__ CUtensorMap tm_wq,
                  const __grid_constant__ CUtensorMap tm_k, const __grid_constant__ CUtensorMap tm_v,
                  const __grid_constant__ CUtensorMap tm_o, const __grid_constant__ CUtensorMap tm_wo,
                  const __grid_constant__ Params P) {
  extern __shared__ uint8_t smem_raw[];
  const uint32_t sb = ((uint32_t)__cvta_generic_to_shared(smem_raw) + 1023) & ~1023u;
  const int warp = __shfl_sync(~0u, threadIdx.x >> 5, 0);
  int lane = threadIdx.x & 31;
  const int rank = blockIdx.x & 1, cl = blockIdx.x >> 1, ncl = gridDim.x >> 1;

  const int nsingle = ncl == 66 ? 44 : NOTILES;
  auto role = [&]() {
    mbar_wait(sb + BAR_ROLE + 16, 0);
    int id;
    asm volatile("ld.shared.u32 %0, [%1];" : "=r"(id) : "r"(sb + BAR_ROLE + 8) : "memory");
    return id;
  };

  if (threadIdx.x == 0) {
    for (int i = 0; i < 6; i++) {
      mbar_init(sb + BAR_RFULL + 8 * i, 1); mbar_init(sb + BAR_REMPTY + 8 * i, 8);
      mbar_init(sb + BAR_BFULL + 8 * i, 1); mbar_init(sb + BAR_BEMPTY + 8 * i, 16);
    }
    for (int i = 0; i < 8; i++) mbar_init(sb + BAR_XFULL + 8 * i, 1);
    for (int i = 0; i < 4; i++) mbar_init(sb + BAR_XEMPTY + 8 * i, 8);
    for (int i = 0; i < 2; i++) { mbar_init(sb + BAR_STAGE + 8 * i, 4); mbar_init(sb + BAR_LSUM + 8 * i, 4); mbar_init(sb + BAR_INV + 8 * i, 1); }
    mbar_init(sb + BAR_ROLE, 1); mbar_init(sb + BAR_ROLE + 16, 1);
    asm volatile("fence.mbarrier_init.release.cluster;" ::: "memory");
  }
  __syncwarp();
  asm volatile("barrier.cluster.arrive.relaxed.aligned;\nbarrier.cluster.wait.aligned;" ::: "memory");

  if (warp >= 8) {
    asm volatile("setmaxnreg.dec.sync.aligned.u32 24;");
    if (warp == 8) {
      uint64_t pol;
      asm volatile("createpolicy.fractional.L2::evict_first.b64 %0, 1.0;" : "=l"(pol));
      Ring r;
      auto load = [&](const CUtensorMap* m, int c1, int c2, bool ef) {
        mbar_wait(sb + BAR_REMPTY + 8 * r.slot, r.phase ^ 1);
        if (lane == 0) {
          mbar_expect(sb + BAR_RFULL + 8 * r.slot, RING_BYTES);
          if (ef) tma3d_hint(sb + r.slot * RING_BYTES, m, 0, c1, c2, sb + BAR_RFULL + 8 * r.slot, pol);
          else tma3d(sb + r.slot * RING_BYTES, m, 0, c1, c2, sb + BAR_RFULL + 8 * r.slot);
        }
        r.next();
      };
      const int rot = ROT * (blockIdx.x * 5 + (blockIdx.x >> 4));
      for (int u0 = 0;; u0 += ncl) {
        const int u = __shfl_sync(~0u, u0 ? role() + u0 : cl, 0);
        if (u >= NUNITS) break;
        const int h = unit_head(u, rank);
        const int krow = (unit_batch(u) * NH + h) * SK;
#pragma unroll 1
        for (int s = 0; s < 10; s++) {
          load(&tm_wq, s * 64, 2 * h, false);
          const int sp = u0 == 0 ? s - PF_HOLD : s;
          if (sp >= 0 && sp < PF_N && lane == 0) l2_prefetch(P.v + (size_t)(krow + ((PF_J0 + sp * PF_STEP + rot) & 15) * 64) * DH, 16384);
        }
#pragma unroll 1
        for (int j = 0; j <= 16; j++) {
          if (j < 16) load(&tm_k, krow + ((j + rot) & 15) * 64, 0, true);
          if (j == 1 + DPRO) load(&tm_v, krow + (rot & 15) * 64, 0, true);
          if (j > 1) load(&tm_v, krow + ((j - 1 + rot) & 15) * 64, 0, true);
        }
      }
      const int id = __shfl_sync(~0u, role(), 0);
      const bool dbl = ncl == 66 && id >= 58;
      for (int t = dbl ? 2 * id - 72 : id; t < (dbl ? NOTILES : nsingle); t += ncl) {
        const int row0 = (t >> 2) * 256 + rank * 128;
        const int b0 = row0 / SQ, b1 = (row0 + 127) / SQ;
#pragma unroll 1
        for (int ks = 0; ks < 64; ks++) {
          if (dbl ? (ks & 15) == 0 : ks == 0 || ks == 48) {
            const unsigned* c = &g_cnt[((lane & 1 ? b1 : b0) * 4 + (ks || dbl ? ks >> 4 : min(lane >> 1, 2))) * 8];
            unsigned v, n = 0;
            do {
              asm volatile("ld.acquire.gpu.global.u32 %0, [%1];" : "=r"(v) : "l"(c) : "memory");
              if (++n > (1u << 26)) __trap();
            } while (v < 16);
            __syncwarp();
            asm volatile("fence.proxy.async.global;" ::: "memory");
          }
          load(&tm_o, (dbl ? ks : bk(ks)) * 64, row0 >> 6, O_EF);
        }
      }
      if (lane == 0 && atomicAdd(&g_cnt[64 * 8], 1) == gridDim.x - 1) {
        for (int i = 0; i < 67; i++) g_cnt[i * 8] = 0;
      }
    } else if (warp == 9) {
      if (lane == 0) {
        uint32_t it = 0;
        for (;; it++) {
          const int u = it ? role() + it * ncl : cl;
          if (u >= NUNITS) break;
          const int row = unit_batch(u) * SQ + rank * 120;
#pragma unroll 1
          for (int s = 0; s < 10; s++) {
            const uint32_t j = s & 3, par = ((s >> 2) + (j < 2 ? it : 0)) & 1;
            mbar_wait(sb + BAR_XEMPTY + 8 * j, par ^ 1);
            const uint32_t fb = sb + BAR_XFULL + 32 * rank + 8 * j;
            mbar_expect(fb, XB);
            mbar_expect_cl(mapa(fb, rank ^ 1), XB);
            tma2d_mc(sb + OFF_Q + x_slot(rank, j), &tm_x, s * 64, row, fb);
          }
        }
        const int id = role();
        const bool dbl = ncl == 66 && id >= 58;
        uint32_t slot = rank, phase = 0;
        for (int t = dbl ? 2 * id - 72 + rank : id; t < (dbl ? NOTILES : nsingle); t += ncl) {
#pragma unroll 1
          for (int ks = dbl ? 0 : rank; ks < 64; ks += dbl ? 1 : 2) {
            mbar_wait(sb + BAR_BEMPTY + 8 * slot, phase);
            const uint32_t fb = sb + BAR_BFULL + 8 * slot;
            mbar_expect(fb, BB);
            mbar_expect_cl(mapa(fb, rank ^ 1), BB);
            tma3d_mc(sb + OFF_Q + slot * BB, &tm_wo, 0, (dbl ? ks : bk(ks)) * 64, (t & 3) * 5, fb);
            if (WO_PF && dbl && ks + WO_PF < 64 && (ks & 3) == ((id >> 1) & 3))
              asm volatile("cp.async.bulk.prefetch.tensor.3d.L2.global [%0, {%1, %2, %3}];" ::"l"(&tm_wo), "r"(0), "r"((ks + WO_PF) * 64), "r"((t & 3) * 5) : "memory");
            slot += 2;
            if (slot >= 6) { slot -= 6; phase ^= 1; }
          }
        }
      }
    } else {
      const int wg = warp - 10;
      {
        mbar_wait(sb + BAR_RFULL, 0);
        const __nv_bfloat16* xs = P.x + (size_t)(unit_batch(cl) * SQ + ((cl & 3) * 2 + rank) * 30 + min(lane, 29)) * DM + 256 + wg * 64;
#pragma unroll
        for (int i = 0; i < 3; i++) asm volatile("prefetch.global.L2 [%0];" ::"l"(xs + i * 128));
        if (lane < 16) asm volatile("prefetch.global.L2 [%0];" ::"l"(P.wq + (size_t)(384 + unit_batch(cl) * 16 + lane) * HD + unit_head(cl, rank) * DH + wg * 64));
      }
      if (wg == 0 && rank == 0 && lane == 0) {
        int id = cl;
        if (ncl == 66) {
          uint32_t smid;
          asm("mov.u32 %0, %smid;" : "=r"(smid));
          id = smid >= SMID_TOP ? 65 - atomicAdd(&g_cnt[65 * 8], 1) : atomicAdd(&g_cnt[66 * 8], 1);
        }
#pragma unroll
        for (int c = 0; c < 2; c++) {
          const uint32_t a = mapa(sb + BAR_ROLE, c);
          asm volatile("st.shared::cluster.u32 [%0 + 8], %1;\nmbarrier.arrive.release.cluster.shared::cluster.b64 _, [%0];" ::"r"(a), "r"(id) : "memory");
        }
      }
      if (wg == 0 && lane == 0) {
        mbar_wait_cl(sb + BAR_ROLE, 0);
        mbar_arrive(sb + BAR_ROLE + 16);
      }
      __syncwarp();
      for (uint32_t it = 0;; it++) {
        const int u = __shfl_sync(~0u, it ? role() + it * ncl : cl, 0);
        if (u >= NUNITS) break;
        mbar_wait(sb + BAR_LSUM + 8 * wg, it & 1);
        float l4[4], v[4];
        const uint32_t a = sb + OFF_L2 + wg * 2048 + lane * 16;
        asm volatile("ld.shared.v4.f32 {%0, %1, %2, %3}, [%4];" : "=f"(l4[0]), "=f"(l4[1]), "=f"(l4[2]), "=f"(l4[3]) : "r"(a) : "memory");
#pragma unroll
        for (int g = 1; g < 4; g++) {
          asm volatile("ld.shared.v4.f32 {%0, %1, %2, %3}, [%4];" : "=f"(v[0]), "=f"(v[1]), "=f"(v[2]), "=f"(v[3]) : "r"(a + g * 512) : "memory");
#pragma unroll
          for (int c = 0; c < 4; c++) l4[c] += v[c];
        }
#pragma unroll
        for (int c = 0; c < 4; c++) {
          float inv;
          asm("rcp.approx.ftz.f32 %0, %1;" : "=f"(inv) : "f"(l4[c]));
          l4[c] = l4[c] >= L_MIN && l4[c] <= L_MAX ? inv : __uint_as_float(0x7FFFFFFFu);
        }
        const uint32_t h0 = pack(l4[0], l4[1]), h1 = pack(l4[2], l4[3]);
        const uint32_t e0 = pack(l4[0] - __uint_as_float(h0 << 16), l4[1] - __uint_as_float(h0 & 0xFFFF0000u));
        const uint32_t e1 = pack(l4[2] - __uint_as_float(h1 << 16), l4[3] - __uint_as_float(h1 & 0xFFFF0000u));
        const uint32_t ia = sb + OFF_INV + wg * 640 + (lane & 1) * 288 + (lane >> 1) * 8;
        asm volatile("st.shared.v2.u32 [%0], {%1, %2};\nst.shared.v2.u32 [%0 + 144], {%3, %4};" ::"r"(ia), "r"(h0), "r"(e0), "r"(h1), "r"(e1) : "memory");
        __syncwarp();
        if (lane == 0) {
          mbar_arrive(sb + BAR_INV + 8 * wg);
          mbar_wait(sb + BAR_STAGE + 8 * wg, it & 1);
          __threadfence();
          asm volatile("red.relaxed.gpu.global.add.u32 [%0], 1;" ::"l"(&g_cnt[(unit_batch(u) * 4 + (u >> 6)) * 8]) : "memory");
        }
        __syncwarp();
      }
    }
  } else {
    asm volatile("setmaxnreg.inc.sync.aligned.u32 240;");
    const int wg = warp >> 2, w = warp & 3;
    const uint32_t qreg = sb + OFF_Q + wg * 2 * XB, preg = sb + OFF_P + (2 + wg) * XB;
    const uint32_t st_off = ((lane >> 4) * 8 + (lane & 7)) * 128 + (((2 * w + ((lane >> 3) & 1)) ^ (lane & 7)) << 4);
    const uint32_t xempty = mapa(sb + BAR_XEMPTY, wg);
    Ring r;
    uint32_t it = 0;
    const uint32_t qd = (qreg & 0x3FFFF) >> 4, pd = (preg & 0x3FFFF) >> 4;
    auto ring_addr = [&]() { return ((sb & 0x3FFFF) + r.slot * RING_BYTES) >> 4; };
    auto ring_wait = [&]() { mbar_wait(sb + BAR_RFULL + 8 * r.slot, r.phase); };
    auto release = [&](uint32_t slot) { if (lane == 0) mbar_arrive(sb + BAR_REMPTY + 8 * slot); };
    auto turn_wait = [&]() {
      if (wg == 0) asm volatile("bar.sync 3, 256;" ::: "memory");
      else asm volatile("bar.sync 4, 256;" ::: "memory");
    };
    auto turn_pass = [&]() {
      if (wg == 0) asm volatile("bar.arrive 4, 256;" ::: "memory");
      else asm volatile("bar.arrive 3, 256;" ::: "memory");
    };

    uint32_t chk = 0;
    auto load_inv = [&](uint32_t (&iv)[30], uint32_t parity) {
      mbar_wait(sb + BAR_INV + 8 * wg, parity);
      chk = 0;
#pragma unroll
      for (int j = 0; j < 7; j++)
        asm volatile("ld.shared.v4.u32 {%0, %1, %2, %3}, [%4];" : "=r"(iv[4 * j]), "=r"(iv[4 * j + 1]), "=r"(iv[4 * j + 2]), "=r"(iv[4 * j + 3])
                     : "r"(sb + OFF_INV + wg * 640 + (lane & 3) * 144 + j * 16) : "memory");
      asm volatile("ld.shared.v2.u32 {%0, %1}, [%2];" : "=r"(iv[28]), "=r"(iv[29]) : "r"(sb + OFF_INV + wg * 640 + (lane & 3) * 144 + 112) : "memory");
    };
    auto norm = [&](uint32_t (&n)[8], const uint32_t (&po)[60], const uint32_t (&iv)[30], auto part) {
      constexpr int k = decltype(part)::value >> 1, j0 = (decltype(part)::value & 1) * 8;
#pragma unroll
      for (int j = 0; j < 8; j++)
        n[j] = j0 + j < 15 ? hfma2(po[15 * k + (j0 + j) % 15], iv[2 * ((j0 + j) % 15)], hfma2(po[15 * k + (j0 + j) % 15], iv[2 * ((j0 + j) % 15) + 1], 0x80008000u)) : 0x3F803F80u;
#pragma unroll
      for (int j = 0; j < 8; j += 2) chk = hfma2(n[j], n[j + 1], chk);
    };
    auto store = [&](const uint32_t (&n)[8], const char* optr, auto part) {
      constexpr int k = decltype(part)::value >> 1;
      const char* o = optr + (size_t)(8 * (k & 1) + 64 * (k >> 1)) * NROWS * 2;
      if ((decltype(part)::value & 1) == 0)
        asm volatile(
            "{\n.reg .pred p;\nsetp.ne.u64 p, %9, 0;\n"
            "@p st.global.v4.u32 [%8], {%0, %1, %2, %3};\n@p st.global.v4.u32 [%8 + 64], {%4, %5, %6, %7};\n}\n"
            ::"r"(n[0]), "r"(n[1]), "r"(n[2]), "r"(n[3]), "r"(n[4]), "r"(n[5]), "r"(n[6]), "r"(n[7]),
            "l"(o + (wg ? 288 : 0) + (lane & 3) * 16), "l"(optr) : "memory");
      else
        asm volatile(
            "{\n.reg .pred p;\nsetp.ne.u64 p, %10, 0;\n"
            "@p st.global.v4.u32 [%7 + 128], {%0, %1, %2, %3};\n@p st.global.v2.u32 [%8], {%4, %5};\n@p st.global.u32 [%9], %6;\n}\n"
            ::"r"(n[0]), "r"(n[1]), "r"(n[2]), "r"(n[3]), "r"(n[4]), "r"(n[5]), "r"(n[6]), "l"(o + (wg ? 288 : 0) + (lane & 3) * 16),
            "l"(o + (wg ? 256 : 192) + (lane & 3) * 8), "l"(o + (wg ? 240 : 224) + (lane & 3) * 4), "l"(optr) : "memory");
    };
    auto put = [&](const uint32_t (&po)[60], const uint32_t (&iv)[30], const char* optr, auto part) {
      uint32_t n[8];
      norm(n, po, iv, part);
      store(n, optr, part);
    };
    auto out_ptr = [&](int u) {
      return reinterpret_cast<const char*>(P.o + (size_t)(unit_head(u, rank) * DH + 16 * w + (lane >> 2)) * NROWS + unit_batch(u) * SQ);
    };
    auto unsafe = [&](bool valid) {
      const bool b = valid && ((chk & 0x7F80u) == 0x7F80u || (chk & 0x7F800000u) == 0x7F800000u);
      return __any_sync(~0u, bar_red_or(wg, b));
    };
    auto publish = [&]() { __syncwarp(); if (lane == 0) mbar_arrive(sb + BAR_STAGE + 8 * wg); };

    uint32_t po[60];
#pragma unroll
    for (int i = 0; i < 60; i++) po[i] = 0;
    int id = 0;
    bool more;
    do {
      float o0[60], o1[60];
      uint32_t prev = 0;
      auto qstep = [&](int s, int acc) {
        const uint32_t j = s & 3, par = ((s >> 2) + (j < 2 ? it : 0)) & 1;
        TR(it * 160 + 3 * s);
        ring_wait();
        TR(it * 160 + 3 * s + 1);
        mbar_wait(sb + BAR_XFULL + 32 * wg + 8 * j, par);
        TR(it * 160 + 3 * s + 2);
        if (s >= ALT_FROM) turn_wait();
        wg_fence();
        mma_tn(o0, o1, ring_addr(), ((sb & 0x3FFFF) + OFF_Q + x_slot(wg, j)) >> 4, acc);
        wg_commit();
        if ((s >= ALT_FROM && !(MERGE89 && s == 8)) || (s == ALT_FROM - 1 && wg == 1)) turn_pass();
        if (s > 0) {
          wg_wait<1>();
          release(prev);
          if (s <= 6 && lane == 0) mbar_arrive_cl(xempty + 8 * ((s - 1) & 3));
        }
        prev = r.slot;
        r.next();
      };
      qstep(0, 0);
      const int up = it > 1 ? id + ((int)it - 1) * ncl : cl;
      const char* optr = it > 0 ? out_ptr(up) : nullptr;
      uint32_t n7[8];
      {
        uint32_t iv[30];
        qstep(1, 1); load_inv(iv, (it + 1) & 1); put(po, iv, optr, IC<0>());
        qstep(2, 1); put(po, iv, optr, IC<1>());
        qstep(3, 1); put(po, iv, optr, IC<2>());
        qstep(4, 1); put(po, iv, optr, IC<3>());
        qstep(5, 1); put(po, iv, optr, IC<4>());
        qstep(6, 1); put(po, iv, optr, IC<5>());
        qstep(7, 1); put(po, iv, optr, IC<6>());
        norm(n7, po, iv, IC<7>());
        if (LATE_AT == 3) store(n7, optr, IC<7>());
        qstep(8, 1);
        if (LATE_AT == 2) store(n7, optr, IC<7>());
      }
      TR(it * 160 + 27);
      ring_wait();
      TR(it * 160 + 28);
      mbar_wait(sb + BAR_XFULL + 32 * wg + 8, it & 1);
      TR(it * 160 + 29);
      if (!MERGE89) turn_wait();
      wg_fence();
      mma_tn_split(o0, o1, ring_addr(), qd + (XB >> 4));
      turn_pass();
      wg_wait<2>();
      release(prev);
      wg_wait<1>();
      reg_fence(o0);
      uint32_t pq[30];
#pragma unroll
      for (int j = 0; j < 30; j++) pq[j] = pack(o0[2 * j] * QSCALE, o0[2 * j + 1] * QSCALE);
      wg_wait<0>();
      reg_fence(o1);
      release(r.slot);
      r.next();
      TR(it * 160 + 30);
      bar_sync(wg);
#pragma unroll
      for (int j = 0; j < 14; j += 2) stsm4t(qreg + st_off + j * 1024, pq[2 * j], pq[2 * j + 1], pq[2 * j + 2], pq[2 * j + 3]);
      stsm2t(qreg + st_off + 14 * 1024, pq[28], pq[29]);
#pragma unroll
      for (int j = 0; j < 14; j += 2)
        stsm4t(qreg + XB + st_off + j * 1024, pack(o1[4 * j] * QSCALE, o1[4 * j + 1] * QSCALE), pack(o1[4 * j + 2] * QSCALE, o1[4 * j + 3] * QSCALE),
               pack(o1[4 * j + 4] * QSCALE, o1[4 * j + 5] * QSCALE), pack(o1[4 * j + 6] * QSCALE, o1[4 * j + 7] * QSCALE));
      stsm2t(qreg + XB + st_off + 14 * 1024, pack(o1[56] * QSCALE, o1[57] * QSCALE), pack(o1[58] * QSCALE, o1[59] * QSCALE));
      fence_async_smem();
      if (unsafe(it > 0)) {
        slow_path(P, unit_batch(up), unit_head(up, rank), wg, w, lane);
        optr = nullptr;
        if (!DPRO) {
#pragma unroll
          for (int i = 0; i < 60; i++) o0[i] = o1[i] = 0.f;
        }
      }
      TR(it * 160 + 32); TG(it * 160 + 142);

      float sc[60], l[30];
      ring_wait();
      TR(it * 160 + 33);
      turn_wait();
      wg_fence();
      mma_qk(sc, ring_addr(), qd);
      wg_commit();
      turn_pass();
      if (LATE_AT < 2) store(n7, optr, IC<7>());
      if (it > 0) publish();
      id = __shfl_sync(~0u, role(), 0);
      wg_wait<0>();
      reg_fence(sc);
      TR(it * 160 + 35);
      release(r.slot);
      r.next();
      exp_store<0, 15, true>(sc, l, preg + st_off);
      fence_async_smem();
      if (!NOBAR) bar_sync(wg);
      more = id + ((int)it + 1) * ncl < NUNITS;
      const bool gemm = id < nsingle || (ncl == 66 && id >= 58);
#pragma unroll 1
      for (int s = DPRO ? 3 : 1; s < 16; s++) {
        const uint32_t kslot = r.slot;
        TR(it * 160 + 32 + 6 * s); TG(it * 160 + 37 + 6 * s);
        ring_wait();
        TR(it * 160 + 33 + 6 * s);
        turn_wait();
        wg_fence();
        mma_qk(sc, ring_addr(), qd);
        wg_commit();
        r.next();
        TR(it * 160 + 36 + 6 * s);
        ring_wait();
        TR(it * 160 + 34 + 6 * s);
        wg_fence();
        mma_tn(o0, o1, ring_addr(), pd - ((s - 1) & 1) * (2 * XB >> 4), DPRO || s != 1);
        wg_commit();
        if (wg == 0 || s < 15) turn_pass();
        wg_wait<1>();
        reg_fence(sc);
        TR(it * 160 + 35 + 6 * s);
        release(kslot);
        if (s == 15) {
          if (more) { if (lane < 2) mbar_arrive_cl(xempty + 8 * lane); }
          else if (lane < 3 && gemm) mbar_arrive_cl(mapa(sb + BAR_BEMPTY + 8 * lane, lane & 1));
        }
        exp_store<0, VREL>(sc, l, preg - (s & 1) * 2 * XB + st_off);
        wg_wait<0>();
        reg_fence(o0); reg_fence(o1);
        release(r.slot);
        r.next();
        exp_store<VREL, 15>(sc, l, preg - (s & 1) * 2 * XB + st_off);
        fence_async_smem();
        if (!NOBAR) bar_sync(wg);
      }
      if (NOBAR) bar_sync(wg);
      TR(it * 160 + 128);
      ring_wait();
      wg_fence();
      mma_tn_split(o0, o1, ring_addr(), pd - (2 * XB >> 4));
      TR(it * 160 + 132);
      {
        const uint32_t a = preg + (8 * w + (lane >> 2)) * 480 + (lane & 3) * 8;
#pragma unroll
        for (int j = 0; j < 15; j++) asm volatile("st.shared.v2.f32 [%0], {%1, %2};" ::"r"(a + j * 32), "f"(l[2 * j]), "f"(l[2 * j + 1]) : "memory");
      }
      __syncwarp();
      float lv[8][4];
#pragma unroll
      for (int g = 0; g < 8; g++)
        asm volatile("ld.shared.v4.f32 {%0, %1, %2, %3}, [%4];" : "=f"(lv[g][0]), "=f"(lv[g][1]), "=f"(lv[g][2]), "=f"(lv[g][3])
                     : "r"(preg + (8 * w + g) * 480 + min(lane, 29) * 16) : "memory");
      TR(it * 160 + 133);
      wg_wait<1>();
      reg_fence(o0);
      TR(it * 160 + 134);
#pragma unroll
      for (int j = 0; j < 15; j++) { po[j] = pack(o0[4 * j], o0[4 * j + 1]); po[15 + j] = pack(o0[4 * j + 2], o0[4 * j + 3]); }
#pragma unroll
      for (int c = 0; c < 4; c++) lv[0][c] = ((lv[0][c] + lv[1][c]) + (lv[2][c] + lv[3][c])) + ((lv[4][c] + lv[5][c]) + (lv[6][c] + lv[7][c]));
      asm volatile("st.shared.v4.f32 [%0], {%1, %2, %3, %4};" ::"r"(sb + OFF_L2 + wg * 2048 + w * 512 + lane * 16), "f"(lv[0][0]), "f"(lv[0][1]),
                   "f"(lv[0][2]), "f"(lv[0][3]) : "memory");
      __syncwarp();
      if (lane == 0) mbar_arrive(sb + BAR_LSUM + 8 * wg);
      wg_wait<0>();
      reg_fence(o1);
      release(r.slot);
      r.next();
      if (more) { if (lane < 2) mbar_arrive_cl(xempty + 16 + 8 * lane); }
      else if (gemm && lane < 3) mbar_arrive_cl(mapa(sb + BAR_BEMPTY + 24 + 8 * lane, (lane + 1) & 1));
      TR(it * 160 + 130);
#pragma unroll
      for (int j = 0; j < 15; j++) { po[30 + j] = pack(o1[4 * j], o1[4 * j + 1]); po[45 + j] = pack(o1[4 * j + 2], o1[4 * j + 3]); }
      TR(it * 160 + 131); TG(it * 160 + 143);
      it++;
    } while (more);
    const bool gemm = id < nsingle || (ncl == 66 && id >= 58);
    const int u = id + ((int)it - 1) * ncl;
    lane = __shfl_sync(~0u, lane, lane);
    uint32_t pb[60];
#pragma unroll
    for (int i = 0; i < 60; i++) pb[i] = po[i] ^ (gridDim.y - 1);

    uint32_t bslot = 0, bphase = 0;
    auto out_tile = [&](const float (&acc)[80], int t) {
      const uint32_t st = sb + w * RING_BYTES + wg * 8192;
      const uint32_t sa = st + (lane & 15) * 336 + (lane >> 4) * 16;
#pragma unroll
      for (int j = 0; j < 20; j += 2)
        asm volatile("stmatrix.sync.aligned.m8n8.x4.shared.b16 [%0], {%1,%2,%3,%4};" ::"r"(sa + j * 16), "r"(pack(acc[4 * j], acc[4 * j + 1])),
                     "r"(pack(acc[4 * j + 2], acc[4 * j + 3])), "r"(pack(acc[4 * j + 4], acc[4 * j + 5])), "r"(pack(acc[4 * j + 6], acc[4 * j + 7])) : "memory");
      fence_async_smem();
      __syncwarp();
      if (lane < 16) {
        __nv_bfloat16* dst = P.out + (size_t)o_row((t >> 2) * 256 + rank * 128 + wg * 64 + w * 16 + lane) * DM + (t & 3) * 160;
        asm volatile("cp.async.bulk.global.shared::cta.bulk_group [%0], [%1], 320;" ::"l"(dst), "r"(st + lane * 336) : "memory");
        asm volatile("cp.async.bulk.commit_group;" ::: "memory");
        asm volatile("cp.async.bulk.wait_group.read 0;" ::: "memory");
      }
      __syncwarp();
    };
    for (int t = id; t < nsingle || t == id; t += ncl) {
      float acc[80];
      uint32_t prev = 0, bprev = 0;
      const bool tile = t < nsingle;
      const bool last = t + ncl >= nsingle;
      auto bstep = [&](int ks, int accf) {
        if (!(ks & 3)) TR(640 + ks / 2); if ((ks & 7) == 0) TG(144 + (ks >> 3));
        ring_wait();
        mbar_wait(sb + BAR_BFULL + 8 * bslot, bphase);
        if (!(ks & 3)) TR(641 + ks / 2);
        wg_fence();
        const uint32_t a = ring_addr() + wg * 512, bd = (((sb & 0x3FFFF) + OFF_Q + bslot * BB) >> 4) | ((4096u >> 4) << 16);
#pragma unroll
        for (int k = 0; k < 4; k++) wgmma_n160<1, 1>(acc, a + k * 128, HI128, bd + k * 64, HI64, k == 0 ? accf : 1);
        wg_commit();
        if (ks > 0) {
          wg_wait<1>();
          release(prev);
          if (lane == 0 && (ks < 59 || !last)) mbar_arrive_cl(mapa(sb + BAR_BEMPTY + 8 * bprev, bprev & 1));
        }
        prev = r.slot; bprev = bslot;
        r.next();
        if (++bslot == 6) { bslot = 0; bphase ^= 1; }
      };
      const char* optr = t == id ? out_ptr(u) : nullptr;
      uint32_t iv[30];
      if (tile) {
        bstep(0, 0);
        bstep(1, 1);
        bstep(2, 1); load_inv(iv, (it + 1) & 1); put(pb, iv, optr, IC<0>()); bstep(3, 1);
        bstep(4, 1); put(pb, iv, optr, IC<1>()); bstep(5, 1);
        bstep(6, 1); put(pb, iv, optr, IC<2>()); bstep(7, 1);
        bstep(8, 1); put(pb, iv, optr, IC<3>()); bstep(9, 1);
        bstep(10, 1); put(pb, iv, optr, IC<4>()); bstep(11, 1);
        bstep(12, 1); put(pb, iv, optr, IC<5>()); bstep(13, 1);
        bstep(14, 1); put(pb, iv, optr, IC<6>()); bstep(15, 1);
        bstep(16, 1); put(pb, iv, optr, IC<7>());
        wg_wait<0>();
        reg_fence(acc);
      } else {
#pragma unroll
        for (int i = 0; i < 80; i++) acc[i] = 0.f;
        load_inv(iv, (it + 1) & 1);
        put(pb, iv, optr, IC<0>()); put(pb, iv, optr, IC<1>()); put(pb, iv, optr, IC<2>()); put(pb, iv, optr, IC<3>());
        put(pb, iv, optr, IC<4>()); put(pb, iv, optr, IC<5>()); put(pb, iv, optr, IC<6>()); put(pb, iv, optr, IC<7>());
      }
      if (unsafe(t == id)) slow_path(P, unit_batch(u), unit_head(u, rank), wg, w, lane);
      if (t == id) publish();
      if (!tile) break;
#pragma unroll 1
      for (int ks = 17; ks < 64; ks++) {
        if (END_SKEW && wg == 1 && ks == 64 - END_SKEW) turn_wait();
        bstep(ks, 1);
      }
      if (END_SKEW && wg == 0) turn_pass();
      wg_wait<0>();
      reg_fence(acc);
      release(prev);
      if (lane == 0 && !last) mbar_arrive_cl(mapa(sb + BAR_BEMPTY + 8 * bprev, bprev & 1));
      TR(158); TG(156);
      const int pos0 = (t >> 2) * 256 + rank * 128 + wg * 64 + w * 16;
      if (last) {
        bar_sync(wg);
        out_tile(acc, t);
      } else {
        __nv_bfloat16* op0 = P.out + (size_t)o_row(pos0 + (lane >> 2)) * DM + (t & 3) * 160 + (lane & 3) * 2;
        __nv_bfloat16* op1 = P.out + (size_t)o_row(pos0 + (lane >> 2) + 8) * DM + (t & 3) * 160 + (lane & 3) * 2;
#pragma unroll
        for (int j = 0; j < 20; j++) {
          *reinterpret_cast<uint32_t*>(op0 + j * 8) = pack(acc[4 * j], acc[4 * j + 1]);
          *reinterpret_cast<uint32_t*>(op1 + j * 8) = pack(acc[4 * j + 2], acc[4 * j + 3]);
        }
      }
#pragma unroll
      for (int i = 0; i < 60; i++) pb[i] = 0;
    }
    if (gemm && id >= nsingle) {
      float ac0[80], ac1[80];
      uint32_t prev = 0, bprev = 0;
      auto half = [&](float (&acc)[80], int hs, int accf) {
        mbar_wait(sb + BAR_BFULL + 8 * bslot, bphase);
        wg_fence();
        const uint32_t a = ring_addr() + wg * 512, bd = (((sb & 0x3FFFF) + OFF_Q + bslot * BB) >> 4) | ((4096u >> 4) << 16);
#pragma unroll
        for (int k = 0; k < 4; k++) wgmma_n160<1, 1>(acc, a + k * 128, HI128, bd + k * 64, HI64, k == 0 ? accf : 1);
        wg_commit();
        if (hs > 0) {
          wg_wait<1>();
          if (lane == 0 && hs < 123) mbar_arrive_cl(mapa(sb + BAR_BEMPTY + 8 * bprev, bprev & 1));
        }
        bprev = bslot;
        if (++bslot == 6) { bslot = 0; bphase ^= 1; }
      };
      auto dstep = [&](int ks, int accf) {
        if (!(ks & 3)) TR(640 + ks / 2); if ((ks & 7) == 0) TG(144 + (ks >> 3));
        ring_wait();
        if (!(ks & 3)) TR(641 + ks / 2);
        half(ac0, 2 * ks, accf);
        if (ks > 0) release(prev);
        half(ac1, 2 * ks + 1, accf);
        prev = r.slot;
        r.next();
      };
      dstep(0, 0);
#pragma unroll 1
      for (int ks = 1; ks < 64; ks++) {
        if (wg == 1 && ks == 62) turn_wait();
        dstep(ks, 1);
      }
      if (wg == 0) turn_pass();
      wg_wait<0>();
      reg_fence(ac0); reg_fence(ac1);
      TR(158); TG(156);
      bar_sync(wg);
      out_tile(ac0, 2 * id - 72);
      out_tile(ac1, 2 * id - 71);
    }
    TR(159);
  }
}

typedef CUresult (*EncodeFn)(CUtensorMap*, CUtensorMapDataType, cuuint32_t, void*, const cuuint64_t*, const cuuint64_t*,
                             const cuuint32_t*, const cuuint32_t*, CUtensorMapInterleave, CUtensorMapSwizzle,
                             CUtensorMapL2promotion, CUtensorMapFloatOOBfill);

void make_map(EncodeFn enc, CUtensorMap* m, const void* p, int rank, const cuuint64_t* dims, const cuuint64_t* strides,
              const cuuint32_t* box, CUtensorMapSwizzle sw, CUtensorMapL2promotion promo) {
  cuuint32_t es[3] = {1, 1, 1};
  enc(m, CU_TENSOR_MAP_DATA_TYPE_BFLOAT16, rank, const_cast<void*>(p), dims, strides, box, es, CU_TENSOR_MAP_INTERLEAVE_NONE, sw,
      promo, CU_TENSOR_MAP_FLOAT_OOB_FILL_NONE);
}

}

extern "C" void kernel_launch(void* const* d_in, const int* in_sizes, int n_in, void* d_out, int out_size) {
  static EncodeFn enc = nullptr;
  static int nclusters = 0;
  static void* o_ptr = nullptr;
  if (!enc) {
    cudaDriverEntryPointQueryResult qr;
    cudaGetDriverEntryPoint("cuTensorMapEncodeTiled", (void**)&enc, cudaEnableDefault, &qr);
    cudaFuncSetAttribute(fused_attn_kernel, cudaFuncAttributeMaxDynamicSharedMemorySize, SMEM_BYTES);
    cudaGetSymbolAddress(&o_ptr, g_o);
    cudaLaunchConfig_t cfg = {};
    cfg.gridDim = 128; cfg.blockDim = 384; cfg.dynamicSmemBytes = SMEM_BYTES;
    cudaLaunchAttribute at; at.id = cudaLaunchAttributeClusterDimension;
    at.val.clusterDim.x = 2; at.val.clusterDim.y = 1; at.val.clusterDim.z = 1;
    cfg.attrs = &at; cfg.numAttrs = 1;
    int n = 0;
    cudaOccupancyMaxActiveClusters(&n, fused_attn_kernel, &cfg);
    nclusters = n >= 66 ? MAXCL : (n >= 64 || n <= 0 ? 64 : n);
  }
  const __nv_bfloat16* x = (const __nv_bfloat16*)d_in[0];
  const __nv_bfloat16* k = (const __nv_bfloat16*)d_in[1];
  const __nv_bfloat16* v = (const __nv_bfloat16*)d_in[2];
  const __nv_bfloat16* wq = (const __nv_bfloat16*)d_in[3];
  const __nv_bfloat16* wo = (const __nv_bfloat16*)d_in[4];
  CUtensorMap tm_x, tm_wq, tm_k, tm_v, tm_o, tm_wo;
  const auto S128 = CU_TENSOR_MAP_SWIZZLE_128B;
  const auto P128 = CU_TENSOR_MAP_L2_PROMOTION_L2_128B, P256 = CU_TENSOR_MAP_L2_PROMOTION_L2_256B;
  { cuuint64_t d[2] = {DM, NB * SQ}, s[1] = {DM * 2}; cuuint32_t b[2] = {64, 120}; make_map(enc, &tm_x, x, 2, d, s, b, S128, P128); }
  { cuuint64_t d[3] = {64, DM, HD / 64}, s[2] = {HD * 2, 128}; cuuint32_t b[3] = {64, 64, 2}; make_map(enc, &tm_wq, wq, 3, d, s, b, S128, P256); }
  { cuuint64_t d[3] = {64, NB * NH * SK, 2}, s[2] = {DH * 2, 128}; cuuint32_t b[3] = {64, 64, 2};
    make_map(enc, &tm_k, k, 3, d, s, b, S128, P128); make_map(enc, &tm_v, v, 3, d, s, b, S128, P128); }
  { cuuint64_t d[3] = {64, HD, NROWS / 64}, s[2] = {NROWS * 2, 128}; cuuint32_t b[3] = {64, 64, 2}; make_map(enc, &tm_o, o_ptr, 3, d, s, b, S128, P256); }
  { cuuint64_t d[3] = {32, HD, DM / 32}, s[2] = {DM * 2, 64}; cuuint32_t b[3] = {32, 64, 5};
    make_map(enc, &tm_wo, wo, 3, d, s, b, CU_TENSOR_MAP_SWIZZLE_64B, P128); }
  Params P{x, k, v, wq, (__nv_bfloat16*)d_out, (__nv_bfloat16*)o_ptr};
  fused_attn_kernel<<<2 * nclusters, 384, SMEM_BYTES>>>(tm_x, tm_wq, tm_k, tm_v, tm_o, tm_wo, P);
}
```

```cpp
#include <cuda_runtime.h>
#include <cuda.h>
#include <cuda_bf16.h>
#include <stdint.h>

namespace {

constexpr int NB = 16, SQ = 240, DM = 640, NH = 32, SK = 1024, DH = 128, HD = NH * DH;
constexpr int NROWS = NB * SQ;
constexpr int NUNITS = 256;
#define DPRO 0
#define LATE_AT 0
#define ALT_FROM 3
#define MERGE89 1
#define END_SKEW 5
#define VREL 8
#define PF_HOLD 6
#define PF_N 4
#define PF_J0 3
#define PF_STEP 3
#define ROT 0
#define O_EF 1
#define B_ORDER 1
#define WO_PF 6
#define ROLE_AT 1
#define ASYM 0
#define ASYM_PASS 1
#define PINLANE 0
#define MAXCL 66
#define SMID_TOP 88
constexpr int NOTILES = 60;
constexpr float QSCALE = 0.08838834764831845f * 1.4426950408889634f;
constexpr float L_MIN = 9.5367431640625e-07f;
constexpr float L_MAX = 1.152921504606846976e18f;

constexpr uint32_t RING_SLOTS = 6, RING_BYTES = 16384;
constexpr uint32_t XB = 15360;
constexpr uint32_t BB = 20480;
constexpr uint32_t OFF_Q = RING_SLOTS * RING_BYTES;
constexpr uint32_t OFF_P = OFF_Q + 4 * XB;
constexpr uint32_t OFF_INV = OFF_P + 4 * XB;
constexpr uint32_t OFF_L2 = OFF_INV + 1280;
constexpr uint32_t OFF_BAR = OFF_L2 + 4096;
constexpr uint32_t BAR_RFULL = OFF_BAR, BAR_REMPTY = BAR_RFULL + 48, BAR_XFULL = BAR_REMPTY + 48,
    BAR_XEMPTY = BAR_XFULL + 64, BAR_BFULL = BAR_XEMPTY + 32, BAR_BEMPTY = BAR_BFULL + 48, BAR_STAGE = BAR_BEMPTY + 48;
constexpr uint32_t BAR_ROLE = BAR_STAGE + 16, BAR_LSUM = BAR_ROLE + 24, BAR_INV = BAR_LSUM + 16;
constexpr uint32_t OFF_TR = BAR_INV + 16;
constexpr uint32_t SMEM_BYTES = OFF_TR + 1024;

constexpr uint32_t HI128 = (1u << 30) | (1024 >> 4);
constexpr uint32_t HI64 = (2u << 30) | (512 >> 4);

__device__ __nv_bfloat16 g_o[HD * NROWS];
__device__ unsigned g_cnt[67 * 8];
#define TR(i)
#define TG(i)

struct Params {
  const __nv_bfloat16 *x, *k, *v, *wq;
  __nv_bfloat16 *out, *o;
};

__device__ __forceinline__ void wg_fence() { asm volatile("wgmma.fence.sync.aligned;" ::: "memory"); }
__device__ __forceinline__ void wg_commit() { asm volatile("wgmma.commit_group.sync.aligned;" ::: "memory"); }
template <int N> __device__ __forceinline__ void wg_wait() { asm volatile("wgmma.wait_group.sync.aligned %0;" ::"n"(N) : "memory"); }
template <int N> __device__ __forceinline__ void reg_fence(float (&r)[N]) {
#pragma unroll
  for (int i = 0; i < N; i++) asm volatile("" : "+f"(r[i])::"memory");
}
template <int TA, int TB>
__device__ __forceinline__ void wgmma_n120(float (&d)[60], uint32_t a_lo, uint32_t a_hi, uint32_t b_lo, uint32_t b_hi, int acc) {
  asm volatile(
      "{\n.reg .pred p;\n.reg .b64 da, db;\nsetp.ne.b32 p, %64, 0;\n"
      "mov.b64 da, {%60, %61};\nmov.b64 db, {%62, %63};\n"
      "wgmma.mma_async.sync.aligned.m64n120k16.f32.bf16.bf16 {"
      "%0, %1, %2, %3, %4, %5, %6, %7, %8, %9, %10, %11, %12, %13, %14, %15, %16, %17, %18, %19, %20, %21, %22, %23, "
      "%24, %25, %26, %27, %28, %29, %30, %31, %32, %33, %34, %35, %36, %37, %38, %39, %40, %41, %42, %43, %44, %45, "
      "%46, %47, %48, %49, %50, %51, %52, %53, %54, %55, %56, %57, %58, %59"
      "}, da, db, p, 1, 1, %65, %66;\n}\n"
      : "+f"(d[0]), "+f"(d[1]), "+f"(d[2]), "+f"(d[3]), "+f"(d[4]), "+f"(d[5]), "+f"(d[6]), "+f"(d[7]), "+f"(d[8]),
        "+f"(d[9]), "+f"(d[10]), "+f"(d[11]), "+f"(d[12]), "+f"(d[13]), "+f"(d[14]), "+f"(d[15]), "+f"(d[16]),
        "+f"(d[17]), "+f"(d[18]), "+f"(d[19]), "+f"(d[20]), "+f"(d[21]), "+f"(d[22]), "+f"(d[23]), "+f"(d[24]),
        "+f"(d[25]), "+f"(d[26]), "+f"(d[27]), "+f"(d[28]), "+f"(d[29]), "+f"(d[30]), "+f"(d[31]), "+f"(d[32]),
        "+f"(d[33]), "+f"(d[34]), "+f"(d[35]), "+f"(d[36]), "+f"(d[37]), "+f"(d[38]), "+f"(d[39]), "+f"(d[40]),
        "+f"(d[41]), "+f"(d[42]), "+f"(d[43]), "+f"(d[44]), "+f"(d[45]), "+f"(d[46]), "+f"(d[47]), "+f"(d[48]),
        "+f"(d[49]), "+f"(d[50]), "+f"(d[51]), "+f"(d[52]), "+f"(d[53]), "+f"(d[54]), "+f"(d[55]), "+f"(d[56]),
        "+f"(d[57]), "+f"(d[58]), "+f"(d[59])
      : "r"(a_lo), "r"(a_hi), "r"(b_lo), "r"(b_hi), "r"(acc), "n"(TA), "n"(TB));
}

template <int TA, int TB>
__device__ __forceinline__ void wgmma_n160(float (&d)[80], uint32_t a_lo, uint32_t a_hi, uint32_t b_lo, uint32_t b_hi, int acc) {
  asm volatile(
      "{\n.reg .pred p;\n.reg .b64 da, db;\nsetp.ne.b32 p, %84, 0;\n"
      "mov.b64 da, {%80, %81};\nmov.b64 db, {%82, %83};\n"
      "wgmma.mma_async.sync.aligned.m64n160k16.f32.bf16.bf16 {"
      "%0, %1, %2, %3, %4, %5, %6, %7, %8, %9, %10, %11, %12, %13, %14, %15, %16, %17, %18, %19, %20, %21, %22, %23, "
      "%24, %25, %26, %27, %28, %29, %30, %31, %32, %33, %34, %35, %36, %37, %38, %39, %40, %41, %42, %43, %44, %45, "
      "%46, %47, %48, %49, %50, %51, %52, %53, %54, %55, %56, %57, %58, %59, %60, %61, %62, %63, %64, %65, %66, %67, "
      "%68, %69, %70, %71, %72, %73, %74, %75, %76, %77, %78, %79"
      "}, da, db, p, 1, 1, %85, %86;\n}\n"
      : "+f"(d[0]), "+f"(d[1]), "+f"(d[2]), "+f"(d[3]), "+f"(d[4]), "+f"(d[5]), "+f"(d[6]), "+f"(d[7]), "+f"(d[8]),
        "+f"(d[9]), "+f"(d[10]), "+f"(d[11]), "+f"(d[12]), "+f"(d[13]), "+f"(d[14]), "+f"(d[15]), "+f"(d[16]),
        "+f"(d[17]), "+f"(d[18]), "+f"(d[19]), "+f"(d[20]), "+f"(d[21]), "+f"(d[22]), "+f"(d[23]), "+f"(d[24]),
        "+f"(d[25]), "+f"(d[26]), "+f"(d[27]), "+f"(d[28]), "+f"(d[29]), "+f"(d[30]), "+f"(d[31]), "+f"(d[32]),
        "+f"(d[33]), "+f"(d[34]), "+f"(d[35]), "+f"(d[36]), "+f"(d[37]), "+f"(d[38]), "+f"(d[39]), "+f"(d[40]),
        "+f"(d[41]), "+f"(d[42]), "+f"(d[43]), "+f"(d[44]), "+f"(d[45]), "+f"(d[46]), "+f"(d[47]), "+f"(d[48]),
        "+f"(d[49]), "+f"(d[50]), "+f"(d[51]), "+f"(d[52]), "+f"(d[53]), "+f"(d[54]), "+f"(d[55]), "+f"(d[56]),
        "+f"(d[57]), "+f"(d[58]), "+f"(d[59]), "+f"(d[60]), "+f"(d[61]), "+f"(d[62]), "+f"(d[63]), "+f"(d[64]),
        "+f"(d[65]), "+f"(d[66]), "+f"(d[67]), "+f"(d[68]), "+f"(d[69]), "+f"(d[70]), "+f"(d[71]), "+f"(d[72]),
        "+f"(d[73]), "+f"(d[74]), "+f"(d[75]), "+f"(d[76]), "+f"(d[77]), "+f"(d[78]), "+f"(d[79])
      : "r"(a_lo), "r"(a_hi), "r"(b_lo), "r"(b_hi), "r"(acc), "n"(TA), "n"(TB));
}
__device__ __forceinline__ void mbar_init(uint32_t bar, int cnt) { asm volatile("mbarrier.init.shared::cta.b64 [%0], %1;" ::"r"(bar), "r"(cnt)); }
__device__ __forceinline__ void mbar_expect(uint32_t bar, uint32_t bytes) {
  asm volatile("mbarrier.arrive.expect_tx.shared::cta.b64 _, [%0], %1;" ::"r"(bar), "r"(bytes) : "memory");
}
__device__ __forceinline__ uint32_t mapa(uint32_t addr, uint32_t cta) {
  uint32_t r; asm("mapa.shared::cluster.u32 %0, %1, %2;" : "=r"(r) : "r"(addr), "r"(cta)); return r;
}
__device__ __forceinline__ void mbar_expect_cl(uint32_t cbar, uint32_t bytes) {
  asm volatile("mbarrier.arrive.expect_tx.shared::cluster.b64 _, [%0], %1;" ::"r"(cbar), "r"(bytes) : "memory");
}
__device__ __forceinline__ void mbar_arrive(uint32_t bar) { asm volatile("mbarrier.arrive.shared::cta.b64 _, [%0];" ::"r"(bar) : "memory"); }
__device__ __forceinline__ void mbar_arrive_cl(uint32_t cbar) { asm volatile("mbarrier.arrive.shared::cluster.b64 _, [%0];" ::"r"(cbar) : "memory"); }
__device__ __forceinline__ void mbar_wait(uint32_t bar, uint32_t parity) {
  asm volatile(
      "{\n.reg .pred p;\n.reg .u32 n;\n"
      "mbarrier.try_wait.parity.shared::cta.b64 p, [%0], %1;\n@p bra WAIT_DONE;\n"
      "mov.u32 n, 0;\n"
      "WAIT_LOOP:\n"
      "mbarrier.try_wait.parity.shared::cta.b64 p, [%0], %1;\n@p bra WAIT_DONE;\n"
      "add.u32 n, n, 1;\nsetp.lt.u32 p, n, 0x4000000;\n@p bra WAIT_LOOP;\ntrap;\n"
      "WAIT_DONE:\n}\n" ::"r"(bar), "r"(parity) : "memory");
}
__device__ __forceinline__ void mbar_wait_cl(uint32_t bar, uint32_t parity) {
  asm volatile(
      "{\n.reg .pred p;\n.reg .u32 n;\nmov.u32 n, 0;\n"
      "WAIT_LOOP:\n"
      "mbarrier.try_wait.parity.acquire.cluster.shared::cta.b64 p, [%0], %1;\n@p bra WAIT_DONE;\n"
      "add.u32 n, n, 1;\nsetp.lt.u32 p, n, 0x4000000;\n@p bra WAIT_LOOP;\ntrap;\n"
      "WAIT_DONE:\n}\n" ::"r"(bar), "r"(parity) : "memory");
}
__device__ __forceinline__ void tma3d(uint32_t dst, const CUtensorMap* m, int c0, int c1, int c2, uint32_t bar) {
  asm volatile("cp.async.bulk.tensor.3d.shared::cluster.global.mbarrier::complete_tx::bytes [%0], [%1, {%3, %4, %5}], [%2];"
               ::"r"(dst), "l"(m), "r"(bar), "r"(c0), "r"(c1), "r"(c2) : "memory");
}
__device__ __forceinline__ void tma3d_hint(uint32_t dst, const CUtensorMap* m, int c0, int c1, int c2, uint32_t bar, uint64_t pol) {
  asm volatile("cp.async.bulk.tensor.3d.shared::cluster.global.mbarrier::complete_tx::bytes.L2::cache_hint [%0], [%1, {%3, %4, %5}], [%2], %6;"
               ::"r"(dst), "l"(m), "r"(bar), "r"(c0), "r"(c1), "r"(c2), "l"(pol) : "memory");
}
__device__ __forceinline__ void tma2d_mc(uint32_t dst, const CUtensorMap* m, int c0, int c1, uint32_t bar) {
  asm volatile("cp.async.bulk.tensor.2d.shared::cluster.global.mbarrier::complete_tx::bytes.multicast::cluster [%0], [%1, {%3, %4}], [%2], %5;"
               ::"r"(dst), "l"(m), "r"(bar), "r"(c0), "r"(c1), "h"((uint16_t)3) : "memory");
}
__device__ __forceinline__ void tma3d_mc(uint32_t dst, const CUtensorMap* m, int c0, int c1, int c2, uint32_t bar) {
  asm volatile("cp.async.bulk.tensor.3d.shared::cluster.global.mbarrier::complete_tx::bytes.multicast::cluster [%0], [%1, {%3, %4, %5}], [%2], %6;"
               ::"r"(dst), "l"(m), "r"(bar), "r"(c0), "r"(c1), "r"(c2), "h"((uint16_t)3) : "memory");
}
__device__ __forceinline__ void l2_prefetch(const void* p, uint32_t bytes) {
  asm volatile("cp.async.bulk.prefetch.L2.global [%0], %1;" ::"l"(p), "r"(bytes) : "memory");
}
__device__ __forceinline__ void fence_async_smem() { asm volatile("fence.proxy.async.shared::cta;" ::: "memory"); }
__device__ __forceinline__ void bar_sync(int wg) {
  if (wg == 0) asm volatile("bar.sync 1, 128;" ::: "memory");
  else asm volatile("bar.sync 2, 128;" ::: "memory");
}
__device__ __forceinline__ bool bar_red_or(int id, bool v) {
  uint32_t r;
  asm volatile("{\n.reg .pred p, q;\nsetp.ne.u32 p, %2, 0;\nbar.red.or.pred q, %1, 128, p;\nselp.u32 %0, 1, 0, q;\n}\n"
               : "=r"(r) : "r"(1 + id), "r"((uint32_t)v) : "memory");
  return r != 0;
}
__device__ __forceinline__ uint32_t hfma2(uint32_t a, uint32_t b, uint32_t c) { uint32_t r; asm("fma.rn.bf16x2 %0, %1, %2, %3;" : "=r"(r) : "r"(a), "r"(b), "r"(c)); return r; }
__device__ __forceinline__ float ex2(float x) { float y; asm("ex2.approx.ftz.f32 %0, %1;" : "=f"(y) : "f"(x)); return y; }
__device__ __forceinline__ uint32_t pack(float lo, float hi) { uint32_t r; asm("cvt.rn.bf16x2.f32 %0, %1, %2;" : "=r"(r) : "f"(hi), "f"(lo)); return r; }
__device__ __forceinline__ void stsm4t(uint32_t a, uint32_t r0, uint32_t r1, uint32_t r2, uint32_t r3) {
  asm volatile("stmatrix.sync.aligned.m8n8.x4.trans.shared.b16 [%0], {%1,%2,%3,%4};" ::"r"(a), "r"(r0), "r"(r1), "r"(r2), "r"(r3) : "memory");
}
__device__ __forceinline__ void stsm2t(uint32_t a, uint32_t r0, uint32_t r1) {
  asm volatile("stmatrix.sync.aligned.m8n8.x2.trans.shared.b16 [%0], {%1,%2};" ::"r"(a), "r"(r0), "r"(r1) : "memory");
}
__device__ __forceinline__ void mma16816(float (&d)[4], const uint32_t (&a)[4], uint32_t b0, uint32_t b1) {
  asm volatile("mma.sync.aligned.m16n8k16.row.col.f32.bf16.bf16.f32 {%0,%1,%2,%3}, {%4,%5,%6,%7}, {%8,%9}, {%0,%1,%2,%3};"
               : "+f"(d[0]), "+f"(d[1]), "+f"(d[2]), "+f"(d[3]) : "r"(a[0]), "r"(a[1]), "r"(a[2]), "r"(a[3]), "r"(b0), "r"(b1));
}

template <int V> struct IC { static constexpr int value = V; };

struct Ring {
  uint32_t slot = 0, phase = 0;
  __device__ __forceinline__ void next() { if (++slot == RING_SLOTS) { slot = 0; phase ^= 1; } }
};

__device__ __forceinline__ void mma_tn(float (&o0)[60], float (&o1)[60], uint32_t a, uint32_t b, int acc) {
#pragma unroll
  for (int k = 0; k < 4; k++) {
    wgmma_n120<1, 0>(o0, a + k * 128, HI128, b + k * 2, HI128, k == 0 ? acc : 1);
    wgmma_n120<1, 0>(o1, a + 512 + k * 128, HI128, b + k * 2, HI128, k == 0 ? acc : 1);
  }
}
__device__ __forceinline__ void mma_tn_split(float (&o0)[60], float (&o1)[60], uint32_t a, uint32_t b) {
#pragma unroll
  for (int k = 0; k < 4; k++) wgmma_n120<1, 0>(o0, a + k * 128, HI128, b + k * 2, HI128, 1);
  wg_commit();
#pragma unroll
  for (int k = 0; k < 4; k++) wgmma_n120<1, 0>(o1, a + 512 + k * 128, HI128, b + k * 2, HI128, 1);
  wg_commit();
}
__device__ __forceinline__ void mma_qk(float (&s)[60], uint32_t a, uint32_t q) {
#pragma unroll
  for (int k = 0; k < 8; k++)
    wgmma_n120<0, 0>(s, a + (k >> 2) * 512 + (k & 3) * 2, HI128, q + (k >> 2) * (XB >> 4) + (k & 3) * 2, HI128, k != 0);
}
template <int J0, int J1, bool FIRST = false>
__device__ __forceinline__ void exp_store(const float (&s)[60], float (&l)[30], uint32_t dst) {
#pragma unroll
  for (int j = J0; j < J1; j += 2) {
    uint32_t p[4];
#pragma unroll
    for (int jj = 0; jj < 2; jj++) {
      if (j + jj < 15) {
        const int c = j + jj;
        float e0 = ex2(s[4 * c]), e1 = ex2(s[4 * c + 1]), e2 = ex2(s[4 * c + 2]), e3 = ex2(s[4 * c + 3]);
        if (FIRST) { l[2 * c] = e0 + e2; l[2 * c + 1] = e1 + e3; }
        else { l[2 * c] += e0; l[2 * c + 1] += e1; l[2 * c] += e2; l[2 * c + 1] += e3; }
        p[2 * jj] = pack(e0, e1); p[2 * jj + 1] = pack(e2, e3);
      }
    }
    if (j + 1 < 15) stsm4t(dst + j * 1024, p[0], p[1], p[2], p[3]);
    else stsm2t(dst + j * 1024, p[0], p[1]);
  }
}

__device__ __forceinline__ int o_pos(int wg, int r) {
  const int j = r >> 3, q = (r >> 1) & 3, c = r & 1;
  if (j < 12) return (wg ? 144 : 0) + (j >> 2) * 32 + q * 8 + (j & 3) * 2 + c;
  if (j < 14) return (wg ? 128 : 96) + q * 4 + (j - 12) * 2 + c;
  return (wg ? 120 : 112) + q * 2 + c;
}
__device__ __forceinline__ int o_row(int p) {
  const int b = p / SQ, r = p - b * SQ, wg = r >= 120, c = r & 1;
  const int a = r - (wg ? 144 : 0), m = r - (wg ? 128 : 96), e = r - (wg ? 120 : 112);
  int row;
  if (a >= 0 && a < 96) row = ((a >> 5) * 4 + ((a >> 1) & 3)) * 8 + ((a >> 3) & 3) * 2 + c;
  else if (m >= 0 && m < 16) row = (12 + ((m >> 1) & 1)) * 8 + (m >> 2) * 2 + c;
  else row = 112 + e;
  return b * SQ + wg * 120 + row;
}

__device__ __forceinline__ void slow_path(const Params& P, int b, int h, int wg, int w, int lane) {
  const int g = lane >> 2, q = lane & 3, row0 = wg * 120;
  const uint16_t* wq = reinterpret_cast<const uint16_t*>(P.wq) + h * DH + g;
  const __nv_bfloat16* kp = P.k + (size_t)(b * NH + h) * SK * DH;
  const uint16_t* vp = reinterpret_cast<const uint16_t*>(P.v) + (size_t)(b * NH + h) * SK * DH + g;
#pragma unroll 1
  for (int t = w; t < 8; t += 4) {
    const int r0 = 16 * t + g, r1 = r0 + 8;
    const __nv_bfloat16* x0 = P.x + (size_t)(b * SQ + row0 + r0) * DM + 2 * q;
    const __nv_bfloat16* x1 = P.x + (size_t)(b * SQ + row0 + min(r1, 119)) * DM + 2 * q;
    float o[16][4];
#pragma unroll
    for (int n = 0; n < 16; n++) o[n][0] = o[n][1] = o[n][2] = o[n][3] = 0.f;
#pragma unroll 1
    for (int k0 = 0; k0 < DM; k0 += 16) {
      uint32_t a[4] = {*(const uint32_t*)(x0 + k0), *(const uint32_t*)(x1 + k0), *(const uint32_t*)(x0 + k0 + 8), *(const uint32_t*)(x1 + k0 + 8)};
      const uint16_t* wr = wq + (size_t)(k0 + 2 * q) * HD;
#pragma unroll
      for (int n = 0; n < 16; n++)
        mma16816(o[n], a, wr[8 * n] | ((uint32_t)wr[8 * n + HD] << 16), wr[8 * n + 8 * HD] | ((uint32_t)wr[8 * n + 9 * HD] << 16));
    }
    uint32_t qa[8][4];
#pragma unroll
    for (int k = 0; k < 8; k++) {
      qa[k][0] = pack(o[2 * k][0] * QSCALE, o[2 * k][1] * QSCALE);
      qa[k][1] = pack(o[2 * k][2] * QSCALE, o[2 * k][3] * QSCALE);
      qa[k][2] = pack(o[2 * k + 1][0] * QSCALE, o[2 * k + 1][1] * QSCALE);
      qa[k][3] = pack(o[2 * k + 1][2] * QSCALE, o[2 * k + 1][3] * QSCALE);
    }
#pragma unroll
    for (int n = 0; n < 16; n++) o[n][0] = o[n][1] = o[n][2] = o[n][3] = 0.f;
    float m0 = -INFINITY, m1 = -INFINITY, l0 = 0.f, l1 = 0.f;
#pragma unroll 1
    for (int key0 = 0; key0 < SK; key0 += 16) {
      float s[2][4];
#pragma unroll
      for (int nt = 0; nt < 2; nt++) {
        s[nt][0] = s[nt][1] = s[nt][2] = s[nt][3] = 0.f;
        const __nv_bfloat16* kr = kp + (size_t)(key0 + 8 * nt + g) * DH + 2 * q;
#pragma unroll
        for (int k = 0; k < 8; k++) mma16816(s[nt], qa[k], *(const uint32_t*)(kr + 16 * k), *(const uint32_t*)(kr + 16 * k + 8));
      }
      float n0 = fmaxf(fmaxf(s[0][0], s[0][1]), fmaxf(s[1][0], s[1][1])), n1 = fmaxf(fmaxf(s[0][2], s[0][3]), fmaxf(s[1][2], s[1][3]));
      n0 = fmaxf(n0, __shfl_xor_sync(~0u, n0, 1)); n1 = fmaxf(n1, __shfl_xor_sync(~0u, n1, 1));
      n0 = fmaxf(n0, __shfl_xor_sync(~0u, n0, 2)); n1 = fmaxf(n1, __shfl_xor_sync(~0u, n1, 2));
      n0 = fmaxf(n0, m0); n1 = fmaxf(n1, m1);
      const float z0 = n0 == -INFINITY ? 0.f : n0, z1 = n1 == -INFINITY ? 0.f : n1;
      const float c0 = ex2(m0 - z0), c1 = ex2(m1 - z1);
      m0 = n0; m1 = n1;
#pragma unroll
      for (int nt = 0; nt < 2; nt++) {
        s[nt][0] = ex2(s[nt][0] - z0); s[nt][1] = ex2(s[nt][1] - z0);
        s[nt][2] = ex2(s[nt][2] - z1); s[nt][3] = ex2(s[nt][3] - z1);
      }
      l0 = l0 * c0 + s[0][0] + s[0][1] + s[1][0] + s[1][1];
      l1 = l1 * c1 + s[0][2] + s[0][3] + s[1][2] + s[1][3];
      uint32_t pa[4] = {pack(s[0][0], s[0][1]), pack(s[0][2], s[0][3]), pack(s[1][0], s[1][1]), pack(s[1][2], s[1][3])};
      const uint16_t* vr = vp + (size_t)(key0 + 2 * q) * DH;
#pragma unroll
      for (int n = 0; n < 16; n++) {
        o[n][0] *= c0; o[n][1] *= c0; o[n][2] *= c1; o[n][3] *= c1;
        mma16816(o[n], pa, vr[8 * n] | ((uint32_t)vr[8 * n + DH] << 16), vr[8 * n + 8 * DH] | ((uint32_t)vr[8 * n + 9 * DH] << 16));
      }
    }
    l0 += __shfl_xor_sync(~0u, l0, 1); l1 += __shfl_xor_sync(~0u, l1, 1);
    l0 += __shfl_xor_sync(~0u, l0, 2); l1 += __shfl_xor_sync(~0u, l1, 2);
    const float i0 = 1.f / l0, i1 = 1.f / l1;
    __nv_bfloat16* oc = P.o + (size_t)(h * DH + 2 * q) * NROWS + b * SQ;
    const int p0 = o_pos(wg, r0), p1 = o_pos(wg, min(r1, 119));
#pragma unroll
    for (int n = 0; n < 16; n++) {
      oc[(size_t)(8 * n) * NROWS + p0] = __float2bfloat16(o[n][0] * i0);
      oc[(size_t)(8 * n + 1) * NROWS + p0] = __float2bfloat16(o[n][1] * i0);
      if (r1 < 120) {
        oc[(size_t)(8 * n) * NROWS + p1] = __float2bfloat16(o[n][2] * i1);
        oc[(size_t)(8 * n + 1) * NROWS + p1] = __float2bfloat16(o[n][3] * i1);
      }
    }
  }
}

__device__ __forceinline__ int bk(int ks) { return B_ORDER && ks < 48 ? 32 - (ks & 48) + (ks & 15) : ks; }
__device__ __forceinline__ uint32_t x_slot(uint32_t wg, uint32_t j) { return j < 2 ? (2 * wg + j) * XB : (2 * j + wg) * XB; }
__device__ __forceinline__ int unit_batch(int u) { return (u & 63) >> 2; }
__device__ __forceinline__ int unit_head(int u, int rank) { return (u >> 6) * 8 + (u & 3) * 2 + rank; }

__global__ void __cluster_dims__(2, 1, 1) __launch_bounds__(384, 1)
fused_attn_kernel(const __grid_constant__ CUtensorMap tm_x, const __grid_constant__ CUtensorMap tm_wq,
                  const __grid_constant__ CUtensorMap tm_k, const __grid_constant__ CUtensorMap tm_v,
                  const __grid_constant__ CUtensorMap tm_o, const __grid_constant__ CUtensorMap tm_wo,
                  const __grid_constant__ Params P) {
  extern __shared__ uint8_t smem_raw[];
  const uint32_t sb = ((uint32_t)__cvta_generic_to_shared(smem_raw) + 1023) & ~1023u;
  const int warp = __shfl_sync(~0u, threadIdx.x >> 5, 0);
  int lane = threadIdx.x & 31;
  const int rank = blockIdx.x & 1, cl = blockIdx.x >> 1, ncl = gridDim.x >> 1;

  const int nsingle = ncl == 66 ? 44 : NOTILES;
  auto role = [&]() {
    mbar_wait(sb + BAR_ROLE + 16, 0);
    int id;
    asm volatile("ld.shared.u32 %0, [%1];" : "=r"(id) : "r"(sb + BAR_ROLE + 8) : "memory");
    return id;
  };

  if (threadIdx.x == 0) {
    for (int i = 0; i < 6; i++) {
      mbar_init(sb + BAR_RFULL + 8 * i, 1); mbar_init(sb + BAR_REMPTY + 8 * i, 8);
      mbar_init(sb + BAR_BFULL + 8 * i, 1); mbar_init(sb + BAR_BEMPTY + 8 * i, 16);
    }
    for (int i = 0; i < 8; i++) mbar_init(sb + BAR_XFULL + 8 * i, 1);
    for (int i = 0; i < 4; i++) mbar_init(sb + BAR_XEMPTY + 8 * i, 8);
    for (int i = 0; i < 2; i++) { mbar_init(sb + BAR_STAGE + 8 * i, 4); mbar_init(sb + BAR_LSUM + 8 * i, 4); mbar_init(sb + BAR_INV + 8 * i, 1); }
    mbar_init(sb + BAR_ROLE, 1); mbar_init(sb + BAR_ROLE + 16, 1);
    asm volatile("fence.mbarrier_init.release.cluster;" ::: "memory");
  }
  __syncwarp();
  asm volatile("barrier.cluster.arrive.relaxed.aligned;\nbarrier.cluster.wait.aligned;" ::: "memory");

  if (warp >= 8) {
    asm volatile("setmaxnreg.dec.sync.aligned.u32 24;");
    if (warp == 8) {
      uint64_t pol;
      asm volatile("createpolicy.fractional.L2::evict_first.b64 %0, 1.0;" : "=l"(pol));
      Ring r;
      auto load = [&](const CUtensorMap* m, int c1, int c2, bool ef) {
        mbar_wait(sb + BAR_REMPTY + 8 * r.slot, r.phase ^ 1);
        if (lane == 0) {
          mbar_expect(sb + BAR_RFULL + 8 * r.slot, RING_BYTES);
          if (ef) tma3d_hint(sb + r.slot * RING_BYTES, m, 0, c1, c2, sb + BAR_RFULL + 8 * r.slot, pol);
          else tma3d(sb + r.slot * RING_BYTES, m, 0, c1, c2, sb + BAR_RFULL + 8 * r.slot);
        }
        r.next();
      };
      const int rot = ROT * (blockIdx.x * 5 + (blockIdx.x >> 4));
      for (int u0 = 0;; u0 += ncl) {
        const int u = __shfl_sync(~0u, (u0 >= 3 * ncl ? role() : cl) + u0, 0);
        if (u >= NUNITS) break;
        const int h = unit_head(u, rank);
        const int krow = (unit_batch(u) * NH + h) * SK;
#pragma unroll 1
        for (int s = 0; s < 10; s++) {
          load(&tm_wq, s * 64, 2 * h, false);
          const int sp = u0 == 0 ? s - PF_HOLD : s;
          if (sp >= 0 && sp < PF_N && lane == 0) l2_prefetch(P.v + (size_t)(krow + ((PF_J0 + sp * PF_STEP + rot) & 15) * 64) * DH, 16384);
        }
#pragma unroll 1
        for (int j = 0; j <= 16; j++) {
          if (j < 16) load(&tm_k, krow + ((j + rot) & 15) * 64, 0, true);
          if (j == 1 + DPRO) load(&tm_v, krow + (rot & 15) * 64, 0, true);
          if (j > 1) load(&tm_v, krow + ((j - 1 + rot) & 15) * 64, 0, true);
        }
      }
      const int id = __shfl_sync(~0u, role(), 0);
      const bool dbl = ncl == 66 && id >= 58;
      for (int t = dbl ? 2 * id - 72 : id; t < (dbl ? NOTILES : nsingle); t += ncl) {
        const int row0 = (t >> 2) * 256 + rank * 128;
        const int b0 = row0 / SQ, b1 = (row0 + 127) / SQ;
#pragma unroll 1
        for (int ks = 0; ks < 64; ks++) {
          if (dbl ? (ks & 15) == 0 : ks == 0 || ks == 48) {
            const unsigned* c = &g_cnt[((lane & 1 ? b1 : b0) * 4 + (ks || dbl ? ks >> 4 : min(lane >> 1, 2))) * 8];
            unsigned v, n = 0;
            do {
              asm volatile("ld.acquire.gpu.global.u32 %0, [%1];" : "=r"(v) : "l"(c) : "memory");
              if (++n > (1u << 26)) __trap();
            } while (v < 16);
            __syncwarp();
            asm volatile("fence.proxy.async.global;" ::: "memory");
          }
          load(&tm_o, (dbl ? ks : bk(ks)) * 64, row0 >> 6, O_EF);
        }
      }
      if (lane == 0 && atomicAdd(&g_cnt[64 * 8], 1) == gridDim.x - 1) {
        for (int i = 0; i < 67; i++) g_cnt[i * 8] = 0;
      }
    } else if (warp == 9) {
      if (lane == 0) {
        uint32_t it = 0;
        for (;; it++) {
          const int u = (it >= 3 ? role() : cl) + it * ncl;
          if (u >= NUNITS) break;
          const int row = unit_batch(u) * SQ + rank * 120;
#pragma unroll 1
          for (int s = 0; s < 10; s++) {
            const uint32_t j = s & 3, par = ((s >> 2) + (j < 2 ? it : 0)) & 1;
            mbar_wait(sb + BAR_XEMPTY + 8 * j, par ^ 1);
            const uint32_t fb = sb + BAR_XFULL + 32 * rank + 8 * j;
            mbar_expect(fb, XB);
            mbar_expect_cl(mapa(fb, rank ^ 1), XB);
            tma2d_mc(sb + OFF_Q + x_slot(rank, j), &tm_x, s * 64, row, fb);
          }
        }
        const int id = role();
        const bool dbl = ncl == 66 && id >= 58;
        uint32_t slot = rank, phase = 0;
        for (int t = dbl ? 2 * id - 72 + rank : id; t < (dbl ? NOTILES : nsingle); t += ncl) {
#pragma unroll 1
          for (int ks = dbl ? 0 : rank; ks < 64; ks += dbl ? 1 : 2) {
            mbar_wait(sb + BAR_BEMPTY + 8 * slot, phase);
            const uint32_t fb = sb + BAR_BFULL + 8 * slot;
            mbar_expect(fb, BB);
            mbar_expect_cl(mapa(fb, rank ^ 1), BB);
            tma3d_mc(sb + OFF_Q + slot * BB, &tm_wo, 0, (dbl ? ks : bk(ks)) * 64, (t & 3) * 5, fb);
            if (WO_PF && dbl && ks + WO_PF < 64 && (ks & 3) == ((id >> 1) & 3))
              asm volatile("cp.async.bulk.prefetch.tensor.3d.L2.global [%0, {%1, %2, %3}];" ::"l"(&tm_wo), "r"(0), "r"((ks + WO_PF) * 64), "r"((t & 3) * 5) : "memory");
            slot += 2;
            if (slot >= 6) { slot -= 6; phase ^= 1; }
          }
        }
      }
    } else {
      const int wg = warp - 10;
      {
        mbar_wait(sb + BAR_RFULL, 0);
        const __nv_bfloat16* xs = P.x + (size_t)(unit_batch(cl) * SQ + ((cl & 3) * 2 + rank) * 30 + min(lane, 29)) * DM + 256 + wg * 64;
#pragma unroll
        for (int i = 0; i < 3; i++) asm volatile("prefetch.global.L2 [%0];" ::"l"(xs + i * 128));
        if (lane < 16) asm volatile("prefetch.global.L2 [%0];" ::"l"(P.wq + (size_t)(384 + unit_batch(cl) * 16 + lane) * HD + unit_head(cl, rank) * DH + wg * 64));
      }
      for (uint32_t it = 0;; it++) {
        const int u = __shfl_sync(~0u, (it >= 3 ? role() : cl) + it * ncl, 0);
        if (u >= NUNITS) break;
        mbar_wait(sb + BAR_LSUM + 8 * wg, it & 1);
        float l4[4], v[4];
        const uint32_t a = sb + OFF_L2 + wg * 2048 + lane * 16;
        asm volatile("ld.shared.v4.f32 {%0, %1, %2, %3}, [%4];" : "=f"(l4[0]), "=f"(l4[1]), "=f"(l4[2]), "=f"(l4[3]) : "r"(a) : "memory");
#pragma unroll
        for (int g = 1; g < 4; g++) {
          asm volatile("ld.shared.v4.f32 {%0, %1, %2, %3}, [%4];" : "=f"(v[0]), "=f"(v[1]), "=f"(v[2]), "=f"(v[3]) : "r"(a + g * 512) : "memory");
#pragma unroll
          for (int c = 0; c < 4; c++) l4[c] += v[c];
        }
#pragma unroll
        for (int c = 0; c < 4; c++) {
          float inv;
          asm("rcp.approx.ftz.f32 %0, %1;" : "=f"(inv) : "f"(l4[c]));
          l4[c] = l4[c] >= L_MIN && l4[c] <= L_MAX ? inv : __uint_as_float(0x7FFFFFFFu);
        }
        const uint32_t h0 = pack(l4[0], l4[1]), h1 = pack(l4[2], l4[3]);
        const uint32_t e0 = pack(l4[0] - __uint_as_float(h0 << 16), l4[1] - __uint_as_float(h0 & 0xFFFF0000u));
        const uint32_t e1 = pack(l4[2] - __uint_as_float(h1 << 16), l4[3] - __uint_as_float(h1 & 0xFFFF0000u));
        const uint32_t ia = sb + OFF_INV + wg * 640 + (lane & 1) * 288 + (lane >> 1) * 8;
        asm volatile("st.shared.v2.u32 [%0], {%1, %2};\nst.shared.v2.u32 [%0 + 144], {%3, %4};" ::"r"(ia), "r"(h0), "r"(e0), "r"(h1), "r"(e1) : "memory");
        __syncwarp();
        if (lane == 0) {
          mbar_arrive(sb + BAR_INV + 8 * wg);
          if (it == ROLE_AT) {
          if (wg == 0 && rank == 0 && lane == 0) {
            int id = cl;
            if (ncl == 66) {
              uint32_t smid;
              asm("mov.u32 %0, %smid;" : "=r"(smid));
              id = smid >= SMID_TOP ? 65 - atomicAdd(&g_cnt[65 * 8], 1) : atomicAdd(&g_cnt[66 * 8], 1);
            }
    #pragma unroll
            for (int c = 0; c < 2; c++) {
              const uint32_t a = mapa(sb + BAR_ROLE, c);
              asm volatile("st.shared::cluster.u32 [%0 + 8], %1;\nmbarrier.arrive.release.cluster.shared::cluster.b64 _, [%0];" ::"r"(a), "r"(id) : "memory");
            }
          }
          if (wg == 0 && lane == 0) {
            mbar_wait_cl(sb + BAR_ROLE, 0);
            mbar_arrive(sb + BAR_ROLE + 16);
          }
          }
          mbar_wait(sb + BAR_STAGE + 8 * wg, it & 1);
          __threadfence();
          asm volatile("red.relaxed.gpu.global.add.u32 [%0], 1;" ::"l"(&g_cnt[(unit_batch(u) * 4 + (u >> 6)) * 8]) : "memory");
        }
        __syncwarp();
      }
    }
  } else {
    asm volatile("setmaxnreg.inc.sync.aligned.u32 240;");
    const int wg = warp >> 2, w = warp & 3;
    if (PINLANE) lane = __shfl_sync(~0u, lane, lane);
    const uint32_t qreg = sb + OFF_Q + wg * 2 * XB, preg = sb + OFF_P + (2 + wg) * XB;
    const uint32_t st_off = ((lane >> 4) * 8 + (lane & 7)) * 128 + (((2 * w + ((lane >> 3) & 1)) ^ (lane & 7)) << 4);
    const uint32_t xempty = mapa(sb + BAR_XEMPTY, wg);
    Ring r;
    uint32_t it = 0;
    const uint32_t qd = (qreg & 0x3FFFF) >> 4, pd = (preg & 0x3FFFF) >> 4;
    auto ring_addr = [&]() { return ((sb & 0x3FFFF) + r.slot * RING_BYTES) >> 4; };
    auto ring_wait = [&]() { mbar_wait(sb + BAR_RFULL + 8 * r.slot, r.phase); };
    auto release = [&](uint32_t slot) { if (lane == 0) mbar_arrive(sb + BAR_REMPTY + 8 * slot); };
    auto turn_wait = [&]() {
      if (wg == 0) asm volatile("bar.sync 3, 256;" ::: "memory");
      else asm volatile("bar.sync 4, 256;" ::: "memory");
    };
    auto turn_pass = [&]() {
      if (wg == 0) asm volatile("bar.arrive 4, 256;" ::: "memory");
      else asm volatile("bar.arrive 3, 256;" ::: "memory");
    };

    uint32_t chk = 0;
    auto load_inv = [&](uint32_t (&iv)[30], uint32_t parity) {
      mbar_wait(sb + BAR_INV + 8 * wg, parity);
      chk = 0;
#pragma unroll
      for (int j = 0; j < 7; j++)
        asm volatile("ld.shared.v4.u32 {%0, %1, %2, %3}, [%4];" : "=r"(iv[4 * j]), "=r"(iv[4 * j + 1]), "=r"(iv[4 * j + 2]), "=r"(iv[4 * j + 3])
                     : "r"(sb + OFF_INV + wg * 640 + (lane & 3) * 144 + j * 16) : "memory");
      asm volatile("ld.shared.v2.u32 {%0, %1}, [%2];" : "=r"(iv[28]), "=r"(iv[29]) : "r"(sb + OFF_INV + wg * 640 + (lane & 3) * 144 + 112) : "memory");
    };
    auto norm = [&](uint32_t (&n)[8], const uint32_t (&po)[60], const uint32_t (&iv)[30], auto part) {
      constexpr int k = decltype(part)::value >> 1, j0 = (decltype(part)::value & 1) * 8;
#pragma unroll
      for (int j = 0; j < 8; j++)
        n[j] = j0 + j < 15 ? hfma2(po[15 * k + (j0 + j) % 15], iv[2 * ((j0 + j) % 15)], hfma2(po[15 * k + (j0 + j) % 15], iv[2 * ((j0 + j) % 15) + 1], 0x80008000u)) : 0x3F803F80u;
#pragma unroll
      for (int j = 0; j < 8; j += 2) chk = hfma2(n[j], n[j + 1], chk);
    };
    auto store = [&](const uint32_t (&n)[8], const char* optr, auto part) {
      constexpr int k = decltype(part)::value >> 1;
      const char* o = optr + (size_t)(8 * (k & 1) + 64 * (k >> 1)) * NROWS * 2;
      if ((decltype(part)::value & 1) == 0)
        asm volatile(
            "{\n.reg .pred p;\nsetp.ne.u64 p, %9, 0;\n"
            "@p st.global.v4.u32 [%8], {%0, %1, %2, %3};\n@p st.global.v4.u32 [%8 + 64], {%4, %5, %6, %7};\n}\n"
            ::"r"(n[0]), "r"(n[1]), "r"(n[2]), "r"(n[3]), "r"(n[4]), "r"(n[5]), "r"(n[6]), "r"(n[7]),
            "l"(o + (wg ? 288 : 0) + (lane & 3) * 16), "l"(optr) : "memory");
      else
        asm volatile(
            "{\n.reg .pred p;\nsetp.ne.u64 p, %10, 0;\n"
            "@p st.global.v4.u32 [%7 + 128], {%0, %1, %2, %3};\n@p st.global.v2.u32 [%8], {%4, %5};\n@p st.global.u32 [%9], %6;\n}\n"
            ::"r"(n[0]), "r"(n[1]), "r"(n[2]), "r"(n[3]), "r"(n[4]), "r"(n[5]), "r"(n[6]), "l"(o + (wg ? 288 : 0) + (lane & 3) * 16),
            "l"(o + (wg ? 256 : 192) + (lane & 3) * 8), "l"(o + (wg ? 240 : 224) + (lane & 3) * 4), "l"(optr) : "memory");
    };
    auto put = [&](const uint32_t (&po)[60], const uint32_t (&iv)[30], const char* optr, auto part) {
      uint32_t n[8];
      norm(n, po, iv, part);
      store(n, optr, part);
    };
    auto out_ptr = [&](int u) {
      return reinterpret_cast<const char*>(P.o + (size_t)(unit_head(u, rank) * DH + 16 * w + (lane >> 2)) * NROWS + unit_batch(u) * SQ);
    };
    auto unsafe = [&](bool valid) {
      const bool b = valid && ((chk & 0x7F80u) == 0x7F80u || (chk & 0x7F800000u) == 0x7F800000u);
      return __any_sync(~0u, bar_red_or(wg, b));
    };
    auto publish = [&]() { __syncwarp(); if (lane == 0) mbar_arrive(sb + BAR_STAGE + 8 * wg); };

    uint32_t po[60];
#pragma unroll
    for (int i = 0; i < 60; i++) po[i] = 0;
    int id = 0;
    bool more;
    do {
      float o0[60], o1[60];
      uint32_t prev = 0;
      auto qstep = [&](int s, int acc) {
        const uint32_t j = s & 3, par = ((s >> 2) + (j < 2 ? it : 0)) & 1;
        TR(it * 160 + 3 * s);
        ring_wait();
        TR(it * 160 + 3 * s + 1);
        mbar_wait(sb + BAR_XFULL + 32 * wg + 8 * j, par);
        TR(it * 160 + 3 * s + 2);
        if (s >= ALT_FROM) turn_wait();
        wg_fence();
        mma_tn(o0, o1, ring_addr(), ((sb & 0x3FFFF) + OFF_Q + x_slot(wg, j)) >> 4, acc);
        wg_commit();
        if ((s >= ALT_FROM && !(MERGE89 && s == 8)) || (s == ALT_FROM - 1 && wg == 1)) turn_pass();
        if (s > 0) {
          wg_wait<1>();
          release(prev);
          if (s <= 6 && lane == 0) mbar_arrive_cl(xempty + 8 * ((s - 1) & 3));
        }
        prev = r.slot;
        r.next();
      };
      qstep(0, 0);
      const int up = (it > 3 ? id : cl) + ((int)it - 1) * ncl;
      const char* optr = it > 0 ? out_ptr(up) : nullptr;
      uint32_t n7[8];
      {
        uint32_t iv[30];
        qstep(1, 1); load_inv(iv, (it + 1) & 1); put(po, iv, optr, IC<0>());
        qstep(2, 1); put(po, iv, optr, IC<1>());
        qstep(3, 1); put(po, iv, optr, IC<2>());
        qstep(4, 1); put(po, iv, optr, IC<3>());
        qstep(5, 1); put(po, iv, optr, IC<4>());
        qstep(6, 1); put(po, iv, optr, IC<5>());
        qstep(7, 1); put(po, iv, optr, IC<6>());
        norm(n7, po, iv, IC<7>());
        if (LATE_AT == 3) store(n7, optr, IC<7>());
        qstep(8, 1);
        if (LATE_AT == 2) store(n7, optr, IC<7>());
      }
      TR(it * 160 + 27);
      ring_wait();
      TR(it * 160 + 28);
      mbar_wait(sb + BAR_XFULL + 32 * wg + 8, it & 1);
      TR(it * 160 + 29);
      if (!MERGE89) turn_wait();
      wg_fence();
      mma_tn_split(o0, o1, ring_addr(), qd + (XB >> 4));
      turn_pass();
      wg_wait<2>();
      release(prev);
      auto put_q = [&](const float (&o)[60], uint32_t dst) {
        bar_sync(wg);
#pragma unroll
        for (int j = 0; j < 14; j += 2)
          stsm4t(dst + j * 1024, pack(o[4 * j] * QSCALE, o[4 * j + 1] * QSCALE), pack(o[4 * j + 2] * QSCALE, o[4 * j + 3] * QSCALE),
                 pack(o[4 * j + 4] * QSCALE, o[4 * j + 5] * QSCALE), pack(o[4 * j + 6] * QSCALE, o[4 * j + 7] * QSCALE));
        stsm2t(dst + 14 * 1024, pack(o[56] * QSCALE, o[57] * QSCALE), pack(o[58] * QSCALE, o[59] * QSCALE));
      };
      wg_wait<1>();
      reg_fence(o0);
      put_q(o0, qreg + st_off);
      wg_wait<0>();
      reg_fence(o1);
      release(r.slot);
      r.next();
      TR(it * 160 + 30);
      put_q(o1, qreg + XB + st_off);
      fence_async_smem();
      if (unsafe(it > 0)) {
        slow_path(P, unit_batch(up), unit_head(up, rank), wg, w, lane);
        optr = nullptr;
        if (!DPRO) {
#pragma unroll
          for (int i = 0; i < 60; i++) o0[i] = o1[i] = 0.f;
        }
      }
      TR(it * 160 + 32); TG(it * 160 + 142);

      float sc[60], l[30];
      ring_wait();
      TR(it * 160 + 33);
      turn_wait();
      wg_fence();
      mma_qk(sc, ring_addr(), qd);
      wg_commit();
      turn_pass();
      if (LATE_AT < 2) store(n7, optr, IC<7>());
      if (it > 0) publish();
      if (it >= 2) id = __shfl_sync(~0u, role(), 0);
      wg_wait<0>();
      reg_fence(sc);
      TR(it * 160 + 35);
      release(r.slot);
      r.next();
      exp_store<0, 15, true>(sc, l, preg + st_off);
      fence_async_smem();
      more = id + ((int)it + 1) * ncl < NUNITS;
      const bool gemm = id < nsingle || (ncl == 66 && id >= 58);
#pragma unroll 1
      for (int s = DPRO ? 3 : 1; s < 16; s++) {
        const uint32_t kslot = r.slot;
        TR(it * 160 + 32 + 6 * s); TG(it * 160 + 37 + 6 * s);
        ring_wait();
        TR(it * 160 + 33 + 6 * s);
        turn_wait();
        wg_fence();
        mma_qk(sc, ring_addr(), qd);
        wg_commit();
        r.next();
        const bool pv = !ASYM || wg == 1 || s < 15;
        TR(it * 160 + 36 + 6 * s);
        if (pv) {
          ring_wait();
          TR(it * 160 + 34 + 6 * s);
          wg_fence();
          mma_tn(o0, o1, ring_addr(), pd - ((s - 1) & 1) * (2 * XB >> 4), DPRO || s != 1);
          wg_commit();
          if (ASYM || wg == 0 || s < 15) turn_pass();
          wg_wait<1>();
        } else {
          turn_pass();
          wg_wait<0>();
        }
        reg_fence(sc);
        TR(it * 160 + 35 + 6 * s);
        release(kslot);
        if (s == 15) {
          if (more) { if (lane < 2 - ASYM) mbar_arrive_cl(xempty + 8 * lane); }
          else if (!ASYM && lane < 3 && gemm) mbar_arrive_cl(mapa(sb + BAR_BEMPTY + 8 * lane, lane & 1));
        }
        exp_store<0, VREL>(sc, l, preg - (s & 1) * 2 * XB + st_off);
        wg_wait<0>();
        reg_fence(o0); reg_fence(o1);
        if (pv) { release(r.slot); r.next(); }
        exp_store<VREL, 15>(sc, l, preg - (s & 1) * 2 * XB + st_off);
        fence_async_smem();
      }
      if (!ASYM) bar_sync(wg);
      TR(it * 160 + 128);
      const uint32_t lscr = ASYM ? qreg + XB : preg;
      auto put_l = [&]() {
        const uint32_t a = lscr + (8 * w + (lane >> 2)) * 480 + (lane & 3) * 8;
#pragma unroll
        for (int j = 0; j < 15; j++) asm volatile("st.shared.v2.f32 [%0], {%1, %2};" ::"r"(a + j * 32), "f"(l[2 * j]), "f"(l[2 * j + 1]) : "memory");
      };
      const uint32_t v14 = r.slot;
      if (ASYM && wg == 0) {
        const uint32_t a14 = ring_addr();
        ring_wait();
        r.next();
        ring_wait();
        turn_wait();
        wg_fence();
#pragma unroll
        for (int k = 0; k < 4; k++) wgmma_n120<1, 0>(o0, a14 + k * 128, HI128, pd + k * 2, HI128, 1);
#pragma unroll
        for (int k = 0; k < 4; k++) wgmma_n120<1, 0>(o0, ring_addr() + k * 128, HI128, pd - (2 * XB >> 4) + k * 2, HI128, 1);
        wg_commit();
        put_l();
        wg_fence();
#pragma unroll
        for (int k = 0; k < 4; k++) wgmma_n120<1, 0>(o1, a14 + 512 + k * 128, HI128, pd + k * 2, HI128, 1);
#pragma unroll
        for (int k = 0; k < 4; k++) wgmma_n120<1, 0>(o1, ring_addr() + 512 + k * 128, HI128, pd - (2 * XB >> 4) + k * 2, HI128, 1);
        wg_commit();
        if (ASYM_PASS == 0) turn_pass();
      } else {
        ring_wait();
        if (ASYM) turn_wait();
        wg_fence();
        mma_tn_split(o0, o1, ring_addr(), pd - (2 * XB >> 4));
        put_l();
      }
      TR(it * 160 + 132);
      __syncwarp();
      float lv[8][4];
#pragma unroll
      for (int g = 0; g < 8; g++)
        asm volatile("ld.shared.v4.f32 {%0, %1, %2, %3}, [%4];" : "=f"(lv[g][0]), "=f"(lv[g][1]), "=f"(lv[g][2]), "=f"(lv[g][3])
                     : "r"(lscr + (8 * w + g) * 480 + min(lane, 29) * 16) : "memory");
      if (ASYM && ASYM_PASS == 1 && wg == 0) turn_pass();
      TR(it * 160 + 133);
      wg_wait<1>();
      reg_fence(o0);
      TR(it * 160 + 134);
#pragma unroll
      for (int j = 0; j < 15; j++) { po[j] = pack(o0[4 * j], o0[4 * j + 1]); po[15 + j] = pack(o0[4 * j + 2], o0[4 * j + 3]); }
#pragma unroll
      for (int c = 0; c < 4; c++) lv[0][c] = ((lv[0][c] + lv[1][c]) + (lv[2][c] + lv[3][c])) + ((lv[4][c] + lv[5][c]) + (lv[6][c] + lv[7][c]));
      asm volatile("st.shared.v4.f32 [%0], {%1, %2, %3, %4};" ::"r"(sb + OFF_L2 + wg * 2048 + w * 512 + lane * 16), "f"(lv[0][0]), "f"(lv[0][1]),
                   "f"(lv[0][2]), "f"(lv[0][3]) : "memory");
      __syncwarp();
      if (lane == 0) mbar_arrive(sb + BAR_LSUM + 8 * wg);
      if (ASYM) {
        if (more) { if (lane == 0) mbar_arrive_cl(xempty + 8); }
        else if (lane < 3 && gemm) mbar_arrive_cl(mapa(sb + BAR_BEMPTY + 8 * lane, lane & 1));
      }
      wg_wait<0>();
      reg_fence(o1);
      if (ASYM && wg == 0) release(v14);
      release(r.slot);
      r.next();
      if (more) { if (lane < 2) mbar_arrive_cl(xempty + 16 + 8 * lane); }
      else if (gemm && lane < 3) mbar_arrive_cl(mapa(sb + BAR_BEMPTY + 24 + 8 * lane, (lane + 1) & 1));
      TR(it * 160 + 130);
#pragma unroll
      for (int j = 0; j < 15; j++) { po[30 + j] = pack(o1[4 * j], o1[4 * j + 1]); po[45 + j] = pack(o1[4 * j + 2], o1[4 * j + 3]); }
      TR(it * 160 + 131); TG(it * 160 + 143);
      it++;
    } while (more);
    const bool gemm = id < nsingle || (ncl == 66 && id >= 58);
    const int u = (it > 3 ? id : cl) + ((int)it - 1) * ncl;
    lane = __shfl_sync(~0u, lane, lane);
    uint32_t pb[60];
#pragma unroll
    for (int i = 0; i < 60; i++) pb[i] = po[i] ^ (gridDim.y - 1);

    uint32_t bslot = 0, bphase = 0;
    auto out_tile = [&](const float (&acc)[80], int t) {
      const uint32_t st = sb + w * RING_BYTES + wg * 8192;
      const uint32_t sa = st + (lane & 15) * 336 + (lane >> 4) * 16;
#pragma unroll
      for (int j = 0; j < 20; j += 2)
        asm volatile("stmatrix.sync.aligned.m8n8.x4.shared.b16 [%0], {%1,%2,%3,%4};" ::"r"(sa + j * 16), "r"(pack(acc[4 * j], acc[4 * j + 1])),
                     "r"(pack(acc[4 * j + 2], acc[4 * j + 3])), "r"(pack(acc[4 * j + 4], acc[4 * j + 5])), "r"(pack(acc[4 * j + 6], acc[4 * j + 7])) : "memory");
      fence_async_smem();
      __syncwarp();
      if (lane < 16) {
        __nv_bfloat16* dst = P.out + (size_t)o_row((t >> 2) * 256 + rank * 128 + wg * 64 + w * 16 + lane) * DM + (t & 3) * 160;
        asm volatile("cp.async.bulk.global.shared::cta.bulk_group [%0], [%1], 320;" ::"l"(dst), "r"(st + lane * 336) : "memory");
        asm volatile("cp.async.bulk.commit_group;" ::: "memory");
        asm volatile("cp.async.bulk.wait_group.read 0;" ::: "memory");
      }
      __syncwarp();
    };
    for (int t = id; t < nsingle || t == id; t += ncl) {
      float acc[80];
      uint32_t prev = 0, bprev = 0;
      const bool tile = t < nsingle;
      const bool last = t + ncl >= nsingle;
      auto bstep = [&](int ks, int accf) {
        if (!(ks & 3)) TR(640 + ks / 2); if ((ks & 7) == 0) TG(144 + (ks >> 3));
        ring_wait();
        mbar_wait(sb + BAR_BFULL + 8 * bslot, bphase);
        if (!(ks & 3)) TR(641 + ks / 2);
        wg_fence();
        const uint32_t a = ring_addr() + wg * 512, bd = (((sb & 0x3FFFF) + OFF_Q + bslot * BB) >> 4) | ((4096u >> 4) << 16);
#pragma unroll
        for (int k = 0; k < 4; k++) wgmma_n160<1, 1>(acc, a + k * 128, HI128, bd + k * 64, HI64, k == 0 ? accf : 1);
        wg_commit();
        if (ks > 0) {
          wg_wait<1>();
          release(prev);
          if (lane == 0 && (ks < 59 || !last)) mbar_arrive_cl(mapa(sb + BAR_BEMPTY + 8 * bprev, bprev & 1));
        }
        prev = r.slot; bprev = bslot;
        r.next();
        if (++bslot == 6) { bslot = 0; bphase ^= 1; }
      };
      const char* optr = t == id ? out_ptr(u) : nullptr;
      uint32_t iv[30];
      if (tile) {
        bstep(0, 0);
        bstep(1, 1);
        bstep(2, 1); load_inv(iv, (it + 1) & 1); put(pb, iv, optr, IC<0>()); bstep(3, 1);
        bstep(4, 1); put(pb, iv, optr, IC<1>()); bstep(5, 1);
        bstep(6, 1); put(pb, iv, optr, IC<2>()); bstep(7, 1);
        bstep(8, 1); put(pb, iv, optr, IC<3>()); bstep(9, 1);
        bstep(10, 1); put(pb, iv, optr, IC<4>()); bstep(11, 1);
        bstep(12, 1); put(pb, iv, optr, IC<5>()); bstep(13, 1);
        bstep(14, 1); put(pb, iv, optr, IC<6>()); bstep(15, 1);
        bstep(16, 1); put(pb, iv, optr, IC<7>());
        wg_wait<0>();
        reg_fence(acc);
      } else {
#pragma unroll
        for (int i = 0; i < 80; i++) acc[i] = 0.f;
        load_inv(iv, (it + 1) & 1);
        put(pb, iv, optr, IC<0>()); put(pb, iv, optr, IC<1>()); put(pb, iv, optr, IC<2>()); put(pb, iv, optr, IC<3>());
        put(pb, iv, optr, IC<4>()); put(pb, iv, optr, IC<5>()); put(pb, iv, optr, IC<6>()); put(pb, iv, optr, IC<7>());
      }
      if (unsafe(t == id)) slow_path(P, unit_batch(u), unit_head(u, rank), wg, w, lane);
      if (t == id) publish();
      if (!tile) break;
#pragma unroll 1
      for (int ks = 17; ks < 64; ks++) {
        if (END_SKEW && wg == 1 && ks == 64 - END_SKEW) turn_wait();
        bstep(ks, 1);
      }
      if (END_SKEW && wg == 0) turn_pass();
      wg_wait<0>();
      reg_fence(acc);
      release(prev);
      if (lane == 0 && !last) mbar_arrive_cl(mapa(sb + BAR_BEMPTY + 8 * bprev, bprev & 1));
      TR(158); TG(156);
      const int pos0 = (t >> 2) * 256 + rank * 128 + wg * 64 + w * 16;
      if (last) {
        bar_sync(wg);
        out_tile(acc, t);
      } else {
        __nv_bfloat16* op0 = P.out + (size_t)o_row(pos0 + (lane >> 2)) * DM + (t & 3) * 160 + (lane & 3) * 2;
        __nv_bfloat16* op1 = P.out + (size_t)o_row(pos0 + (lane >> 2) + 8) * DM + (t & 3) * 160 + (lane & 3) * 2;
#pragma unroll
        for (int j = 0; j < 20; j++) {
          *reinterpret_cast<uint32_t*>(op0 + j * 8) = pack(acc[4 * j], acc[4 * j + 1]);
          *reinterpret_cast<uint32_t*>(op1 + j * 8) = pack(acc[4 * j + 2], acc[4 * j + 3]);
        }
      }
#pragma unroll
      for (int i = 0; i < 60; i++) pb[i] = 0;
    }
    if (gemm && id >= nsingle) {
      float ac0[80], ac1[80];
      uint32_t prev = 0, bprev = 0;
      auto half = [&](float (&acc)[80], int hs, int accf) {
        mbar_wait(sb + BAR_BFULL + 8 * bslot, bphase);
        wg_fence();
        const uint32_t a = ring_addr() + wg * 512, bd = (((sb & 0x3FFFF) + OFF_Q + bslot * BB) >> 4) | ((4096u >> 4) << 16);
#pragma unroll
        for (int k = 0; k < 4; k++) wgmma_n160<1, 1>(acc, a + k * 128, HI128, bd + k * 64, HI64, k == 0 ? accf : 1);
        wg_commit();
        if (hs > 0) {
          wg_wait<1>();
          if (lane == 0 && hs < 123) mbar_arrive_cl(mapa(sb + BAR_BEMPTY + 8 * bprev, bprev & 1));
        }
        bprev = bslot;
        if (++bslot == 6) { bslot = 0; bphase ^= 1; }
      };
      auto dstep = [&](int ks, int accf) {
        if (!(ks & 3)) TR(640 + ks / 2); if ((ks & 7) == 0) TG(144 + (ks >> 3));
        ring_wait();
        if (!(ks & 3)) TR(641 + ks / 2);
        half(ac0, 2 * ks, accf);
        if (ks > 0) release(prev);
        half(ac1, 2 * ks + 1, accf);
        prev = r.slot;
        r.next();
      };
      dstep(0, 0);
#pragma unroll 1
      for (int ks = 1; ks < 64; ks++) {
        if (wg == 1 && ks == 62) turn_wait();
        dstep(ks, 1);
      }
      if (wg == 0) turn_pass();
      wg_wait<0>();
      reg_fence(ac0); reg_fence(ac1);
      TR(158); TG(156);
      bar_sync(wg);
      out_tile(ac0, 2 * id - 72);
      out_tile(ac1, 2 * id - 71);
    }
    TR(159);
  }
}

typedef CUresult (*EncodeFn)(CUtensorMap*, CUtensorMapDataType, cuuint32_t, void*, const cuuint64_t*, const cuuint64_t*,
                             const cuuint32_t*, const cuuint32_t*, CUtensorMapInterleave, CUtensorMapSwizzle,
                             CUtensorMapL2promotion, CUtensorMapFloatOOBfill);

void make_map(EncodeFn enc, CUtensorMap* m, const void* p, int rank, const cuuint64_t* dims, const cuuint64_t* strides,
              const cuuint32_t* box, CUtensorMapSwizzle sw, CUtensorMapL2promotion promo) {
  cuuint32_t es[3] = {1, 1, 1};
  enc(m, CU_TENSOR_MAP_DATA_TYPE_BFLOAT16, rank, const_cast<void*>(p), dims, strides, box, es, CU_TENSOR_MAP_INTERLEAVE_NONE, sw,
      promo, CU_TENSOR_MAP_FLOAT_OOB_FILL_NONE);
}

}

extern "C" void kernel_launch(void* const* d_in, const int* in_sizes, int n_in, void* d_out, int out_size) {
  static EncodeFn enc = nullptr;
  static int nclusters = 0;
  static void* o_ptr = nullptr;
  if (!enc) {
    cudaDriverEntryPointQueryResult qr;
    cudaGetDriverEntryPoint("cuTensorMapEncodeTiled", (void**)&enc, cudaEnableDefault, &qr);
    cudaFuncSetAttribute(fused_attn_kernel, cudaFuncAttributeMaxDynamicSharedMemorySize, SMEM_BYTES);
    cudaGetSymbolAddress(&o_ptr, g_o);
    cudaLaunchConfig_t cfg = {};
    cfg.gridDim = 128; cfg.blockDim = 384; cfg.dynamicSmemBytes = SMEM_BYTES;
    cudaLaunchAttribute at; at.id = cudaLaunchAttributeClusterDimension;
    at.val.clusterDim.x = 2; at.val.clusterDim.y = 1; at.val.clusterDim.z = 1;
    cfg.attrs = &at; cfg.numAttrs = 1;
    int n = 0;
    cudaOccupancyMaxActiveClusters(&n, fused_attn_kernel, &cfg);
    nclusters = n >= 66 ? MAXCL : (n >= 64 || n <= 0 ? 64 : n);
  }
  const __nv_bfloat16* x = (const __nv_bfloat16*)d_in[0];
  const __nv_bfloat16* k = (const __nv_bfloat16*)d_in[1];
  const __nv_bfloat16* v = (const __nv_bfloat16*)d_in[2];
  const __nv_bfloat16* wq = (const __nv_bfloat16*)d_in[3];
  const __nv_bfloat16* wo = (const __nv_bfloat16*)d_in[4];
  CUtensorMap tm_x, tm_wq, tm_k, tm_v, tm_o, tm_wo;
  const auto S128 = CU_TENSOR_MAP_SWIZZLE_128B;
  const auto P128 = CU_TENSOR_MAP_L2_PROMOTION_L2_128B, P256 = CU_TENSOR_MAP_L2_PROMOTION_L2_256B;
  { cuuint64_t d[2] = {DM, NB * SQ}, s[1] = {DM * 2}; cuuint32_t b[2] = {64, 120}; make_map(enc, &tm_x, x, 2, d, s, b, S128, P128); }
  { cuuint64_t d[3] = {64, DM, HD / 64}, s[2] = {HD * 2, 128}; cuuint32_t b[3] = {64, 64, 2}; make_map(enc, &tm_wq, wq, 3, d, s, b, S128, P256); }
  { cuuint64_t d[3] = {64, NB * NH * SK, 2}, s[2] = {DH * 2, 128}; cuuint32_t b[3] = {64, 64, 2};
    make_map(enc, &tm_k, k, 3, d, s, b, S128, P128); make_map(enc, &tm_v, v, 3, d, s, b, S128, P128); }
  { cuuint64_t d[3] = {64, HD, NROWS / 64}, s[2] = {NROWS * 2, 128}; cuuint32_t b[3] = {64, 64, 2}; make_map(enc, &tm_o, o_ptr, 3, d, s, b, S128, P256); }
  { cuuint64_t d[3] = {32, HD, DM / 32}, s[2] = {DM * 2, 64}; cuuint32_t b[3] = {32, 64, 5};
    make_map(enc, &tm_wo, wo, 3, d, s, b, CU_TENSOR_MAP_SWIZZLE_64B, P128); }
  Params P{x, k, v, wq, (__nv_bfloat16*)d_out, (__nv_bfloat16*)o_ptr};
  fused_attn_kernel<<<2 * nclusters, 384, SMEM_BYTES>>>(tm_x, tm_wq, tm_k, tm_v, tm_o, tm_wo, P);
}
```

```cpp
#include <cuda_runtime.h>
#include <cuda.h>
#include <cuda_bf16.h>
#include <stdint.h>

namespace {

constexpr int NB = 16, SQ = 240, DM = 640, NH = 32, SK = 1024, DH = 128, HD = NH * DH;
constexpr int NROWS = NB * SQ;
constexpr int NUNITS = 256;
#define DPRO 0
#define LATE_AT 0
#define ALT_FROM 3
#define MERGE89 1
#define END_SKEW 5
#define VREL 8
#define PF_HOLD 6
#define PF_N 4
#define PF_J0 3
#define PF_STEP 3
#define ROT 0
#define O_EF 1
#define B_ORDER 1
#define WO_PF 6
#define ROLE_AT 1
#define ASYM 0
#define ASYM_PASS 1
#define PINLANE 0
#define MAXCL 66
#define SMID_TOP 88
constexpr int NOTILES = 60;
constexpr float QSCALE = 0.08838834764831845f * 1.4426950408889634f;
constexpr float L_MIN = 9.5367431640625e-07f;
constexpr float L_MAX = 1.152921504606846976e18f;

constexpr uint32_t RING_SLOTS = 6, RING_BYTES = 16384;
constexpr uint32_t XB = 15360;
constexpr uint32_t BB = 20480;
constexpr uint32_t OFF_Q = RING_SLOTS * RING_BYTES;
constexpr uint32_t OFF_P = OFF_Q + 4 * XB;
constexpr uint32_t OFF_INV = OFF_P + 4 * XB;
constexpr uint32_t OFF_L2 = OFF_INV + 1280;
constexpr uint32_t OFF_BAR = OFF_L2 + 4096;
constexpr uint32_t BAR_RFULL = OFF_BAR, BAR_REMPTY = BAR_RFULL + 48, BAR_XFULL = BAR_REMPTY + 48,
    BAR_XEMPTY = BAR_XFULL + 64, BAR_BFULL = BAR_XEMPTY + 32, BAR_BEMPTY = BAR_BFULL + 48, BAR_STAGE = BAR_BEMPTY + 48;
constexpr uint32_t BAR_ROLE = BAR_STAGE + 16, BAR_LSUM = BAR_ROLE + 24, BAR_INV = BAR_LSUM + 16;
constexpr uint32_t OFF_TR = BAR_INV + 16;
constexpr uint32_t SMEM_BYTES = OFF_TR + 1024;

constexpr uint32_t HI128 = (1u << 30) | (1024 >> 4);
constexpr uint32_t HI64 = (2u << 30) | (512 >> 4);

__device__ __nv_bfloat16 g_o[HD * NROWS];
__device__ unsigned g_cnt[67 * 8];
#define TR(i)
#define TG(i)

struct Params {
  const __nv_bfloat16 *x, *k, *v, *wq;
  __nv_bfloat16 *out, *o;
};

__device__ __forceinline__ void wg_fence() { asm volatile("wgmma.fence.sync.aligned;" ::: "memory"); }
__device__ __forceinline__ void wg_commit() { asm volatile("wgmma.commit_group.sync.aligned;" ::: "memory"); }
template <int N> __device__ __forceinline__ void wg_wait() { asm volatile("wgmma.wait_group.sync.aligned %0;" ::"n"(N) : "memory"); }
template <int N> __device__ __forceinline__ void reg_fence(float (&r)[N]) {
#pragma unroll
  for (int i = 0; i < N; i++) asm volatile("" : "+f"(r[i])::"memory");
}
template <int TA, int TB>
__device__ __forceinline__ void wgmma_n120(float (&d)[60], uint32_t a_lo, uint32_t a_hi, uint32_t b_lo, uint32_t b_hi, int acc) {
  asm volatile(
      "{\n.reg .pred p;\n.reg .b64 da, db;\nsetp.ne.b32 p, %64, 0;\n"
      "mov.b64 da, {%60, %61};\nmov.b64 db, {%62, %63};\n"
      "wgmma.mma_async.sync.aligned.m64n120k16.f32.bf16.bf16 {"
      "%0, %1, %2, %3, %4, %5, %6, %7, %8, %9, %10, %11, %12, %13, %14, %15, %16, %17, %18, %19, %20, %21, %22, %23, "
      "%24, %25, %26, %27, %28, %29, %30, %31, %32, %33, %34, %35, %36, %37, %38, %39, %40, %41, %42, %43, %44, %45, "
      "%46, %47, %48, %49, %50, %51, %52, %53, %54, %55, %56, %57, %58, %59"
      "}, da, db, p, 1, 1, %65, %66;\n}\n"
      : "+f"(d[0]), "+f"(d[1]), "+f"(d[2]), "+f"(d[3]), "+f"(d[4]), "+f"(d[5]), "+f"(d[6]), "+f"(d[7]), "+f"(d[8]),
        "+f"(d[9]), "+f"(d[10]), "+f"(d[11]), "+f"(d[12]), "+f"(d[13]), "+f"(d[14]), "+f"(d[15]), "+f"(d[16]),
        "+f"(d[17]), "+f"(d[18]), "+f"(d[19]), "+f"(d[20]), "+f"(d[21]), "+f"(d[22]), "+f"(d[23]), "+f"(d[24]),
        "+f"(d[25]), "+f"(d[26]), "+f"(d[27]), "+f"(d[28]), "+f"(d[29]), "+f"(d[30]), "+f"(d[31]), "+f"(d[32]),
        "+f"(d[33]), "+f"(d[34]), "+f"(d[35]), "+f"(d[36]), "+f"(d[37]), "+f"(d[38]), "+f"(d[39]), "+f"(d[40]),
        "+f"(d[41]), "+f"(d[42]), "+f"(d[43]), "+f"(d[44]), "+f"(d[45]), "+f"(d[46]), "+f"(d[47]), "+f"(d[48]),
        "+f"(d[49]), "+f"(d[50]), "+f"(d[51]), "+f"(d[52]), "+f"(d[53]), "+f"(d[54]), "+f"(d[55]), "+f"(d[56]),
        "+f"(d[57]), "+f"(d[58]), "+f"(d[59])
      : "r"(a_lo), "r"(a_hi), "r"(b_lo), "r"(b_hi), "r"(acc), "n"(TA), "n"(TB));
}

template <int TA, int TB>
__device__ __forceinline__ void wgmma_n160(float (&d)[80], uint32_t a_lo, uint32_t a_hi, uint32_t b_lo, uint32_t b_hi, int acc) {
  asm volatile(
      "{\n.reg .pred p;\n.reg .b64 da, db;\nsetp.ne.b32 p, %84, 0;\n"
      "mov.b64 da, {%80, %81};\nmov.b64 db, {%82, %83};\n"
      "wgmma.mma_async.sync.aligned.m64n160k16.f32.bf16.bf16 {"
      "%0, %1, %2, %3, %4, %5, %6, %7, %8, %9, %10, %11, %12, %13, %14, %15, %16, %17, %18, %19, %20, %21, %22, %23, "
      "%24, %25, %26, %27, %28, %29, %30, %31, %32, %33, %34, %35, %36, %37, %38, %39, %40, %41, %42, %43, %44, %45, "
      "%46, %47, %48, %49, %50, %51, %52, %53, %54, %55, %56, %57, %58, %59, %60, %61, %62, %63, %64, %65, %66, %67, "
      "%68, %69, %70, %71, %72, %73, %74, %75, %76, %77, %78, %79"
      "}, da, db, p, 1, 1, %85, %86;\n}\n"
      : "+f"(d[0]), "+f"(d[1]), "+f"(d[2]), "+f"(d[3]), "+f"(d[4]), "+f"(d[5]), "+f"(d[6]), "+f"(d[7]), "+f"(d[8]),
        "+f"(d[9]), "+f"(d[10]), "+f"(d[11]), "+f"(d[12]), "+f"(d[13]), "+f"(d[14]), "+f"(d[15]), "+f"(d[16]),
        "+f"(d[17]), "+f"(d[18]), "+f"(d[19]), "+f"(d[20]), "+f"(d[21]), "+f"(d[22]), "+f"(d[23]), "+f"(d[24]),
        "+f"(d[25]), "+f"(d[26]), "+f"(d[27]), "+f"(d[28]), "+f"(d[29]), "+f"(d[30]), "+f"(d[31]), "+f"(d[32]),
        "+f"(d[33]), "+f"(d[34]), "+f"(d[35]), "+f"(d[36]), "+f"(d[37]), "+f"(d[38]), "+f"(d[39]), "+f"(d[40]),
        "+f"(d[41]), "+f"(d[42]), "+f"(d[43]), "+f"(d[44]), "+f"(d[45]), "+f"(d[46]), "+f"(d[47]), "+f"(d[48]),
        "+f"(d[49]), "+f"(d[50]), "+f"(d[51]), "+f"(d[52]), "+f"(d[53]), "+f"(d[54]), "+f"(d[55]), "+f"(d[56]),
        "+f"(d[57]), "+f"(d[58]), "+f"(d[59]), "+f"(d[60]), "+f"(d[61]), "+f"(d[62]), "+f"(d[63]), "+f"(d[64]),
        "+f"(d[65]), "+f"(d[66]), "+f"(d[67]), "+f"(d[68]), "+f"(d[69]), "+f"(d[70]), "+f"(d[71]), "+f"(d[72]),
        "+f"(d[73]), "+f"(d[74]), "+f"(d[75]), "+f"(d[76]), "+f"(d[77]), "+f"(d[78]), "+f"(d[79])
      : "r"(a_lo), "r"(a_hi), "r"(b_lo), "r"(b_hi), "r"(acc), "n"(TA), "n"(TB));
}
__device__ __forceinline__ void mbar_init(uint32_t bar, int cnt) { asm volatile("mbarrier.init.shared::cta.b64 [%0], %1;" ::"r"(bar), "r"(cnt)); }
__device__ __forceinline__ void mbar_expect(uint32_t bar, uint32_t bytes) {
  asm volatile("mbarrier.arrive.expect_tx.shared::cta.b64 _, [%0], %1;" ::"r"(bar), "r"(bytes) : "memory");
}
__device__ __forceinline__ uint32_t mapa(uint32_t addr, uint32_t cta) {
  uint32_t r; asm("mapa.shared::cluster.u32 %0, %1, %2;" : "=r"(r) : "r"(addr), "r"(cta)); return r;
}
__device__ __forceinline__ void mbar_expect_cl(uint32_t cbar, uint32_t bytes) {
  asm volatile("mbarrier.arrive.expect_tx.shared::cluster.b64 _, [%0], %1;" ::"r"(cbar), "r"(bytes) : "memory");
}
__device__ __forceinline__ void mbar_arrive(uint32_t bar) { asm volatile("mbarrier.arrive.shared::cta.b64 _, [%0];" ::"r"(bar) : "memory"); }
__device__ __forceinline__ void mbar_arrive_cl(uint32_t cbar) { asm volatile("mbarrier.arrive.shared::cluster.b64 _, [%0];" ::"r"(cbar) : "memory"); }
__device__ __forceinline__ void mbar_wait(uint32_t bar, uint32_t parity) {
  asm volatile(
      "{\n.reg .pred p;\n.reg .u32 n;\n"
      "mbarrier.try_wait.parity.shared::cta.b64 p, [%0], %1;\n@p bra WAIT_DONE;\n"
      "mov.u32 n, 0;\n"
      "WAIT_LOOP:\n"
      "mbarrier.try_wait.parity.shared::cta.b64 p, [%0], %1;\n@p bra WAIT_DONE;\n"
      "add.u32 n, n, 1;\nsetp.lt.u32 p, n, 0x4000000;\n@p bra WAIT_LOOP;\ntrap;\n"
      "WAIT_DONE:\n}\n" ::"r"(bar), "r"(parity) : "memory");
}
__device__ __forceinline__ void mbar_wait_cl(uint32_t bar, uint32_t parity) {
  asm volatile(
      "{\n.reg .pred p;\n.reg .u32 n;\nmov.u32 n, 0;\n"
      "WAIT_LOOP:\n"
      "mbarrier.try_wait.parity.acquire.cluster.shared::cta.b64 p, [%0], %1;\n@p bra WAIT_DONE;\n"
      "add.u32 n, n, 1;\nsetp.lt.u32 p, n, 0x4000000;\n@p bra WAIT_LOOP;\ntrap;\n"
      "WAIT_DONE:\n}\n" ::"r"(bar), "r"(parity) : "memory");
}
__device__ __forceinline__ void tma3d(uint32_t dst, const CUtensorMap* m, int c0, int c1, int c2, uint32_t bar) {
  asm volatile("cp.async.bulk.tensor.3d.shared::cluster.global.mbarrier::complete_tx::bytes [%0], [%1, {%3, %4, %5}], [%2];"
               ::"r"(dst), "l"(m), "r"(bar), "r"(c0), "r"(c1), "r"(c2) : "memory");
}
__device__ __forceinline__ void tma3d_hint(uint32_t dst, const CUtensorMap* m, int c0, int c1, int c2, uint32_t bar, uint64_t pol) {
  asm volatile("cp.async.bulk.tensor.3d.shared::cluster.global.mbarrier::complete_tx::bytes.L2::cache_hint [%0], [%1, {%3, %4, %5}], [%2], %6;"
               ::"r"(dst), "l"(m), "r"(bar), "r"(c0), "r"(c1), "r"(c2), "l"(pol) : "memory");
}
__device__ __forceinline__ void tma2d_mc(uint32_t dst, const CUtensorMap* m, int c0, int c1, uint32_t bar) {
  asm volatile("cp.async.bulk.tensor.2d.shared::cluster.global.mbarrier::complete_tx::bytes.multicast::cluster [%0], [%1, {%3, %4}], [%2], %5;"
               ::"r"(dst), "l"(m), "r"(bar), "r"(c0), "r"(c1), "h"((uint16_t)3) : "memory");
}
__device__ __forceinline__ void tma3d_mc(uint32_t dst, const CUtensorMap* m, int c0, int c1, int c2, uint32_t bar) {
  asm volatile("cp.async.bulk.tensor.3d.shared::cluster.global.mbarrier::complete_tx::bytes.multicast::cluster [%0], [%1, {%3, %4, %5}], [%2], %6;"
               ::"r"(dst), "l"(m), "r"(bar), "r"(c0), "r"(c1), "r"(c2), "h"((uint16_t)3) : "memory");
}
__device__ __forceinline__ void l2_prefetch(const void* p, uint32_t bytes) {
  asm volatile("cp.async.bulk.prefetch.L2.global [%0], %1;" ::"l"(p), "r"(bytes) : "memory");
}
__device__ __forceinline__ void fence_async_smem() { asm volatile("fence.proxy.async.shared::cta;" ::: "memory"); }
__device__ __forceinline__ void bar_sync(int wg) {
  if (wg == 0) asm volatile("bar.sync 1, 128;" ::: "memory");
  else asm volatile("bar.sync 2, 128;" ::: "memory");
}
__device__ __forceinline__ bool bar_red_or(int id, bool v) {
  uint32_t r;
  asm volatile("{\n.reg .pred p, q;\nsetp.ne.u32 p, %2, 0;\nbar.red.or.pred q, %1, 128, p;\nselp.u32 %0, 1, 0, q;\n}\n"
               : "=r"(r) : "r"(1 + id), "r"((uint32_t)v) : "memory");
  return r != 0;
}
__device__ __forceinline__ uint32_t hfma2(uint32_t a, uint32_t b, uint32_t c) { uint32_t r; asm("fma.rn.bf16x2 %0, %1, %2, %3;" : "=r"(r) : "r"(a), "r"(b), "r"(c)); return r; }
__device__ __forceinline__ float ex2(float x) { float y; asm("ex2.approx.ftz.f32 %0, %1;" : "=f"(y) : "f"(x)); return y; }
__device__ __forceinline__ uint32_t pack(float lo, float hi) { uint32_t r; asm("cvt.rn.bf16x2.f32 %0, %1, %2;" : "=r"(r) : "f"(hi), "f"(lo)); return r; }
__device__ __forceinline__ void stsm4t(uint32_t a, uint32_t r0, uint32_t r1, uint32_t r2, uint32_t r3) {
  asm volatile("stmatrix.sync.aligned.m8n8.x4.trans.shared.b16 [%0], {%1,%2,%3,%4};" ::"r"(a), "r"(r0), "r"(r1), "r"(r2), "r"(r3) : "memory");
}
__device__ __forceinline__ void stsm2t(uint32_t a, uint32_t r0, uint32_t r1) {
  asm volatile("stmatrix.sync.aligned.m8n8.x2.trans.shared.b16 [%0], {%1,%2};" ::"r"(a), "r"(r0), "r"(r1) : "memory");
}
__device__ __forceinline__ void mma16816(float (&d)[4], const uint32_t (&a)[4], uint32_t b0, uint32_t b1) {
  asm volatile("mma.sync.aligned.m16n8k16.row.col.f32.bf16.bf16.f32 {%0,%1,%2,%3}, {%4,%5,%6,%7}, {%8,%9}, {%0,%1,%2,%3};"
               : "+f"(d[0]), "+f"(d[1]), "+f"(d[2]), "+f"(d[3]) : "r"(a[0]), "r"(a[1]), "r"(a[2]), "r"(a[3]), "r"(b0), "r"(b1));
}

template <int V> struct IC { static constexpr int value = V; };

struct Ring {
  uint32_t slot = 0, phase = 0;
  __device__ __forceinline__ void next() { if (++slot == RING_SLOTS) { slot = 0; phase ^= 1; } }
};

__device__ __forceinline__ void mma_tn(float (&o0)[60], float (&o1)[60], uint32_t a, uint32_t b, int acc) {
#pragma unroll
  for (int k = 0; k < 4; k++) {
    wgmma_n120<1, 0>(o0, a + k * 128, HI128, b + k * 2, HI128, k == 0 ? acc : 1);
    wgmma_n120<1, 0>(o1, a + 512 + k * 128, HI128, b + k * 2, HI128, k == 0 ? acc : 1);
  }
}
__device__ __forceinline__ void mma_tn_split(float (&o0)[60], float (&o1)[60], uint32_t a, uint32_t b) {
#pragma unroll
  for (int k = 0; k < 4; k++) wgmma_n120<1, 0>(o0, a + k * 128, HI128, b + k * 2, HI128, 1);
  wg_commit();
#pragma unroll
  for (int k = 0; k < 4; k++) wgmma_n120<1, 0>(o1, a + 512 + k * 128, HI128, b + k * 2, HI128, 1);
  wg_commit();
}
__device__ __forceinline__ void mma_qk(float (&s)[60], uint32_t a, uint32_t q) {
#pragma unroll
  for (int k = 0; k < 8; k++)
    wgmma_n120<0, 0>(s, a + (k >> 2) * 512 + (k & 3) * 2, HI128, q + (k >> 2) * (XB >> 4) + (k & 3) * 2, HI128, k != 0);
}
template <int J0, int J1, bool FIRST = false>
__device__ __forceinline__ void exp_store(const float (&s)[60], float (&l)[30], uint32_t dst) {
#pragma unroll
  for (int j = J0; j < J1; j += 2) {
    uint32_t p[4];
#pragma unroll
    for (int jj = 0; jj < 2; jj++) {
      if (j + jj < 15) {
        const int c = j + jj;
        float e0 = ex2(s[4 * c]), e1 = ex2(s[4 * c + 1]), e2 = ex2(s[4 * c + 2]), e3 = ex2(s[4 * c + 3]);
        if (FIRST) { l[2 * c] = e0 + e2; l[2 * c + 1] = e1 + e3; }
        else { l[2 * c] += e0; l[2 * c + 1] += e1; l[2 * c] += e2; l[2 * c + 1] += e3; }
        p[2 * jj] = pack(e0, e1); p[2 * jj + 1] = pack(e2, e3);
      }
    }
    if (j + 1 < 15) stsm4t(dst + j * 1024, p[0], p[1], p[2], p[3]);
    else stsm2t(dst + j * 1024, p[0], p[1]);
  }
}

__device__ __forceinline__ int o_pos(int wg, int r) {
  const int j = r >> 3, q = (r >> 1) & 3, c = r & 1;
  if (j < 12) return (wg ? 144 : 0) + (j >> 2) * 32 + q * 8 + (j & 3) * 2 + c;
  if (j < 14) return (wg ? 128 : 96) + q * 4 + (j - 12) * 2 + c;
  return (wg ? 120 : 112) + q * 2 + c;
}
__device__ __forceinline__ int o_row(int p) {
  const int b = p / SQ, r = p - b * SQ, wg = r >= 120, c = r & 1;
  const int a = r - (wg ? 144 : 0), m = r - (wg ? 128 : 96), e = r - (wg ? 120 : 112);
  int row;
  if (a >= 0 && a < 96) row = ((a >> 5) * 4 + ((a >> 1) & 3)) * 8 + ((a >> 3) & 3) * 2 + c;
  else if (m >= 0 && m < 16) row = (12 + ((m >> 1) & 1)) * 8 + (m >> 2) * 2 + c;
  else row = 112 + e;
  return b * SQ + wg * 120 + row;
}

__device__ __forceinline__ void slow_path(const Params& P, int b, int h, int wg, int w, int lane) {
  const int g = lane >> 2, q = lane & 3, row0 = wg * 120;
  const uint16_t* wq = reinterpret_cast<const uint16_t*>(P.wq) + h * DH + g;
  const __nv_bfloat16* kp = P.k + (size_t)(b * NH + h) * SK * DH;
  const uint16_t* vp = reinterpret_cast<const uint16_t*>(P.v) + (size_t)(b * NH + h) * SK * DH + g;
#pragma unroll 1
  for (int t = w; t < 8; t += 4) {
    const int r0 = 16 * t + g, r1 = r0 + 8;
    const __nv_bfloat16* x0 = P.x + (size_t)(b * SQ + row0 + r0) * DM + 2 * q;
    const __nv_bfloat16* x1 = P.x + (size_t)(b * SQ + row0 + min(r1, 119)) * DM + 2 * q;
    float o[16][4];
#pragma unroll
    for (int n = 0; n < 16; n++) o[n][0] = o[n][1] = o[n][2] = o[n][3] = 0.f;
#pragma unroll 1
    for (int k0 = 0; k0 < DM; k0 += 16) {
      uint32_t a[4] = {*(const uint32_t*)(x0 + k0), *(const uint32_t*)(x1 + k0), *(const uint32_t*)(x0 + k0 + 8), *(const uint32_t*)(x1 + k0 + 8)};
      const uint16_t* wr = wq + (size_t)(k0 + 2 * q) * HD;
#pragma unroll
      for (int n = 0; n < 16; n++)
        mma16816(o[n], a, wr[8 * n] | ((uint32_t)wr[8 * n + HD] << 16), wr[8 * n + 8 * HD] | ((uint32_t)wr[8 * n + 9 * HD] << 16));
    }
    uint32_t qa[8][4];
#pragma unroll
    for (int k = 0; k < 8; k++) {
      qa[k][0] = pack(o[2 * k][0] * QSCALE, o[2 * k][1] * QSCALE);
      qa[k][1] = pack(o[2 * k][2] * QSCALE, o[2 * k][3] * QSCALE);
      qa[k][2] = pack(o[2 * k + 1][0] * QSCALE, o[2 * k + 1][1] * QSCALE);
      qa[k][3] = pack(o[2 * k + 1][2] * QSCALE, o[2 * k + 1][3] * QSCALE);
    }
#pragma unroll
    for (int n = 0; n < 16; n++) o[n][0] = o[n][1] = o[n][2] = o[n][3] = 0.f;
    float m0 = -INFINITY, m1 = -INFINITY, l0 = 0.f, l1 = 0.f;
#pragma unroll 1
    for (int key0 = 0; key0 < SK; key0 += 16) {
      float s[2][4];
#pragma unroll
      for (int nt = 0; nt < 2; nt++) {
        s[nt][0] = s[nt][1] = s[nt][2] = s[nt][3] = 0.f;
        const __nv_bfloat16* kr = kp + (size_t)(key0 + 8 * nt + g) * DH + 2 * q;
#pragma unroll
        for (int k = 0; k < 8; k++) mma16816(s[nt], qa[k], *(const uint32_t*)(kr + 16 * k), *(const uint32_t*)(kr + 16 * k + 8));
      }
      float n0 = fmaxf(fmaxf(s[0][0], s[0][1]), fmaxf(s[1][0], s[1][1])), n1 = fmaxf(fmaxf(s[0][2], s[0][3]), fmaxf(s[1][2], s[1][3]));
      n0 = fmaxf(n0, __shfl_xor_sync(~0u, n0, 1)); n1 = fmaxf(n1, __shfl_xor_sync(~0u, n1, 1));
      n0 = fmaxf(n0, __shfl_xor_sync(~0u, n0, 2)); n1 = fmaxf(n1, __shfl_xor_sync(~0u, n1, 2));
      n0 = fmaxf(n0, m0); n1 = fmaxf(n1, m1);
      const float z0 = n0 == -INFINITY ? 0.f : n0, z1 = n1 == -INFINITY ? 0.f : n1;
      const float c0 = ex2(m0 - z0), c1 = ex2(m1 - z1);
      m0 = n0; m1 = n1;
#pragma unroll
      for (int nt = 0; nt < 2; nt++) {
        s[nt][0] = ex2(s[nt][0] - z0); s[nt][1] = ex2(s[nt][1] - z0);
        s[nt][2] = ex2(s[nt][2] - z1); s[nt][3] = ex2(s[nt][3] - z1);
      }
      l0 = l0 * c0 + s[0][0] + s[0][1] + s[1][0] + s[1][1];
      l1 = l1 * c1 + s[0][2] + s[0][3] + s[1][2] + s[1][3];
      uint32_t pa[4] = {pack(s[0][0], s[0][1]), pack(s[0][2], s[0][3]), pack(s[1][0], s[1][1]), pack(s[1][2], s[1][3])};
      const uint16_t* vr = vp + (size_t)(key0 + 2 * q) * DH;
#pragma unroll
      for (int n = 0; n < 16; n++) {
        o[n][0] *= c0; o[n][1] *= c0; o[n][2] *= c1; o[n][3] *= c1;
        mma16816(o[n], pa, vr[8 * n] | ((uint32_t)vr[8 * n + DH] << 16), vr[8 * n + 8 * DH] | ((uint32_t)vr[8 * n + 9 * DH] << 16));
      }
    }
    l0 += __shfl_xor_sync(~0u, l0, 1); l1 += __shfl_xor_sync(~0u, l1, 1);
    l0 += __shfl_xor_sync(~0u, l0, 2); l1 += __shfl_xor_sync(~0u, l1, 2);
    const float i0 = 1.f / l0, i1 = 1.f / l1;
    __nv_bfloat16* oc = P.o + (size_t)(h * DH + 2 * q) * NROWS + b * SQ;
    const int p0 = o_pos(wg, r0), p1 = o_pos(wg, min(r1, 119));
#pragma unroll
    for (int n = 0; n < 16; n++) {
      oc[(size_t)(8 * n) * NROWS + p0] = __float2bfloat16(o[n][0] * i0);
      oc[(size_t)(8 * n + 1) * NROWS + p0] = __float2bfloat16(o[n][1] * i0);
      if (r1 < 120) {
        oc[(size_t)(8 * n) * NROWS + p1] = __float2bfloat16(o[n][2] * i1);
        oc[(size_t)(8 * n + 1) * NROWS + p1] = __float2bfloat16(o[n][3] * i1);
      }
    }
  }
}

__device__ __forceinline__ int bk(int ks) { return B_ORDER && ks < 48 ? 32 - (ks & 48) + (ks & 15) : ks; }
__device__ __forceinline__ uint32_t x_slot(uint32_t wg, uint32_t j) { return j < 2 ? (2 * wg + j) * XB : (2 * j + wg) * XB; }
__device__ __forceinline__ int unit_batch(int u) { return (u & 63) >> 2; }
__device__ __forceinline__ int unit_head(int u, int rank) { return (u >> 6) * 8 + (u & 3) * 2 + rank; }

__global__ void __cluster_dims__(2, 1, 1) __launch_bounds__(384, 1)
fused_attn_kernel(const __grid_constant__ CUtensorMap tm_x, const __grid_constant__ CUtensorMap tm_wq,
                  const __grid_constant__ CUtensorMap tm_k, const __grid_constant__ CUtensorMap tm_v,
                  const __grid_constant__ CUtensorMap tm_o, const __grid_constant__ CUtensorMap tm_wo,
                  const __grid_constant__ Params P) {
  extern __shared__ uint8_t smem_raw[];
  const uint32_t sb = ((uint32_t)__cvta_generic_to_shared(smem_raw) + 1023) & ~1023u;
  const int warp = __shfl_sync(~0u, threadIdx.x >> 5, 0);
  int lane = threadIdx.x & 31;
  const int rank = blockIdx.x & 1, cl = blockIdx.x >> 1, ncl = gridDim.x >> 1;

  const int nsingle = ncl == 66 ? 44 : NOTILES;
  auto role = [&]() {
    mbar_wait(sb + BAR_ROLE + 16, 0);
    int id;
    asm volatile("ld.shared.u32 %0, [%1];" : "=r"(id) : "r"(sb + BAR_ROLE + 8) : "memory");
    return id;
  };

  if (threadIdx.x == 0) {
    for (int i = 0; i < 6; i++) {
      mbar_init(sb + BAR_RFULL + 8 * i, 1); mbar_init(sb + BAR_REMPTY + 8 * i, 8);
      mbar_init(sb + BAR_BFULL + 8 * i, 1); mbar_init(sb + BAR_BEMPTY + 8 * i, 16);
    }
    for (int i = 0; i < 8; i++) mbar_init(sb + BAR_XFULL + 8 * i, 1);
    for (int i = 0; i < 4; i++) mbar_init(sb + BAR_XEMPTY + 8 * i, 8);
    for (int i = 0; i < 2; i++) { mbar_init(sb + BAR_STAGE + 8 * i, 4); mbar_init(sb + BAR_LSUM + 8 * i, 4); mbar_init(sb + BAR_INV + 8 * i, 1); }
    mbar_init(sb + BAR_ROLE, 1); mbar_init(sb + BAR_ROLE + 16, 1);
    asm volatile("fence.mbarrier_init.release.cluster;" ::: "memory");
  }
  __syncwarp();
  asm volatile("barrier.cluster.arrive.relaxed.aligned;\nbarrier.cluster.wait.aligned;" ::: "memory");

  if (warp >= 8) {
    asm volatile("setmaxnreg.dec.sync.aligned.u32 24;");
    if (warp == 8) {
      uint64_t pol;
      asm volatile("createpolicy.fractional.L2::evict_first.b64 %0, 1.0;" : "=l"(pol));
      Ring r;
      auto load = [&](const CUtensorMap* m, int c1, int c2, bool ef) {
        mbar_wait(sb + BAR_REMPTY + 8 * r.slot, r.phase ^ 1);
        if (lane == 0) {
          mbar_expect(sb + BAR_RFULL + 8 * r.slot, RING_BYTES);
          if (ef) tma3d_hint(sb + r.slot * RING_BYTES, m, 0, c1, c2, sb + BAR_RFULL + 8 * r.slot, pol);
          else tma3d(sb + r.slot * RING_BYTES, m, 0, c1, c2, sb + BAR_RFULL + 8 * r.slot);
        }
        r.next();
      };
      const int rot = ROT * (blockIdx.x * 5 + (blockIdx.x >> 4));
      for (int u0 = 0;; u0 += ncl) {
        const int u = __shfl_sync(~0u, (u0 >= 3 * ncl ? role() : cl) + u0, 0);
        if (u >= NUNITS) break;
        const int h = unit_head(u, rank);
        const int krow = (unit_batch(u) * NH + h) * SK;
#pragma unroll 1
        for (int s = 0; s < 10; s++) {
          load(&tm_wq, s * 64, 2 * h, false);
          const int sp = u0 == 0 ? s - PF_HOLD : s;
          if (sp >= 0 && sp < PF_N && lane == 0) l2_prefetch(P.v + (size_t)(krow + ((PF_J0 + sp * PF_STEP + rot) & 15) * 64) * DH, 16384);
        }
#pragma unroll 1
        for (int j = 0; j <= 16; j++) {
          if (j < 16) load(&tm_k, krow + ((j + rot) & 15) * 64, 0, true);
          if (j == 1 + DPRO) load(&tm_v, krow + (rot & 15) * 64, 0, true);
          if (j > 1) load(&tm_v, krow + ((j - 1 + rot) & 15) * 64, 0, true);
        }
      }
      const int id = __shfl_sync(~0u, role(), 0);
      const bool dbl = ncl == 66 && id >= 58;
      for (int t = dbl ? 2 * id - 72 : id; t < (dbl ? NOTILES : nsingle); t += ncl) {
        const int row0 = (t >> 2) * 256 + rank * 128;
        const int b0 = row0 / SQ, b1 = (row0 + 127) / SQ;
#pragma unroll 1
        for (int ks = 0; ks < 64; ks++) {
          if (dbl ? (ks & 15) == 0 : ks == 0 || ks == 48) {
            const unsigned* c = &g_cnt[((lane & 1 ? b1 : b0) * 4 + (ks || dbl ? ks >> 4 : min(lane >> 1, 2))) * 8];
            unsigned v, n = 0;
            do {
              asm volatile("ld.acquire.gpu.global.u32 %0, [%1];" : "=r"(v) : "l"(c) : "memory");
              if (++n > (1u << 26)) __trap();
            } while (v < 16);
            __syncwarp();
            asm volatile("fence.proxy.async.global;" ::: "memory");
          }
          load(&tm_o, (dbl ? ks : bk(ks)) * 64, row0 >> 6, O_EF);
        }
      }
      if (lane == 0 && atomicAdd(&g_cnt[64 * 8], 1) == gridDim.x - 1) {
        for (int i = 0; i < 67; i++) g_cnt[i * 8] = 0;
      }
    } else if (warp == 9) {
      if (lane == 0) {
        uint32_t it = 0;
        for (;; it++) {
          const int u = (it >= 3 ? role() : cl) + it * ncl;
          if (u >= NUNITS) break;
          const int row = unit_batch(u) * SQ + rank * 120;
#pragma unroll 1
          for (int s = 0; s < 10; s++) {
            const uint32_t j = s & 3, par = ((s >> 2) + (j < 2 ? it : 0)) & 1;
            mbar_wait(sb + BAR_XEMPTY + 8 * j, par ^ 1);
            const uint32_t fb = sb + BAR_XFULL + 32 * rank + 8 * j;
            mbar_expect(fb, XB);
            mbar_expect_cl(mapa(fb, rank ^ 1), XB);
            tma2d_mc(sb + OFF_Q + x_slot(rank, j), &tm_x, s * 64, row, fb);
          }
        }
        const int id = role();
        const bool dbl = ncl == 66 && id >= 58;
        uint32_t slot = rank, phase = 0;
        for (int t = dbl ? 2 * id - 72 + rank : id; t < (dbl ? NOTILES : nsingle); t += ncl) {
#pragma unroll 1
          for (int ks = dbl ? 0 : rank; ks < 64; ks += dbl ? 1 : 2) {
            mbar_wait(sb + BAR_BEMPTY + 8 * slot, phase);
            const uint32_t fb = sb + BAR_BFULL + 8 * slot;
            mbar_expect(fb, BB);
            mbar_expect_cl(mapa(fb, rank ^ 1), BB);
            tma3d_mc(sb + OFF_Q + slot * BB, &tm_wo, 0, (dbl ? ks : bk(ks)) * 64, (t & 3) * 5, fb);
            if (WO_PF && dbl && ks + WO_PF < 64 && (ks & 3) == ((id >> 1) & 3))
              asm volatile("cp.async.bulk.prefetch.tensor.3d.L2.global [%0, {%1, %2, %3}];" ::"l"(&tm_wo), "r"(0), "r"((ks + WO_PF) * 64), "r"((t & 3) * 5) : "memory");
            slot += 2;
            if (slot >= 6) { slot -= 6; phase ^= 1; }
          }
        }
      }
    } else {
      const int wg = warp - 10;
      {
        mbar_wait(sb + BAR_RFULL, 0);
        const __nv_bfloat16* xs = P.x + (size_t)(unit_batch(cl) * SQ + ((cl & 3) * 2 + rank) * 30 + min(lane, 29)) * DM + 256 + wg * 64;
#pragma unroll
        for (int i = 0; i < 3; i++) asm volatile("prefetch.global.L2 [%0];" ::"l"(xs + i * 128));
        if (lane < 16) asm volatile("prefetch.global.L2 [%0];" ::"l"(P.wq + (size_t)(384 + unit_batch(cl) * 16 + lane) * HD + unit_head(cl, rank) * DH + wg * 64));
      }
      for (uint32_t it = 0;; it++) {
        const int u = __shfl_sync(~0u, (it >= 3 ? role() : cl) + it * ncl, 0);
        if (u >= NUNITS) break;
        mbar_wait(sb + BAR_LSUM + 8 * wg, it & 1);
        float l4[4], v[4];
        const uint32_t a = sb + OFF_L2 + wg * 2048 + lane * 16;
        asm volatile("ld.shared.v4.f32 {%0, %1, %2, %3}, [%4];" : "=f"(l4[0]), "=f"(l4[1]), "=f"(l4[2]), "=f"(l4[3]) : "r"(a) : "memory");
#pragma unroll
        for (int g = 1; g < 4; g++) {
          asm volatile("ld.shared.v4.f32 {%0, %1, %2, %3}, [%4];" : "=f"(v[0]), "=f"(v[1]), "=f"(v[2]), "=f"(v[3]) : "r"(a + g * 512) : "memory");
#pragma unroll
          for (int c = 0; c < 4; c++) l4[c] += v[c];
        }
#pragma unroll
        for (int c = 0; c < 4; c++) {
          float inv;
          asm("rcp.approx.ftz.f32 %0, %1;" : "=f"(inv) : "f"(l4[c]));
          l4[c] = l4[c] >= L_MIN && l4[c] <= L_MAX ? inv : __uint_as_float(0x7FFFFFFFu);
        }
        const uint32_t h0 = pack(l4[0], l4[1]), h1 = pack(l4[2], l4[3]);
        const uint32_t e0 = pack(l4[0] - __uint_as_float(h0 << 16), l4[1] - __uint_as_float(h0 & 0xFFFF0000u));
        const uint32_t e1 = pack(l4[2] - __uint_as_float(h1 << 16), l4[3] - __uint_as_float(h1 & 0xFFFF0000u));
        const uint32_t ia = sb + OFF_INV + wg * 640 + (lane & 1) * 288 + (lane >> 1) * 8;
        asm volatile("st.shared.v2.u32 [%0], {%1, %2};\nst.shared.v2.u32 [%0 + 144], {%3, %4};" ::"r"(ia), "r"(h0), "r"(e0), "r"(h1), "r"(e1) : "memory");
        __syncwarp();
        if (lane == 0) {
          mbar_arrive(sb + BAR_INV + 8 * wg);
          if (it == ROLE_AT) {
          if (wg == 0 && rank == 0 && lane == 0) {
            int id = cl;
            if (ncl == 66) {
              uint32_t smid;
              asm("mov.u32 %0, %smid;" : "=r"(smid));
              id = smid >= SMID_TOP ? 65 - atomicAdd(&g_cnt[65 * 8], 1) : atomicAdd(&g_cnt[66 * 8], 1);
            }
    #pragma unroll
            for (int c = 0; c < 2; c++) {
              const uint32_t a = mapa(sb + BAR_ROLE, c);
              asm volatile("st.shared::cluster.u32 [%0 + 8], %1;\nmbarrier.arrive.release.cluster.shared::cluster.b64 _, [%0];" ::"r"(a), "r"(id) : "memory");
            }
          }
          if (wg == 0 && lane == 0) {
            mbar_wait_cl(sb + BAR_ROLE, 0);
            mbar_arrive(sb + BAR_ROLE + 16);
          }
          }
          mbar_wait(sb + BAR_STAGE + 8 * wg, it & 1);
          __threadfence();
          asm volatile("red.relaxed.gpu.global.add.u32 [%0], 1;" ::"l"(&g_cnt[(unit_batch(u) * 4 + (u >> 6)) * 8]) : "memory");
        }
        __syncwarp();
      }
    }
  } else {
    asm volatile("setmaxnreg.inc.sync.aligned.u32 240;");
    const int wg = warp >> 2, w = warp & 3;
    if (PINLANE) lane = __shfl_sync(~0u, lane, lane);
    const uint32_t qreg = sb + OFF_Q + wg * 2 * XB, preg = sb + OFF_P + (2 + wg) * XB;
    const uint32_t st_off = ((lane >> 4) * 8 + (lane & 7)) * 128 + (((2 * w + ((lane >> 3) & 1)) ^ (lane & 7)) << 4);
    const uint32_t xempty = mapa(sb + BAR_XEMPTY, wg);
    Ring r;
    uint32_t it = 0;
    const uint32_t qd = (qreg & 0x3FFFF) >> 4, pd = (preg & 0x3FFFF) >> 4;
    auto ring_addr = [&]() { return ((sb & 0x3FFFF) + r.slot * RING_BYTES) >> 4; };
    auto ring_wait = [&]() { mbar_wait(sb + BAR_RFULL + 8 * r.slot, r.phase); };
    auto release = [&](uint32_t slot) { if (lane == 0) mbar_arrive(sb + BAR_REMPTY + 8 * slot); };
    auto turn_wait = [&]() {
      if (wg == 0) asm volatile("bar.sync 3, 256;" ::: "memory");
      else asm volatile("bar.sync 4, 256;" ::: "memory");
    };
    auto turn_pass = [&]() {
      if (wg == 0) asm volatile("bar.arrive 4, 256;" ::: "memory");
      else asm volatile("bar.arrive 3, 256;" ::: "memory");
    };

    uint32_t chk = 0;
    auto load_inv = [&](uint32_t (&iv)[30], uint32_t parity) {
      mbar_wait(sb + BAR_INV + 8 * wg, parity);
      chk = 0;
#pragma unroll
      for (int j = 0; j < 7; j++)
        asm volatile("ld.shared.v4.u32 {%0, %1, %2, %3}, [%4];" : "=r"(iv[4 * j]), "=r"(iv[4 * j + 1]), "=r"(iv[4 * j + 2]), "=r"(iv[4 * j + 3])
                     : "r"(sb + OFF_INV + wg * 640 + (lane & 3) * 144 + j * 16) : "memory");
      asm volatile("ld.shared.v2.u32 {%0, %1}, [%2];" : "=r"(iv[28]), "=r"(iv[29]) : "r"(sb + OFF_INV + wg * 640 + (lane & 3) * 144 + 112) : "memory");
    };
    auto norm = [&](uint32_t (&n)[8], const uint32_t (&po)[60], const uint32_t (&iv)[30], auto part) {
      constexpr int k = decltype(part)::value >> 1, j0 = (decltype(part)::value & 1) * 8;
#pragma unroll
      for (int j = 0; j < 8; j++)
        n[j] = j0 + j < 15 ? hfma2(po[15 * k + (j0 + j) % 15], iv[2 * ((j0 + j) % 15)], hfma2(po[15 * k + (j0 + j) % 15], iv[2 * ((j0 + j) % 15) + 1], 0x80008000u)) : 0x3F803F80u;
#pragma unroll
      for (int j = 0; j < 8; j += 2) chk = hfma2(n[j], n[j + 1], chk);
    };
    auto store = [&](const uint32_t (&n)[8], const char* optr, auto part) {
      constexpr int k = decltype(part)::value >> 1;
      const char* o = optr + (size_t)(8 * (k & 1) + 64 * (k >> 1)) * NROWS * 2;
      if ((decltype(part)::value & 1) == 0)
        asm volatile(
            "{\n.reg .pred p;\nsetp.ne.u64 p, %9, 0;\n"
            "@p st.global.v4.u32 [%8], {%0, %1, %2, %3};\n@p st.global.v4.u32 [%8 + 64], {%4, %5, %6, %7};\n}\n"
            ::"r"(n[0]), "r"(n[1]), "r"(n[2]), "r"(n[3]), "r"(n[4]), "r"(n[5]), "r"(n[6]), "r"(n[7]),
            "l"(o + (wg ? 288 : 0) + (lane & 3) * 16), "l"(optr) : "memory");
      else
        asm volatile(
            "{\n.reg .pred p;\nsetp.ne.u64 p, %10, 0;\n"
            "@p st.global.v4.u32 [%7 + 128], {%0, %1, %2, %3};\n@p st.global.v2.u32 [%8], {%4, %5};\n@p st.global.u32 [%9], %6;\n}\n"
            ::"r"(n[0]), "r"(n[1]), "r"(n[2]), "r"(n[3]), "r"(n[4]), "r"(n[5]), "r"(n[6]), "l"(o + (wg ? 288 : 0) + (lane & 3) * 16),
            "l"(o + (wg ? 256 : 192) + (lane & 3) * 8), "l"(o + (wg ? 240 : 224) + (lane & 3) * 4), "l"(optr) : "memory");
    };
    auto put = [&](const uint32_t (&po)[60], const uint32_t (&iv)[30], const char* optr, auto part) {
      uint32_t n[8];
      norm(n, po, iv, part);
      store(n, optr, part);
    };
    auto out_ptr = [&](int u) {
      return reinterpret_cast<const char*>(P.o + (size_t)(unit_head(u, rank) * DH + 16 * w + (lane >> 2)) * NROWS + unit_batch(u) * SQ);
    };
    auto unsafe = [&](bool valid) {
      const bool b = valid && ((chk & 0x7F80u) == 0x7F80u || (chk & 0x7F800000u) == 0x7F800000u);
      return __any_sync(~0u, bar_red_or(wg, b));
    };
    auto publish = [&]() { __syncwarp(); if (lane == 0) mbar_arrive(sb + BAR_STAGE + 8 * wg); };

    uint32_t po[60];
#pragma unroll
    for (int i = 0; i < 60; i++) po[i] = 0;
    int id = 0;
    bool more;
    do {
      float o0[60], o1[60];
      uint32_t prev = 0;
      auto qstep = [&](int s, int acc) {
        const uint32_t j = s & 3, par = ((s >> 2) + (j < 2 ? it : 0)) & 1;
        TR(it * 160 + 3 * s);
        ring_wait();
        TR(it * 160 + 3 * s + 1);
        mbar_wait(sb + BAR_XFULL + 32 * wg + 8 * j, par);
        TR(it * 160 + 3 * s + 2);
        if (s >= ALT_FROM) turn_wait();
        wg_fence();
        mma_tn(o0, o1, ring_addr(), ((sb & 0x3FFFF) + OFF_Q + x_slot(wg, j)) >> 4, acc);
        wg_commit();
        if ((s >= ALT_FROM && !(MERGE89 && s == 8)) || (s == ALT_FROM - 1 && wg == 1)) turn_pass();
        if (s > 0) {
          wg_wait<1>();
          release(prev);
          if (s <= 6 && lane == 0) mbar_arrive_cl(xempty + 8 * ((s - 1) & 3));
        }
        prev = r.slot;
        r.next();
      };
      qstep(0, 0);
      const int up = (it > 3 ? id : cl) + ((int)it - 1) * ncl;
      const char* optr = it > 0 ? out_ptr(up) : nullptr;
      uint32_t n7[8];
      {
        uint32_t iv[30];
        qstep(1, 1); load_inv(iv, (it + 1) & 1); put(po, iv, optr, IC<0>());
        qstep(2, 1); put(po, iv, optr, IC<1>());
        qstep(3, 1); put(po, iv, optr, IC<2>());
        qstep(4, 1); put(po, iv, optr, IC<3>());
        qstep(5, 1); put(po, iv, optr, IC<4>());
        qstep(6, 1); put(po, iv, optr, IC<5>());
        qstep(7, 1); put(po, iv, optr, IC<6>());
        norm(n7, po, iv, IC<7>());
        if (LATE_AT == 3) store(n7, optr, IC<7>());
        qstep(8, 1);
        if (LATE_AT == 2) store(n7, optr, IC<7>());
      }
      TR(it * 160 + 27);
      ring_wait();
      TR(it * 160 + 28);
      mbar_wait(sb + BAR_XFULL + 32 * wg + 8, it & 1);
      TR(it * 160 + 29);
      if (!MERGE89) turn_wait();
      wg_fence();
      mma_tn_split(o0, o1, ring_addr(), qd + (XB >> 4));
      turn_pass();
      wg_wait<2>();
      release(prev);
      auto put_q = [&](const float (&o)[60], uint32_t dst) {
        bar_sync(wg);
#pragma unroll
        for (int j = 0; j < 14; j += 2)
          stsm4t(dst + j * 1024, pack(o[4 * j] * QSCALE, o[4 * j + 1] * QSCALE), pack(o[4 * j + 2] * QSCALE, o[4 * j + 3] * QSCALE),
                 pack(o[4 * j + 4] * QSCALE, o[4 * j + 5] * QSCALE), pack(o[4 * j + 6] * QSCALE, o[4 * j + 7] * QSCALE));
        stsm2t(dst + 14 * 1024, pack(o[56] * QSCALE, o[57] * QSCALE), pack(o[58] * QSCALE, o[59] * QSCALE));
      };
      wg_wait<1>();
      reg_fence(o0);
      put_q(o0, qreg + st_off);
      wg_wait<0>();
      reg_fence(o1);
      release(r.slot);
      r.next();
      TR(it * 160 + 30);
      put_q(o1, qreg + XB + st_off);
      fence_async_smem();
      if (unsafe(it > 0)) {
        slow_path(P, unit_batch(up), unit_head(up, rank), wg, w, lane);
        optr = nullptr;
        if (!DPRO) {
#pragma unroll
          for (int i = 0; i < 60; i++) o0[i] = o1[i] = 0.f;
        }
      }
      TR(it * 160 + 32); TG(it * 160 + 142);

      float sc[60], l[30];
      ring_wait();
      TR(it * 160 + 33);
      turn_wait();
      wg_fence();
      mma_qk(sc, ring_addr(), qd);
      wg_commit();
      turn_pass();
      if (LATE_AT < 2) store(n7, optr, IC<7>());
      if (it > 0) publish();
      if (it >= 2) id = __shfl_sync(~0u, role(), 0);
      wg_wait<0>();
      reg_fence(sc);
      TR(it * 160 + 35);
      release(r.slot);
      r.next();
      exp_store<0, 15, true>(sc, l, preg + st_off);
      fence_async_smem();
      more = id + ((int)it + 1) * ncl < NUNITS;
      const bool gemm = id < nsingle || (ncl == 66 && id >= 58);
#pragma unroll 1
      for (int s = DPRO ? 3 : 1; s < 16; s++) {
        const uint32_t kslot = r.slot;
        TR(it * 160 + 32 + 6 * s); TG(it * 160 + 37 + 6 * s);
        ring_wait();
        TR(it * 160 + 33 + 6 * s);
        turn_wait();
        wg_fence();
        mma_qk(sc, ring_addr(), qd);
        wg_commit();
        r.next();
        const bool pv = !ASYM || wg == 1 || s < 15;
        TR(it * 160 + 36 + 6 * s);
        if (pv) {
          ring_wait();
          TR(it * 160 + 34 + 6 * s);
          wg_fence();
          mma_tn(o0, o1, ring_addr(), pd - ((s - 1) & 1) * (2 * XB >> 4), DPRO || s != 1);
          wg_commit();
          if (ASYM || wg == 0 || s < 15) turn_pass();
          wg_wait<1>();
        } else {
          turn_pass();
          wg_wait<0>();
        }
        reg_fence(sc);
        TR(it * 160 + 35 + 6 * s);
        release(kslot);
        if (s == 15) {
          if (more) { if (lane < 2 - ASYM) mbar_arrive_cl(xempty + 8 * lane); }
          else if (!ASYM && lane < 3 && gemm) mbar_arrive_cl(mapa(sb + BAR_BEMPTY + 8 * lane, lane & 1));
        }
        exp_store<0, VREL>(sc, l, preg - (s & 1) * 2 * XB + st_off);
        wg_wait<0>();
        reg_fence(o0); reg_fence(o1);
        if (pv) { release(r.slot); r.next(); }
        exp_store<VREL, 15>(sc, l, preg - (s & 1) * 2 * XB + st_off);
        fence_async_smem();
      }
      if (!ASYM) bar_sync(wg);
      TR(it * 160 + 128);
      const uint32_t lscr = ASYM ? qreg + XB : preg;
      auto put_l = [&]() {
        const uint32_t a = lscr + (8 * w + (lane >> 2)) * 480 + (lane & 3) * 8;
#pragma unroll
        for (int j = 0; j < 15; j++) asm volatile("st.shared.v2.f32 [%0], {%1, %2};" ::"r"(a + j * 32), "f"(l[2 * j]), "f"(l[2 * j + 1]) : "memory");
      };
      const uint32_t v14 = r.slot;
      if (ASYM && wg == 0) {
        const uint32_t a14 = ring_addr();
        ring_wait();
        r.next();
        ring_wait();
        turn_wait();
        wg_fence();
#pragma unroll
        for (int k = 0; k < 4; k++) wgmma_n120<1, 0>(o0, a14 + k * 128, HI128, pd + k * 2, HI128, 1);
#pragma unroll
        for (int k = 0; k < 4; k++) wgmma_n120<1, 0>(o0, ring_addr() + k * 128, HI128, pd - (2 * XB >> 4) + k * 2, HI128, 1);
        wg_commit();
        put_l();
        wg_fence();
#pragma unroll
        for (int k = 0; k < 4; k++) wgmma_n120<1, 0>(o1, a14 + 512 + k * 128, HI128, pd + k * 2, HI128, 1);
#pragma unroll
        for (int k = 0; k < 4; k++) wgmma_n120<1, 0>(o1, ring_addr() + 512 + k * 128, HI128, pd - (2 * XB >> 4) + k * 2, HI128, 1);
        wg_commit();
        if (ASYM_PASS == 0) turn_pass();
      } else {
        ring_wait();
        if (ASYM) turn_wait();
        wg_fence();
        mma_tn_split(o0, o1, ring_addr(), pd - (2 * XB >> 4));
        put_l();
      }
      TR(it * 160 + 132);
      __syncwarp();
      float lv[8][4];
#pragma unroll
      for (int g = 0; g < 8; g++)
        asm volatile("ld.shared.v4.f32 {%0, %1, %2, %3}, [%4];" : "=f"(lv[g][0]), "=f"(lv[g][1]), "=f"(lv[g][2]), "=f"(lv[g][3])
                     : "r"(lscr + (8 * w + g) * 480 + min(lane, 29) * 16) : "memory");
      if (ASYM && ASYM_PASS == 1 && wg == 0) turn_pass();
      TR(it * 160 + 133);
      wg_wait<1>();
      reg_fence(o0);
      TR(it * 160 + 134);
#pragma unroll
      for (int j = 0; j < 15; j++) { po[j] = pack(o0[4 * j], o0[4 * j + 1]); po[15 + j] = pack(o0[4 * j + 2], o0[4 * j + 3]); }
#pragma unroll
      for (int c = 0; c < 4; c++) lv[0][c] = ((lv[0][c] + lv[1][c]) + (lv[2][c] + lv[3][c])) + ((lv[4][c] + lv[5][c]) + (lv[6][c] + lv[7][c]));
      asm volatile("st.shared.v4.f32 [%0], {%1, %2, %3, %4};" ::"r"(sb + OFF_L2 + wg * 2048 + w * 512 + lane * 16), "f"(lv[0][0]), "f"(lv[0][1]),
                   "f"(lv[0][2]), "f"(lv[0][3]) : "memory");
      __syncwarp();
      if (lane == 0) mbar_arrive(sb + BAR_LSUM + 8 * wg);
      if (ASYM) {
        if (more) { if (lane == 0) mbar_arrive_cl(xempty + 8); }
        else if (lane < 3 && gemm) mbar_arrive_cl(mapa(sb + BAR_BEMPTY + 8 * lane, lane & 1));
      }
      wg_wait<0>();
      reg_fence(o1);
      if (ASYM && wg == 0) release(v14);
      release(r.slot);
      r.next();
      if (more) { if (lane < 2) mbar_arrive_cl(xempty + 16 + 8 * lane); }
      else if (gemm && lane < 3) mbar_arrive_cl(mapa(sb + BAR_BEMPTY + 24 + 8 * lane, (lane + 1) & 1));
      TR(it * 160 + 130);
#pragma unroll
      for (int j = 0; j < 15; j++) { po[30 + j] = pack(o1[4 * j], o1[4 * j + 1]); po[45 + j] = pack(o1[4 * j + 2], o1[4 * j + 3]); }
      TR(it * 160 + 131); TG(it * 160 + 143);
      it++;
    } while (more);
    const bool gemm = id < nsingle || (ncl == 66 && id >= 58);
    const int u = (it > 3 ? id : cl) + ((int)it - 1) * ncl;
    lane = __shfl_sync(~0u, lane, lane);
    uint32_t pb[60];
#pragma unroll
    for (int i = 0; i < 60; i++) pb[i] = po[i] ^ (gridDim.y - 1);

    uint32_t bslot = 0, bphase = 0;
    auto out_tile = [&](const float (&acc)[80], int t) {
      const uint32_t st = sb + w * RING_BYTES + wg * 8192;
      const uint32_t sa = st + (lane & 15) * 336 + (lane >> 4) * 16;
#pragma unroll
      for (int j = 0; j < 20; j += 2)
        asm volatile("stmatrix.sync.aligned.m8n8.x4.shared.b16 [%0], {%1,%2,%3,%4};" ::"r"(sa + j * 16), "r"(pack(acc[4 * j], acc[4 * j + 1])),
                     "r"(pack(acc[4 * j + 2], acc[4 * j + 3])), "r"(pack(acc[4 * j + 4], acc[4 * j + 5])), "r"(pack(acc[4 * j + 6], acc[4 * j + 7])) : "memory");
      fence_async_smem();
      __syncwarp();
      if (lane < 16) {
        __nv_bfloat16* dst = P.out + (size_t)o_row((t >> 2) * 256 + rank * 128 + wg * 64 + w * 16 + lane) * DM + (t & 3) * 160;
        asm volatile("cp.async.bulk.global.shared::cta.bulk_group [%0], [%1], 320;" ::"l"(dst), "r"(st + lane * 336) : "memory");
        asm volatile("cp.async.bulk.commit_group;" ::: "memory");
        asm volatile("cp.async.bulk.wait_group.read 0;" ::: "memory");
      }
      __syncwarp();
    };
    for (int t = id; t < nsingle || t == id; t += ncl) {
      float acc[80];
      uint32_t prev = 0, bprev = 0;
      const bool tile = t < nsingle;
      const bool last = t + ncl >= nsingle;
      auto bstep = [&](int ks, int accf) {
        if (!(ks & 3)) TR(640 + ks / 2); if ((ks & 7) == 0) TG(144 + (ks >> 3));
        ring_wait();
        mbar_wait(sb + BAR_BFULL + 8 * bslot, bphase);
        if (!(ks & 3)) TR(641 + ks / 2);
        wg_fence();
        const uint32_t a = ring_addr() + wg * 512, bd = (((sb & 0x3FFFF) + OFF_Q + bslot * BB) >> 4) | ((4096u >> 4) << 16);
#pragma unroll
        for (int k = 0; k < 4; k++) wgmma_n160<1, 1>(acc, a + k * 128, HI128, bd + k * 64, HI64, k == 0 ? accf : 1);
        wg_commit();
        if (ks > 0) {
          wg_wait<1>();
          release(prev);
          if (lane == 0 && (ks < 59 || !last)) mbar_arrive_cl(mapa(sb + BAR_BEMPTY + 8 * bprev, bprev & 1));
        }
        prev = r.slot; bprev = bslot;
        r.next();
        if (++bslot == 6) { bslot = 0; bphase ^= 1; }
      };
      const char* optr = t == id ? out_ptr(u) : nullptr;
      uint32_t iv[30];
      if (tile) {
        bstep(0, 0);
        bstep(1, 1);
        load_inv(iv, (it + 1) & 1);
#pragma unroll 1
        for (int ks = 2; ks < 17; ks++) {
          bstep(ks, 1);
          switch (ks) {
            case 2: put(pb, iv, optr, IC<0>()); break;
            case 4: put(pb, iv, optr, IC<1>()); break;
            case 6: put(pb, iv, optr, IC<2>()); break;
            case 8: put(pb, iv, optr, IC<3>()); break;
            case 10: put(pb, iv, optr, IC<4>()); break;
            case 12: put(pb, iv, optr, IC<5>()); break;
            case 14: put(pb, iv, optr, IC<6>()); break;
            case 16: put(pb, iv, optr, IC<7>()); break;
            default: break;
          }
        }
        wg_wait<0>();
        reg_fence(acc);
      } else {
#pragma unroll
        for (int i = 0; i < 80; i++) acc[i] = 0.f;
        load_inv(iv, (it + 1) & 1);
        put(pb, iv, optr, IC<0>()); put(pb, iv, optr, IC<1>()); put(pb, iv, optr, IC<2>()); put(pb, iv, optr, IC<3>());
        put(pb, iv, optr, IC<4>()); put(pb, iv, optr, IC<5>()); put(pb, iv, optr, IC<6>()); put(pb, iv, optr, IC<7>());
      }
      if (unsafe(t == id)) slow_path(P, unit_batch(u), unit_head(u, rank), wg, w, lane);
      if (t == id) publish();
      if (!tile) break;
#pragma unroll 1
      for (int ks = 17; ks < 64; ks++) {
        if (END_SKEW && wg == 1 && ks == 64 - END_SKEW) turn_wait();
        bstep(ks, 1);
      }
      if (END_SKEW && wg == 0) turn_pass();
      wg_wait<0>();
      reg_fence(acc);
      release(prev);
      if (lane == 0 && !last) mbar_arrive_cl(mapa(sb + BAR_BEMPTY + 8 * bprev, bprev & 1));
      TR(158); TG(156);
      const int pos0 = (t >> 2) * 256 + rank * 128 + wg * 64 + w * 16;
      if (last) {
        bar_sync(wg);
        out_tile(acc, t);
      } else {
        __nv_bfloat16* op0 = P.out + (size_t)o_row(pos0 + (lane >> 2)) * DM + (t & 3) * 160 + (lane & 3) * 2;
        __nv_bfloat16* op1 = P.out + (size_t)o_row(pos0 + (lane >> 2) + 8) * DM + (t & 3) * 160 + (lane & 3) * 2;
#pragma unroll
        for (int j = 0; j < 20; j++) {
          *reinterpret_cast<uint32_t*>(op0 + j * 8) = pack(acc[4 * j], acc[4 * j + 1]);
          *reinterpret_cast<uint32_t*>(op1 + j * 8) = pack(acc[4 * j + 2], acc[4 * j + 3]);
        }
      }
#pragma unroll
      for (int i = 0; i < 60; i++) pb[i] = 0;
    }
    if (gemm && id >= nsingle) {
      float ac0[80], ac1[80];
      uint32_t prev = 0, bprev = 0;
      auto half = [&](float (&acc)[80], int hs, int accf) {
        mbar_wait(sb + BAR_BFULL + 8 * bslot, bphase);
        wg_fence();
        const uint32_t a = ring_addr() + wg * 512, bd = (((sb & 0x3FFFF) + OFF_Q + bslot * BB) >> 4) | ((4096u >> 4) << 16);
#pragma unroll
        for (int k = 0; k < 4; k++) wgmma_n160<1, 1>(acc, a + k * 128, HI128, bd + k * 64, HI64, k == 0 ? accf : 1);
        wg_commit();
        if (hs > 0) {
          wg_wait<1>();
          if (lane == 0 && hs < 123) mbar_arrive_cl(mapa(sb + BAR_BEMPTY + 8 * bprev, bprev & 1));
        }
        bprev = bslot;
        if (++bslot == 6) { bslot = 0; bphase ^= 1; }
      };
      auto dstep = [&](int ks, int accf) {
        if (!(ks & 3)) TR(640 + ks / 2); if ((ks & 7) == 0) TG(144 + (ks >> 3));
        ring_wait();
        if (!(ks & 3)) TR(641 + ks / 2);
        half(ac0, 2 * ks, accf);
        if (ks > 0) release(prev);
        half(ac1, 2 * ks + 1, accf);
        prev = r.slot;
        r.next();
      };
      dstep(0, 0);
#pragma unroll 1
      for (int ks = 1; ks < 64; ks++) {
        if (wg == 1 && ks == 62) turn_wait();
        dstep(ks, 1);
      }
      if (wg == 0) turn_pass();
      wg_wait<0>();
      reg_fence(ac0); reg_fence(ac1);
      TR(158); TG(156);
      bar_sync(wg);
      out_tile(ac0, 2 * id - 72);
      out_tile(ac1, 2 * id - 71);
    }
    TR(159);
  }
}

typedef CUresult (*EncodeFn)(CUtensorMap*, CUtensorMapDataType, cuuint32_t, void*, const cuuint64_t*, const cuuint64_t*,
                             const cuuint32_t*, const cuuint32_t*, CUtensorMapInterleave, CUtensorMapSwizzle,
                             CUtensorMapL2promotion, CUtensorMapFloatOOBfill);

void make_map(EncodeFn enc, CUtensorMap* m, const void* p, int rank, const cuuint64_t* dims, const cuuint64_t* strides,
              const cuuint32_t* box, CUtensorMapSwizzle sw, CUtensorMapL2promotion promo) {
  cuuint32_t es[3] = {1, 1, 1};
  enc(m, CU_TENSOR_MAP_DATA_TYPE_BFLOAT16, rank, const_cast<void*>(p), dims, strides, box, es, CU_TENSOR_MAP_INTERLEAVE_NONE, sw,
      promo, CU_TENSOR_MAP_FLOAT_OOB_FILL_NONE);
}

}

extern "C" void kernel_launch(void* const* d_in, const int* in_sizes, int n_in, void* d_out, int out_size) {
  static EncodeFn enc = nullptr;
  static int nclusters = 0;
  static void* o_ptr = nullptr;
  if (!enc) {
    cudaDriverEntryPointQueryResult qr;
    cudaGetDriverEntryPoint("cuTensorMapEncodeTiled", (void**)&enc, cudaEnableDefault, &qr);
    cudaFuncSetAttribute(fused_attn_kernel, cudaFuncAttributeMaxDynamicSharedMemorySize, SMEM_BYTES);
    cudaGetSymbolAddress(&o_ptr, g_o);
    cudaLaunchConfig_t cfg = {};
    cfg.gridDim = 128; cfg.blockDim = 384; cfg.dynamicSmemBytes = SMEM_BYTES;
    cudaLaunchAttribute at; at.id = cudaLaunchAttributeClusterDimension;
    at.val.clusterDim.x = 2; at.val.clusterDim.y = 1; at.val.clusterDim.z = 1;
    cfg.attrs = &at; cfg.numAttrs = 1;
    int n = 0;
    cudaOccupancyMaxActiveClusters(&n, fused_attn_kernel, &cfg);
    nclusters = n >= 66 ? MAXCL : (n >= 64 || n <= 0 ? 64 : n);
  }
  const __nv_bfloat16* x = (const __nv_bfloat16*)d_in[0];
  const __nv_bfloat16* k = (const __nv_bfloat16*)d_in[1];
  const __nv_bfloat16* v = (const __nv_bfloat16*)d_in[2];
  const __nv_bfloat16* wq = (const __nv_bfloat16*)d_in[3];
  const __nv_bfloat16* wo = (const __nv_bfloat16*)d_in[4];
  CUtensorMap tm_x, tm_wq, tm_k, tm_v, tm_o, tm_wo;
  const auto S128 = CU_TENSOR_MAP_SWIZZLE_128B;
  const auto P128 = CU_TENSOR_MAP_L2_PROMOTION_L2_128B, P256 = CU_TENSOR_MAP_L2_PROMOTION_L2_256B;
  { cuuint64_t d[2] = {DM, NB * SQ}, s[1] = {DM * 2}; cuuint32_t b[2] = {64, 120}; make_map(enc, &tm_x, x, 2, d, s, b, S128, P128); }
  { cuuint64_t d[3] = {64, DM, HD / 64}, s[2] = {HD * 2, 128}; cuuint32_t b[3] = {64, 64, 2}; make_map(enc, &tm_wq, wq, 3, d, s, b, S128, P256); }
  { cuuint64_t d[3] = {64, NB * NH * SK, 2}, s[2] = {DH * 2, 128}; cuuint32_t b[3] = {64, 64, 2};
    make_map(enc, &tm_k, k, 3, d, s, b, S128, P128); make_map(enc, &tm_v, v, 3, d, s, b, S128, P128); }
  { cuuint64_t d[3] = {64, HD, NROWS / 64}, s[2] = {NROWS * 2, 128}; cuuint32_t b[3] = {64, 64, 2}; make_map(enc, &tm_o, o_ptr, 3, d, s, b, S128, P256); }
  { cuuint64_t d[3] = {32, HD, DM / 32}, s[2] = {DM * 2, 64}; cuuint32_t b[3] = {32, 64, 5};
    make_map(enc, &tm_wo, wo, 3, d, s, b, CU_TENSOR_MAP_SWIZZLE_64B, P128); }
  Params P{x, k, v, wq, (__nv_bfloat16*)d_out, (__nv_bfloat16*)o_ptr};
  fused_attn_kernel<<<2 * nclusters, 384, SMEM_BYTES>>>(tm_x, tm_wq, tm_k, tm_v, tm_o, tm_wo, P);
}
```

```cpp
#include <cuda_runtime.h>
#include <cuda.h>
#include <cuda_bf16.h>
#include <stdint.h>

namespace {

constexpr int NB = 16, SQ = 240, DM = 640, NH = 32, SK = 1024, DH = 128, HD = NH * DH;
constexpr int NROWS = NB * SQ;
constexpr int NUNITS = 256;
#define DPRO 0
#define LATE_AT 0
#define ALT_FROM 3
#define MERGE89 1
#define END_SKEW 5
#define VREL 8
#define PF_HOLD 6
#define PF_N 4
#define PF_J0 3
#define PF_STEP 3
#define ROT 0
#define O_EF 1
#define B_ORDER 1
#define WO_PF 6
#define ROLE_AT 0
#define PAUSE_NS 9000
#define PAUSE_AT 2
#define ASYM 0
#define ASYM_PASS 1
#define PINLANE 0
#define MAXCL 66
#define SMID_TOP 88
constexpr int NOTILES = 60;
constexpr float QSCALE = 0.08838834764831845f * 1.4426950408889634f;
constexpr float L_MIN = 9.5367431640625e-07f;
constexpr float L_MAX = 1.152921504606846976e18f;

constexpr uint32_t RING_SLOTS = 6, RING_BYTES = 16384;
constexpr uint32_t XB = 15360;
constexpr uint32_t BB = 20480;
constexpr uint32_t OFF_Q = RING_SLOTS * RING_BYTES;
constexpr uint32_t OFF_P = OFF_Q + 4 * XB;
constexpr uint32_t OFF_INV = OFF_P + 4 * XB;
constexpr uint32_t OFF_L2 = OFF_INV + 1280;
constexpr uint32_t OFF_BAR = OFF_L2 + 4096;
constexpr uint32_t BAR_RFULL = OFF_BAR, BAR_REMPTY = BAR_RFULL + 48, BAR_XFULL = BAR_REMPTY + 48,
    BAR_XEMPTY = BAR_XFULL + 64, BAR_BFULL = BAR_XEMPTY + 32, BAR_BEMPTY = BAR_BFULL + 48, BAR_STAGE = BAR_BEMPTY + 48;
constexpr uint32_t BAR_ROLE = BAR_STAGE + 16, BAR_LSUM = BAR_ROLE + 24, BAR_INV = BAR_LSUM + 16;
constexpr uint32_t OFF_TR = BAR_INV + 16;
constexpr uint32_t SMEM_BYTES = OFF_TR + 1024;

constexpr uint32_t HI128 = (1u << 30) | (1024 >> 4);
constexpr uint32_t HI64 = (2u << 30) | (512 >> 4);

__device__ __nv_bfloat16 g_o[HD * NROWS];
__device__ unsigned g_cnt[67 * 8];
#define TR(i)
#define TG(i)

struct Params {
  const __nv_bfloat16 *x, *k, *v, *wq;
  __nv_bfloat16 *out, *o;
};

__device__ __forceinline__ void wg_fence() { asm volatile("wgmma.fence.sync.aligned;" ::: "memory"); }
__device__ __forceinline__ void wg_commit() { asm volatile("wgmma.commit_group.sync.aligned;" ::: "memory"); }
template <int N> __device__ __forceinline__ void wg_wait() { asm volatile("wgmma.wait_group.sync.aligned %0;" ::"n"(N) : "memory"); }
template <int N> __device__ __forceinline__ void reg_fence(float (&r)[N]) {
#pragma unroll
  for (int i = 0; i < N; i++) asm volatile("" : "+f"(r[i])::"memory");
}
template <int TA, int TB>
__device__ __forceinline__ void wgmma_n120(float (&d)[60], uint32_t a_lo, uint32_t a_hi, uint32_t b_lo, uint32_t b_hi, int acc) {
  asm volatile(
      "{\n.reg .pred p;\n.reg .b64 da, db;\nsetp.ne.b32 p, %64, 0;\n"
      "mov.b64 da, {%60, %61};\nmov.b64 db, {%62, %63};\n"
      "wgmma.mma_async.sync.aligned.m64n120k16.f32.bf16.bf16 {"
      "%0, %1, %2, %3, %4, %5, %6, %7, %8, %9, %10, %11, %12, %13, %14, %15, %16, %17, %18, %19, %20, %21, %22, %23, "
      "%24, %25, %26, %27, %28, %29, %30, %31, %32, %33, %34, %35, %36, %37, %38, %39, %40, %41, %42, %43, %44, %45, "
      "%46, %47, %48, %49, %50, %51, %52, %53, %54, %55, %56, %57, %58, %59"
      "}, da, db, p, 1, 1, %65, %66;\n}\n"
      : "+f"(d[0]), "+f"(d[1]), "+f"(d[2]), "+f"(d[3]), "+f"(d[4]), "+f"(d[5]), "+f"(d[6]), "+f"(d[7]), "+f"(d[8]),
        "+f"(d[9]), "+f"(d[10]), "+f"(d[11]), "+f"(d[12]), "+f"(d[13]), "+f"(d[14]), "+f"(d[15]), "+f"(d[16]),
        "+f"(d[17]), "+f"(d[18]), "+f"(d[19]), "+f"(d[20]), "+f"(d[21]), "+f"(d[22]), "+f"(d[23]), "+f"(d[24]),
        "+f"(d[25]), "+f"(d[26]), "+f"(d[27]), "+f"(d[28]), "+f"(d[29]), "+f"(d[30]), "+f"(d[31]), "+f"(d[32]),
        "+f"(d[33]), "+f"(d[34]), "+f"(d[35]), "+f"(d[36]), "+f"(d[37]), "+f"(d[38]), "+f"(d[39]), "+f"(d[40]),
        "+f"(d[41]), "+f"(d[42]), "+f"(d[43]), "+f"(d[44]), "+f"(d[45]), "+f"(d[46]), "+f"(d[47]), "+f"(d[48]),
        "+f"(d[49]), "+f"(d[50]), "+f"(d[51]), "+f"(d[52]), "+f"(d[53]), "+f"(d[54]), "+f"(d[55]), "+f"(d[56]),
        "+f"(d[57]), "+f"(d[58]), "+f"(d[59])
      : "r"(a_lo), "r"(a_hi), "r"(b_lo), "r"(b_hi), "r"(acc), "n"(TA), "n"(TB));
}

template <int TA, int TB>
__device__ __forceinline__ void wgmma_n160(float (&d)[80], uint32_t a_lo, uint32_t a_hi, uint32_t b_lo, uint32_t b_hi, int acc) {
  asm volatile(
      "{\n.reg .pred p;\n.reg .b64 da, db;\nsetp.ne.b32 p, %84, 0;\n"
      "mov.b64 da, {%80, %81};\nmov.b64 db, {%82, %83};\n"
      "wgmma.mma_async.sync.aligned.m64n160k16.f32.bf16.bf16 {"
      "%0, %1, %2, %3, %4, %5, %6, %7, %8, %9, %10, %11, %12, %13, %14, %15, %16, %17, %18, %19, %20, %21, %22, %23, "
      "%24, %25, %26, %27, %28, %29, %30, %31, %32, %33, %34, %35, %36, %37, %38, %39, %40, %41, %42, %43, %44, %45, "
      "%46, %47, %48, %49, %50, %51, %52, %53, %54, %55, %56, %57, %58, %59, %60, %61, %62, %63, %64, %65, %66, %67, "
      "%68, %69, %70, %71, %72, %73, %74, %75, %76, %77, %78, %79"
      "}, da, db, p, 1, 1, %85, %86;\n}\n"
      : "+f"(d[0]), "+f"(d[1]), "+f"(d[2]), "+f"(d[3]), "+f"(d[4]), "+f"(d[5]), "+f"(d[6]), "+f"(d[7]), "+f"(d[8]),
        "+f"(d[9]), "+f"(d[10]), "+f"(d[11]), "+f"(d[12]), "+f"(d[13]), "+f"(d[14]), "+f"(d[15]), "+f"(d[16]),
        "+f"(d[17]), "+f"(d[18]), "+f"(d[19]), "+f"(d[20]), "+f"(d[21]), "+f"(d[22]), "+f"(d[23]), "+f"(d[24]),
        "+f"(d[25]), "+f"(d[26]), "+f"(d[27]), "+f"(d[28]), "+f"(d[29]), "+f"(d[30]), "+f"(d[31]), "+f"(d[32]),
        "+f"(d[33]), "+f"(d[34]), "+f"(d[35]), "+f"(d[36]), "+f"(d[37]), "+f"(d[38]), "+f"(d[39]), "+f"(d[40]),
        "+f"(d[41]), "+f"(d[42]), "+f"(d[43]), "+f"(d[44]), "+f"(d[45]), "+f"(d[46]), "+f"(d[47]), "+f"(d[48]),
        "+f"(d[49]), "+f"(d[50]), "+f"(d[51]), "+f"(d[52]), "+f"(d[53]), "+f"(d[54]), "+f"(d[55]), "+f"(d[56]),
        "+f"(d[57]), "+f"(d[58]), "+f"(d[59]), "+f"(d[60]), "+f"(d[61]), "+f"(d[62]), "+f"(d[63]), "+f"(d[64]),
        "+f"(d[65]), "+f"(d[66]), "+f"(d[67]), "+f"(d[68]), "+f"(d[69]), "+f"(d[70]), "+f"(d[71]), "+f"(d[72]),
        "+f"(d[73]), "+f"(d[74]), "+f"(d[75]), "+f"(d[76]), "+f"(d[77]), "+f"(d[78]), "+f"(d[79])
      : "r"(a_lo), "r"(a_hi), "r"(b_lo), "r"(b_hi), "r"(acc), "n"(TA), "n"(TB));
}
__device__ __forceinline__ void mbar_init(uint32_t bar, int cnt) { asm volatile("mbarrier.init.shared::cta.b64 [%0], %1;" ::"r"(bar), "r"(cnt)); }
__device__ __forceinline__ void mbar_expect(uint32_t bar, uint32_t bytes) {
  asm volatile("mbarrier.arrive.expect_tx.shared::cta.b64 _, [%0], %1;" ::"r"(bar), "r"(bytes) : "memory");
}
__device__ __forceinline__ uint32_t mapa(uint32_t addr, uint32_t cta) {
  uint32_t r; asm("mapa.shared::cluster.u32 %0, %1, %2;" : "=r"(r) : "r"(addr), "r"(cta)); return r;
}
__device__ __forceinline__ void mbar_expect_cl(uint32_t cbar, uint32_t bytes) {
  asm volatile("mbarrier.arrive.expect_tx.shared::cluster.b64 _, [%0], %1;" ::"r"(cbar), "r"(bytes) : "memory");
}
__device__ __forceinline__ void mbar_arrive(uint32_t bar) { asm volatile("mbarrier.arrive.shared::cta.b64 _, [%0];" ::"r"(bar) : "memory"); }
__device__ __forceinline__ void mbar_arrive_cl(uint32_t cbar) { asm volatile("mbarrier.arrive.shared::cluster.b64 _, [%0];" ::"r"(cbar) : "memory"); }
__device__ __forceinline__ void mbar_wait(uint32_t bar, uint32_t parity) {
  asm volatile(
      "{\n.reg .pred p;\n.reg .u32 n;\n"
      "mbarrier.try_wait.parity.shared::cta.b64 p, [%0], %1;\n@p bra WAIT_DONE;\n"
      "mov.u32 n, 0;\n"
      "WAIT_LOOP:\n"
      "mbarrier.try_wait.parity.shared::cta.b64 p, [%0], %1;\n@p bra WAIT_DONE;\n"
      "add.u32 n, n, 1;\nsetp.lt.u32 p, n, 0x4000000;\n@p bra WAIT_LOOP;\ntrap;\n"
      "WAIT_DONE:\n}\n" ::"r"(bar), "r"(parity) : "memory");
}
__device__ __forceinline__ void mbar_wait_cl(uint32_t bar, uint32_t parity) {
  asm volatile(
      "{\n.reg .pred p;\n.reg .u32 n;\nmov.u32 n, 0;\n"
      "WAIT_LOOP:\n"
      "mbarrier.try_wait.parity.acquire.cluster.shared::cta.b64 p, [%0], %1;\n@p bra WAIT_DONE;\n"
      "add.u32 n, n, 1;\nsetp.lt.u32 p, n, 0x4000000;\n@p bra WAIT_LOOP;\ntrap;\n"
      "WAIT_DONE:\n}\n" ::"r"(bar), "r"(parity) : "memory");
}
__device__ __forceinline__ void tma3d(uint32_t dst, const CUtensorMap* m, int c0, int c1, int c2, uint32_t bar) {
  asm volatile("cp.async.bulk.tensor.3d.shared::cluster.global.mbarrier::complete_tx::bytes [%0], [%1, {%3, %4, %5}], [%2];"
               ::"r"(dst), "l"(m), "r"(bar), "r"(c0), "r"(c1), "r"(c2) : "memory");
}
__device__ __forceinline__ void tma3d_hint(uint32_t dst, const CUtensorMap* m, int c0, int c1, int c2, uint32_t bar, uint64_t pol) {
  asm volatile("cp.async.bulk.tensor.3d.shared::cluster.global.mbarrier::complete_tx::bytes.L2::cache_hint [%0], [%1, {%3, %4, %5}], [%2], %6;"
               ::"r"(dst), "l"(m), "r"(bar), "r"(c0), "r"(c1), "r"(c2), "l"(pol) : "memory");
}
__device__ __forceinline__ void tma2d_mc(uint32_t dst, const CUtensorMap* m, int c0, int c1, uint32_t bar) {
  asm volatile("cp.async.bulk.tensor.2d.shared::cluster.global.mbarrier::complete_tx::bytes.multicast::cluster [%0], [%1, {%3, %4}], [%2], %5;"
               ::"r"(dst), "l"(m), "r"(bar), "r"(c0), "r"(c1), "h"((uint16_t)3) : "memory");
}
__device__ __forceinline__ void tma3d_mc(uint32_t dst, const CUtensorMap* m, int c0, int c1, int c2, uint32_t bar) {
  asm volatile("cp.async.bulk.tensor.3d.shared::cluster.global.mbarrier::complete_tx::bytes.multicast::cluster [%0], [%1, {%3, %4, %5}], [%2], %6;"
               ::"r"(dst), "l"(m), "r"(bar), "r"(c0), "r"(c1), "r"(c2), "h"((uint16_t)3) : "memory");
}
__device__ __forceinline__ void l2_prefetch(const void* p, uint32_t bytes) {
  asm volatile("cp.async.bulk.prefetch.L2.global [%0], %1;" ::"l"(p), "r"(bytes) : "memory");
}
__device__ __forceinline__ void fence_async_smem() { asm volatile("fence.proxy.async.shared::cta;" ::: "memory"); }
__device__ __forceinline__ void bar_sync(int wg) {
  if (wg == 0) asm volatile("bar.sync 1, 128;" ::: "memory");
  else asm volatile("bar.sync 2, 128;" ::: "memory");
}
__device__ __forceinline__ bool bar_red_or(int id, bool v) {
  uint32_t r;
  asm volatile("{\n.reg .pred p, q;\nsetp.ne.u32 p, %2, 0;\nbar.red.or.pred q, %1, 128, p;\nselp.u32 %0, 1, 0, q;\n}\n"
               : "=r"(r) : "r"(1 + id), "r"((uint32_t)v) : "memory");
  return r != 0;
}
__device__ __forceinline__ uint32_t hfma2(uint32_t a, uint32_t b, uint32_t c) { uint32_t r; asm("fma.rn.bf16x2 %0, %1, %2, %3;" : "=r"(r) : "r"(a), "r"(b), "r"(c)); return r; }
__device__ __forceinline__ float ex2(float x) { float y; asm("ex2.approx.ftz.f32 %0, %1;" : "=f"(y) : "f"(x)); return y; }
__device__ __forceinline__ uint32_t pack(float lo, float hi) { uint32_t r; asm("cvt.rn.bf16x2.f32 %0, %1, %2;" : "=r"(r) : "f"(hi), "f"(lo)); return r; }
__device__ __forceinline__ void stsm4t(uint32_t a, uint32_t r0, uint32_t r1, uint32_t r2, uint32_t r3) {
  asm volatile("stmatrix.sync.aligned.m8n8.x4.trans.shared.b16 [%0], {%1,%2,%3,%4};" ::"r"(a), "r"(r0), "r"(r1), "r"(r2), "r"(r3) : "memory");
}
__device__ __forceinline__ void stsm2t(uint32_t a, uint32_t r0, uint32_t r1) {
  asm volatile("stmatrix.sync.aligned.m8n8.x2.trans.shared.b16 [%0], {%1,%2};" ::"r"(a), "r"(r0), "r"(r1) : "memory");
}
__device__ __forceinline__ void mma16816(float (&d)[4], const uint32_t (&a)[4], uint32_t b0, uint32_t b1) {
  asm volatile("mma.sync.aligned.m16n8k16.row.col.f32.bf16.bf16.f32 {%0,%1,%2,%3}, {%4,%5,%6,%7}, {%8,%9}, {%0,%1,%2,%3};"
               : "+f"(d[0]), "+f"(d[1]), "+f"(d[2]), "+f"(d[3]) : "r"(a[0]), "r"(a[1]), "r"(a[2]), "r"(a[3]), "r"(b0), "r"(b1));
}

template <int V> struct IC { static constexpr int value = V; };

struct Ring {
  uint32_t slot = 0, phase = 0;
  __device__ __forceinline__ void next() { if (++slot == RING_SLOTS) { slot = 0; phase ^= 1; } }
};

__device__ __forceinline__ void mma_tn(float (&o0)[60], float (&o1)[60], uint32_t a, uint32_t b, int acc) {
#pragma unroll
  for (int k = 0; k < 4; k++) {
    wgmma_n120<1, 0>(o0, a + k * 128, HI128, b + k * 2, HI128, k == 0 ? acc : 1);
    wgmma_n120<1, 0>(o1, a + 512 + k * 128, HI128, b + k * 2, HI128, k == 0 ? acc : 1);
  }
}
__device__ __forceinline__ void mma_tn_split(float (&o0)[60], float (&o1)[60], uint32_t a, uint32_t b) {
#pragma unroll
  for (int k = 0; k < 4; k++) wgmma_n120<1, 0>(o0, a + k * 128, HI128, b + k * 2, HI128, 1);
  wg_commit();
#pragma unroll
  for (int k = 0; k < 4; k++) wgmma_n120<1, 0>(o1, a + 512 + k * 128, HI128, b + k * 2, HI128, 1);
  wg_commit();
}
__device__ __forceinline__ void mma_qk(float (&s)[60], uint32_t a, uint32_t q) {
#pragma unroll
  for (int k = 0; k < 8; k++)
    wgmma_n120<0, 0>(s, a + (k >> 2) * 512 + (k & 3) * 2, HI128, q + (k >> 2) * (XB >> 4) + (k & 3) * 2, HI128, k != 0);
}
template <int J0, int J1, bool FIRST = false>
__device__ __forceinline__ void exp_store(const float (&s)[60], float (&l)[30], uint32_t dst) {
#pragma unroll
  for (int j = J0; j < J1; j += 2) {
    uint32_t p[4];
#pragma unroll
    for (int jj = 0; jj < 2; jj++) {
      if (j + jj < 15) {
        const int c = j + jj;
        float e0 = ex2(s[4 * c]), e1 = ex2(s[4 * c + 1]), e2 = ex2(s[4 * c + 2]), e3 = ex2(s[4 * c + 3]);
        if (FIRST) { l[2 * c] = e0 + e2; l[2 * c + 1] = e1 + e3; }
        else { l[2 * c] += e0; l[2 * c + 1] += e1; l[2 * c] += e2; l[2 * c + 1] += e3; }
        p[2 * jj] = pack(e0, e1); p[2 * jj + 1] = pack(e2, e3);
      }
    }
    if (j + 1 < 15) stsm4t(dst + j * 1024, p[0], p[1], p[2], p[3]);
    else stsm2t(dst + j * 1024, p[0], p[1]);
  }
}

__device__ __forceinline__ int o_pos(int wg, int r) {
  const int j = r >> 3, q = (r >> 1) & 3, c = r & 1;
  if (j < 12) return (wg ? 144 : 0) + (j >> 2) * 32 + q * 8 + (j & 3) * 2 + c;
  if (j < 14) return (wg ? 128 : 96) + q * 4 + (j - 12) * 2 + c;
  return (wg ? 120 : 112) + q * 2 + c;
}
__device__ __forceinline__ int o_row(int p) {
  const int b = p / SQ, r = p - b * SQ, wg = r >= 120, c = r & 1;
  const int a = r - (wg ? 144 : 0), m = r - (wg ? 128 : 96), e = r - (wg ? 120 : 112);
  int row;
  if (a >= 0 && a < 96) row = ((a >> 5) * 4 + ((a >> 1) & 3)) * 8 + ((a >> 3) & 3) * 2 + c;
  else if (m >= 0 && m < 16) row = (12 + ((m >> 1) & 1)) * 8 + (m >> 2) * 2 + c;
  else row = 112 + e;
  return b * SQ + wg * 120 + row;
}

__device__ __forceinline__ void slow_path(const Params& P, int b, int h, int wg, int w, int lane) {
  const int g = lane >> 2, q = lane & 3, row0 = wg * 120;
  const uint16_t* wq = reinterpret_cast<const uint16_t*>(P.wq) + h * DH + g;
  const __nv_bfloat16* kp = P.k + (size_t)(b * NH + h) * SK * DH;
  const uint16_t* vp = reinterpret_cast<const uint16_t*>(P.v) + (size_t)(b * NH + h) * SK * DH + g;
#pragma unroll 1
  for (int t = w; t < 8; t += 4) {
    const int r0 = 16 * t + g, r1 = r0 + 8;
    const __nv_bfloat16* x0 = P.x + (size_t)(b * SQ + row0 + r0) * DM + 2 * q;
    const __nv_bfloat16* x1 = P.x + (size_t)(b * SQ + row0 + min(r1, 119)) * DM + 2 * q;
    float o[16][4];
#pragma unroll
    for (int n = 0; n < 16; n++) o[n][0] = o[n][1] = o[n][2] = o[n][3] = 0.f;
#pragma unroll 1
    for (int k0 = 0; k0 < DM; k0 += 16) {
      uint32_t a[4] = {*(const uint32_t*)(x0 + k0), *(const uint32_t*)(x1 + k0), *(const uint32_t*)(x0 + k0 + 8), *(const uint32_t*)(x1 + k0 + 8)};
      const uint16_t* wr = wq + (size_t)(k0 + 2 * q) * HD;
#pragma unroll
      for (int n = 0; n < 16; n++)
        mma16816(o[n], a, wr[8 * n] | ((uint32_t)wr[8 * n + HD] << 16), wr[8 * n + 8 * HD] | ((uint32_t)wr[8 * n + 9 * HD] << 16));
    }
    uint32_t qa[8][4];
#pragma unroll
    for (int k = 0; k < 8; k++) {
      qa[k][0] = pack(o[2 * k][0] * QSCALE, o[2 * k][1] * QSCALE);
      qa[k][1] = pack(o[2 * k][2] * QSCALE, o[2 * k][3] * QSCALE);
      qa[k][2] = pack(o[2 * k + 1][0] * QSCALE, o[2 * k + 1][1] * QSCALE);
      qa[k][3] = pack(o[2 * k + 1][2] * QSCALE, o[2 * k + 1][3] * QSCALE);
    }
#pragma unroll
    for (int n = 0; n < 16; n++) o[n][0] = o[n][1] = o[n][2] = o[n][3] = 0.f;
    float m0 = -INFINITY, m1 = -INFINITY, l0 = 0.f, l1 = 0.f;
#pragma unroll 1
    for (int key0 = 0; key0 < SK; key0 += 16) {
      float s[2][4];
#pragma unroll
      for (int nt = 0; nt < 2; nt++) {
        s[nt][0] = s[nt][1] = s[nt][2] = s[nt][3] = 0.f;
        const __nv_bfloat16* kr = kp + (size_t)(key0 + 8 * nt + g) * DH + 2 * q;
#pragma unroll
        for (int k = 0; k < 8; k++) mma16816(s[nt], qa[k], *(const uint32_t*)(kr + 16 * k), *(const uint32_t*)(kr + 16 * k + 8));
      }
      float n0 = fmaxf(fmaxf(s[0][0], s[0][1]), fmaxf(s[1][0], s[1][1])), n1 = fmaxf(fmaxf(s[0][2], s[0][3]), fmaxf(s[1][2], s[1][3]));
      n0 = fmaxf(n0, __shfl_xor_sync(~0u, n0, 1)); n1 = fmaxf(n1, __shfl_xor_sync(~0u, n1, 1));
      n0 = fmaxf(n0, __shfl_xor_sync(~0u, n0, 2)); n1 = fmaxf(n1, __shfl_xor_sync(~0u, n1, 2));
      n0 = fmaxf(n0, m0); n1 = fmaxf(n1, m1);
      const float z0 = n0 == -INFINITY ? 0.f : n0, z1 = n1 == -INFINITY ? 0.f : n1;
      const float c0 = ex2(m0 - z0), c1 = ex2(m1 - z1);
      m0 = n0; m1 = n1;
#pragma unroll
      for (int nt = 0; nt < 2; nt++) {
        s[nt][0] = ex2(s[nt][0] - z0); s[nt][1] = ex2(s[nt][1] - z0);
        s[nt][2] = ex2(s[nt][2] - z1); s[nt][3] = ex2(s[nt][3] - z1);
      }
      l0 = l0 * c0 + s[0][0] + s[0][1] + s[1][0] + s[1][1];
      l1 = l1 * c1 + s[0][2] + s[0][3] + s[1][2] + s[1][3];
      uint32_t pa[4] = {pack(s[0][0], s[0][1]), pack(s[0][2], s[0][3]), pack(s[1][0], s[1][1]), pack(s[1][2], s[1][3])};
      const uint16_t* vr = vp + (size_t)(key0 + 2 * q) * DH;
#pragma unroll
      for (int n = 0; n < 16; n++) {
        o[n][0] *= c0; o[n][1] *= c0; o[n][2] *= c1; o[n][3] *= c1;
        mma16816(o[n], pa, vr[8 * n] | ((uint32_t)vr[8 * n + DH] << 16), vr[8 * n + 8 * DH] | ((uint32_t)vr[8 * n + 9 * DH] << 16));
      }
    }
    l0 += __shfl_xor_sync(~0u, l0, 1); l1 += __shfl_xor_sync(~0u, l1, 1);
    l0 += __shfl_xor_sync(~0u, l0, 2); l1 += __shfl_xor_sync(~0u, l1, 2);
    const float i0 = 1.f / l0, i1 = 1.f / l1;
    __nv_bfloat16* oc = P.o + (size_t)(h * DH + 2 * q) * NROWS + b * SQ;
    const int p0 = o_pos(wg, r0), p1 = o_pos(wg, min(r1, 119));
#pragma unroll
    for (int n = 0; n < 16; n++) {
      oc[(size_t)(8 * n) * NROWS + p0] = __float2bfloat16(o[n][0] * i0);
      oc[(size_t)(8 * n + 1) * NROWS + p0] = __float2bfloat16(o[n][1] * i0);
      if (r1 < 120) {
        oc[(size_t)(8 * n) * NROWS + p1] = __float2bfloat16(o[n][2] * i1);
        oc[(size_t)(8 * n + 1) * NROWS + p1] = __float2bfloat16(o[n][3] * i1);
      }
    }
  }
}

__device__ __forceinline__ int bk(int ks) { return B_ORDER && ks < 48 ? 32 - (ks & 48) + (ks & 15) : ks; }
__device__ __forceinline__ uint32_t x_slot(uint32_t wg, uint32_t j) { return j < 2 ? (2 * wg + j) * XB : (2 * j + wg) * XB; }
__device__ __forceinline__ int unit_batch(int u) { return (u & 63) >> 2; }
__device__ __forceinline__ int unit_head(int u, int rank) { return (u >> 6) * 8 + (u & 3) * 2 + rank; }

__global__ void __cluster_dims__(2, 1, 1) __launch_bounds__(384, 1)
fused_attn_kernel(const __grid_constant__ CUtensorMap tm_x, const __grid_constant__ CUtensorMap tm_wq,
                  const __grid_constant__ CUtensorMap tm_k, const __grid_constant__ CUtensorMap tm_v,
                  const __grid_constant__ CUtensorMap tm_o, const __grid_constant__ CUtensorMap tm_wo,
                  const __grid_constant__ Params P) {
  extern __shared__ uint8_t smem_raw[];
  const uint32_t sb = ((uint32_t)__cvta_generic_to_shared(smem_raw) + 1023) & ~1023u;
  const int warp = __shfl_sync(~0u, threadIdx.x >> 5, 0);
  int lane = threadIdx.x & 31;
  const int rank = blockIdx.x & 1, cl = blockIdx.x >> 1, ncl = gridDim.x >> 1;

  const int nsingle = ncl == 66 ? 44 : NOTILES;
  auto role = [&]() {
    mbar_wait(sb + BAR_ROLE + 16, 0);
    int id;
    asm volatile("ld.shared.u32 %0, [%1];" : "=r"(id) : "r"(sb + BAR_ROLE + 8) : "memory");
    return id;
  };

  if (threadIdx.x == 0) {
    for (int i = 0; i < 6; i++) {
      mbar_init(sb + BAR_RFULL + 8 * i, 1); mbar_init(sb + BAR_REMPTY + 8 * i, 8);
      mbar_init(sb + BAR_BFULL + 8 * i, 1); mbar_init(sb + BAR_BEMPTY + 8 * i, 16);
    }
    for (int i = 0; i < 8; i++) mbar_init(sb + BAR_XFULL + 8 * i, 1);
    for (int i = 0; i < 4; i++) mbar_init(sb + BAR_XEMPTY + 8 * i, 8);
    for (int i = 0; i < 2; i++) { mbar_init(sb + BAR_STAGE + 8 * i, 4); mbar_init(sb + BAR_LSUM + 8 * i, 4); mbar_init(sb + BAR_INV + 8 * i, 1); }
    mbar_init(sb + BAR_ROLE, 1); mbar_init(sb + BAR_ROLE + 16, 1);
    asm volatile("fence.mbarrier_init.release.cluster;" ::: "memory");
  }
  __syncwarp();
  asm volatile("barrier.cluster.arrive.relaxed.aligned;\nbarrier.cluster.wait.aligned;" ::: "memory");

  if (warp >= 8) {
    asm volatile("setmaxnreg.dec.sync.aligned.u32 24;");
    if (warp == 8) {
      uint64_t pol;
      asm volatile("createpolicy.fractional.L2::evict_first.b64 %0, 1.0;" : "=l"(pol));
      Ring r;
      auto load = [&](const CUtensorMap* m, int c1, int c2, bool ef) {
        mbar_wait(sb + BAR_REMPTY + 8 * r.slot, r.phase ^ 1);
        if (lane == 0) {
          mbar_expect(sb + BAR_RFULL + 8 * r.slot, RING_BYTES);
          if (ef) tma3d_hint(sb + r.slot * RING_BYTES, m, 0, c1, c2, sb + BAR_RFULL + 8 * r.slot, pol);
          else tma3d(sb + r.slot * RING_BYTES, m, 0, c1, c2, sb + BAR_RFULL + 8 * r.slot);
        }
        r.next();
      };
      const int rot = ROT * (blockIdx.x * 5 + (blockIdx.x >> 4));
      for (int u0 = 0;; u0 += ncl) {
        const int u = __shfl_sync(~0u, (u0 >= 3 * ncl ? role() : cl) + u0, 0);
        if (u >= NUNITS) break;
        if (PAUSE_NS && ncl == 66 && u0 == PAUSE_AT * 66) {
          const int id = role();
          if (id >= 44 && id < 58) {
            unsigned t0, t1;
            asm volatile("mov.u32 %0, %globaltimer_lo;" : "=r"(t0));
            do { __nanosleep(200); asm volatile("mov.u32 %0, %globaltimer_lo;" : "=r"(t1)); } while (t1 - t0 < PAUSE_NS);
          }
        }
        const int h = unit_head(u, rank);
        const int krow = (unit_batch(u) * NH + h) * SK;
#pragma unroll 1
        for (int s = 0; s < 10; s++) {
          load(&tm_wq, s * 64, 2 * h, false);
          const int sp = u0 == 0 ? s - PF_HOLD : s;
          if (sp >= 0 && sp < PF_N && lane == 0) l2_prefetch(P.v + (size_t)(krow + ((PF_J0 + sp * PF_STEP + rot) & 15) * 64) * DH, 16384);
        }
#pragma unroll 1
        for (int j = 0; j <= 16; j++) {
          if (j < 16) load(&tm_k, krow + ((j + rot) & 15) * 64, 0, true);
          if (j == 1 + DPRO) load(&tm_v, krow + (rot & 15) * 64, 0, true);
          if (j > 1) load(&tm_v, krow + ((j - 1 + rot) & 15) * 64, 0, true);
        }
      }
      const int id = __shfl_sync(~0u, role(), 0);
      const bool dbl = ncl == 66 && id >= 58;
      for (int t = dbl ? 2 * id - 72 : id; t < (dbl ? NOTILES : nsingle); t += ncl) {
        const int row0 = (t >> 2) * 256 + rank * 128;
        const int b0 = row0 / SQ, b1 = (row0 + 127) / SQ;
#pragma unroll 1
        for (int ks = 0; ks < 64; ks++) {
          if (dbl ? (ks & 15) == 0 : ks == 0 || ks == 48) {
            const unsigned* c = &g_cnt[((lane & 1 ? b1 : b0) * 4 + (ks || dbl ? ks >> 4 : min(lane >> 1, 2))) * 8];
            unsigned v, n = 0;
            do {
              asm volatile("ld.acquire.gpu.global.u32 %0, [%1];" : "=r"(v) : "l"(c) : "memory");
              if (++n > (1u << 26)) __trap();
            } while (v < 16);
            __syncwarp();
            asm volatile("fence.proxy.async.global;" ::: "memory");
          }
          load(&tm_o, (dbl ? ks : bk(ks)) * 64, row0 >> 6, O_EF);
        }
      }
      if (lane == 0 && atomicAdd(&g_cnt[64 * 8], 1) == gridDim.x - 1) {
        for (int i = 0; i < 67; i++) g_cnt[i * 8] = 0;
      }
    } else if (warp == 9) {
      if (lane == 0) {
        uint32_t it = 0;
        for (;; it++) {
          const int u = (it >= 3 ? role() : cl) + it * ncl;
          if (u >= NUNITS) break;
          const int row = unit_batch(u) * SQ + rank * 120;
#pragma unroll 1
          for (int s = 0; s < 10; s++) {
            const uint32_t j = s & 3, par = ((s >> 2) + (j < 2 ? it : 0)) & 1;
            mbar_wait(sb + BAR_XEMPTY + 8 * j, par ^ 1);
            const uint32_t fb = sb + BAR_XFULL + 32 * rank + 8 * j;
            mbar_expect(fb, XB);
            mbar_expect_cl(mapa(fb, rank ^ 1), XB);
            tma2d_mc(sb + OFF_Q + x_slot(rank, j), &tm_x, s * 64, row, fb);
          }
        }
        const int id = role();
        const bool dbl = ncl == 66 && id >= 58;
        uint32_t slot = rank, phase = 0;
        for (int t = dbl ? 2 * id - 72 + rank : id; t < (dbl ? NOTILES : nsingle); t += ncl) {
#pragma unroll 1
          for (int ks = dbl ? 0 : rank; ks < 64; ks += dbl ? 1 : 2) {
            mbar_wait(sb + BAR_BEMPTY + 8 * slot, phase);
            const uint32_t fb = sb + BAR_BFULL + 8 * slot;
            mbar_expect(fb, BB);
            mbar_expect_cl(mapa(fb, rank ^ 1), BB);
            tma3d_mc(sb + OFF_Q + slot * BB, &tm_wo, 0, (dbl ? ks : bk(ks)) * 64, (t & 3) * 5, fb);
            if (WO_PF && dbl && ks + WO_PF < 64 && (ks & 3) == ((id >> 1) & 3))
              asm volatile("cp.async.bulk.prefetch.tensor.3d.L2.global [%0, {%1, %2, %3}];" ::"l"(&tm_wo), "r"(0), "r"((ks + WO_PF) * 64), "r"((t & 3) * 5) : "memory");
            slot += 2;
            if (slot >= 6) { slot -= 6; phase ^= 1; }
          }
        }
      }
    } else {
      const int wg = warp - 10;
      {
        mbar_wait(sb + BAR_RFULL, 0);
        const __nv_bfloat16* xs = P.x + (size_t)(unit_batch(cl) * SQ + ((cl & 3) * 2 + rank) * 30 + min(lane, 29)) * DM + 256 + wg * 64;
#pragma unroll
        for (int i = 0; i < 3; i++) asm volatile("prefetch.global.L2 [%0];" ::"l"(xs + i * 128));
        if (lane < 16) asm volatile("prefetch.global.L2 [%0];" ::"l"(P.wq + (size_t)(384 + unit_batch(cl) * 16 + lane) * HD + unit_head(cl, rank) * DH + wg * 64));
      }
      auto take_role = [&]() {
          if (wg == 0 && rank == 0 && lane == 0) {
            int id = cl;
            if (ncl == 66) {
              uint32_t smid;
              asm("mov.u32 %0, %smid;" : "=r"(smid));
              id = smid >= SMID_TOP ? 65 - atomicAdd(&g_cnt[65 * 8], 1) : atomicAdd(&g_cnt[66 * 8], 1);
            }
    #pragma unroll
            for (int c = 0; c < 2; c++) {
              const uint32_t a = mapa(sb + BAR_ROLE, c);
              asm volatile("st.shared::cluster.u32 [%0 + 8], %1;\nmbarrier.arrive.release.cluster.shared::cluster.b64 _, [%0];" ::"r"(a), "r"(id) : "memory");
            }
          }
          if (wg == 0 && lane == 0) {
            mbar_wait_cl(sb + BAR_ROLE, 0);
            mbar_arrive(sb + BAR_ROLE + 16);
          }
      };
      if (ROLE_AT < 0) { take_role(); __syncwarp(); }
      for (uint32_t it = 0;; it++) {
        const int u = __shfl_sync(~0u, (it >= 3 ? role() : cl) + it * ncl, 0);
        if (u >= NUNITS) break;
        mbar_wait(sb + BAR_LSUM + 8 * wg, it & 1);
        float l4[4], v[4];
        const uint32_t a = sb + OFF_L2 + wg * 2048 + lane * 16;
        asm volatile("ld.shared.v4.f32 {%0, %1, %2, %3}, [%4];" : "=f"(l4[0]), "=f"(l4[1]), "=f"(l4[2]), "=f"(l4[3]) : "r"(a) : "memory");
#pragma unroll
        for (int g = 1; g < 4; g++) {
          asm volatile("ld.shared.v4.f32 {%0, %1, %2, %3}, [%4];" : "=f"(v[0]), "=f"(v[1]), "=f"(v[2]), "=f"(v[3]) : "r"(a + g * 512) : "memory");
#pragma unroll
          for (int c = 0; c < 4; c++) l4[c] += v[c];
        }
#pragma unroll
        for (int c = 0; c < 4; c++) {
          float inv;
          asm("rcp.approx.ftz.f32 %0, %1;" : "=f"(inv) : "f"(l4[c]));
          l4[c] = l4[c] >= L_MIN && l4[c] <= L_MAX ? inv : __uint_as_float(0x7FFFFFFFu);
        }
        const uint32_t h0 = pack(l4[0], l4[1]), h1 = pack(l4[2], l4[3]);
        const uint32_t e0 = pack(l4[0] - __uint_as_float(h0 << 16), l4[1] - __uint_as_float(h0 & 0xFFFF0000u));
        const uint32_t e1 = pack(l4[2] - __uint_as_float(h1 << 16), l4[3] - __uint_as_float(h1 & 0xFFFF0000u));
        const uint32_t ia = sb + OFF_INV + wg * 640 + (lane & 1) * 288 + (lane >> 1) * 8;
        asm volatile("st.shared.v2.u32 [%0], {%1, %2};\nst.shared.v2.u32 [%0 + 144], {%3, %4};" ::"r"(ia), "r"(h0), "r"(e0), "r"(h1), "r"(e1) : "memory");
        __syncwarp();
        if (lane == 0) {
          mbar_arrive(sb + BAR_INV + 8 * wg);
          if ((int)it == ROLE_AT) {
            take_role();
          }
          mbar_wait(sb + BAR_STAGE + 8 * wg, it & 1);
          __threadfence();
          asm volatile("red.relaxed.gpu.global.add.u32 [%0], 1;" ::"l"(&g_cnt[(unit_batch(u) * 4 + (u >> 6)) * 8]) : "memory");
        }
        __syncwarp();
      }
    }
  } else {
    asm volatile("setmaxnreg.inc.sync.aligned.u32 240;");
    const int wg = warp >> 2, w = warp & 3;
    if (PINLANE) lane = __shfl_sync(~0u, lane, lane);
    const uint32_t qreg = sb + OFF_Q + wg * 2 * XB, preg = sb + OFF_P + (2 + wg) * XB;
    const uint32_t st_off = ((lane >> 4) * 8 + (lane & 7)) * 128 + (((2 * w + ((lane >> 3) & 1)) ^ (lane & 7)) << 4);
    const uint32_t xempty = mapa(sb + BAR_XEMPTY, wg);
    Ring r;
    uint32_t it = 0;
    const uint32_t qd = (qreg & 0x3FFFF) >> 4, pd = (preg & 0x3FFFF) >> 4;
    auto ring_addr = [&]() { return ((sb & 0x3FFFF) + r.slot * RING_BYTES) >> 4; };
    auto ring_wait = [&]() { mbar_wait(sb + BAR_RFULL + 8 * r.slot, r.phase); };
    auto release = [&](uint32_t slot) { if (lane == 0) mbar_arrive(sb + BAR_REMPTY + 8 * slot); };
    auto turn_wait = [&]() {
      if (wg == 0) asm volatile("bar.sync 3, 256;" ::: "memory");
      else asm volatile("bar.sync 4, 256;" ::: "memory");
    };
    auto turn_pass = [&]() {
      if (wg == 0) asm volatile("bar.arrive 4, 256;" ::: "memory");
      else asm volatile("bar.arrive 3, 256;" ::: "memory");
    };

    uint32_t chk = 0;
    auto load_inv = [&](uint32_t (&iv)[30], uint32_t parity) {
      mbar_wait(sb + BAR_INV + 8 * wg, parity);
      chk = 0;
#pragma unroll
      for (int j = 0; j < 7; j++)
        asm volatile("ld.shared.v4.u32 {%0, %1, %2, %3}, [%4];" : "=r"(iv[4 * j]), "=r"(iv[4 * j + 1]), "=r"(iv[4 * j + 2]), "=r"(iv[4 * j + 3])
                     : "r"(sb + OFF_INV + wg * 640 + (lane & 3) * 144 + j * 16) : "memory");
      asm volatile("ld.shared.v2.u32 {%0, %1}, [%2];" : "=r"(iv[28]), "=r"(iv[29]) : "r"(sb + OFF_INV + wg * 640 + (lane & 3) * 144 + 112) : "memory");
    };
    auto norm = [&](uint32_t (&n)[8], const uint32_t (&po)[60], const uint32_t (&iv)[30], auto part) {
      constexpr int k = decltype(part)::value >> 1, j0 = (decltype(part)::value & 1) * 8;
#pragma unroll
      for (int j = 0; j < 8; j++)
        n[j] = j0 + j < 15 ? hfma2(po[15 * k + (j0 + j) % 15], iv[2 * ((j0 + j) % 15)], hfma2(po[15 * k + (j0 + j) % 15], iv[2 * ((j0 + j) % 15) + 1], 0x80008000u)) : 0x3F803F80u;
#pragma unroll
      for (int j = 0; j < 8; j += 2) chk = hfma2(n[j], n[j + 1], chk);
    };
    auto store = [&](const uint32_t (&n)[8], const char* optr, auto part) {
      constexpr int k = decltype(part)::value >> 1;
      const char* o = optr + (size_t)(8 * (k & 1) + 64 * (k >> 1)) * NROWS * 2;
      if ((decltype(part)::value & 1) == 0)
        asm volatile(
            "{\n.reg .pred p;\nsetp.ne.u64 p, %9, 0;\n"
            "@p st.global.v4.u32 [%8], {%0, %1, %2, %3};\n@p st.global.v4.u32 [%8 + 64], {%4, %5, %6, %7};\n}\n"
            ::"r"(n[0]), "r"(n[1]), "r"(n[2]), "r"(n[3]), "r"(n[4]), "r"(n[5]), "r"(n[6]), "r"(n[7]),
            "l"(o + (wg ? 288 : 0) + (lane & 3) * 16), "l"(optr) : "memory");
      else
        asm volatile(
            "{\n.reg .pred p;\nsetp.ne.u64 p, %10, 0;\n"
            "@p st.global.v4.u32 [%7 + 128], {%0, %1, %2, %3};\n@p st.global.v2.u32 [%8], {%4, %5};\n@p st.global.u32 [%9], %6;\n}\n"
            ::"r"(n[0]), "r"(n[1]), "r"(n[2]), "r"(n[3]), "r"(n[4]), "r"(n[5]), "r"(n[6]), "l"(o + (wg ? 288 : 0) + (lane & 3) * 16),
            "l"(o + (wg ? 256 : 192) + (lane & 3) * 8), "l"(o + (wg ? 240 : 224) + (lane & 3) * 4), "l"(optr) : "memory");
    };
    auto put = [&](const uint32_t (&po)[60], const uint32_t (&iv)[30], const char* optr, auto part) {
      uint32_t n[8];
      norm(n, po, iv, part);
      store(n, optr, part);
    };
    auto out_ptr = [&](int u) {
      return reinterpret_cast<const char*>(P.o + (size_t)(unit_head(u, rank) * DH + 16 * w + (lane >> 2)) * NROWS + unit_batch(u) * SQ);
    };
    auto unsafe = [&](bool valid) {
      const bool b = valid && ((chk & 0x7F80u) == 0x7F80u || (chk & 0x7F800000u) == 0x7F800000u);
      return __any_sync(~0u, bar_red_or(wg, b));
    };
    auto publish = [&]() { __syncwarp(); if (lane == 0) mbar_arrive(sb + BAR_STAGE + 8 * wg); };

    uint32_t po[60];
#pragma unroll
    for (int i = 0; i < 60; i++) po[i] = 0;
    int id = 0;
    bool more;
    do {
      float o0[60], o1[60];
      uint32_t prev = 0;
      auto qstep = [&](int s, int acc) {
        const uint32_t j = s & 3, par = ((s >> 2) + (j < 2 ? it : 0)) & 1;
        TR(it * 160 + 3 * s);
        ring_wait();
        TR(it * 160 + 3 * s + 1);
        mbar_wait(sb + BAR_XFULL + 32 * wg + 8 * j, par);
        TR(it * 160 + 3 * s + 2);
        if (s >= ALT_FROM) turn_wait();
        wg_fence();
        mma_tn(o0, o1, ring_addr(), ((sb & 0x3FFFF) + OFF_Q + x_slot(wg, j)) >> 4, acc);
        wg_commit();
        if ((s >= ALT_FROM && !(MERGE89 && s == 8)) || (s == ALT_FROM - 1 && wg == 1)) turn_pass();
        if (s > 0) {
          wg_wait<1>();
          release(prev);
          if (s <= 6 && lane == 0) mbar_arrive_cl(xempty + 8 * ((s - 1) & 3));
        }
        prev = r.slot;
        r.next();
      };
      qstep(0, 0);
      const int up = (it > 3 ? id : cl) + ((int)it - 1) * ncl;
      const char* optr = it > 0 ? out_ptr(up) : nullptr;
      uint32_t n7[8];
      {
        uint32_t iv[30];
        qstep(1, 1); load_inv(iv, (it + 1) & 1); put(po, iv, optr, IC<0>());
        qstep(2, 1); put(po, iv, optr, IC<1>());
        qstep(3, 1); put(po, iv, optr, IC<2>());
        qstep(4, 1); put(po, iv, optr, IC<3>());
        qstep(5, 1); put(po, iv, optr, IC<4>());
        qstep(6, 1); put(po, iv, optr, IC<5>());
        qstep(7, 1); put(po, iv, optr, IC<6>());
        norm(n7, po, iv, IC<7>());
        if (LATE_AT == 3) store(n7, optr, IC<7>());
        qstep(8, 1);
        if (LATE_AT == 2) store(n7, optr, IC<7>());
      }
      TR(it * 160 + 27);
      ring_wait();
      TR(it * 160 + 28);
      mbar_wait(sb + BAR_XFULL + 32 * wg + 8, it & 1);
      TR(it * 160 + 29);
      if (!MERGE89) turn_wait();
      wg_fence();
      mma_tn_split(o0, o1, ring_addr(), qd + (XB >> 4));
      turn_pass();
      wg_wait<2>();
      release(prev);
      auto put_q = [&](const float (&o)[60], uint32_t dst) {
        bar_sync(wg);
#pragma unroll
        for (int j = 0; j < 14; j += 2)
          stsm4t(dst + j * 1024, pack(o[4 * j] * QSCALE, o[4 * j + 1] * QSCALE), pack(o[4 * j + 2] * QSCALE, o[4 * j + 3] * QSCALE),
                 pack(o[4 * j + 4] * QSCALE, o[4 * j + 5] * QSCALE), pack(o[4 * j + 6] * QSCALE, o[4 * j + 7] * QSCALE));
        stsm2t(dst + 14 * 1024, pack(o[56] * QSCALE, o[57] * QSCALE), pack(o[58] * QSCALE, o[59] * QSCALE));
      };
      wg_wait<1>();
      reg_fence(o0);
      put_q(o0, qreg + st_off);
      wg_wait<0>();
      reg_fence(o1);
      release(r.slot);
      r.next();
      TR(it * 160 + 30);
      put_q(o1, qreg + XB + st_off);
      fence_async_smem();
      if (unsafe(it > 0)) {
        slow_path(P, unit_batch(up), unit_head(up, rank), wg, w, lane);
        optr = nullptr;
        if (!DPRO) {
#pragma unroll
          for (int i = 0; i < 60; i++) o0[i] = o1[i] = 0.f;
        }
      }
      TR(it * 160 + 32); TG(it * 160 + 142);

      float sc[60], l[30];
      ring_wait();
      TR(it * 160 + 33);
      turn_wait();
      wg_fence();
      mma_qk(sc, ring_addr(), qd);
      wg_commit();
      turn_pass();
      if (LATE_AT < 2) store(n7, optr, IC<7>());
      if (it > 0) publish();
      if (it >= 2) id = __shfl_sync(~0u, role(), 0);
      wg_wait<0>();
      reg_fence(sc);
      TR(it * 160 + 35);
      release(r.slot);
      r.next();
      exp_store<0, 15, true>(sc, l, preg + st_off);
      fence_async_smem();
      more = id + ((int)it + 1) * ncl < NUNITS;
      const bool gemm = id < nsingle || (ncl == 66 && id >= 58);
#pragma unroll 1
      for (int s = DPRO ? 3 : 1; s < 16; s++) {
        const uint32_t kslot = r.slot;
        TR(it * 160 + 32 + 6 * s); TG(it * 160 + 37 + 6 * s);
        ring_wait();
        TR(it * 160 + 33 + 6 * s);
        turn_wait();
        wg_fence();
        mma_qk(sc, ring_addr(), qd);
        wg_commit();
        r.next();
        const bool pv = !ASYM || wg == 1 || s < 15;
        TR(it * 160 + 36 + 6 * s);
        if (pv) {
          ring_wait();
          TR(it * 160 + 34 + 6 * s);
          wg_fence();
          mma_tn(o0, o1, ring_addr(), pd - ((s - 1) & 1) * (2 * XB >> 4), DPRO || s != 1);
          wg_commit();
          if (ASYM || wg == 0 || s < 15) turn_pass();
          wg_wait<1>();
        } else {
          turn_pass();
          wg_wait<0>();
        }
        reg_fence(sc);
        TR(it * 160 + 35 + 6 * s);
        release(kslot);
        if (s == 15) {
          if (more) { if (lane < 2 - ASYM) mbar_arrive_cl(xempty + 8 * lane); }
          else if (!ASYM && lane < 3 && gemm) mbar_arrive_cl(mapa(sb + BAR_BEMPTY + 8 * lane, lane & 1));
        }
        exp_store<0, VREL>(sc, l, preg - (s & 1) * 2 * XB + st_off);
        wg_wait<0>();
        reg_fence(o0); reg_fence(o1);
        if (pv) { release(r.slot); r.next(); }
        exp_store<VREL, 15>(sc, l, preg - (s & 1) * 2 * XB + st_off);
        fence_async_smem();
      }
      if (!ASYM) bar_sync(wg);
      TR(it * 160 + 128);
      const uint32_t lscr = ASYM ? qreg + XB : preg;
      auto put_l = [&]() {
        const uint32_t a = lscr + (8 * w + (lane >> 2)) * 480 + (lane & 3) * 8;
#pragma unroll
        for (int j = 0; j < 15; j++) asm volatile("st.shared.v2.f32 [%0], {%1, %2};" ::"r"(a + j * 32), "f"(l[2 * j]), "f"(l[2 * j + 1]) : "memory");
      };
      const uint32_t v14 = r.slot;
      if (ASYM && wg == 0) {
        const uint32_t a14 = ring_addr();
        ring_wait();
        r.next();
        ring_wait();
        turn_wait();
        wg_fence();
#pragma unroll
        for (int k = 0; k < 4; k++) wgmma_n120<1, 0>(o0, a14 + k * 128, HI128, pd + k * 2, HI128, 1);
#pragma unroll
        for (int k = 0; k < 4; k++) wgmma_n120<1, 0>(o0, ring_addr() + k * 128, HI128, pd - (2 * XB >> 4) + k * 2, HI128, 1);
        wg_commit();
        put_l();
        wg_fence();
#pragma unroll
        for (int k = 0; k < 4; k++) wgmma_n120<1, 0>(o1, a14 + 512 + k * 128, HI128, pd + k * 2, HI128, 1);
#pragma unroll
        for (int k = 0; k < 4; k++) wgmma_n120<1, 0>(o1, ring_addr() + 512 + k * 128, HI128, pd - (2 * XB >> 4) + k * 2, HI128, 1);
        wg_commit();
        if (ASYM_PASS == 0) turn_pass();
      } else {
        ring_wait();
        if (ASYM) turn_wait();
        wg_fence();
        mma_tn_split(o0, o1, ring_addr(), pd - (2 * XB >> 4));
        put_l();
      }
      TR(it * 160 + 132);
      __syncwarp();
      float lv[8][4];
#pragma unroll
      for (int g = 0; g < 8; g++)
        asm volatile("ld.shared.v4.f32 {%0, %1, %2, %3}, [%4];" : "=f"(lv[g][0]), "=f"(lv[g][1]), "=f"(lv[g][2]), "=f"(lv[g][3])
                     : "r"(lscr + (8 * w + g) * 480 + min(lane, 29) * 16) : "memory");
      if (ASYM && ASYM_PASS == 1 && wg == 0) turn_pass();
      TR(it * 160 + 133);
      wg_wait<1>();
      reg_fence(o0);
      TR(it * 160 + 134);
#pragma unroll
      for (int j = 0; j < 15; j++) { po[j] = pack(o0[4 * j], o0[4 * j + 1]); po[15 + j] = pack(o0[4 * j + 2], o0[4 * j + 3]); }
#pragma unroll
      for (int c = 0; c < 4; c++) lv[0][c] = ((lv[0][c] + lv[1][c]) + (lv[2][c] + lv[3][c])) + ((lv[4][c] + lv[5][c]) + (lv[6][c] + lv[7][c]));
      asm volatile("st.shared.v4.f32 [%0], {%1, %2, %3, %4};" ::"r"(sb + OFF_L2 + wg * 2048 + w * 512 + lane * 16), "f"(lv[0][0]), "f"(lv[0][1]),
                   "f"(lv[0][2]), "f"(lv[0][3]) : "memory");
      __syncwarp();
      if (lane == 0) mbar_arrive(sb + BAR_LSUM + 8 * wg);
      if (ASYM) {
        if (more) { if (lane == 0) mbar_arrive_cl(xempty + 8); }
        else if (lane < 3 && gemm) mbar_arrive_cl(mapa(sb + BAR_BEMPTY + 8 * lane, lane & 1));
      }
      wg_wait<0>();
      reg_fence(o1);
      if (ASYM && wg == 0) release(v14);
      release(r.slot);
      r.next();
      if (more) { if (lane < 2) mbar_arrive_cl(xempty + 16 + 8 * lane); }
      else if (gemm && lane < 3) mbar_arrive_cl(mapa(sb + BAR_BEMPTY + 24 + 8 * lane, (lane + 1) & 1));
      TR(it * 160 + 130);
#pragma unroll
      for (int j = 0; j < 15; j++) { po[30 + j] = pack(o1[4 * j], o1[4 * j + 1]); po[45 + j] = pack(o1[4 * j + 2], o1[4 * j + 3]); }
      TR(it * 160 + 131); TG(it * 160 + 143);
      it++;
    } while (more);
    const bool gemm = id < nsingle || (ncl == 66 && id >= 58);
    const int u = (it > 3 ? id : cl) + ((int)it - 1) * ncl;
    lane = __shfl_sync(~0u, lane, lane);
    uint32_t pb[60];
#pragma unroll
    for (int i = 0; i < 60; i++) pb[i] = po[i] ^ (gridDim.y - 1);

    uint32_t bslot = 0, bphase = 0;
    auto out_tile = [&](const float (&acc)[80], int t) {
      const uint32_t st = sb + w * RING_BYTES + wg * 8192;
      const uint32_t sa = st + (lane & 15) * 336 + (lane >> 4) * 16;
#pragma unroll
      for (int j = 0; j < 20; j += 2)
        asm volatile("stmatrix.sync.aligned.m8n8.x4.shared.b16 [%0], {%1,%2,%3,%4};" ::"r"(sa + j * 16), "r"(pack(acc[4 * j], acc[4 * j + 1])),
                     "r"(pack(acc[4 * j + 2], acc[4 * j + 3])), "r"(pack(acc[4 * j + 4], acc[4 * j + 5])), "r"(pack(acc[4 * j + 6], acc[4 * j + 7])) : "memory");
      fence_async_smem();
      __syncwarp();
      if (lane < 16) {
        __nv_bfloat16* dst = P.out + (size_t)o_row((t >> 2) * 256 + rank * 128 + wg * 64 + w * 16 + lane) * DM + (t & 3) * 160;
        asm volatile("cp.async.bulk.global.shared::cta.bulk_group [%0], [%1], 320;" ::"l"(dst), "r"(st + lane * 336) : "memory");
        asm volatile("cp.async.bulk.commit_group;" ::: "memory");
        asm volatile("cp.async.bulk.wait_group.read 0;" ::: "memory");
      }
      __syncwarp();
    };
    for (int t = id; t < nsingle || t == id; t += ncl) {
      float acc[80];
      uint32_t prev = 0, bprev = 0;
      const bool tile = t < nsingle;
      const bool last = t + ncl >= nsingle;
      auto bstep = [&](int ks, int accf) {
        if (!(ks & 3)) TR(640 + ks / 2); if ((ks & 7) == 0) TG(144 + (ks >> 3));
        ring_wait();
        mbar_wait(sb + BAR_BFULL + 8 * bslot, bphase);
        if (!(ks & 3)) TR(641 + ks / 2);
        wg_fence();
        const uint32_t a = ring_addr() + wg * 512, bd = (((sb & 0x3FFFF) + OFF_Q + bslot * BB) >> 4) | ((4096u >> 4) << 16);
#pragma unroll
        for (int k = 0; k < 4; k++) wgmma_n160<1, 1>(acc, a + k * 128, HI128, bd + k * 64, HI64, k == 0 ? accf : 1);
        wg_commit();
        if (ks > 0) {
          wg_wait<1>();
          release(prev);
          if (lane == 0 && (ks < 59 || !last)) mbar_arrive_cl(mapa(sb + BAR_BEMPTY + 8 * bprev, bprev & 1));
        }
        prev = r.slot; bprev = bslot;
        r.next();
        if (++bslot == 6) { bslot = 0; bphase ^= 1; }
      };
      const char* optr = t == id ? out_ptr(u) : nullptr;
      uint32_t iv[30];
      if (tile) {
        bstep(0, 0);
        bstep(1, 1);
        load_inv(iv, (it + 1) & 1);
#pragma unroll 1
        for (int ks = 2; ks < 17; ks++) {
          bstep(ks, 1);
          switch (ks) {
            case 2: put(pb, iv, optr, IC<0>()); break;
            case 4: put(pb, iv, optr, IC<1>()); break;
            case 6: put(pb, iv, optr, IC<2>()); break;
            case 8: put(pb, iv, optr, IC<3>()); break;
            case 10: put(pb, iv, optr, IC<4>()); break;
            case 12: put(pb, iv, optr, IC<5>()); break;
            case 14: put(pb, iv, optr, IC<6>()); break;
            case 16: put(pb, iv, optr, IC<7>()); break;
            default: break;
          }
        }
        wg_wait<0>();
        reg_fence(acc);
      } else {
        Ring r2 = r;
        auto first = [&](int ks) {
          if (ks == 0) { TR(640); TG(144); }
          if (gemm) { mbar_wait(sb + BAR_RFULL + 8 * r2.slot, r2.phase); mbar_wait(sb + BAR_BFULL + 16 * ks, 0); }
          wg_fence();
          const uint32_t a = (((sb & 0x3FFFF) + r2.slot * RING_BYTES) >> 4) + wg * 512;
          const uint32_t bd = (((sb & 0x3FFFF) + OFF_Q + 2 * ks * BB) >> 4) | ((4096u >> 4) << 16);
#pragma unroll
          for (int k = 0; k < 4; k++) wgmma_n160<1, 1>(acc, a + k * 128, HI128, bd + k * 64, HI64, k + ks != 0);
          wg_commit();
          if (ks > 0) {
            wg_wait<1>();
            if (gemm && lane == 0) mbar_arrive_cl(mapa(sb + BAR_BEMPTY + 16 * (ks - 1), 0));
          }
          r2.next();
        };
        first(0);
        load_inv(iv, (it + 1) & 1);
        put(pb, iv, optr, IC<0>()); put(pb, iv, optr, IC<1>());
        first(1);
        put(pb, iv, optr, IC<2>()); put(pb, iv, optr, IC<3>()); put(pb, iv, optr, IC<4>());
        first(2);
        put(pb, iv, optr, IC<5>()); put(pb, iv, optr, IC<6>()); put(pb, iv, optr, IC<7>());
        wg_wait<0>();
        reg_fence(acc);
      }
      if (unsafe(t == id)) slow_path(P, unit_batch(u), unit_head(u, rank), wg, w, lane);
      if (t == id) publish();
      if (!tile) {
        if (gemm) {
          float ac1[80];
          auto half = [&](float (&ac)[80], bool rel, int accf) {
            mbar_wait(sb + BAR_BFULL + 8 * bslot, bphase);
            wg_fence();
            const uint32_t a = ring_addr() + wg * 512, bd = (((sb & 0x3FFFF) + OFF_Q + bslot * BB) >> 4) | ((4096u >> 4) << 16);
#pragma unroll
            for (int k = 0; k < 4; k++) wgmma_n160<1, 1>(ac, a + k * 128, HI128, bd + k * 64, HI64, k == 0 ? accf : 1);
            wg_commit();
            wg_wait<1>();
            if (lane == 0 && rel) mbar_arrive_cl(mapa(sb + BAR_BEMPTY + 8 * bprev, bprev & 1));
            bprev = bslot;
          };
          bprev = 4; bslot = 1;
          half(ac1, true, 0);
          prev = r.slot; r.next(); bslot = 3;
          half(ac1, true, 1);
          release(prev); prev = r.slot; r.next(); bslot = 5;
          half(ac1, true, 1);
          release(prev); prev = r.slot; r.next(); bslot = 0; bphase = 1;
#pragma unroll 1
          for (int ks = 3; ks < 64; ks++) {
            if (wg == 1 && ks == 62) turn_wait();
            if (!(ks & 3)) TR(640 + ks / 2); if ((ks & 7) == 0) TG(144 + (ks >> 3));
            ring_wait();
            if (!(ks & 3)) TR(641 + ks / 2);
            half(acc, ks < 62, 1);
            release(prev);
            bslot++;
            half(ac1, ks < 61, 1);
            if (++bslot == 6) { bslot = 0; bphase ^= 1; }
            prev = r.slot; r.next();
          }
          if (wg == 0) turn_pass();
          wg_wait<0>();
          reg_fence(acc); reg_fence(ac1);
          TR(158); TG(156);
          bar_sync(wg);
          out_tile(acc, 2 * id - 72);
          out_tile(ac1, 2 * id - 71);
        }
        break;
      }
#pragma unroll 1
      for (int ks = 17; ks < 64; ks++) {
        if (END_SKEW && wg == 1 && ks == 64 - END_SKEW) turn_wait();
        bstep(ks, 1);
      }
      if (END_SKEW && wg == 0) turn_pass();
      wg_wait<0>();
      reg_fence(acc);
      release(prev);
      if (lane == 0 && !last) mbar_arrive_cl(mapa(sb + BAR_BEMPTY + 8 * bprev, bprev & 1));
      TR(158); TG(156);
      const int pos0 = (t >> 2) * 256 + rank * 128 + wg * 64 + w * 16;
      if (last) {
        bar_sync(wg);
        out_tile(acc, t);
      } else {
        __nv_bfloat16* op0 = P.out + (size_t)o_row(pos0 + (lane >> 2)) * DM + (t & 3) * 160 + (lane & 3) * 2;
        __nv_bfloat16* op1 = P.out + (size_t)o_row(pos0 + (lane >> 2) + 8) * DM + (t & 3) * 160 + (lane & 3) * 2;
#pragma unroll
        for (int j = 0; j < 20; j++) {
          *reinterpret_cast<uint32_t*>(op0 + j * 8) = pack(acc[4 * j], acc[4 * j + 1]);
          *reinterpret_cast<uint32_t*>(op1 + j * 8) = pack(acc[4 * j + 2], acc[4 * j + 3]);
        }
      }
#pragma unroll
      for (int i = 0; i < 60; i++) pb[i] = 0;
    }
    TR(159);
  }
}

typedef CUresult (*EncodeFn)(CUtensorMap*, CUtensorMapDataType, cuuint32_t, void*, const cuuint64_t*, const cuuint64_t*,
                             const cuuint32_t*, const cuuint32_t*, CUtensorMapInterleave, CUtensorMapSwizzle,
                             CUtensorMapL2promotion, CUtensorMapFloatOOBfill);

void make_map(EncodeFn enc, CUtensorMap* m, const void* p, int rank, const cuuint64_t* dims, const cuuint64_t* strides,
              const cuuint32_t* box, CUtensorMapSwizzle sw, CUtensorMapL2promotion promo) {
  cuuint32_t es[3] = {1, 1, 1};
  enc(m, CU_TENSOR_MAP_DATA_TYPE_BFLOAT16, rank, const_cast<void*>(p), dims, strides, box, es, CU_TENSOR_MAP_INTERLEAVE_NONE, sw,
      promo, CU_TENSOR_MAP_FLOAT_OOB_FILL_NONE);
}

}

extern "C" void kernel_launch(void* const* d_in, const int* in_sizes, int n_in, void* d_out, int out_size) {
  static EncodeFn enc = nullptr;
  static int nclusters = 0;
  static void* o_ptr = nullptr;
  if (!enc) {
    cudaDriverEntryPointQueryResult qr;
    cudaGetDriverEntryPoint("cuTensorMapEncodeTiled", (void**)&enc, cudaEnableDefault, &qr);
    cudaFuncSetAttribute(fused_attn_kernel, cudaFuncAttributeMaxDynamicSharedMemorySize, SMEM_BYTES);
    cudaGetSymbolAddress(&o_ptr, g_o);
    cudaLaunchConfig_t cfg = {};
    cfg.gridDim = 128; cfg.blockDim = 384; cfg.dynamicSmemBytes = SMEM_BYTES;
    cudaLaunchAttribute at; at.id = cudaLaunchAttributeClusterDimension;
    at.val.clusterDim.x = 2; at.val.clusterDim.y = 1; at.val.clusterDim.z = 1;
    cfg.attrs = &at; cfg.numAttrs = 1;
    int n = 0;
    cudaOccupancyMaxActiveClusters(&n, fused_attn_kernel, &cfg);
    nclusters = n >= 66 ? MAXCL : (n >= 64 || n <= 0 ? 64 : n);
  }
  const __nv_bfloat16* x = (const __nv_bfloat16*)d_in[0];
  const __nv_bfloat16* k = (const __nv_bfloat16*)d_in[1];
  const __nv_bfloat16* v = (const __nv_bfloat16*)d_in[2];
  const __nv_bfloat16* wq = (const __nv_bfloat16*)d_in[3];
  const __nv_bfloat16* wo = (const __nv_bfloat16*)d_in[4];
  CUtensorMap tm_x, tm_wq, tm_k, tm_v, tm_o, tm_wo;
  const auto S128 = CU_TENSOR_MAP_SWIZZLE_128B;
  const auto P128 = CU_TENSOR_MAP_L2_PROMOTION_L2_128B, P256 = CU_TENSOR_MAP_L2_PROMOTION_L2_256B;
  { cuuint64_t d[2] = {DM, NB * SQ}, s[1] = {DM * 2}; cuuint32_t b[2] = {64, 120}; make_map(enc, &tm_x, x, 2, d, s, b, S128, P128); }
  { cuuint64_t d[3] = {64, DM, HD / 64}, s[2] = {HD * 2, 128}; cuuint32_t b[3] = {64, 64, 2}; make_map(enc, &tm_wq, wq, 3, d, s, b, S128, P256); }
  { cuuint64_t d[3] = {64, NB * NH * SK, 2}, s[2] = {DH * 2, 128}; cuuint32_t b[3] = {64, 64, 2};
    make_map(enc, &tm_k, k, 3, d, s, b, S128, P128); make_map(enc, &tm_v, v, 3, d, s, b, S128, P128); }
  { cuuint64_t d[3] = {64, HD, NROWS / 64}, s[2] = {NROWS * 2, 128}; cuuint32_t b[3] = {64, 64, 2}; make_map(enc, &tm_o, o_ptr, 3, d, s, b, S128, P256); }
  { cuuint64_t d[3] = {32, HD, DM / 32}, s[2] = {DM * 2, 64}; cuuint32_t b[3] = {32, 64, 5};
    make_map(enc, &tm_wo, wo, 3, d, s, b, CU_TENSOR_MAP_SWIZZLE_64B, P128); }
  Params P{x, k, v, wq, (__nv_bfloat16*)d_out, (__nv_bfloat16*)o_ptr};
  fused_attn_kernel<<<2 * nclusters, 384, SMEM_BYTES>>>(tm_x, tm_wq, tm_k, tm_v, tm_o, tm_wo, P);
}
```

```cpp
#include <cuda_runtime.h>
#include <cuda.h>
#include <cuda_bf16.h>
#include <stdint.h>

namespace {

constexpr int NB = 16, SQ = 240, DM = 640, NH = 32, SK = 1024, DH = 128, HD = NH * DH;
constexpr int NROWS = NB * SQ;
constexpr int NUNITS = 256;
#define DPRO 0
#define LATE_AT 0
#define ALT_FROM 3
#define MERGE89 1
#define END_SKEW 5
#define VREL 8
#define PF_HOLD 6
#define PF_N 4
#define PF_J0 3
#define PF_STEP 3
#define ROT 0
#define O_EF 1
#define B_ORDER 1
#define WO_PF 6
#define ROLE_AT 0
#define PAUSE_NS 11000
#define PAUSE_AT 2
#define EARLY 1
#define EARLY_X 2
#define EARLY_W 2
#define X_PROMO P128
#define ASYM 0
#define ASYM_PASS 1
#define PINLANE 0
#define MAXCL 66
#define SMID_TOP 88
constexpr int NOTILES = 60;
constexpr float QSCALE = 0.08838834764831845f * 1.4426950408889634f;
constexpr float L_MIN = 9.5367431640625e-07f;
constexpr float L_MAX = 1.152921504606846976e18f;

constexpr uint32_t RING_SLOTS = 6, RING_BYTES = 16384;
constexpr uint32_t XB = 15360;
constexpr uint32_t BB = 20480;
constexpr uint32_t OFF_Q = RING_SLOTS * RING_BYTES;
constexpr uint32_t OFF_P = OFF_Q + 4 * XB;
constexpr uint32_t OFF_INV = OFF_P + 4 * XB;
constexpr uint32_t OFF_L2 = OFF_INV + 1280;
constexpr uint32_t OFF_BAR = OFF_L2 + 4096;
constexpr uint32_t BAR_RFULL = OFF_BAR, BAR_REMPTY = BAR_RFULL + 48, BAR_XFULL = BAR_REMPTY + 48,
    BAR_XEMPTY = BAR_XFULL + 64, BAR_BFULL = BAR_XEMPTY + 32, BAR_BEMPTY = BAR_BFULL + 48, BAR_STAGE = BAR_BEMPTY + 48;
constexpr uint32_t BAR_ROLE = BAR_STAGE + 16, BAR_LSUM = BAR_ROLE + 24, BAR_INV = BAR_LSUM + 16;
constexpr uint32_t OFF_TR = BAR_INV + 16;
constexpr uint32_t SMEM_BYTES = OFF_TR + 1024;

constexpr uint32_t HI128 = (1u << 30) | (1024 >> 4);
constexpr uint32_t HI64 = (2u << 30) | (512 >> 4);

__device__ __nv_bfloat16 g_o[HD * NROWS];
__device__ unsigned g_cnt[67 * 8];
#define TS(i)
#define TR(i)
#define TG(i)

struct Params {
  const __nv_bfloat16 *x, *k, *v, *wq;
  __nv_bfloat16 *out, *o;
};

__device__ __forceinline__ void wg_fence() { asm volatile("wgmma.fence.sync.aligned;" ::: "memory"); }
__device__ __forceinline__ void wg_commit() { asm volatile("wgmma.commit_group.sync.aligned;" ::: "memory"); }
template <int N> __device__ __forceinline__ void wg_wait() { asm volatile("wgmma.wait_group.sync.aligned %0;" ::"n"(N) : "memory"); }
template <int N> __device__ __forceinline__ void reg_fence(float (&r)[N]) {
#pragma unroll
  for (int i = 0; i < N; i++) asm volatile("" : "+f"(r[i])::"memory");
}
template <int TA, int TB>
__device__ __forceinline__ void wgmma_n120(float (&d)[60], uint32_t a_lo, uint32_t a_hi, uint32_t b_lo, uint32_t b_hi, int acc) {
  asm volatile(
      "{\n.reg .pred p;\n.reg .b64 da, db;\nsetp.ne.b32 p, %64, 0;\n"
      "mov.b64 da, {%60, %61};\nmov.b64 db, {%62, %63};\n"
      "wgmma.mma_async.sync.aligned.m64n120k16.f32.bf16.bf16 {"
      "%0, %1, %2, %3, %4, %5, %6, %7, %8, %9, %10, %11, %12, %13, %14, %15, %16, %17, %18, %19, %20, %21, %22, %23, "
      "%24, %25, %26, %27, %28, %29, %30, %31, %32, %33, %34, %35, %36, %37, %38, %39, %40, %41, %42, %43, %44, %45, "
      "%46, %47, %48, %49, %50, %51, %52, %53, %54, %55, %56, %57, %58, %59"
      "}, da, db, p, 1, 1, %65, %66;\n}\n"
      : "+f"(d[0]), "+f"(d[1]), "+f"(d[2]), "+f"(d[3]), "+f"(d[4]), "+f"(d[5]), "+f"(d[6]), "+f"(d[7]), "+f"(d[8]),
        "+f"(d[9]), "+f"(d[10]), "+f"(d[11]), "+f"(d[12]), "+f"(d[13]), "+f"(d[14]), "+f"(d[15]), "+f"(d[16]),
        "+f"(d[17]), "+f"(d[18]), "+f"(d[19]), "+f"(d[20]), "+f"(d[21]), "+f"(d[22]), "+f"(d[23]), "+f"(d[24]),
        "+f"(d[25]), "+f"(d[26]), "+f"(d[27]), "+f"(d[28]), "+f"(d[29]), "+f"(d[30]), "+f"(d[31]), "+f"(d[32]),
        "+f"(d[33]), "+f"(d[34]), "+f"(d[35]), "+f"(d[36]), "+f"(d[37]), "+f"(d[38]), "+f"(d[39]), "+f"(d[40]),
        "+f"(d[41]), "+f"(d[42]), "+f"(d[43]), "+f"(d[44]), "+f"(d[45]), "+f"(d[46]), "+f"(d[47]), "+f"(d[48]),
        "+f"(d[49]), "+f"(d[50]), "+f"(d[51]), "+f"(d[52]), "+f"(d[53]), "+f"(d[54]), "+f"(d[55]), "+f"(d[56]),
        "+f"(d[57]), "+f"(d[58]), "+f"(d[59])
      : "r"(a_lo), "r"(a_hi), "r"(b_lo), "r"(b_hi), "r"(acc), "n"(TA), "n"(TB));
}

template <int TA, int TB>
__device__ __forceinline__ void wgmma_n160(float (&d)[80], uint32_t a_lo, uint32_t a_hi, uint32_t b_lo, uint32_t b_hi, int acc) {
  asm volatile(
      "{\n.reg .pred p;\n.reg .b64 da, db;\nsetp.ne.b32 p, %84, 0;\n"
      "mov.b64 da, {%80, %81};\nmov.b64 db, {%82, %83};\n"
      "wgmma.mma_async.sync.aligned.m64n160k16.f32.bf16.bf16 {"
      "%0, %1, %2, %3, %4, %5, %6, %7, %8, %9, %10, %11, %12, %13, %14, %15, %16, %17, %18, %19, %20, %21, %22, %23, "
      "%24, %25, %26, %27, %28, %29, %30, %31, %32, %33, %34, %35, %36, %37, %38, %39, %40, %41, %42, %43, %44, %45, "
      "%46, %47, %48, %49, %50, %51, %52, %53, %54, %55, %56, %57, %58, %59, %60, %61, %62, %63, %64, %65, %66, %67, "
      "%68, %69, %70, %71, %72, %73, %74, %75, %76, %77, %78, %79"
      "}, da, db, p, 1, 1, %85, %86;\n}\n"
      : "+f"(d[0]), "+f"(d[1]), "+f"(d[2]), "+f"(d[3]), "+f"(d[4]), "+f"(d[5]), "+f"(d[6]), "+f"(d[7]), "+f"(d[8]),
        "+f"(d[9]), "+f"(d[10]), "+f"(d[11]), "+f"(d[12]), "+f"(d[13]), "+f"(d[14]), "+f"(d[15]), "+f"(d[16]),
        "+f"(d[17]), "+f"(d[18]), "+f"(d[19]), "+f"(d[20]), "+f"(d[21]), "+f"(d[22]), "+f"(d[23]), "+f"(d[24]),
        "+f"(d[25]), "+f"(d[26]), "+f"(d[27]), "+f"(d[28]), "+f"(d[29]), "+f"(d[30]), "+f"(d[31]), "+f"(d[32]),
        "+f"(d[33]), "+f"(d[34]), "+f"(d[35]), "+f"(d[36]), "+f"(d[37]), "+f"(d[38]), "+f"(d[39]), "+f"(d[40]),
        "+f"(d[41]), "+f"(d[42]), "+f"(d[43]), "+f"(d[44]), "+f"(d[45]), "+f"(d[46]), "+f"(d[47]), "+f"(d[48]),
        "+f"(d[49]), "+f"(d[50]), "+f"(d[51]), "+f"(d[52]), "+f"(d[53]), "+f"(d[54]), "+f"(d[55]), "+f"(d[56]),
        "+f"(d[57]), "+f"(d[58]), "+f"(d[59]), "+f"(d[60]), "+f"(d[61]), "+f"(d[62]), "+f"(d[63]), "+f"(d[64]),
        "+f"(d[65]), "+f"(d[66]), "+f"(d[67]), "+f"(d[68]), "+f"(d[69]), "+f"(d[70]), "+f"(d[71]), "+f"(d[72]),
        "+f"(d[73]), "+f"(d[74]), "+f"(d[75]), "+f"(d[76]), "+f"(d[77]), "+f"(d[78]), "+f"(d[79])
      : "r"(a_lo), "r"(a_hi), "r"(b_lo), "r"(b_hi), "r"(acc), "n"(TA), "n"(TB));
}
__device__ __forceinline__ void mbar_init(uint32_t bar, int cnt) { asm volatile("mbarrier.init.shared::cta.b64 [%0], %1;" ::"r"(bar), "r"(cnt)); }
__device__ __forceinline__ void mbar_expect(uint32_t bar, uint32_t bytes) {
  asm volatile("mbarrier.arrive.expect_tx.shared::cta.b64 _, [%0], %1;" ::"r"(bar), "r"(bytes) : "memory");
}
__device__ __forceinline__ uint32_t mapa(uint32_t addr, uint32_t cta) {
  uint32_t r; asm("mapa.shared::cluster.u32 %0, %1, %2;" : "=r"(r) : "r"(addr), "r"(cta)); return r;
}
__device__ __forceinline__ void mbar_expect_cl(uint32_t cbar, uint32_t bytes) {
  asm volatile("mbarrier.arrive.expect_tx.shared::cluster.b64 _, [%0], %1;" ::"r"(cbar), "r"(bytes) : "memory");
}
__device__ __forceinline__ void mbar_arrive(uint32_t bar) { asm volatile("mbarrier.arrive.shared::cta.b64 _, [%0];" ::"r"(bar) : "memory"); }
__device__ __forceinline__ void mbar_arrive_cl(uint32_t cbar) { asm volatile("mbarrier.arrive.shared::cluster.b64 _, [%0];" ::"r"(cbar) : "memory"); }
__device__ __forceinline__ void mbar_wait(uint32_t bar, uint32_t parity) {
  asm volatile(
      "{\n.reg .pred p;\n.reg .u32 n;\n"
      "mbarrier.try_wait.parity.shared::cta.b64 p, [%0], %1;\n@p bra WAIT_DONE;\n"
      "mov.u32 n, 0;\n"
      "WAIT_LOOP:\n"
      "mbarrier.try_wait.parity.shared::cta.b64 p, [%0], %1;\n@p bra WAIT_DONE;\n"
      "add.u32 n, n, 1;\nsetp.lt.u32 p, n, 0x4000000;\n@p bra WAIT_LOOP;\ntrap;\n"
      "WAIT_DONE:\n}\n" ::"r"(bar), "r"(parity) : "memory");
}
__device__ __forceinline__ void mbar_wait_cl(uint32_t bar, uint32_t parity) {
  asm volatile(
      "{\n.reg .pred p;\n.reg .u32 n;\nmov.u32 n, 0;\n"
      "WAIT_LOOP:\n"
      "mbarrier.try_wait.parity.acquire.cluster.shared::cta.b64 p, [%0], %1;\n@p bra WAIT_DONE;\n"
      "add.u32 n, n, 1;\nsetp.lt.u32 p, n, 0x4000000;\n@p bra WAIT_LOOP;\ntrap;\n"
      "WAIT_DONE:\n}\n" ::"r"(bar), "r"(parity) : "memory");
}
__device__ __forceinline__ void tma3d(uint32_t dst, const CUtensorMap* m, int c0, int c1, int c2, uint32_t bar) {
  asm volatile("cp.async.bulk.tensor.3d.shared::cluster.global.mbarrier::complete_tx::bytes [%0], [%1, {%3, %4, %5}], [%2];"
               ::"r"(dst), "l"(m), "r"(bar), "r"(c0), "r"(c1), "r"(c2) : "memory");
}
__device__ __forceinline__ void tma3d_hint(uint32_t dst, const CUtensorMap* m, int c0, int c1, int c2, uint32_t bar, uint64_t pol) {
  asm volatile("cp.async.bulk.tensor.3d.shared::cluster.global.mbarrier::complete_tx::bytes.L2::cache_hint [%0], [%1, {%3, %4, %5}], [%2], %6;"
               ::"r"(dst), "l"(m), "r"(bar), "r"(c0), "r"(c1), "r"(c2), "l"(pol) : "memory");
}
__device__ __forceinline__ void tma2d_mc(uint32_t dst, const CUtensorMap* m, int c0, int c1, uint32_t bar) {
  asm volatile("cp.async.bulk.tensor.2d.shared::cluster.global.mbarrier::complete_tx::bytes.multicast::cluster [%0], [%1, {%3, %4}], [%2], %5;"
               ::"r"(dst), "l"(m), "r"(bar), "r"(c0), "r"(c1), "h"((uint16_t)3) : "memory");
}
__device__ __forceinline__ void tma3d_mc(uint32_t dst, const CUtensorMap* m, int c0, int c1, int c2, uint32_t bar) {
  asm volatile("cp.async.bulk.tensor.3d.shared::cluster.global.mbarrier::complete_tx::bytes.multicast::cluster [%0], [%1, {%3, %4, %5}], [%2], %6;"
               ::"r"(dst), "l"(m), "r"(bar), "r"(c0), "r"(c1), "r"(c2), "h"((uint16_t)3) : "memory");
}
__device__ __forceinline__ void l2_prefetch(const void* p, uint32_t bytes) {
  asm volatile("cp.async.bulk.prefetch.L2.global [%0], %1;" ::"l"(p), "r"(bytes) : "memory");
}
__device__ __forceinline__ void fence_async_smem() { asm volatile("fence.proxy.async.shared::cta;" ::: "memory"); }
__device__ __forceinline__ void bar_sync(int wg) {
  if (wg == 0) asm volatile("bar.sync 1, 128;" ::: "memory");
  else asm volatile("bar.sync 2, 128;" ::: "memory");
}
__device__ __forceinline__ bool bar_red_or(int id, bool v) {
  uint32_t r;
  asm volatile("{\n.reg .pred p, q;\nsetp.ne.u32 p, %2, 0;\nbar.red.or.pred q, %1, 128, p;\nselp.u32 %0, 1, 0, q;\n}\n"
               : "=r"(r) : "r"(1 + id), "r"((uint32_t)v) : "memory");
  return r != 0;
}
__device__ __forceinline__ uint32_t hfma2(uint32_t a, uint32_t b, uint32_t c) { uint32_t r; asm("fma.rn.bf16x2 %0, %1, %2, %3;" : "=r"(r) : "r"(a), "r"(b), "r"(c)); return r; }
__device__ __forceinline__ float ex2(float x) { float y; asm("ex2.approx.ftz.f32 %0, %1;" : "=f"(y) : "f"(x)); return y; }
__device__ __forceinline__ uint32_t pack(float lo, float hi) { uint32_t r; asm("cvt.rn.bf16x2.f32 %0, %1, %2;" : "=r"(r) : "f"(hi), "f"(lo)); return r; }
__device__ __forceinline__ void stsm4t(uint32_t a, uint32_t r0, uint32_t r1, uint32_t r2, uint32_t r3) {
  asm volatile("stmatrix.sync.aligned.m8n8.x4.trans.shared.b16 [%0], {%1,%2,%3,%4};" ::"r"(a), "r"(r0), "r"(r1), "r"(r2), "r"(r3) : "memory");
}
__device__ __forceinline__ void stsm2t(uint32_t a, uint32_t r0, uint32_t r1) {
  asm volatile("stmatrix.sync.aligned.m8n8.x2.trans.shared.b16 [%0], {%1,%2};" ::"r"(a), "r"(r0), "r"(r1) : "memory");
}
__device__ __forceinline__ void mma16816(float (&d)[4], const uint32_t (&a)[4], uint32_t b0, uint32_t b1) {
  asm volatile("mma.sync.aligned.m16n8k16.row.col.f32.bf16.bf16.f32 {%0,%1,%2,%3}, {%4,%5,%6,%7}, {%8,%9}, {%0,%1,%2,%3};"
               : "+f"(d[0]), "+f"(d[1]), "+f"(d[2]), "+f"(d[3]) : "r"(a[0]), "r"(a[1]), "r"(a[2]), "r"(a[3]), "r"(b0), "r"(b1));
}

template <int V> struct IC { static constexpr int value = V; };

struct Ring {
  uint32_t slot = 0, phase = 0;
  __device__ __forceinline__ void next() { if (++slot == RING_SLOTS) { slot = 0; phase ^= 1; } }
};

__device__ __forceinline__ void mma_tn(float (&o0)[60], float (&o1)[60], uint32_t a, uint32_t b, int acc) {
#pragma unroll
  for (int k = 0; k < 4; k++) {
    wgmma_n120<1, 0>(o0, a + k * 128, HI128, b + k * 2, HI128, k == 0 ? acc : 1);
    wgmma_n120<1, 0>(o1, a + 512 + k * 128, HI128, b + k * 2, HI128, k == 0 ? acc : 1);
  }
}
__device__ __forceinline__ void mma_tn_split(float (&o0)[60], float (&o1)[60], uint32_t a, uint32_t b) {
#pragma unroll
  for (int k = 0; k < 4; k++) wgmma_n120<1, 0>(o0, a + k * 128, HI128, b + k * 2, HI128, 1);
  wg_commit();
#pragma unroll
  for (int k = 0; k < 4; k++) wgmma_n120<1, 0>(o1, a + 512 + k * 128, HI128, b + k * 2, HI128, 1);
  wg_commit();
}
__device__ __forceinline__ void mma_qk(float (&s)[60], uint32_t a, uint32_t q) {
#pragma unroll
  for (int k = 0; k < 8; k++)
    wgmma_n120<0, 0>(s, a + (k >> 2) * 512 + (k & 3) * 2, HI128, q + (k >> 2) * (XB >> 4) + (k & 3) * 2, HI128, k != 0);
}
template <int J0, int J1, bool FIRST = false>
__device__ __forceinline__ void exp_store(const float (&s)[60], float (&l)[30], uint32_t dst) {
#pragma unroll
  for (int j = J0; j < J1; j += 2) {
    uint32_t p[4];
#pragma unroll
    for (int jj = 0; jj < 2; jj++) {
      if (j + jj < 15) {
        const int c = j + jj;
        float e0 = ex2(s[4 * c]), e1 = ex2(s[4 * c + 1]), e2 = ex2(s[4 * c + 2]), e3 = ex2(s[4 * c + 3]);
        if (FIRST) { l[2 * c] = e0 + e2; l[2 * c + 1] = e1 + e3; }
        else { l[2 * c] += e0; l[2 * c + 1] += e1; l[2 * c] += e2; l[2 * c + 1] += e3; }
        p[2 * jj] = pack(e0, e1); p[2 * jj + 1] = pack(e2, e3);
      }
    }
    if (j + 1 < 15) stsm4t(dst + j * 1024, p[0], p[1], p[2], p[3]);
    else stsm2t(dst + j * 1024, p[0], p[1]);
  }
}

__device__ __forceinline__ int o_pos(int wg, int r) {
  const int j = r >> 3, q = (r >> 1) & 3, c = r & 1;
  if (j < 12) return (wg ? 144 : 0) + (j >> 2) * 32 + q * 8 + (j & 3) * 2 + c;
  if (j < 14) return (wg ? 128 : 96) + q * 4 + (j - 12) * 2 + c;
  return (wg ? 120 : 112) + q * 2 + c;
}
__device__ __forceinline__ int o_row(int p) {
  const int b = p / SQ, r = p - b * SQ, wg = r >= 120, c = r & 1;
  const int a = r - (wg ? 144 : 0), m = r - (wg ? 128 : 96), e = r - (wg ? 120 : 112);
  int row;
  if (a >= 0 && a < 96) row = ((a >> 5) * 4 + ((a >> 1) & 3)) * 8 + ((a >> 3) & 3) * 2 + c;
  else if (m >= 0 && m < 16) row = (12 + ((m >> 1) & 1)) * 8 + (m >> 2) * 2 + c;
  else row = 112 + e;
  return b * SQ + wg * 120 + row;
}

__device__ __forceinline__ void slow_path(const Params& P, int b, int h, int wg, int w, int lane) {
  const int g = lane >> 2, q = lane & 3, row0 = wg * 120;
  const uint16_t* wq = reinterpret_cast<const uint16_t*>(P.wq) + h * DH + g;
  const __nv_bfloat16* kp = P.k + (size_t)(b * NH + h) * SK * DH;
  const uint16_t* vp = reinterpret_cast<const uint16_t*>(P.v) + (size_t)(b * NH + h) * SK * DH + g;
#pragma unroll 1
  for (int t = w; t < 8; t += 4) {
    const int r0 = 16 * t + g, r1 = r0 + 8;
    const __nv_bfloat16* x0 = P.x + (size_t)(b * SQ + row0 + r0) * DM + 2 * q;
    const __nv_bfloat16* x1 = P.x + (size_t)(b * SQ + row0 + min(r1, 119)) * DM + 2 * q;
    float o[16][4];
#pragma unroll
    for (int n = 0; n < 16; n++) o[n][0] = o[n][1] = o[n][2] = o[n][3] = 0.f;
#pragma unroll 1
    for (int k0 = 0; k0 < DM; k0 += 16) {
      uint32_t a[4] = {*(const uint32_t*)(x0 + k0), *(const uint32_t*)(x1 + k0), *(const uint32_t*)(x0 + k0 + 8), *(const uint32_t*)(x1 + k0 + 8)};
      const uint16_t* wr = wq + (size_t)(k0 + 2 * q) * HD;
#pragma unroll
      for (int n = 0; n < 16; n++)
        mma16816(o[n], a, wr[8 * n] | ((uint32_t)wr[8 * n + HD] << 16), wr[8 * n + 8 * HD] | ((uint32_t)wr[8 * n + 9 * HD] << 16));
    }
    uint32_t qa[8][4];
#pragma unroll
    for (int k = 0; k < 8; k++) {
      qa[k][0] = pack(o[2 * k][0] * QSCALE, o[2 * k][1] * QSCALE);
      qa[k][1] = pack(o[2 * k][2] * QSCALE, o[2 * k][3] * QSCALE);
      qa[k][2] = pack(o[2 * k + 1][0] * QSCALE, o[2 * k + 1][1] * QSCALE);
      qa[k][3] = pack(o[2 * k + 1][2] * QSCALE, o[2 * k + 1][3] * QSCALE);
    }
#pragma unroll
    for (int n = 0; n < 16; n++) o[n][0] = o[n][1] = o[n][2] = o[n][3] = 0.f;
    float m0 = -INFINITY, m1 = -INFINITY, l0 = 0.f, l1 = 0.f;
#pragma unroll 1
    for (int key0 = 0; key0 < SK; key0 += 16) {
      float s[2][4];
#pragma unroll
      for (int nt = 0; nt < 2; nt++) {
        s[nt][0] = s[nt][1] = s[nt][2] = s[nt][3] = 0.f;
        const __nv_bfloat16* kr = kp + (size_t)(key0 + 8 * nt + g) * DH + 2 * q;
#pragma unroll
        for (int k = 0; k < 8; k++) mma16816(s[nt], qa[k], *(const uint32_t*)(kr + 16 * k), *(const uint32_t*)(kr + 16 * k + 8));
      }
      float n0 = fmaxf(fmaxf(s[0][0], s[0][1]), fmaxf(s[1][0], s[1][1])), n1 = fmaxf(fmaxf(s[0][2], s[0][3]), fmaxf(s[1][2], s[1][3]));
      n0 = fmaxf(n0, __shfl_xor_sync(~0u, n0, 1)); n1 = fmaxf(n1, __shfl_xor_sync(~0u, n1, 1));
      n0 = fmaxf(n0, __shfl_xor_sync(~0u, n0, 2)); n1 = fmaxf(n1, __shfl_xor_sync(~0u, n1, 2));
      n0 = fmaxf(n0, m0); n1 = fmaxf(n1, m1);
      const float z0 = n0 == -INFINITY ? 0.f : n0, z1 = n1 == -INFINITY ? 0.f : n1;
      const float c0 = ex2(m0 - z0), c1 = ex2(m1 - z1);
      m0 = n0; m1 = n1;
#pragma unroll
      for (int nt = 0; nt < 2; nt++) {
        s[nt][0] = ex2(s[nt][0] - z0); s[nt][1] = ex2(s[nt][1] - z0);
        s[nt][2] = ex2(s[nt][2] - z1); s[nt][3] = ex2(s[nt][3] - z1);
      }
      l0 = l0 * c0 + s[0][0] + s[0][1] + s[1][0] + s[1][1];
      l1 = l1 * c1 + s[0][2] + s[0][3] + s[1][2] + s[1][3];
      uint32_t pa[4] = {pack(s[0][0], s[0][1]), pack(s[0][2], s[0][3]), pack(s[1][0], s[1][1]), pack(s[1][2], s[1][3])};
      const uint16_t* vr = vp + (size_t)(key0 + 2 * q) * DH;
#pragma unroll
      for (int n = 0; n < 16; n++) {
        o[n][0] *= c0; o[n][1] *= c0; o[n][2] *= c1; o[n][3] *= c1;
        mma16816(o[n], pa, vr[8 * n] | ((uint32_t)vr[8 * n + DH] << 16), vr[8 * n + 8 * DH] | ((uint32_t)vr[8 * n + 9 * DH] << 16));
      }
    }
    l0 += __shfl_xor_sync(~0u, l0, 1); l1 += __shfl_xor_sync(~0u, l1, 1);
    l0 += __shfl_xor_sync(~0u, l0, 2); l1 += __shfl_xor_sync(~0u, l1, 2);
    const float i0 = 1.f / l0, i1 = 1.f / l1;
    __nv_bfloat16* oc = P.o + (size_t)(h * DH + 2 * q) * NROWS + b * SQ;
    const int p0 = o_pos(wg, r0), p1 = o_pos(wg, min(r1, 119));
#pragma unroll
    for (int n = 0; n < 16; n++) {
      oc[(size_t)(8 * n) * NROWS + p0] = __float2bfloat16(o[n][0] * i0);
      oc[(size_t)(8 * n + 1) * NROWS + p0] = __float2bfloat16(o[n][1] * i0);
      if (r1 < 120) {
        oc[(size_t)(8 * n) * NROWS + p1] = __float2bfloat16(o[n][2] * i1);
        oc[(size_t)(8 * n + 1) * NROWS + p1] = __float2bfloat16(o[n][3] * i1);
      }
    }
  }
}

__device__ __forceinline__ int bk(int ks) { return B_ORDER && ks < 48 ? 32 - (ks & 48) + (ks & 15) : ks; }
__device__ __forceinline__ uint32_t x_slot(uint32_t wg, uint32_t j) { return j < 2 ? (2 * wg + j) * XB : (2 * j + wg) * XB; }
__device__ __forceinline__ int row_block(int t) { return t >= 44 ? (t >> 2) - 11 : (t >> 2) + 4; }
__device__ __forceinline__ int unit_batch(int u) { return (u & 63) >> 2; }
__device__ __forceinline__ int unit_head(int u, int rank) { return (u >> 6) * 8 + (u & 3) * 2 + rank; }

__global__ void __cluster_dims__(2, 1, 1) __launch_bounds__(384, 1)
fused_attn_kernel(const __grid_constant__ CUtensorMap tm_x, const __grid_constant__ CUtensorMap tm_wq,
                  const __grid_constant__ CUtensorMap tm_k, const __grid_constant__ CUtensorMap tm_v,
                  const __grid_constant__ CUtensorMap tm_o, const __grid_constant__ CUtensorMap tm_wo,
                  const __grid_constant__ Params P) {
  extern __shared__ uint8_t smem_raw[];
  const uint32_t sb = ((uint32_t)__cvta_generic_to_shared(smem_raw) + 1023) & ~1023u;
  if (threadIdx.x == 0) TS(152);
  const int warp = __shfl_sync(~0u, threadIdx.x >> 5, 0);
  int lane = threadIdx.x & 31;
  const int rank = blockIdx.x & 1, cl = blockIdx.x >> 1, ncl = gridDim.x >> 1;

  const int nsingle = ncl == 66 ? 44 : NOTILES;
  auto role = [&]() {
    mbar_wait(sb + BAR_ROLE + 16, 0);
    int id;
    asm volatile("ld.shared.u32 %0, [%1];" : "=r"(id) : "r"(sb + BAR_ROLE + 8) : "memory");
    return id;
  };

  if (EARLY && threadIdx.x == 128) asm volatile("prefetch.tensormap [%0];" ::"l"(&tm_x) : "memory");
  if (threadIdx.x == 0) {
    if (EARLY) asm volatile("prefetch.tensormap [%0];" ::"l"(&tm_wq) : "memory");
    for (int i = 0; i < 6; i++) {
      mbar_init(sb + BAR_RFULL + 8 * i, 1); mbar_init(sb + BAR_REMPTY + 8 * i, 8);
      mbar_init(sb + BAR_BFULL + 8 * i, 1); mbar_init(sb + BAR_BEMPTY + 8 * i, 16);
    }
    for (int i = 0; i < 8; i++) mbar_init(sb + BAR_XFULL + 8 * i, 1);
    for (int i = 0; i < 4; i++) mbar_init(sb + BAR_XEMPTY + 8 * i, 8);
    for (int i = 0; i < 2; i++) { mbar_init(sb + BAR_STAGE + 8 * i, 4); mbar_init(sb + BAR_LSUM + 8 * i, 4); mbar_init(sb + BAR_INV + 8 * i, 1); }
    mbar_init(sb + BAR_ROLE, 1); mbar_init(sb + BAR_ROLE + 16, 1);
    asm volatile("fence.mbarrier_init.release.cluster;" ::: "memory");
  }
  __syncwarp();
  asm volatile("barrier.cluster.arrive.relaxed.aligned;" ::: "memory");
  auto first_w = [&](int s) {
    mbar_expect(sb + BAR_RFULL + 8 * s, RING_BYTES);
    tma3d(sb + s * RING_BYTES, &tm_wq, 0, s * 64, 2 * unit_head(cl, rank), sb + BAR_RFULL + 8 * s);
  };
  if (EARLY && threadIdx.x == 0) first_w(0);
  __syncwarp();
  asm volatile("barrier.cluster.wait.aligned;" ::: "memory");
  if (EARLY && threadIdx.x == 128) {
#pragma unroll 1
    for (int s = 0; s < EARLY_X; s++) {
      const uint32_t fb = sb + BAR_XFULL + 32 * rank + 8 * s;
      mbar_expect(fb, XB);
      mbar_expect_cl(mapa(fb, rank ^ 1), XB);
      tma2d_mc(sb + OFF_Q + x_slot(rank, s), &tm_x, s * 64, unit_batch(cl) * SQ + rank * 120, fb);
      if (s + 1 < EARLY_W) first_w(s + 1);
    }
  }
  __syncwarp();
  if (threadIdx.x == 0) TS(153);

  if (warp >= 8) {
    asm volatile("setmaxnreg.dec.sync.aligned.u32 24;");
    if (warp == 8) {
      uint64_t pol;
      asm volatile("createpolicy.fractional.L2::evict_first.b64 %0, 1.0;" : "=l"(pol));
      Ring r;
      if (EARLY) r.slot = EARLY_W;
      auto load = [&](const CUtensorMap* m, int c1, int c2, bool ef) {
        mbar_wait(sb + BAR_REMPTY + 8 * r.slot, r.phase ^ 1);
        if (lane == 0) {
          mbar_expect(sb + BAR_RFULL + 8 * r.slot, RING_BYTES);
          if (ef) tma3d_hint(sb + r.slot * RING_BYTES, m, 0, c1, c2, sb + BAR_RFULL + 8 * r.slot, pol);
          else tma3d(sb + r.slot * RING_BYTES, m, 0, c1, c2, sb + BAR_RFULL + 8 * r.slot);
        }
        r.next();
      };
      const int rot = ROT * (blockIdx.x * 5 + (blockIdx.x >> 4));
      for (int u0 = 0;; u0 += ncl) {
        const int u = __shfl_sync(~0u, (u0 >= 3 * ncl ? role() : cl) + u0, 0);
        if (u >= NUNITS) break;
        if (PAUSE_NS && ncl == 66 && u0 == PAUSE_AT * 66) {
          const int id = role();
          if (id >= 44 && id < 58) {
            unsigned t0, t1;
            asm volatile("mov.u32 %0, %globaltimer_lo;" : "=r"(t0));
            do { __nanosleep(200); asm volatile("mov.u32 %0, %globaltimer_lo;" : "=r"(t1)); } while (t1 - t0 < PAUSE_NS);
          }
        }
        const int h = unit_head(u, rank);
        const int krow = (unit_batch(u) * NH + h) * SK;
#pragma unroll 1
        for (int s = EARLY && u0 == 0 ? EARLY_W : 0; s < 10; s++) {
          if (u0 == 0 && s == 0 && lane == 0) TS(154);
          load(&tm_wq, s * 64, 2 * h, false);
          if (u0 == 0 && s == 0 && lane == 0) TS(155);
          const int sp = u0 == 0 ? s - PF_HOLD : s;
          if (sp >= 0 && sp < PF_N && lane == 0) l2_prefetch(P.v + (size_t)(krow + ((PF_J0 + sp * PF_STEP + rot) & 15) * 64) * DH, 16384);
        }
#pragma unroll 1
        for (int j = 0; j <= 16; j++) {
          if (j < 16) load(&tm_k, krow + ((j + rot) & 15) * 64, 0, true);
          if (j == 1 + DPRO) load(&tm_v, krow + (rot & 15) * 64, 0, true);
          if (j > 1) load(&tm_v, krow + ((j - 1 + rot) & 15) * 64, 0, true);
        }
      }
      const int id = __shfl_sync(~0u, role(), 0);
      const bool dbl = ncl == 66 && id >= 58;
      for (int t = dbl ? 2 * id - 72 : id; t < (dbl ? NOTILES : nsingle); t += ncl) {
        const int row0 = row_block(t) * 256 + rank * 128;
        const int b0 = row0 / SQ, b1 = (row0 + 127) / SQ;
#pragma unroll 1
        for (int ks = 0; ks < 64; ks++) {
          if (dbl ? (ks & 15) == 0 : ks == 0 || ks == 48) {
            const unsigned* c = &g_cnt[((lane & 1 ? b1 : b0) * 4 + (ks || dbl ? ks >> 4 : min(lane >> 1, 2))) * 8];
            unsigned v, n = 0;
            do {
              asm volatile("ld.acquire.gpu.global.u32 %0, [%1];" : "=r"(v) : "l"(c) : "memory");
              if (++n > (1u << 26)) __trap();
            } while (v < 16);
            __syncwarp();
            asm volatile("fence.proxy.async.global;" ::: "memory");
          }
          load(&tm_o, (dbl ? ks : bk(ks)) * 64, row0 >> 6, O_EF);
        }
      }
      if (lane == 0 && atomicAdd(&g_cnt[64 * 8], 1) == gridDim.x - 1) {
        for (int i = 0; i < 67; i++) g_cnt[i * 8] = 0;
      }
    } else if (warp == 9) {
      if (lane == 0) {
        uint32_t it = 0;
        for (;; it++) {
          const int u = (it >= 3 ? role() : cl) + it * ncl;
          if (u >= NUNITS) break;
          const int row = unit_batch(u) * SQ + rank * 120;
#pragma unroll 1
          for (int s = EARLY && it == 0 ? EARLY_X : 0; s < 10; s++) {
            const uint32_t j = s & 3, par = ((s >> 2) + (j < 2 ? it : 0)) & 1;
            mbar_wait(sb + BAR_XEMPTY + 8 * j, par ^ 1);
            const uint32_t fb = sb + BAR_XFULL + 32 * rank + 8 * j;
            mbar_expect(fb, XB);
            mbar_expect_cl(mapa(fb, rank ^ 1), XB);
            tma2d_mc(sb + OFF_Q + x_slot(rank, j), &tm_x, s * 64, row, fb);
          }
        }
        const int id = role();
        const bool dbl = ncl == 66 && id >= 58;
        uint32_t slot = rank, phase = 0;
        for (int t = dbl ? 2 * id - 72 + rank : id; t < (dbl ? NOTILES : nsingle); t += ncl) {
#pragma unroll 1
          for (int ks = dbl ? 0 : rank; ks < 64; ks += dbl ? 1 : 2) {
            mbar_wait(sb + BAR_BEMPTY + 8 * slot, phase);
            const uint32_t fb = sb + BAR_BFULL + 8 * slot;
            mbar_expect(fb, BB);
            mbar_expect_cl(mapa(fb, rank ^ 1), BB);
            tma3d_mc(sb + OFF_Q + slot * BB, &tm_wo, 0, (dbl ? ks : bk(ks)) * 64, (t & 3) * 5, fb);
            if (WO_PF && dbl && ks + WO_PF < 64 && (ks & 3) == ((id >> 1) & 3))
              asm volatile("cp.async.bulk.prefetch.tensor.3d.L2.global [%0, {%1, %2, %3}];" ::"l"(&tm_wo), "r"(0), "r"((ks + WO_PF) * 64), "r"((t & 3) * 5) : "memory");
            slot += 2;
            if (slot >= 6) { slot -= 6; phase ^= 1; }
          }
        }
      }
    } else {
      const int wg = warp - 10;
      {
        mbar_wait(sb + BAR_RFULL, 0);
        const __nv_bfloat16* xs = P.x + (size_t)(unit_batch(cl) * SQ + ((cl & 3) * 2 + rank) * 30 + min(lane, 29)) * DM + 256 + wg * 64;
#pragma unroll
        for (int i = 0; i < 3; i++) asm volatile("prefetch.global.L2 [%0];" ::"l"(xs + i * 128));
        if (lane < 16) asm volatile("prefetch.global.L2 [%0];" ::"l"(P.wq + (size_t)(384 + unit_batch(cl) * 16 + lane) * HD + unit_head(cl, rank) * DH + wg * 64));
      }
      auto take_role = [&]() {
          if (wg == 0 && rank == 0 && lane == 0) {
            int id = cl;
            if (ncl == 66) {
              uint32_t smid;
              asm("mov.u32 %0, %smid;" : "=r"(smid));
              id = smid >= SMID_TOP ? 65 - atomicAdd(&g_cnt[65 * 8], 1) : atomicAdd(&g_cnt[66 * 8], 1);
            }
    #pragma unroll
            for (int c = 0; c < 2; c++) {
              const uint32_t a = mapa(sb + BAR_ROLE, c);
              asm volatile("st.shared::cluster.u32 [%0 + 8], %1;\nmbarrier.arrive.release.cluster.shared::cluster.b64 _, [%0];" ::"r"(a), "r"(id) : "memory");
            }
          }
          if (wg == 0 && lane == 0) {
            mbar_wait_cl(sb + BAR_ROLE, 0);
            mbar_arrive(sb + BAR_ROLE + 16);
          }
      };
      if (ROLE_AT < 0) { take_role(); __syncwarp(); }
      for (uint32_t it = 0;; it++) {
        const int u = __shfl_sync(~0u, (it >= 3 ? role() : cl) + it * ncl, 0);
        if (u >= NUNITS) break;
        mbar_wait(sb + BAR_LSUM + 8 * wg, it & 1);
        float l4[4], v[4];
        const uint32_t a = sb + OFF_L2 + wg * 2048 + lane * 16;
        asm volatile("ld.shared.v4.f32 {%0, %1, %2, %3}, [%4];" : "=f"(l4[0]), "=f"(l4[1]), "=f"(l4[2]), "=f"(l4[3]) : "r"(a) : "memory");
#pragma unroll
        for (int g = 1; g < 4; g++) {
          asm volatile("ld.shared.v4.f32 {%0, %1, %2, %3}, [%4];" : "=f"(v[0]), "=f"(v[1]), "=f"(v[2]), "=f"(v[3]) : "r"(a + g * 512) : "memory");
#pragma unroll
          for (int c = 0; c < 4; c++) l4[c] += v[c];
        }
#pragma unroll
        for (int c = 0; c < 4; c++) {
          float inv;
          asm("rcp.approx.ftz.f32 %0, %1;" : "=f"(inv) : "f"(l4[c]));
          l4[c] = l4[c] >= L_MIN && l4[c] <= L_MAX ? inv : __uint_as_float(0x7FFFFFFFu);
        }
        const uint32_t h0 = pack(l4[0], l4[1]), h1 = pack(l4[2], l4[3]);
        const uint32_t e0 = pack(l4[0] - __uint_as_float(h0 << 16), l4[1] - __uint_as_float(h0 & 0xFFFF0000u));
        const uint32_t e1 = pack(l4[2] - __uint_as_float(h1 << 16), l4[3] - __uint_as_float(h1 & 0xFFFF0000u));
        const uint32_t ia = sb + OFF_INV + wg * 640 + (lane & 1) * 288 + (lane >> 1) * 8;
        asm volatile("st.shared.v2.u32 [%0], {%1, %2};\nst.shared.v2.u32 [%0 + 144], {%3, %4};" ::"r"(ia), "r"(h0), "r"(e0), "r"(h1), "r"(e1) : "memory");
        __syncwarp();
        if (lane == 0) {
          mbar_arrive(sb + BAR_INV + 8 * wg);
          if ((int)it == ROLE_AT) {
            take_role();
          }
          mbar_wait(sb + BAR_STAGE + 8 * wg, it & 1);
          __threadfence();
          asm volatile("red.relaxed.gpu.global.add.u32 [%0], 1;" ::"l"(&g_cnt[(unit_batch(u) * 4 + (u >> 6)) * 8]) : "memory");
        }
        __syncwarp();
      }
    }
  } else {
    asm volatile("setmaxnreg.inc.sync.aligned.u32 240;");
    const int wg = warp >> 2, w = warp & 3;
    if (PINLANE) lane = __shfl_sync(~0u, lane, lane);
    const uint32_t qreg = sb + OFF_Q + wg * 2 * XB, preg = sb + OFF_P + (2 + wg) * XB;
    const uint32_t st_off = ((lane >> 4) * 8 + (lane & 7)) * 128 + (((2 * w + ((lane >> 3) & 1)) ^ (lane & 7)) << 4);
    const uint32_t xempty = mapa(sb + BAR_XEMPTY, wg);
    Ring r;
    uint32_t it = 0;
    const uint32_t qd = (qreg & 0x3FFFF) >> 4, pd = (preg & 0x3FFFF) >> 4;
    auto ring_addr = [&]() { return ((sb & 0x3FFFF) + r.slot * RING_BYTES) >> 4; };
    auto ring_wait = [&]() { mbar_wait(sb + BAR_RFULL + 8 * r.slot, r.phase); };
    auto release = [&](uint32_t slot) { if (lane == 0) mbar_arrive(sb + BAR_REMPTY + 8 * slot); };
    auto turn_wait = [&]() {
      if (wg == 0) asm volatile("bar.sync 3, 256;" ::: "memory");
      else asm volatile("bar.sync 4, 256;" ::: "memory");
    };
    auto turn_pass = [&]() {
      if (wg == 0) asm volatile("bar.arrive 4, 256;" ::: "memory");
      else asm volatile("bar.arrive 3, 256;" ::: "memory");
    };

    uint32_t chk = 0;
    auto load_inv = [&](uint32_t (&iv)[30], uint32_t parity) {
      mbar_wait(sb + BAR_INV + 8 * wg, parity);
      chk = 0;
#pragma unroll
      for (int j = 0; j < 7; j++)
        asm volatile("ld.shared.v4.u32 {%0, %1, %2, %3}, [%4];" : "=r"(iv[4 * j]), "=r"(iv[4 * j + 1]), "=r"(iv[4 * j + 2]), "=r"(iv[4 * j + 3])
                     : "r"(sb + OFF_INV + wg * 640 + (lane & 3) * 144 + j * 16) : "memory");
      asm volatile("ld.shared.v2.u32 {%0, %1}, [%2];" : "=r"(iv[28]), "=r"(iv[29]) : "r"(sb + OFF_INV + wg * 640 + (lane & 3) * 144 + 112) : "memory");
    };
    auto norm = [&](uint32_t (&n)[8], const uint32_t (&po)[60], const uint32_t (&iv)[30], auto part) {
      constexpr int k = decltype(part)::value >> 1, j0 = (decltype(part)::value & 1) * 8;
#pragma unroll
      for (int j = 0; j < 8; j++)
        n[j] = j0 + j < 15 ? hfma2(po[15 * k + (j0 + j) % 15], iv[2 * ((j0 + j) % 15)], hfma2(po[15 * k + (j0 + j) % 15], iv[2 * ((j0 + j) % 15) + 1], 0x80008000u)) : 0x3F803F80u;
#pragma unroll
      for (int j = 0; j < 8; j += 2) chk = hfma2(n[j], n[j + 1], chk);
    };
    auto store = [&](const uint32_t (&n)[8], const char* optr, auto part) {
      constexpr int k = decltype(part)::value >> 1;
      const char* o = optr + (size_t)(8 * (k & 1) + 64 * (k >> 1)) * NROWS * 2;
      if ((decltype(part)::value & 1) == 0)
        asm volatile(
            "{\n.reg .pred p;\nsetp.ne.u64 p, %9, 0;\n"
            "@p st.global.v4.u32 [%8], {%0, %1, %2, %3};\n@p st.global.v4.u32 [%8 + 64], {%4, %5, %6, %7};\n}\n"
            ::"r"(n[0]), "r"(n[1]), "r"(n[2]), "r"(n[3]), "r"(n[4]), "r"(n[5]), "r"(n[6]), "r"(n[7]),
            "l"(o + (wg ? 288 : 0) + (lane & 3) * 16), "l"(optr) : "memory");
      else
        asm volatile(
            "{\n.reg .pred p;\nsetp.ne.u64 p, %10, 0;\n"
            "@p st.global.v4.u32 [%7 + 128], {%0, %1, %2, %3};\n@p st.global.v2.u32 [%8], {%4, %5};\n@p st.global.u32 [%9], %6;\n}\n"
            ::"r"(n[0]), "r"(n[1]), "r"(n[2]), "r"(n[3]), "r"(n[4]), "r"(n[5]), "r"(n[6]), "l"(o + (wg ? 288 : 0) + (lane & 3) * 16),
            "l"(o + (wg ? 256 : 192) + (lane & 3) * 8), "l"(o + (wg ? 240 : 224) + (lane & 3) * 4), "l"(optr) : "memory");
    };
    auto put = [&](const uint32_t (&po)[60], const uint32_t (&iv)[30], const char* optr, auto part) {
      uint32_t n[8];
      norm(n, po, iv, part);
      store(n, optr, part);
    };
    auto out_ptr = [&](int u) {
      return reinterpret_cast<const char*>(P.o + (size_t)(unit_head(u, rank) * DH + 16 * w + (lane >> 2)) * NROWS + unit_batch(u) * SQ);
    };
    auto unsafe = [&](bool valid) {
      const bool b = valid && ((chk & 0x7F80u) == 0x7F80u || (chk & 0x7F800000u) == 0x7F800000u);
      return __any_sync(~0u, bar_red_or(wg, b));
    };
    auto publish = [&]() { __syncwarp(); if (lane == 0) mbar_arrive(sb + BAR_STAGE + 8 * wg); };

    uint32_t po[60];
#pragma unroll
    for (int i = 0; i < 60; i++) po[i] = 0;
    int id = 0;
    bool more;
    do {
      float o0[60], o1[60];
      uint32_t prev = 0;
      auto qstep = [&](int s, int acc) {
        const uint32_t j = s & 3, par = ((s >> 2) + (j < 2 ? it : 0)) & 1;
        TR(it * 160 + 3 * s);
        ring_wait();
        TR(it * 160 + 3 * s + 1);
        mbar_wait(sb + BAR_XFULL + 32 * wg + 8 * j, par);
        TR(it * 160 + 3 * s + 2);
        if (s >= ALT_FROM) turn_wait();
        wg_fence();
        mma_tn(o0, o1, ring_addr(), ((sb & 0x3FFFF) + OFF_Q + x_slot(wg, j)) >> 4, acc);
        wg_commit();
        if ((s >= ALT_FROM && !(MERGE89 && s == 8)) || (s == ALT_FROM - 1 && wg == 1)) turn_pass();
        if (s > 0) {
          wg_wait<1>();
          release(prev);
          if (s <= 6 && lane == 0) mbar_arrive_cl(xempty + 8 * ((s - 1) & 3));
        }
        prev = r.slot;
        r.next();
      };
      qstep(0, 0);
      const int up = (it > 3 ? id : cl) + ((int)it - 1) * ncl;
      const char* optr = it > 0 ? out_ptr(up) : nullptr;
      uint32_t n7[8];
      {
        uint32_t iv[30];
        qstep(1, 1); load_inv(iv, (it + 1) & 1); put(po, iv, optr, IC<0>());
        qstep(2, 1); put(po, iv, optr, IC<1>());
        qstep(3, 1); put(po, iv, optr, IC<2>());
        qstep(4, 1); put(po, iv, optr, IC<3>());
        qstep(5, 1); put(po, iv, optr, IC<4>());
        qstep(6, 1); put(po, iv, optr, IC<5>());
        qstep(7, 1); put(po, iv, optr, IC<6>());
        norm(n7, po, iv, IC<7>());
        if (LATE_AT == 3) store(n7, optr, IC<7>());
        qstep(8, 1);
        if (LATE_AT == 2) store(n7, optr, IC<7>());
      }
      TR(it * 160 + 27);
      ring_wait();
      TR(it * 160 + 28);
      mbar_wait(sb + BAR_XFULL + 32 * wg + 8, it & 1);
      TR(it * 160 + 29);
      if (!MERGE89) turn_wait();
      wg_fence();
      mma_tn_split(o0, o1, ring_addr(), qd + (XB >> 4));
      turn_pass();
      wg_wait<2>();
      release(prev);
      auto put_q = [&](const float (&o)[60], uint32_t dst) {
        bar_sync(wg);
#pragma unroll
        for (int j = 0; j < 14; j += 2)
          stsm4t(dst + j * 1024, pack(o[4 * j] * QSCALE, o[4 * j + 1] * QSCALE), pack(o[4 * j + 2] * QSCALE, o[4 * j + 3] * QSCALE),
                 pack(o[4 * j + 4] * QSCALE, o[4 * j + 5] * QSCALE), pack(o[4 * j + 6] * QSCALE, o[4 * j + 7] * QSCALE));
        stsm2t(dst + 14 * 1024, pack(o[56] * QSCALE, o[57] * QSCALE), pack(o[58] * QSCALE, o[59] * QSCALE));
      };
      wg_wait<1>();
      reg_fence(o0);
      put_q(o0, qreg + st_off);
      wg_wait<0>();
      reg_fence(o1);
      release(r.slot);
      r.next();
      TR(it * 160 + 30);
      put_q(o1, qreg + XB + st_off);
      fence_async_smem();
      if (unsafe(it > 0)) {
        slow_path(P, unit_batch(up), unit_head(up, rank), wg, w, lane);
        optr = nullptr;
        if (!DPRO) {
#pragma unroll
          for (int i = 0; i < 60; i++) o0[i] = o1[i] = 0.f;
        }
      }
      TR(it * 160 + 32); TG(it * 160 + 142);

      float sc[60], l[30];
      ring_wait();
      TR(it * 160 + 33);
      turn_wait();
      wg_fence();
      mma_qk(sc, ring_addr(), qd);
      wg_commit();
      turn_pass();
      if (LATE_AT < 2) store(n7, optr, IC<7>());
      if (it > 0) publish();
      if (it >= 2) id = __shfl_sync(~0u, role(), 0);
      wg_wait<0>();
      reg_fence(sc);
      TR(it * 160 + 35);
      release(r.slot);
      r.next();
      exp_store<0, 15, true>(sc, l, preg + st_off);
      fence_async_smem();
      more = id + ((int)it + 1) * ncl < NUNITS;
      const bool gemm = id < nsingle || (ncl == 66 && id >= 58);
#pragma unroll 1
      for (int s = DPRO ? 3 : 1; s < 16; s++) {
        const uint32_t kslot = r.slot;
        TR(it * 160 + 32 + 6 * s); TG(it * 160 + 37 + 6 * s);
        ring_wait();
        TR(it * 160 + 33 + 6 * s);
        turn_wait();
        wg_fence();
        mma_qk(sc, ring_addr(), qd);
        wg_commit();
        r.next();
        const bool pv = !ASYM || wg == 1 || s < 15;
        TR(it * 160 + 36 + 6 * s);
        if (pv) {
          ring_wait();
          TR(it * 160 + 34 + 6 * s);
          wg_fence();
          mma_tn(o0, o1, ring_addr(), pd - ((s - 1) & 1) * (2 * XB >> 4), DPRO || s != 1);
          wg_commit();
          if (ASYM || wg == 0 || s < 15) turn_pass();
          wg_wait<1>();
        } else {
          turn_pass();
          wg_wait<0>();
        }
        reg_fence(sc);
        TR(it * 160 + 35 + 6 * s);
        release(kslot);
        if (s == 15) {
          if (more) { if (lane < 2 - ASYM) mbar_arrive_cl(xempty + 8 * lane); }
          else if (!ASYM && lane < 3 && gemm) mbar_arrive_cl(mapa(sb + BAR_BEMPTY + 8 * lane, lane & 1));
        }
        exp_store<0, VREL>(sc, l, preg - (s & 1) * 2 * XB + st_off);
        wg_wait<0>();
        reg_fence(o0); reg_fence(o1);
        if (pv) { release(r.slot); r.next(); }
        exp_store<VREL, 15>(sc, l, preg - (s & 1) * 2 * XB + st_off);
        fence_async_smem();
      }
      if (!ASYM) bar_sync(wg);
      TR(it * 160 + 128);
      const uint32_t lscr = ASYM ? qreg + XB : preg;
      auto put_l = [&]() {
        const uint32_t a = lscr + (8 * w + (lane >> 2)) * 480 + (lane & 3) * 8;
#pragma unroll
        for (int j = 0; j < 15; j++) asm volatile("st.shared.v2.f32 [%0], {%1, %2};" ::"r"(a + j * 32), "f"(l[2 * j]), "f"(l[2 * j + 1]) : "memory");
      };
      const uint32_t v14 = r.slot;
      if (ASYM && wg == 0) {
        const uint32_t a14 = ring_addr();
        ring_wait();
        r.next();
        ring_wait();
        turn_wait();
        wg_fence();
#pragma unroll
        for (int k = 0; k < 4; k++) wgmma_n120<1, 0>(o0, a14 + k * 128, HI128, pd + k * 2, HI128, 1);
#pragma unroll
        for (int k = 0; k < 4; k++) wgmma_n120<1, 0>(o0, ring_addr() + k * 128, HI128, pd - (2 * XB >> 4) + k * 2, HI128, 1);
        wg_commit();
        put_l();
        wg_fence();
#pragma unroll
        for (int k = 0; k < 4; k++) wgmma_n120<1, 0>(o1, a14 + 512 + k * 128, HI128, pd + k * 2, HI128, 1);
#pragma unroll
        for (int k = 0; k < 4; k++) wgmma_n120<1, 0>(o1, ring_addr() + 512 + k * 128, HI128, pd - (2 * XB >> 4) + k * 2, HI128, 1);
        wg_commit();
        if (ASYM_PASS == 0) turn_pass();
      } else {
        ring_wait();
        if (ASYM) turn_wait();
        wg_fence();
        mma_tn_split(o0, o1, ring_addr(), pd - (2 * XB >> 4));
        put_l();
      }
      TR(it * 160 + 132);
      __syncwarp();
      float lv[8][4];
#pragma unroll
      for (int g = 0; g < 8; g++)
        asm volatile("ld.shared.v4.f32 {%0, %1, %2, %3}, [%4];" : "=f"(lv[g][0]), "=f"(lv[g][1]), "=f"(lv[g][2]), "=f"(lv[g][3])
                     : "r"(lscr + (8 * w + g) * 480 + min(lane, 29) * 16) : "memory");
      if (ASYM && ASYM_PASS == 1 && wg == 0) turn_pass();
      TR(it * 160 + 133);
      wg_wait<1>();
      reg_fence(o0);
      TR(it * 160 + 134);
#pragma unroll
      for (int j = 0; j < 15; j++) { po[j] = pack(o0[4 * j], o0[4 * j + 1]); po[15 + j] = pack(o0[4 * j + 2], o0[4 * j + 3]); }
#pragma unroll
      for (int c = 0; c < 4; c++) lv[0][c] = ((lv[0][c] + lv[1][c]) + (lv[2][c] + lv[3][c])) + ((lv[4][c] + lv[5][c]) + (lv[6][c] + lv[7][c]));
      asm volatile("st.shared.v4.f32 [%0], {%1, %2, %3, %4};" ::"r"(sb + OFF_L2 + wg * 2048 + w * 512 + lane * 16), "f"(lv[0][0]), "f"(lv[0][1]),
                   "f"(lv[0][2]), "f"(lv[0][3]) : "memory");
      __syncwarp();
      if (lane == 0) mbar_arrive(sb + BAR_LSUM + 8 * wg);
      if (ASYM) {
        if (more) { if (lane == 0) mbar_arrive_cl(xempty + 8); }
        else if (lane < 3 && gemm) mbar_arrive_cl(mapa(sb + BAR_BEMPTY + 8 * lane, lane & 1));
      }
      wg_wait<0>();
      reg_fence(o1);
      if (ASYM && wg == 0) release(v14);
      release(r.slot);
      r.next();
      if (more) { if (lane < 2) mbar_arrive_cl(xempty + 16 + 8 * lane); }
      else if (gemm && lane < 3) mbar_arrive_cl(mapa(sb + BAR_BEMPTY + 24 + 8 * lane, (lane + 1) & 1));
      TR(it * 160 + 130);
#pragma unroll
      for (int j = 0; j < 15; j++) { po[30 + j] = pack(o1[4 * j], o1[4 * j + 1]); po[45 + j] = pack(o1[4 * j + 2], o1[4 * j + 3]); }
      TR(it * 160 + 131); TG(it * 160 + 143);
      it++;
    } while (more);
    const bool gemm = id < nsingle || (ncl == 66 && id >= 58);
    const int u = (it > 3 ? id : cl) + ((int)it - 1) * ncl;
    lane = __shfl_sync(~0u, lane, lane);
    uint32_t pb[60];
#pragma unroll
    for (int i = 0; i < 60; i++) pb[i] = po[i] ^ (gridDim.y - 1);

    uint32_t bslot = 0, bphase = 0;
    auto out_tile = [&](const float (&acc)[80], int t) {
      const uint32_t st = sb + w * RING_BYTES + wg * 8192;
      const uint32_t sa = st + (lane & 15) * 336 + (lane >> 4) * 16;
#pragma unroll
      for (int j = 0; j < 20; j += 2)
        asm volatile("stmatrix.sync.aligned.m8n8.x4.shared.b16 [%0], {%1,%2,%3,%4};" ::"r"(sa + j * 16), "r"(pack(acc[4 * j], acc[4 * j + 1])),
                     "r"(pack(acc[4 * j + 2], acc[4 * j + 3])), "r"(pack(acc[4 * j + 4], acc[4 * j + 5])), "r"(pack(acc[4 * j + 6], acc[4 * j + 7])) : "memory");
      fence_async_smem();
      __syncwarp();
      if (lane < 16) {
        __nv_bfloat16* dst = P.out + (size_t)o_row(row_block(t) * 256 + rank * 128 + wg * 64 + w * 16 + lane) * DM + (t & 3) * 160;
        asm volatile("cp.async.bulk.global.shared::cta.bulk_group [%0], [%1], 320;" ::"l"(dst), "r"(st + lane * 336) : "memory");
        asm volatile("cp.async.bulk.commit_group;" ::: "memory");
        asm volatile("cp.async.bulk.wait_group.read 0;" ::: "memory");
      }
      __syncwarp();
    };
    for (int t = id; t < nsingle || t == id; t += ncl) {
      float acc[80];
      uint32_t prev = 0, bprev = 0;
      const bool tile = t < nsingle;
      const bool last = t + ncl >= nsingle;
      auto bstep = [&](int ks, int accf) {
        if (!(ks & 3)) TR(640 + ks / 2); if ((ks & 7) == 0) TG(144 + (ks >> 3));
        ring_wait();
        mbar_wait(sb + BAR_BFULL + 8 * bslot, bphase);
        if (!(ks & 3)) TR(641 + ks / 2);
        wg_fence();
        const uint32_t a = ring_addr() + wg * 512, bd = (((sb & 0x3FFFF) + OFF_Q + bslot * BB) >> 4) | ((4096u >> 4) << 16);
#pragma unroll
        for (int k = 0; k < 4; k++) wgmma_n160<1, 1>(acc, a + k * 128, HI128, bd + k * 64, HI64, k == 0 ? accf : 1);
        wg_commit();
        if (ks > 0) {
          wg_wait<1>();
          release(prev);
          if (lane == 0 && (ks < 59 || !last)) mbar_arrive_cl(mapa(sb + BAR_BEMPTY + 8 * bprev, bprev & 1));
        }
        prev = r.slot; bprev = bslot;
        r.next();
        if (++bslot == 6) { bslot = 0; bphase ^= 1; }
      };
      const char* optr = t == id ? out_ptr(u) : nullptr;
      uint32_t iv[30];
      if (tile) {
        bstep(0, 0);
        bstep(1, 1);
        load_inv(iv, (it + 1) & 1);
#pragma unroll 1
        for (int ks = 2; ks < 17; ks++) {
          bstep(ks, 1);
          switch (ks) {
            case 2: put(pb, iv, optr, IC<0>()); break;
            case 4: put(pb, iv, optr, IC<1>()); break;
            case 6: put(pb, iv, optr, IC<2>()); break;
            case 8: put(pb, iv, optr, IC<3>()); break;
            case 10: put(pb, iv, optr, IC<4>()); break;
            case 12: put(pb, iv, optr, IC<5>()); break;
            case 14: put(pb, iv, optr, IC<6>()); break;
            case 16: put(pb, iv, optr, IC<7>()); break;
            default: break;
          }
        }
        wg_wait<0>();
        reg_fence(acc);
      } else {
        Ring r2 = r;
        auto first = [&](int ks) {
          if (ks == 0) { TR(640); TG(144); }
          if (gemm) { mbar_wait(sb + BAR_RFULL + 8 * r2.slot, r2.phase); mbar_wait(sb + BAR_BFULL + 16 * ks, 0); }
          wg_fence();
          const uint32_t a = (((sb & 0x3FFFF) + r2.slot * RING_BYTES) >> 4) + wg * 512;
          const uint32_t bd = (((sb & 0x3FFFF) + OFF_Q + 2 * ks * BB) >> 4) | ((4096u >> 4) << 16);
#pragma unroll
          for (int k = 0; k < 4; k++) wgmma_n160<1, 1>(acc, a + k * 128, HI128, bd + k * 64, HI64, k + ks != 0);
          wg_commit();
          if (ks > 0) {
            wg_wait<1>();
            if (gemm && lane == 0) mbar_arrive_cl(mapa(sb + BAR_BEMPTY + 16 * (ks - 1), 0));
          }
          r2.next();
        };
        first(0);
        load_inv(iv, (it + 1) & 1);
        put(pb, iv, optr, IC<0>()); put(pb, iv, optr, IC<1>());
        first(1);
        put(pb, iv, optr, IC<2>()); put(pb, iv, optr, IC<3>()); put(pb, iv, optr, IC<4>());
        first(2);
        put(pb, iv, optr, IC<5>()); put(pb, iv, optr, IC<6>()); put(pb, iv, optr, IC<7>());
        wg_wait<0>();
        reg_fence(acc);
      }
      if (unsafe(t == id)) slow_path(P, unit_batch(u), unit_head(u, rank), wg, w, lane);
      if (t == id) publish();
      if (!tile) {
        if (gemm) {
          float ac1[80];
          auto half = [&](float (&ac)[80], bool rel, int accf) {
            mbar_wait(sb + BAR_BFULL + 8 * bslot, bphase);
            wg_fence();
            const uint32_t a = ring_addr() + wg * 512, bd = (((sb & 0x3FFFF) + OFF_Q + bslot * BB) >> 4) | ((4096u >> 4) << 16);
#pragma unroll
            for (int k = 0; k < 4; k++) wgmma_n160<1, 1>(ac, a + k * 128, HI128, bd + k * 64, HI64, k == 0 ? accf : 1);
            wg_commit();
            wg_wait<1>();
            if (lane == 0 && rel) mbar_arrive_cl(mapa(sb + BAR_BEMPTY + 8 * bprev, bprev & 1));
            bprev = bslot;
          };
          bprev = 4; bslot = 1;
          half(ac1, true, 0);
          prev = r.slot; r.next(); bslot = 3;
          half(ac1, true, 1);
          release(prev); prev = r.slot; r.next(); bslot = 5;
          half(ac1, true, 1);
          release(prev); prev = r.slot; r.next(); bslot = 0; bphase = 1;
#pragma unroll 1
          for (int ks = 3; ks < 64; ks++) {
            if (wg == 1 && ks == 62) turn_wait();
            if (!(ks & 3)) TR(640 + ks / 2); if ((ks & 7) == 0) TG(144 + (ks >> 3));
            ring_wait();
            if (!(ks & 3)) TR(641 + ks / 2);
            half(acc, ks < 62, 1);
            release(prev);
            bslot++;
            half(ac1, ks < 61, 1);
            if (++bslot == 6) { bslot = 0; bphase ^= 1; }
            prev = r.slot; r.next();
          }
          if (wg == 0) turn_pass();
          wg_wait<0>();
          reg_fence(acc); reg_fence(ac1);
          TR(158); TG(156);
          bar_sync(wg);
          out_tile(acc, 2 * id - 72);
          out_tile(ac1, 2 * id - 71);
        }
        break;
      }
#pragma unroll 1
      for (int ks = 17; ks < 64; ks++) {
        if (END_SKEW && wg == 1 && ks == 64 - END_SKEW) turn_wait();
        bstep(ks, 1);
      }
      if (END_SKEW && wg == 0) turn_pass();
      wg_wait<0>();
      reg_fence(acc);
      release(prev);
      if (lane == 0 && !last) mbar_arrive_cl(mapa(sb + BAR_BEMPTY + 8 * bprev, bprev & 1));
      TR(158); TG(156);
      const int pos0 = row_block(t) * 256 + rank * 128 + wg * 64 + w * 16;
      if (last) {
        bar_sync(wg);
        out_tile(acc, t);
      } else {
        __nv_bfloat16* op0 = P.out + (size_t)o_row(pos0 + (lane >> 2)) * DM + (t & 3) * 160 + (lane & 3) * 2;
        __nv_bfloat16* op1 = P.out + (size_t)o_row(pos0 + (lane >> 2) + 8) * DM + (t & 3) * 160 + (lane & 3) * 2;
#pragma unroll
        for (int j = 0; j < 20; j++) {
          *reinterpret_cast<uint32_t*>(op0 + j * 8) = pack(acc[4 * j], acc[4 * j + 1]);
          *reinterpret_cast<uint32_t*>(op1 + j * 8) = pack(acc[4 * j + 2], acc[4 * j + 3]);
        }
      }
#pragma unroll
      for (int i = 0; i < 60; i++) pb[i] = 0;
    }
    TR(159);
  }
}

typedef CUresult (*EncodeFn)(CUtensorMap*, CUtensorMapDataType, cuuint32_t, void*, const cuuint64_t*, const cuuint64_t*,
                             const cuuint32_t*, const cuuint32_t*, CUtensorMapInterleave, CUtensorMapSwizzle,
                             CUtensorMapL2promotion, CUtensorMapFloatOOBfill);

void make_map(EncodeFn enc, CUtensorMap* m, const void* p, int rank, const cuuint64_t* dims, const cuuint64_t* strides,
              const cuuint32_t* box, CUtensorMapSwizzle sw, CUtensorMapL2promotion promo) {
  cuuint32_t es[3] = {1, 1, 1};
  enc(m, CU_TENSOR_MAP_DATA_TYPE_BFLOAT16, rank, const_cast<void*>(p), dims, strides, box, es, CU_TENSOR_MAP_INTERLEAVE_NONE, sw,
      promo, CU_TENSOR_MAP_FLOAT_OOB_FILL_NONE);
}

}

extern "C" void kernel_launch(void* const* d_in, const int* in_sizes, int n_in, void* d_out, int out_size) {
  static EncodeFn enc = nullptr;
  static int nclusters = 0;
  static void* o_ptr = nullptr;
  if (!enc) {
    cudaDriverEntryPointQueryResult qr;
    cudaGetDriverEntryPoint("cuTensorMapEncodeTiled", (void**)&enc, cudaEnableDefault, &qr);
    cudaFuncSetAttribute(fused_attn_kernel, cudaFuncAttributeMaxDynamicSharedMemorySize, SMEM_BYTES);
    cudaGetSymbolAddress(&o_ptr, g_o);
    cudaLaunchConfig_t cfg = {};
    cfg.gridDim = 128; cfg.blockDim = 384; cfg.dynamicSmemBytes = SMEM_BYTES;
    cudaLaunchAttribute at; at.id = cudaLaunchAttributeClusterDimension;
    at.val.clusterDim.x = 2; at.val.clusterDim.y = 1; at.val.clusterDim.z = 1;
    cfg.attrs = &at; cfg.numAttrs = 1;
    int n = 0;
    cudaOccupancyMaxActiveClusters(&n, fused_attn_kernel, &cfg);
    nclusters = n >= 66 ? MAXCL : (n >= 64 || n <= 0 ? 64 : n);
  }
  const __nv_bfloat16* x = (const __nv_bfloat16*)d_in[0];
  const __nv_bfloat16* k = (const __nv_bfloat16*)d_in[1];
  const __nv_bfloat16* v = (const __nv_bfloat16*)d_in[2];
  const __nv_bfloat16* wq = (const __nv_bfloat16*)d_in[3];
  const __nv_bfloat16* wo = (const __nv_bfloat16*)d_in[4];
  CUtensorMap tm_x, tm_wq, tm_k, tm_v, tm_o, tm_wo;
  const auto S128 = CU_TENSOR_MAP_SWIZZLE_128B;
  const auto P128 = CU_TENSOR_MAP_L2_PROMOTION_L2_128B, P256 = CU_TENSOR_MAP_L2_PROMOTION_L2_256B;
  { cuuint64_t d[2] = {DM, NB * SQ}, s[1] = {DM * 2}; cuuint32_t b[2] = {64, 120}; make_map(enc, &tm_x, x, 2, d, s, b, S128, X_PROMO); }
  { cuuint64_t d[3] = {64, DM, HD / 64}, s[2] = {HD * 2, 128}; cuuint32_t b[3] = {64, 64, 2}; make_map(enc, &tm_wq, wq, 3, d, s, b, S128, P256); }
  { cuuint64_t d[3] = {64, NB * NH * SK, 2}, s[2] = {DH * 2, 128}; cuuint32_t b[3] = {64, 64, 2};
    make_map(enc, &tm_k, k, 3, d, s, b, S128, P128); make_map(enc, &tm_v, v, 3, d, s, b, S128, P128); }
  { cuuint64_t d[3] = {64, HD, NROWS / 64}, s[2] = {NROWS * 2, 128}; cuuint32_t b[3] = {64, 64, 2}; make_map(enc, &tm_o, o_ptr, 3, d, s, b, S128, P256); }
  { cuuint64_t d[3] = {32, HD, DM / 32}, s[2] = {DM * 2, 64}; cuuint32_t b[3] = {32, 64, 5};
    make_map(enc, &tm_wo, wo, 3, d, s, b, CU_TENSOR_MAP_SWIZZLE_64B, P128); }
  Params P{x, k, v, wq, (__nv_bfloat16*)d_out, (__nv_bfloat16*)o_ptr};
  fused_attn_kernel<<<2 * nclusters, 384, SMEM_BYTES>>>(tm_x, tm_wq, tm_k, tm_v, tm_o, tm_wo, P);
}
```

```cpp
#include <cuda_runtime.h>
#include <cuda.h>
#include <cuda_bf16.h>
#include <stdint.h>

namespace {

constexpr int NB = 16, SQ = 240, DM = 640, NH = 32, SK = 1024, DH = 128, HD = NH * DH;
constexpr int NROWS = NB * SQ;
constexpr int NUNITS = 256;
#define DPRO 0
#define LATE_AT 0
#define ALT_FROM 3
#define MERGE89 1
#define END_SKEW 5
#define VREL 8
#define PF_HOLD 6
#define PF_N 4
#define PF_J0 3
#define PF_STEP 3
#define ROT 0
#define O_EF 1
#define B_ORDER 1
#define WO_PF 6
#define ROLE_AT 0
#define PAUSE_NS 11000
#define PAUSE_AT 2
#define EARLY 1
#define EARLY_X 2
#define EARLY_W 2
#define X_PROMO P128
#define PAUSE_J -1
#define PAUSE_SPREAD 0
#define ASYM 0
#define ASYM_PASS 1
#define PINLANE 0
#define MAXCL 66
#define SMID_TOP 88
constexpr int NOTILES = 60;
constexpr float QSCALE = 0.08838834764831845f * 1.4426950408889634f;
constexpr float L_MIN = 9.5367431640625e-07f;
constexpr float L_MAX = 1.152921504606846976e18f;

constexpr uint32_t RING_SLOTS = 6, RING_BYTES = 16384;
constexpr uint32_t XB = 15360;
constexpr uint32_t BB = 20480;
constexpr uint32_t OFF_Q = RING_SLOTS * RING_BYTES;
constexpr uint32_t OFF_P = OFF_Q + 4 * XB;
constexpr uint32_t OFF_INV = OFF_P + 4 * XB;
constexpr uint32_t OFF_L2 = OFF_INV + 1280;
constexpr uint32_t OFF_BAR = OFF_L2 + 4096;
constexpr uint32_t BAR_RFULL = OFF_BAR, BAR_REMPTY = BAR_RFULL + 48, BAR_XFULL = BAR_REMPTY + 48,
    BAR_XEMPTY = BAR_XFULL + 64, BAR_BFULL = BAR_XEMPTY + 32, BAR_BEMPTY = BAR_BFULL + 48, BAR_STAGE = BAR_BEMPTY + 48;
constexpr uint32_t BAR_ROLE = BAR_STAGE + 16, BAR_LSUM = BAR_ROLE + 24, BAR_INV = BAR_LSUM + 16;
constexpr uint32_t OFF_TR = BAR_INV + 16;
constexpr uint32_t SMEM_BYTES = OFF_TR + 1024;

constexpr uint32_t HI128 = (1u << 30) | (1024 >> 4);
constexpr uint32_t HI64 = (2u << 30) | (512 >> 4);

__device__ __nv_bfloat16 g_o[HD * NROWS];
__device__ unsigned g_cnt[67 * 8];
#define TS(i)
#define TR(i)
#define TG(i)

struct Params {
  const __nv_bfloat16 *x, *k, *v, *wq;
  __nv_bfloat16 *out, *o;
};

__device__ __forceinline__ void wg_fence() { asm volatile("wgmma.fence.sync.aligned;" ::: "memory"); }
__device__ __forceinline__ void wg_commit() { asm volatile("wgmma.commit_group.sync.aligned;" ::: "memory"); }
template <int N> __device__ __forceinline__ void wg_wait() { asm volatile("wgmma.wait_group.sync.aligned %0;" ::"n"(N) : "memory"); }
template <int N> __device__ __forceinline__ void reg_fence(float (&r)[N]) {
#pragma unroll
  for (int i = 0; i < N; i++) asm volatile("" : "+f"(r[i])::"memory");
}
template <int TA, int TB>
__device__ __forceinline__ void wgmma_n120(float (&d)[60], uint32_t a_lo, uint32_t a_hi, uint32_t b_lo, uint32_t b_hi, int acc) {
  asm volatile(
      "{\n.reg .pred p;\n.reg .b64 da, db;\nsetp.ne.b32 p, %64, 0;\n"
      "mov.b64 da, {%60, %61};\nmov.b64 db, {%62, %63};\n"
      "wgmma.mma_async.sync.aligned.m64n120k16.f32.bf16.bf16 {"
      "%0, %1, %2, %3, %4, %5, %6, %7, %8, %9, %10, %11, %12, %13, %14, %15, %16, %17, %18, %19, %20, %21, %22, %23, "
      "%24, %25, %26, %27, %28, %29, %30, %31, %32, %33, %34, %35, %36, %37, %38, %39, %40, %41, %42, %43, %44, %45, "
      "%46, %47, %48, %49, %50, %51, %52, %53, %54, %55, %56, %57, %58, %59"
      "}, da, db, p, 1, 1, %65, %66;\n}\n"
      : "+f"(d[0]), "+f"(d[1]), "+f"(d[2]), "+f"(d[3]), "+f"(d[4]), "+f"(d[5]), "+f"(d[6]), "+f"(d[7]), "+f"(d[8]),
        "+f"(d[9]), "+f"(d[10]), "+f"(d[11]), "+f"(d[12]), "+f"(d[13]), "+f"(d[14]), "+f"(d[15]), "+f"(d[16]),
        "+f"(d[17]), "+f"(d[18]), "+f"(d[19]), "+f"(d[20]), "+f"(d[21]), "+f"(d[22]), "+f"(d[23]), "+f"(d[24]),
        "+f"(d[25]), "+f"(d[26]), "+f"(d[27]), "+f"(d[28]), "+f"(d[29]), "+f"(d[30]), "+f"(d[31]), "+f"(d[32]),
        "+f"(d[33]), "+f"(d[34]), "+f"(d[35]), "+f"(d[36]), "+f"(d[37]), "+f"(d[38]), "+f"(d[39]), "+f"(d[40]),
        "+f"(d[41]), "+f"(d[42]), "+f"(d[43]), "+f"(d[44]), "+f"(d[45]), "+f"(d[46]), "+f"(d[47]), "+f"(d[48]),
        "+f"(d[49]), "+f"(d[50]), "+f"(d[51]), "+f"(d[52]), "+f"(d[53]), "+f"(d[54]), "+f"(d[55]), "+f"(d[56]),
        "+f"(d[57]), "+f"(d[58]), "+f"(d[59])
      : "r"(a_lo), "r"(a_hi), "r"(b_lo), "r"(b_hi), "r"(acc), "n"(TA), "n"(TB));
}

template <int TA, int TB>
__device__ __forceinline__ void wgmma_n160(float (&d)[80], uint32_t a_lo, uint32_t a_hi, uint32_t b_lo, uint32_t b_hi, int acc) {
  asm volatile(
      "{\n.reg .pred p;\n.reg .b64 da, db;\nsetp.ne.b32 p, %84, 0;\n"
      "mov.b64 da, {%80, %81};\nmov.b64 db, {%82, %83};\n"
      "wgmma.mma_async.sync.aligned.m64n160k16.f32.bf16.bf16 {"
      "%0, %1, %2, %3, %4, %5, %6, %7, %8, %9, %10, %11, %12, %13, %14, %15, %16, %17, %18, %19, %20, %21, %22, %23, "
      "%24, %25, %26, %27, %28, %29, %30, %31, %32, %33, %34, %35, %36, %37, %38, %39, %40, %41, %42, %43, %44, %45, "
      "%46, %47, %48, %49, %50, %51, %52, %53, %54, %55, %56, %57, %58, %59, %60, %61, %62, %63, %64, %65, %66, %67, "
      "%68, %69, %70, %71, %72, %73, %74, %75, %76, %77, %78, %79"
      "}, da, db, p, 1, 1, %85, %86;\n}\n"
      : "+f"(d[0]), "+f"(d[1]), "+f"(d[2]), "+f"(d[3]), "+f"(d[4]), "+f"(d[5]), "+f"(d[6]), "+f"(d[7]), "+f"(d[8]),
        "+f"(d[9]), "+f"(d[10]), "+f"(d[11]), "+f"(d[12]), "+f"(d[13]), "+f"(d[14]), "+f"(d[15]), "+f"(d[16]),
        "+f"(d[17]), "+f"(d[18]), "+f"(d[19]), "+f"(d[20]), "+f"(d[21]), "+f"(d[22]), "+f"(d[23]), "+f"(d[24]),
        "+f"(d[25]), "+f"(d[26]), "+f"(d[27]), "+f"(d[28]), "+f"(d[29]), "+f"(d[30]), "+f"(d[31]), "+f"(d[32]),
        "+f"(d[33]), "+f"(d[34]), "+f"(d[35]), "+f"(d[36]), "+f"(d[37]), "+f"(d[38]), "+f"(d[39]), "+f"(d[40]),
        "+f"(d[41]), "+f"(d[42]), "+f"(d[43]), "+f"(d[44]), "+f"(d[45]), "+f"(d[46]), "+f"(d[47]), "+f"(d[48]),
        "+f"(d[49]), "+f"(d[50]), "+f"(d[51]), "+f"(d[52]), "+f"(d[53]), "+f"(d[54]), "+f"(d[55]), "+f"(d[56]),
        "+f"(d[57]), "+f"(d[58]), "+f"(d[59]), "+f"(d[60]), "+f"(d[61]), "+f"(d[62]), "+f"(d[63]), "+f"(d[64]),
        "+f"(d[65]), "+f"(d[66]), "+f"(d[67]), "+f"(d[68]), "+f"(d[69]), "+f"(d[70]), "+f"(d[71]), "+f"(d[72]),
        "+f"(d[73]), "+f"(d[74]), "+f"(d[75]), "+f"(d[76]), "+f"(d[77]), "+f"(d[78]), "+f"(d[79])
      : "r"(a_lo), "r"(a_hi), "r"(b_lo), "r"(b_hi), "r"(acc), "n"(TA), "n"(TB));
}
__device__ __forceinline__ void mbar_init(uint32_t bar, int cnt) { asm volatile("mbarrier.init.shared::cta.b64 [%0], %1;" ::"r"(bar), "r"(cnt)); }
__device__ __forceinline__ void mbar_expect(uint32_t bar, uint32_t bytes) {
  asm volatile("mbarrier.arrive.expect_tx.shared::cta.b64 _, [%0], %1;" ::"r"(bar), "r"(bytes) : "memory");
}
__device__ __forceinline__ uint32_t mapa(uint32_t addr, uint32_t cta) {
  uint32_t r; asm("mapa.shared::cluster.u32 %0, %1, %2;" : "=r"(r) : "r"(addr), "r"(cta)); return r;
}
__device__ __forceinline__ void mbar_expect_cl(uint32_t cbar, uint32_t bytes) {
  asm volatile("mbarrier.arrive.expect_tx.shared::cluster.b64 _, [%0], %1;" ::"r"(cbar), "r"(bytes) : "memory");
}
__device__ __forceinline__ void mbar_arrive(uint32_t bar) { asm volatile("mbarrier.arrive.shared::cta.b64 _, [%0];" ::"r"(bar) : "memory"); }
__device__ __forceinline__ void mbar_arrive_cl(uint32_t cbar) { asm volatile("mbarrier.arrive.shared::cluster.b64 _, [%0];" ::"r"(cbar) : "memory"); }
__device__ __forceinline__ void mbar_wait(uint32_t bar, uint32_t parity) {
  asm volatile(
      "{\n.reg .pred p;\n.reg .u32 n;\n"
      "mbarrier.try_wait.parity.shared::cta.b64 p, [%0], %1;\n@p bra WAIT_DONE;\n"
      "mov.u32 n, 0;\n"
      "WAIT_LOOP:\n"
      "mbarrier.try_wait.parity.shared::cta.b64 p, [%0], %1;\n@p bra WAIT_DONE;\n"
      "add.u32 n, n, 1;\nsetp.lt.u32 p, n, 0x4000000;\n@p bra WAIT_LOOP;\ntrap;\n"
      "WAIT_DONE:\n}\n" ::"r"(bar), "r"(parity) : "memory");
}
__device__ __forceinline__ void mbar_wait_cl(uint32_t bar, uint32_t parity) {
  asm volatile(
      "{\n.reg .pred p;\n.reg .u32 n;\nmov.u32 n, 0;\n"
      "WAIT_LOOP:\n"
      "mbarrier.try_wait.parity.acquire.cluster.shared::cta.b64 p, [%0], %1;\n@p bra WAIT_DONE;\n"
      "add.u32 n, n, 1;\nsetp.lt.u32 p, n, 0x4000000;\n@p bra WAIT_LOOP;\ntrap;\n"
      "WAIT_DONE:\n}\n" ::"r"(bar), "r"(parity) : "memory");
}
__device__ __forceinline__ void tma3d(uint32_t dst, const CUtensorMap* m, int c0, int c1, int c2, uint32_t bar) {
  asm volatile("cp.async.bulk.tensor.3d.shared::cluster.global.mbarrier::complete_tx::bytes [%0], [%1, {%3, %4, %5}], [%2];"
               ::"r"(dst), "l"(m), "r"(bar), "r"(c0), "r"(c1), "r"(c2) : "memory");
}
__device__ __forceinline__ void tma3d_hint(uint32_t dst, const CUtensorMap* m, int c0, int c1, int c2, uint32_t bar, uint64_t pol) {
  asm volatile("cp.async.bulk.tensor.3d.shared::cluster.global.mbarrier::complete_tx::bytes.L2::cache_hint [%0], [%1, {%3, %4, %5}], [%2], %6;"
               ::"r"(dst), "l"(m), "r"(bar), "r"(c0), "r"(c1), "r"(c2), "l"(pol) : "memory");
}
__device__ __forceinline__ void tma2d_mc(uint32_t dst, const CUtensorMap* m, int c0, int c1, uint32_t bar) {
  asm volatile("cp.async.bulk.tensor.2d.shared::cluster.global.mbarrier::complete_tx::bytes.multicast::cluster [%0], [%1, {%3, %4}], [%2], %5;"
               ::"r"(dst), "l"(m), "r"(bar), "r"(c0), "r"(c1), "h"((uint16_t)3) : "memory");
}
__device__ __forceinline__ void tma3d_mc(uint32_t dst, const CUtensorMap* m, int c0, int c1, int c2, uint32_t bar) {
  asm volatile("cp.async.bulk.tensor.3d.shared::cluster.global.mbarrier::complete_tx::bytes.multicast::cluster [%0], [%1, {%3, %4, %5}], [%2], %6;"
               ::"r"(dst), "l"(m), "r"(bar), "r"(c0), "r"(c1), "r"(c2), "h"((uint16_t)3) : "memory");
}
__device__ __forceinline__ void l2_prefetch(const void* p, uint32_t bytes) {
  asm volatile("cp.async.bulk.prefetch.L2.global [%0], %1;" ::"l"(p), "r"(bytes) : "memory");
}
__device__ __forceinline__ void fence_async_smem() { asm volatile("fence.proxy.async.shared::cta;" ::: "memory"); }
__device__ __forceinline__ void bar_sync(int wg) {
  if (wg == 0) asm volatile("bar.sync 1, 128;" ::: "memory");
  else asm volatile("bar.sync 2, 128;" ::: "memory");
}
__device__ __forceinline__ bool bar_red_or(int id, bool v) {
  uint32_t r;
  asm volatile("{\n.reg .pred p, q;\nsetp.ne.u32 p, %2, 0;\nbar.red.or.pred q, %1, 128, p;\nselp.u32 %0, 1, 0, q;\n}\n"
               : "=r"(r) : "r"(1 + id), "r"((uint32_t)v) : "memory");
  return r != 0;
}
__device__ __forceinline__ uint32_t hfma2(uint32_t a, uint32_t b, uint32_t c) { uint32_t r; asm("fma.rn.bf16x2 %0, %1, %2, %3;" : "=r"(r) : "r"(a), "r"(b), "r"(c)); return r; }
__device__ __forceinline__ float ex2(float x) { float y; asm("ex2.approx.ftz.f32 %0, %1;" : "=f"(y) : "f"(x)); return y; }
__device__ __forceinline__ uint32_t pack(float lo, float hi) { uint32_t r; asm("cvt.rn.bf16x2.f32 %0, %1, %2;" : "=r"(r) : "f"(hi), "f"(lo)); return r; }
__device__ __forceinline__ void stsm4t(uint32_t a, uint32_t r0, uint32_t r1, uint32_t r2, uint32_t r3) {
  asm volatile("stmatrix.sync.aligned.m8n8.x4.trans.shared.b16 [%0], {%1,%2,%3,%4};" ::"r"(a), "r"(r0), "r"(r1), "r"(r2), "r"(r3) : "memory");
}
__device__ __forceinline__ void stsm2t(uint32_t a, uint32_t r0, uint32_t r1) {
  asm volatile("stmatrix.sync.aligned.m8n8.x2.trans.shared.b16 [%0], {%1,%2};" ::"r"(a), "r"(r0), "r"(r1) : "memory");
}
__device__ __forceinline__ void mma16816(float (&d)[4], const uint32_t (&a)[4], uint32_t b0, uint32_t b1) {
  asm volatile("mma.sync.aligned.m16n8k16.row.col.f32.bf16.bf16.f32 {%0,%1,%2,%3}, {%4,%5,%6,%7}, {%8,%9}, {%0,%1,%2,%3};"
               : "+f"(d[0]), "+f"(d[1]), "+f"(d[2]), "+f"(d[3]) : "r"(a[0]), "r"(a[1]), "r"(a[2]), "r"(a[3]), "r"(b0), "r"(b1));
}

template <int V> struct IC { static constexpr int value = V; };

struct Ring {
  uint32_t slot = 0, phase = 0;
  __device__ __forceinline__ void next() { if (++slot == RING_SLOTS) { slot = 0; phase ^= 1; } }
};

__device__ __forceinline__ void mma_tn(float (&o0)[60], float (&o1)[60], uint32_t a, uint32_t b, int acc) {
#pragma unroll
  for (int k = 0; k < 4; k++) {
    wgmma_n120<1, 0>(o0, a + k * 128, HI128, b + k * 2, HI128, k == 0 ? acc : 1);
    wgmma_n120<1, 0>(o1, a + 512 + k * 128, HI128, b + k * 2, HI128, k == 0 ? acc : 1);
  }
}
__device__ __forceinline__ void mma_tn_split(float (&o0)[60], float (&o1)[60], uint32_t a, uint32_t b) {
#pragma unroll
  for (int k = 0; k < 4; k++) wgmma_n120<1, 0>(o0, a + k * 128, HI128, b + k * 2, HI128, 1);
  wg_commit();
#pragma unroll
  for (int k = 0; k < 4; k++) wgmma_n120<1, 0>(o1, a + 512 + k * 128, HI128, b + k * 2, HI128, 1);
  wg_commit();
}
__device__ __forceinline__ void mma_qk(float (&s)[60], uint32_t a, uint32_t q) {
#pragma unroll
  for (int k = 0; k < 8; k++)
    wgmma_n120<0, 0>(s, a + (k >> 2) * 512 + (k & 3) * 2, HI128, q + (k >> 2) * (XB >> 4) + (k & 3) * 2, HI128, k != 0);
}
template <int J0, int J1, bool FIRST = false>
__device__ __forceinline__ void exp_store(const float (&s)[60], float (&l)[30], uint32_t dst) {
#pragma unroll
  for (int j = J0; j < J1; j += 2) {
    uint32_t p[4];
#pragma unroll
    for (int jj = 0; jj < 2; jj++) {
      if (j + jj < 15) {
        const int c = j + jj;
        float e0 = ex2(s[4 * c]), e1 = ex2(s[4 * c + 1]), e2 = ex2(s[4 * c + 2]), e3 = ex2(s[4 * c + 3]);
        if (FIRST) { l[2 * c] = e0 + e2; l[2 * c + 1] = e1 + e3; }
        else { l[2 * c] += e0; l[2 * c + 1] += e1; l[2 * c] += e2; l[2 * c + 1] += e3; }
        p[2 * jj] = pack(e0, e1); p[2 * jj + 1] = pack(e2, e3);
      }
    }
    if (j + 1 < 15) stsm4t(dst + j * 1024, p[0], p[1], p[2], p[3]);
    else stsm2t(dst + j * 1024, p[0], p[1]);
  }
}

__device__ __forceinline__ int o_pos(int wg, int r) {
  const int j = r >> 3, q = (r >> 1) & 3, c = r & 1;
  if (j < 12) return (wg ? 144 : 0) + (j >> 2) * 32 + q * 8 + (j & 3) * 2 + c;
  if (j < 14) return (wg ? 128 : 96) + q * 4 + (j - 12) * 2 + c;
  return (wg ? 120 : 112) + q * 2 + c;
}
__device__ __forceinline__ int o_row(int p) {
  const int b = p / SQ, r = p - b * SQ, wg = r >= 120, c = r & 1;
  const int a = r - (wg ? 144 : 0), m = r - (wg ? 128 : 96), e = r - (wg ? 120 : 112);
  int row;
  if (a >= 0 && a < 96) row = ((a >> 5) * 4 + ((a >> 1) & 3)) * 8 + ((a >> 3) & 3) * 2 + c;
  else if (m >= 0 && m < 16) row = (12 + ((m >> 1) & 1)) * 8 + (m >> 2) * 2 + c;
  else row = 112 + e;
  return b * SQ + wg * 120 + row;
}

__device__ __forceinline__ void slow_path(const Params& P, int b, int h, int wg, int w, int lane) {
  const int g = lane >> 2, q = lane & 3, row0 = wg * 120;
  const uint16_t* wq = reinterpret_cast<const uint16_t*>(P.wq) + h * DH + g;
  const __nv_bfloat16* kp = P.k + (size_t)(b * NH + h) * SK * DH;
  const uint16_t* vp = reinterpret_cast<const uint16_t*>(P.v) + (size_t)(b * NH + h) * SK * DH + g;
#pragma unroll 1
  for (int t = w; t < 8; t += 4) {
    const int r0 = 16 * t + g, r1 = r0 + 8;
    const __nv_bfloat16* x0 = P.x + (size_t)(b * SQ + row0 + r0) * DM + 2 * q;
    const __nv_bfloat16* x1 = P.x + (size_t)(b * SQ + row0 + min(r1, 119)) * DM + 2 * q;
    float o[16][4];
#pragma unroll
    for (int n = 0; n < 16; n++) o[n][0] = o[n][1] = o[n][2] = o[n][3] = 0.f;
#pragma unroll 1
    for (int k0 = 0; k0 < DM; k0 += 16) {
      uint32_t a[4] = {*(const uint32_t*)(x0 + k0), *(const uint32_t*)(x1 + k0), *(const uint32_t*)(x0 + k0 + 8), *(const uint32_t*)(x1 + k0 + 8)};
      const uint16_t* wr = wq + (size_t)(k0 + 2 * q) * HD;
#pragma unroll
      for (int n = 0; n < 16; n++)
        mma16816(o[n], a, wr[8 * n] | ((uint32_t)wr[8 * n + HD] << 16), wr[8 * n + 8 * HD] | ((uint32_t)wr[8 * n + 9 * HD] << 16));
    }
    uint32_t qa[8][4];
#pragma unroll
    for (int k = 0; k < 8; k++) {
      qa[k][0] = pack(o[2 * k][0] * QSCALE, o[2 * k][1] * QSCALE);
      qa[k][1] = pack(o[2 * k][2] * QSCALE, o[2 * k][3] * QSCALE);
      qa[k][2] = pack(o[2 * k + 1][0] * QSCALE, o[2 * k + 1][1] * QSCALE);
      qa[k][3] = pack(o[2 * k + 1][2] * QSCALE, o[2 * k + 1][3] * QSCALE);
    }
#pragma unroll
    for (int n = 0; n < 16; n++) o[n][0] = o[n][1] = o[n][2] = o[n][3] = 0.f;
    float m0 = -INFINITY, m1 = -INFINITY, l0 = 0.f, l1 = 0.f;
#pragma unroll 1
    for (int key0 = 0; key0 < SK; key0 += 16) {
      float s[2][4];
#pragma unroll
      for (int nt = 0; nt < 2; nt++) {
        s[nt][0] = s[nt][1] = s[nt][2] = s[nt][3] = 0.f;
        const __nv_bfloat16* kr = kp + (size_t)(key0 + 8 * nt + g) * DH + 2 * q;
#pragma unroll
        for (int k = 0; k < 8; k++) mma16816(s[nt], qa[k], *(const uint32_t*)(kr + 16 * k), *(const uint32_t*)(kr + 16 * k + 8));
      }
      float n0 = fmaxf(fmaxf(s[0][0], s[0][1]), fmaxf(s[1][0], s[1][1])), n1 = fmaxf(fmaxf(s[0][2], s[0][3]), fmaxf(s[1][2], s[1][3]));
      n0 = fmaxf(n0, __shfl_xor_sync(~0u, n0, 1)); n1 = fmaxf(n1, __shfl_xor_sync(~0u, n1, 1));
      n0 = fmaxf(n0, __shfl_xor_sync(~0u, n0, 2)); n1 = fmaxf(n1, __shfl_xor_sync(~0u, n1, 2));
      n0 = fmaxf(n0, m0); n1 = fmaxf(n1, m1);
      const float z0 = n0 == -INFINITY ? 0.f : n0, z1 = n1 == -INFINITY ? 0.f : n1;
      const float c0 = ex2(m0 - z0), c1 = ex2(m1 - z1);
      m0 = n0; m1 = n1;
#pragma unroll
      for (int nt = 0; nt < 2; nt++) {
        s[nt][0] = ex2(s[nt][0] - z0); s[nt][1] = ex2(s[nt][1] - z0);
        s[nt][2] = ex2(s[nt][2] - z1); s[nt][3] = ex2(s[nt][3] - z1);
      }
      l0 = l0 * c0 + s[0][0] + s[0][1] + s[1][0] + s[1][1];
      l1 = l1 * c1 + s[0][2] + s[0][3] + s[1][2] + s[1][3];
      uint32_t pa[4] = {pack(s[0][0], s[0][1]), pack(s[0][2], s[0][3]), pack(s[1][0], s[1][1]), pack(s[1][2], s[1][3])};
      const uint16_t* vr = vp + (size_t)(key0 + 2 * q) * DH;
#pragma unroll
      for (int n = 0; n < 16; n++) {
        o[n][0] *= c0; o[n][1] *= c0; o[n][2] *= c1; o[n][3] *= c1;
        mma16816(o[n], pa, vr[8 * n] | ((uint32_t)vr[8 * n + DH] << 16), vr[8 * n + 8 * DH] | ((uint32_t)vr[8 * n + 9 * DH] << 16));
      }
    }
    l0 += __shfl_xor_sync(~0u, l0, 1); l1 += __shfl_xor_sync(~0u, l1, 1);
    l0 += __shfl_xor_sync(~0u, l0, 2); l1 += __shfl_xor_sync(~0u, l1, 2);
    const float i0 = 1.f / l0, i1 = 1.f / l1;
    __nv_bfloat16* oc = P.o + (size_t)(h * DH + 2 * q) * NROWS + b * SQ;
    const int p0 = o_pos(wg, r0), p1 = o_pos(wg, min(r1, 119));
#pragma unroll
    for (int n = 0; n < 16; n++) {
      oc[(size_t)(8 * n) * NROWS + p0] = __float2bfloat16(o[n][0] * i0);
      oc[(size_t)(8 * n + 1) * NROWS + p0] = __float2bfloat16(o[n][1] * i0);
      if (r1 < 120) {
        oc[(size_t)(8 * n) * NROWS + p1] = __float2bfloat16(o[n][2] * i1);
        oc[(size_t)(8 * n + 1) * NROWS + p1] = __float2bfloat16(o[n][3] * i1);
      }
    }
  }
}

__device__ __forceinline__ int bk(int ks) { return B_ORDER && ks < 48 ? 32 - (ks & 48) + (ks & 15) : ks; }
__device__ __forceinline__ uint32_t x_slot(uint32_t wg, uint32_t j) { return j < 2 ? (2 * wg + j) * XB : (2 * j + wg) * XB; }
__device__ __forceinline__ int row_block(int t) { return t >= 44 ? (t >> 2) - 11 : (t >> 2) + 4; }
__device__ __forceinline__ int unit_batch(int u) { return (u & 63) >> 2; }
__device__ __forceinline__ int unit_head(int u, int rank) { return (u >> 6) * 8 + (u & 3) * 2 + rank; }

__global__ void __cluster_dims__(2, 1, 1) __launch_bounds__(384, 1)
fused_attn_kernel(const __grid_constant__ CUtensorMap tm_x, const __grid_constant__ CUtensorMap tm_wq,
                  const __grid_constant__ CUtensorMap tm_k, const __grid_constant__ CUtensorMap tm_v,
                  const __grid_constant__ CUtensorMap tm_o, const __grid_constant__ CUtensorMap tm_wo,
                  const __grid_constant__ Params P) {
  extern __shared__ uint8_t smem_raw[];
  const uint32_t sb = ((uint32_t)__cvta_generic_to_shared(smem_raw) + 1023) & ~1023u;
  if (threadIdx.x == 0) TS(152);
  const int warp = __shfl_sync(~0u, threadIdx.x >> 5, 0);
  int lane = threadIdx.x & 31;
  const int rank = blockIdx.x & 1, cl = blockIdx.x >> 1, ncl = gridDim.x >> 1;

  const int nsingle = ncl == 66 ? 44 : NOTILES;
  auto role = [&]() {
    mbar_wait(sb + BAR_ROLE + 16, 0);
    int id;
    asm volatile("ld.shared.u32 %0, [%1];" : "=r"(id) : "r"(sb + BAR_ROLE + 8) : "memory");
    return id;
  };

  if (EARLY && threadIdx.x == 128) asm volatile("prefetch.tensormap [%0];" ::"l"(&tm_x) : "memory");
  if (threadIdx.x == 0) {
    if (EARLY) asm volatile("prefetch.tensormap [%0];" ::"l"(&tm_wq) : "memory");
    for (int i = 0; i < 6; i++) {
      mbar_init(sb + BAR_RFULL + 8 * i, 1); mbar_init(sb + BAR_REMPTY + 8 * i, 8);
      mbar_init(sb + BAR_BFULL + 8 * i, 1); mbar_init(sb + BAR_BEMPTY + 8 * i, 16);
    }
    for (int i = 0; i < 8; i++) mbar_init(sb + BAR_XFULL + 8 * i, 1);
    for (int i = 0; i < 4; i++) mbar_init(sb + BAR_XEMPTY + 8 * i, 8);
    for (int i = 0; i < 2; i++) { mbar_init(sb + BAR_STAGE + 8 * i, 4); mbar_init(sb + BAR_LSUM + 8 * i, 4); mbar_init(sb + BAR_INV + 8 * i, 1); }
    mbar_init(sb + BAR_ROLE, 1); mbar_init(sb + BAR_ROLE + 16, 1);
    asm volatile("fence.mbarrier_init.release.cluster;" ::: "memory");
  }
  __syncwarp();
  asm volatile("barrier.cluster.arrive.relaxed.aligned;" ::: "memory");
  auto first_w = [&](int s) {
    mbar_expect(sb + BAR_RFULL + 8 * s, RING_BYTES);
    tma3d(sb + s * RING_BYTES, &tm_wq, 0, s * 64, 2 * unit_head(cl, rank), sb + BAR_RFULL + 8 * s);
  };
  if (EARLY && threadIdx.x == 0) first_w(0);
  __syncwarp();
  asm volatile("barrier.cluster.wait.aligned;" ::: "memory");
  if (EARLY && threadIdx.x == 128) {
#pragma unroll 1
    for (int s = 0; s < EARLY_X; s++) {
      const uint32_t fb = sb + BAR_XFULL + 32 * rank + 8 * s;
      mbar_expect(fb, XB);
      mbar_expect_cl(mapa(fb, rank ^ 1), XB);
      tma2d_mc(sb + OFF_Q + x_slot(rank, s), &tm_x, s * 64, unit_batch(cl) * SQ + rank * 120, fb);
      if (s + 1 < EARLY_W) first_w(s + 1);
    }
  }
  __syncwarp();
  if (threadIdx.x == 0) TS(153);

  if (warp >= 8) {
    asm volatile("setmaxnreg.dec.sync.aligned.u32 24;");
    if (warp == 8) {
      uint64_t pol;
      asm volatile("createpolicy.fractional.L2::evict_first.b64 %0, 1.0;" : "=l"(pol));
      Ring r;
      if (EARLY) r.slot = EARLY_W;
      auto load = [&](const CUtensorMap* m, int c1, int c2, bool ef) {
        mbar_wait(sb + BAR_REMPTY + 8 * r.slot, r.phase ^ 1);
        if (lane == 0) {
          mbar_expect(sb + BAR_RFULL + 8 * r.slot, RING_BYTES);
          if (ef) tma3d_hint(sb + r.slot * RING_BYTES, m, 0, c1, c2, sb + BAR_RFULL + 8 * r.slot, pol);
          else tma3d(sb + r.slot * RING_BYTES, m, 0, c1, c2, sb + BAR_RFULL + 8 * r.slot);
        }
        r.next();
      };
      const int rot = ROT * (blockIdx.x * 5 + (blockIdx.x >> 4));
      auto pause = [&](int u0) {
        if (PAUSE_NS && ncl == 66 && u0 == PAUSE_AT * 66) {
          const int id = role();
          if (id >= 44 && id < 58) {
            unsigned t0, t1;
            asm volatile("mov.u32 %0, %globaltimer_lo;" : "=r"(t0));
            do { __nanosleep(200); asm volatile("mov.u32 %0, %globaltimer_lo;" : "=r"(t1)); } while (t1 - t0 < PAUSE_NS + (id - 44) * PAUSE_SPREAD);
          }
        }
      };
      for (int u0 = 0;; u0 += ncl) {
        const int u = __shfl_sync(~0u, (u0 >= 3 * ncl ? role() : cl) + u0, 0);
        if (u >= NUNITS) break;
        if (PAUSE_J < 0) pause(u0);
        const int h = unit_head(u, rank);
        const int krow = (unit_batch(u) * NH + h) * SK;
#pragma unroll 1
        for (int s = EARLY && u0 == 0 ? EARLY_W : 0; s < 10; s++) {
          if (u0 == 0 && s == 0 && lane == 0) TS(154);
          load(&tm_wq, s * 64, 2 * h, false);
          if (u0 == 0 && s == 0 && lane == 0) TS(155);
          const int sp = u0 == 0 ? s - PF_HOLD : s;
          if (sp >= 0 && sp < PF_N && lane == 0) l2_prefetch(P.v + (size_t)(krow + ((PF_J0 + sp * PF_STEP + rot) & 15) * 64) * DH, 16384);
        }
#pragma unroll 1
        for (int j = 0; j <= 16; j++) {
          if (j == PAUSE_J) pause(u0);
          if (j < 16) load(&tm_k, krow + ((j + rot) & 15) * 64, 0, true);
          if (j == 1 + DPRO) load(&tm_v, krow + (rot & 15) * 64, 0, true);
          if (j > 1) load(&tm_v, krow + ((j - 1 + rot) & 15) * 64, 0, true);
        }
      }
      const int id = __shfl_sync(~0u, role(), 0);
      const bool dbl = ncl == 66 && id >= 58;
      for (int t = dbl ? 2 * id - 72 : id; t < (dbl ? NOTILES : nsingle); t += ncl) {
        const int row0 = row_block(t) * 256 + rank * 128;
        const int b0 = row0 / SQ, b1 = (row0 + 127) / SQ;
#pragma unroll 1
        for (int ks = 0; ks < 64; ks++) {
          if (dbl ? (ks & 15) == 0 : ks == 0 || ks == 48) {
            const unsigned* c = &g_cnt[((lane & 1 ? b1 : b0) * 4 + (ks || dbl ? ks >> 4 : min(lane >> 1, 2))) * 8];
            unsigned v, n = 0;
            do {
              asm volatile("ld.acquire.gpu.global.u32 %0, [%1];" : "=r"(v) : "l"(c) : "memory");
              if (++n > (1u << 26)) __trap();
            } while (v < 16);
            __syncwarp();
            asm volatile("fence.proxy.async.global;" ::: "memory");
          }
          load(&tm_o, (dbl ? ks : bk(ks)) * 64, row0 >> 6, O_EF);
        }
      }
      if (lane == 0 && atomicAdd(&g_cnt[64 * 8], 1) == gridDim.x - 1) {
        for (int i = 0; i < 67; i++) g_cnt[i * 8] = 0;
      }
    } else if (warp == 9) {
      if (lane == 0) {
        uint32_t it = 0;
        for (;; it++) {
          const int u = (it >= 3 ? role() : cl) + it * ncl;
          if (u >= NUNITS) break;
          const int row = unit_batch(u) * SQ + rank * 120;
#pragma unroll 1
          for (int s = EARLY && it == 0 ? EARLY_X : 0; s < 10; s++) {
            const uint32_t j = s & 3, par = ((s >> 2) + (j < 2 ? it : 0)) & 1;
            mbar_wait(sb + BAR_XEMPTY + 8 * j, par ^ 1);
            const uint32_t fb = sb + BAR_XFULL + 32 * rank + 8 * j;
            mbar_expect(fb, XB);
            mbar_expect_cl(mapa(fb, rank ^ 1), XB);
            tma2d_mc(sb + OFF_Q + x_slot(rank, j), &tm_x, s * 64, row, fb);
          }
        }
        const int id = role();
        const bool dbl = ncl == 66 && id >= 58;
        uint32_t slot = rank, phase = 0;
        for (int t = dbl ? 2 * id - 72 + rank : id; t < (dbl ? NOTILES : nsingle); t += ncl) {
#pragma unroll 1
          for (int ks = dbl ? 0 : rank; ks < 64; ks += dbl ? 1 : 2) {
            mbar_wait(sb + BAR_BEMPTY + 8 * slot, phase);
            const uint32_t fb = sb + BAR_BFULL + 8 * slot;
            mbar_expect(fb, BB);
            mbar_expect_cl(mapa(fb, rank ^ 1), BB);
            tma3d_mc(sb + OFF_Q + slot * BB, &tm_wo, 0, (dbl ? ks : bk(ks)) * 64, (t & 3) * 5, fb);
            if (WO_PF && dbl && ks + WO_PF < 64 && (ks & 3) == ((id >> 1) & 3))
              asm volatile("cp.async.bulk.prefetch.tensor.3d.L2.global [%0, {%1, %2, %3}];" ::"l"(&tm_wo), "r"(0), "r"((ks + WO_PF) * 64), "r"((t & 3) * 5) : "memory");
            slot += 2;
            if (slot >= 6) { slot -= 6; phase ^= 1; }
          }
        }
      }
    } else {
      const int wg = warp - 10;
      {
        mbar_wait(sb + BAR_RFULL, 0);
        const __nv_bfloat16* xs = P.x + (size_t)(unit_batch(cl) * SQ + ((cl & 3) * 2 + rank) * 30 + min(lane, 29)) * DM + 256 + wg * 64;
#pragma unroll
        for (int i = 0; i < 3; i++) asm volatile("prefetch.global.L2 [%0];" ::"l"(xs + i * 128));
        if (lane < 16) asm volatile("prefetch.global.L2 [%0];" ::"l"(P.wq + (size_t)(384 + unit_batch(cl) * 16 + lane) * HD + unit_head(cl, rank) * DH + wg * 64));
      }
      auto take_role = [&]() {
          if (wg == 0 && rank == 0 && lane == 0) {
            int id = cl;
            if (ncl == 66) {
              uint32_t smid;
              asm("mov.u32 %0, %smid;" : "=r"(smid));
              id = smid >= SMID_TOP ? 65 - atomicAdd(&g_cnt[65 * 8], 1) : atomicAdd(&g_cnt[66 * 8], 1);
            }
    #pragma unroll
            for (int c = 0; c < 2; c++) {
              const uint32_t a = mapa(sb + BAR_ROLE, c);
              asm volatile("st.shared::cluster.u32 [%0 + 8], %1;\nmbarrier.arrive.release.cluster.shared::cluster.b64 _, [%0];" ::"r"(a), "r"(id) : "memory");
            }
          }
          if (wg == 0 && lane == 0) {
            mbar_wait_cl(sb + BAR_ROLE, 0);
            mbar_arrive(sb + BAR_ROLE + 16);
          }
      };
      if (ROLE_AT < 0) { take_role(); __syncwarp(); }
      for (uint32_t it = 0;; it++) {
        const int u = __shfl_sync(~0u, (it >= 3 ? role() : cl) + it * ncl, 0);
        if (u >= NUNITS) break;
        mbar_wait(sb + BAR_LSUM + 8 * wg, it & 1);
        float l4[4], v[4];
        const uint32_t a = sb + OFF_L2 + wg * 2048 + lane * 16;
        asm volatile("ld.shared.v4.f32 {%0, %1, %2, %3}, [%4];" : "=f"(l4[0]), "=f"(l4[1]), "=f"(l4[2]), "=f"(l4[3]) : "r"(a) : "memory");
#pragma unroll
        for (int g = 1; g < 4; g++) {
          asm volatile("ld.shared.v4.f32 {%0, %1, %2, %3}, [%4];" : "=f"(v[0]), "=f"(v[1]), "=f"(v[2]), "=f"(v[3]) : "r"(a + g * 512) : "memory");
#pragma unroll
          for (int c = 0; c < 4; c++) l4[c] += v[c];
        }
#pragma unroll
        for (int c = 0; c < 4; c++) {
          float inv;
          asm("rcp.approx.ftz.f32 %0, %1;" : "=f"(inv) : "f"(l4[c]));
          l4[c] = l4[c] >= L_MIN && l4[c] <= L_MAX ? inv : __uint_as_float(0x7FFFFFFFu);
        }
        const uint32_t h0 = pack(l4[0], l4[1]), h1 = pack(l4[2], l4[3]);
        const uint32_t e0 = pack(l4[0] - __uint_as_float(h0 << 16), l4[1] - __uint_as_float(h0 & 0xFFFF0000u));
        const uint32_t e1 = pack(l4[2] - __uint_as_float(h1 << 16), l4[3] - __uint_as_float(h1 & 0xFFFF0000u));
        const uint32_t ia = sb + OFF_INV + wg * 640 + (lane & 1) * 288 + (lane >> 1) * 8;
        asm volatile("st.shared.v2.u32 [%0], {%1, %2};\nst.shared.v2.u32 [%0 + 144], {%3, %4};" ::"r"(ia), "r"(h0), "r"(e0), "r"(h1), "r"(e1) : "memory");
        __syncwarp();
        if (lane == 0) {
          mbar_arrive(sb + BAR_INV + 8 * wg);
          if ((int)it == ROLE_AT) {
            take_role();
          }
          mbar_wait(sb + BAR_STAGE + 8 * wg, it & 1);
          __threadfence();
          asm volatile("red.relaxed.gpu.global.add.u32 [%0], 1;" ::"l"(&g_cnt[(unit_batch(u) * 4 + (u >> 6)) * 8]) : "memory");
        }
        __syncwarp();
      }
    }
  } else {
    asm volatile("setmaxnreg.inc.sync.aligned.u32 240;");
    const int wg = warp >> 2, w = warp & 3;
    if (PINLANE) lane = __shfl_sync(~0u, lane, lane);
    const uint32_t qreg = sb + OFF_Q + wg * 2 * XB, preg = sb + OFF_P + (2 + wg) * XB;
    const uint32_t st_off = ((lane >> 4) * 8 + (lane & 7)) * 128 + (((2 * w + ((lane >> 3) & 1)) ^ (lane & 7)) << 4);
    const uint32_t xempty = mapa(sb + BAR_XEMPTY, wg);
    Ring r;
    uint32_t it = 0;
    const uint32_t qd = (qreg & 0x3FFFF) >> 4, pd = (preg & 0x3FFFF) >> 4;
    auto ring_addr = [&]() { return ((sb & 0x3FFFF) + r.slot * RING_BYTES) >> 4; };
    auto ring_wait = [&]() { mbar_wait(sb + BAR_RFULL + 8 * r.slot, r.phase); };
    auto release = [&](uint32_t slot) { if (lane == 0) mbar_arrive(sb + BAR_REMPTY + 8 * slot); };
    auto turn_wait = [&]() {
      if (wg == 0) asm volatile("bar.sync 3, 256;" ::: "memory");
      else asm volatile("bar.sync 4, 256;" ::: "memory");
    };
    auto turn_pass = [&]() {
      if (wg == 0) asm volatile("bar.arrive 4, 256;" ::: "memory");
      else asm volatile("bar.arrive 3, 256;" ::: "memory");
    };

    uint32_t chk = 0;
    auto load_inv = [&](uint32_t (&iv)[30], uint32_t parity) {
      mbar_wait(sb + BAR_INV + 8 * wg, parity);
      chk = 0;
#pragma unroll
      for (int j = 0; j < 7; j++)
        asm volatile("ld.shared.v4.u32 {%0, %1, %2, %3}, [%4];" : "=r"(iv[4 * j]), "=r"(iv[4 * j + 1]), "=r"(iv[4 * j + 2]), "=r"(iv[4 * j + 3])
                     : "r"(sb + OFF_INV + wg * 640 + (lane & 3) * 144 + j * 16) : "memory");
      asm volatile("ld.shared.v2.u32 {%0, %1}, [%2];" : "=r"(iv[28]), "=r"(iv[29]) : "r"(sb + OFF_INV + wg * 640 + (lane & 3) * 144 + 112) : "memory");
    };
    auto norm = [&](uint32_t (&n)[8], const uint32_t (&po)[60], const uint32_t (&iv)[30], auto part) {
      constexpr int k = decltype(part)::value >> 1, j0 = (decltype(part)::value & 1) * 8;
#pragma unroll
      for (int j = 0; j < 8; j++)
        n[j] = j0 + j < 15 ? hfma2(po[15 * k + (j0 + j) % 15], iv[2 * ((j0 + j) % 15)], hfma2(po[15 * k + (j0 + j) % 15], iv[2 * ((j0 + j) % 15) + 1], 0x80008000u)) : 0x3F803F80u;
#pragma unroll
      for (int j = 0; j < 8; j += 2) chk = hfma2(n[j], n[j + 1], chk);
    };
    auto store = [&](const uint32_t (&n)[8], const char* optr, auto part) {
      constexpr int k = decltype(part)::value >> 1;
      const char* o = optr + (size_t)(8 * (k & 1) + 64 * (k >> 1)) * NROWS * 2;
      if ((decltype(part)::value & 1) == 0)
        asm volatile(
            "{\n.reg .pred p;\nsetp.ne.u64 p, %9, 0;\n"
            "@p st.global.v4.u32 [%8], {%0, %1, %2, %3};\n@p st.global.v4.u32 [%8 + 64], {%4, %5, %6, %7};\n}\n"
            ::"r"(n[0]), "r"(n[1]), "r"(n[2]), "r"(n[3]), "r"(n[4]), "r"(n[5]), "r"(n[6]), "r"(n[7]),
            "l"(o + (wg ? 288 : 0) + (lane & 3) * 16), "l"(optr) : "memory");
      else
        asm volatile(
            "{\n.reg .pred p;\nsetp.ne.u64 p, %10, 0;\n"
            "@p st.global.v4.u32 [%7 + 128], {%0, %1, %2, %3};\n@p st.global.v2.u32 [%8], {%4, %5};\n@p st.global.u32 [%9], %6;\n}\n"
            ::"r"(n[0]), "r"(n[1]), "r"(n[2]), "r"(n[3]), "r"(n[4]), "r"(n[5]), "r"(n[6]), "l"(o + (wg ? 288 : 0) + (lane & 3) * 16),
            "l"(o + (wg ? 256 : 192) + (lane & 3) * 8), "l"(o + (wg ? 240 : 224) + (lane & 3) * 4), "l"(optr) : "memory");
    };
    auto put = [&](const uint32_t (&po)[60], const uint32_t (&iv)[30], const char* optr, auto part) {
      uint32_t n[8];
      norm(n, po, iv, part);
      store(n, optr, part);
    };
    auto out_ptr = [&](int u) {
      return reinterpret_cast<const char*>(P.o + (size_t)(unit_head(u, rank) * DH + 16 * w + (lane >> 2)) * NROWS + unit_batch(u) * SQ);
    };
    auto unsafe = [&](bool valid) {
      const bool b = valid && ((chk & 0x7F80u) == 0x7F80u || (chk & 0x7F800000u) == 0x7F800000u);
      return __any_sync(~0u, bar_red_or(wg, b));
    };
    auto publish = [&]() { __syncwarp(); if (lane == 0) mbar_arrive(sb + BAR_STAGE + 8 * wg); };

    uint32_t po[60];
#pragma unroll
    for (int i = 0; i < 60; i++) po[i] = 0;
    int id = 0;
    bool more;
    do {
      float o0[60], o1[60];
      uint32_t prev = 0;
      auto qstep = [&](int s, int acc) {
        const uint32_t j = s & 3, par = ((s >> 2) + (j < 2 ? it : 0)) & 1;
        TR(it * 160 + 3 * s);
        ring_wait();
        TR(it * 160 + 3 * s + 1);
        mbar_wait(sb + BAR_XFULL + 32 * wg + 8 * j, par);
        TR(it * 160 + 3 * s + 2);
        if (s >= ALT_FROM) turn_wait();
        wg_fence();
        mma_tn(o0, o1, ring_addr(), ((sb & 0x3FFFF) + OFF_Q + x_slot(wg, j)) >> 4, acc);
        wg_commit();
        if ((s >= ALT_FROM && !(MERGE89 && s == 8)) || (s == ALT_FROM - 1 && wg == 1)) turn_pass();
        if (s > 0) {
          wg_wait<1>();
          release(prev);
          if (s <= 6 && lane == 0) mbar_arrive_cl(xempty + 8 * ((s - 1) & 3));
        }
        prev = r.slot;
        r.next();
      };
      qstep(0, 0);
      const int up = (it > 3 ? id : cl) + ((int)it - 1) * ncl;
      const char* optr = it > 0 ? out_ptr(up) : nullptr;
      uint32_t n7[8];
      {
        uint32_t iv[30];
        qstep(1, 1); load_inv(iv, (it + 1) & 1); put(po, iv, optr, IC<0>());
        qstep(2, 1); put(po, iv, optr, IC<1>());
        qstep(3, 1); put(po, iv, optr, IC<2>());
        qstep(4, 1); put(po, iv, optr, IC<3>());
        qstep(5, 1); put(po, iv, optr, IC<4>());
        qstep(6, 1); put(po, iv, optr, IC<5>());
        qstep(7, 1); put(po, iv, optr, IC<6>());
        norm(n7, po, iv, IC<7>());
        if (LATE_AT == 3) store(n7, optr, IC<7>());
        qstep(8, 1);
        if (LATE_AT == 2) store(n7, optr, IC<7>());
      }
      TR(it * 160 + 27);
      ring_wait();
      TR(it * 160 + 28);
      mbar_wait(sb + BAR_XFULL + 32 * wg + 8, it & 1);
      TR(it * 160 + 29);
      if (!MERGE89) turn_wait();
      wg_fence();
      mma_tn_split(o0, o1, ring_addr(), qd + (XB >> 4));
      turn_pass();
      wg_wait<2>();
      release(prev);
      auto put_q = [&](const float (&o)[60], uint32_t dst) {
        bar_sync(wg);
#pragma unroll
        for (int j = 0; j < 14; j += 2)
          stsm4t(dst + j * 1024, pack(o[4 * j] * QSCALE, o[4 * j + 1] * QSCALE), pack(o[4 * j + 2] * QSCALE, o[4 * j + 3] * QSCALE),
                 pack(o[4 * j + 4] * QSCALE, o[4 * j + 5] * QSCALE), pack(o[4 * j + 6] * QSCALE, o[4 * j + 7] * QSCALE));
        stsm2t(dst + 14 * 1024, pack(o[56] * QSCALE, o[57] * QSCALE), pack(o[58] * QSCALE, o[59] * QSCALE));
      };
      wg_wait<1>();
      reg_fence(o0);
      put_q(o0, qreg + st_off);
      wg_wait<0>();
      reg_fence(o1);
      release(r.slot);
      r.next();
      TR(it * 160 + 30);
      put_q(o1, qreg + XB + st_off);
      fence_async_smem();
      if (unsafe(it > 0)) {
        slow_path(P, unit_batch(up), unit_head(up, rank), wg, w, lane);
        optr = nullptr;
        if (!DPRO) {
#pragma unroll
          for (int i = 0; i < 60; i++) o0[i] = o1[i] = 0.f;
        }
      }
      TR(it * 160 + 32); TG(it * 160 + 142);

      float sc[60], l[30];
      ring_wait();
      TR(it * 160 + 33);
      turn_wait();
      wg_fence();
      mma_qk(sc, ring_addr(), qd);
      wg_commit();
      turn_pass();
      if (LATE_AT < 2) store(n7, optr, IC<7>());
      if (it > 0) publish();
      if (it >= 2) id = __shfl_sync(~0u, role(), 0);
      wg_wait<0>();
      reg_fence(sc);
      TR(it * 160 + 35);
      release(r.slot);
      r.next();
      exp_store<0, 15, true>(sc, l, preg + st_off);
      fence_async_smem();
      more = id + ((int)it + 1) * ncl < NUNITS;
      const bool gemm = id < nsingle || (ncl == 66 && id >= 58);
#pragma unroll 1
      for (int s = DPRO ? 3 : 1; s < 16; s++) {
        const uint32_t kslot = r.slot;
        TR(it * 160 + 32 + 6 * s); TG(it * 160 + 37 + 6 * s);
        ring_wait();
        TR(it * 160 + 33 + 6 * s);
        turn_wait();
        wg_fence();
        mma_qk(sc, ring_addr(), qd);
        wg_commit();
        r.next();
        const bool pv = !ASYM || wg == 1 || s < 15;
        TR(it * 160 + 36 + 6 * s);
        if (pv) {
          ring_wait();
          TR(it * 160 + 34 + 6 * s);
          wg_fence();
          mma_tn(o0, o1, ring_addr(), pd - ((s - 1) & 1) * (2 * XB >> 4), DPRO || s != 1);
          wg_commit();
          if (ASYM || wg == 0 || s < 15) turn_pass();
          wg_wait<1>();
        } else {
          turn_pass();
          wg_wait<0>();
        }
        reg_fence(sc);
        TR(it * 160 + 35 + 6 * s);
        release(kslot);
        if (s == 15) {
          if (more) { if (lane < 2 - ASYM) mbar_arrive_cl(xempty + 8 * lane); }
          else if (!ASYM && lane < 3 && gemm) mbar_arrive_cl(mapa(sb + BAR_BEMPTY + 8 * lane, lane & 1));
        }
        exp_store<0, VREL>(sc, l, preg - (s & 1) * 2 * XB + st_off);
        wg_wait<0>();
        reg_fence(o0); reg_fence(o1);
        if (pv) { release(r.slot); r.next(); }
        exp_store<VREL, 15>(sc, l, preg - (s & 1) * 2 * XB + st_off);
        fence_async_smem();
      }
      if (!ASYM) bar_sync(wg);
      TR(it * 160 + 128);
      const uint32_t lscr = ASYM ? qreg + XB : preg;
      auto put_l = [&]() {
        const uint32_t a = lscr + (8 * w + (lane >> 2)) * 480 + (lane & 3) * 8;
#pragma unroll
        for (int j = 0; j < 15; j++) asm volatile("st.shared.v2.f32 [%0], {%1, %2};" ::"r"(a + j * 32), "f"(l[2 * j]), "f"(l[2 * j + 1]) : "memory");
      };
      const uint32_t v14 = r.slot;
      if (ASYM && wg == 0) {
        const uint32_t a14 = ring_addr();
        ring_wait();
        r.next();
        ring_wait();
        turn_wait();
        wg_fence();
#pragma unroll
        for (int k = 0; k < 4; k++) wgmma_n120<1, 0>(o0, a14 + k * 128, HI128, pd + k * 2, HI128, 1);
#pragma unroll
        for (int k = 0; k < 4; k++) wgmma_n120<1, 0>(o0, ring_addr() + k * 128, HI128, pd - (2 * XB >> 4) + k * 2, HI128, 1);
        wg_commit();
        put_l();
        wg_fence();
#pragma unroll
        for (int k = 0; k < 4; k++) wgmma_n120<1, 0>(o1, a14 + 512 + k * 128, HI128, pd + k * 2, HI128, 1);
#pragma unroll
        for (int k = 0; k < 4; k++) wgmma_n120<1, 0>(o1, ring_addr() + 512 + k * 128, HI128, pd - (2 * XB >> 4) + k * 2, HI128, 1);
        wg_commit();
        if (ASYM_PASS == 0) turn_pass();
      } else {
        ring_wait();
        if (ASYM) turn_wait();
        wg_fence();
        mma_tn_split(o0, o1, ring_addr(), pd - (2 * XB >> 4));
        put_l();
      }
      TR(it * 160 + 132);
      __syncwarp();
      float lv[8][4];
#pragma unroll
      for (int g = 0; g < 8; g++)
        asm volatile("ld.shared.v4.f32 {%0, %1, %2, %3}, [%4];" : "=f"(lv[g][0]), "=f"(lv[g][1]), "=f"(lv[g][2]), "=f"(lv[g][3])
                     : "r"(lscr + (8 * w + g) * 480 + min(lane, 29) * 16) : "memory");
      if (ASYM && ASYM_PASS == 1 && wg == 0) turn_pass();
      TR(it * 160 + 133);
      wg_wait<1>();
      reg_fence(o0);
      TR(it * 160 + 134);
#pragma unroll
      for (int j = 0; j < 15; j++) { po[j] = pack(o0[4 * j], o0[4 * j + 1]); po[15 + j] = pack(o0[4 * j + 2], o0[4 * j + 3]); }
#pragma unroll
      for (int c = 0; c < 4; c++) lv[0][c] = ((lv[0][c] + lv[1][c]) + (lv[2][c] + lv[3][c])) + ((lv[4][c] + lv[5][c]) + (lv[6][c] + lv[7][c]));
      asm volatile("st.shared.v4.f32 [%0], {%1, %2, %3, %4};" ::"r"(sb + OFF_L2 + wg * 2048 + w * 512 + lane * 16), "f"(lv[0][0]), "f"(lv[0][1]),
                   "f"(lv[0][2]), "f"(lv[0][3]) : "memory");
      __syncwarp();
      if (lane == 0) mbar_arrive(sb + BAR_LSUM + 8 * wg);
      if (ASYM) {
        if (more) { if (lane == 0) mbar_arrive_cl(xempty + 8); }
        else if (lane < 3 && gemm) mbar_arrive_cl(mapa(sb + BAR_BEMPTY + 8 * lane, lane & 1));
      }
      wg_wait<0>();
      reg_fence(o1);
      if (ASYM && wg == 0) release(v14);
      release(r.slot);
      r.next();
      if (more) { if (lane < 2) mbar_arrive_cl(xempty + 16 + 8 * lane); }
      else if (gemm && lane < 3) mbar_arrive_cl(mapa(sb + BAR_BEMPTY + 24 + 8 * lane, (lane + 1) & 1));
      TR(it * 160 + 130);
#pragma unroll
      for (int j = 0; j < 15; j++) { po[30 + j] = pack(o1[4 * j], o1[4 * j + 1]); po[45 + j] = pack(o1[4 * j + 2], o1[4 * j + 3]); }
      TR(it * 160 + 131); TG(it * 160 + 143);
      it++;
    } while (more);
    const bool gemm = id < nsingle || (ncl == 66 && id >= 58);
    const int u = (it > 3 ? id : cl) + ((int)it - 1) * ncl;
    lane = __shfl_sync(~0u, lane, lane);
    uint32_t pb[60];
#pragma unroll
    for (int i = 0; i < 60; i++) pb[i] = po[i] ^ (gridDim.y - 1);

    uint32_t bslot = 0, bphase = 0;
    auto out_tile = [&](const float (&acc)[80], int t) {
      const uint32_t st = sb + w * RING_BYTES + wg * 8192;
      const uint32_t sa = st + (lane & 15) * 336 + (lane >> 4) * 16;
#pragma unroll
      for (int j = 0; j < 20; j += 2)
        asm volatile("stmatrix.sync.aligned.m8n8.x4.shared.b16 [%0], {%1,%2,%3,%4};" ::"r"(sa + j * 16), "r"(pack(acc[4 * j], acc[4 * j + 1])),
                     "r"(pack(acc[4 * j + 2], acc[4 * j + 3])), "r"(pack(acc[4 * j + 4], acc[4 * j + 5])), "r"(pack(acc[4 * j + 6], acc[4 * j + 7])) : "memory");
      fence_async_smem();
      __syncwarp();
      if (lane < 16) {
        __nv_bfloat16* dst = P.out + (size_t)o_row(row_block(t) * 256 + rank * 128 + wg * 64 + w * 16 + lane) * DM + (t & 3) * 160;
        asm volatile("cp.async.bulk.global.shared::cta.bulk_group [%0], [%1], 320;" ::"l"(dst), "r"(st + lane * 336) : "memory");
        asm volatile("cp.async.bulk.commit_group;" ::: "memory");
        asm volatile("cp.async.bulk.wait_group.read 0;" ::: "memory");
      }
      __syncwarp();
    };
    for (int t = id; t < nsingle || t == id; t += ncl) {
      float acc[80];
      uint32_t prev = 0, bprev = 0;
      const bool tile = t < nsingle;
      const bool last = t + ncl >= nsingle;
      auto bstep = [&](int ks, int accf) {
        if (!(ks & 3)) TR(640 + ks / 2); if ((ks & 7) == 0) TG(144 + (ks >> 3));
        ring_wait();
        mbar_wait(sb + BAR_BFULL + 8 * bslot, bphase);
        if (!(ks & 3)) TR(641 + ks / 2);
        wg_fence();
        const uint32_t a = ring_addr() + wg * 512, bd = (((sb & 0x3FFFF) + OFF_Q + bslot * BB) >> 4) | ((4096u >> 4) << 16);
#pragma unroll
        for (int k = 0; k < 4; k++) wgmma_n160<1, 1>(acc, a + k * 128, HI128, bd + k * 64, HI64, k == 0 ? accf : 1);
        wg_commit();
        if (ks > 0) {
          wg_wait<1>();
          release(prev);
          if (lane == 0 && (ks < 59 || !last)) mbar_arrive_cl(mapa(sb + BAR_BEMPTY + 8 * bprev, bprev & 1));
        }
        prev = r.slot; bprev = bslot;
        r.next();
        if (++bslot == 6) { bslot = 0; bphase ^= 1; }
      };
      const char* optr = t == id ? out_ptr(u) : nullptr;
      uint32_t iv[30];
      if (tile) {
        bstep(0, 0);
        bstep(1, 1);
        load_inv(iv, (it + 1) & 1);
#pragma unroll 1
        for (int ks = 2; ks < 17; ks++) {
          bstep(ks, 1);
          switch (ks) {
            case 2: put(pb, iv, optr, IC<0>()); break;
            case 4: put(pb, iv, optr, IC<1>()); break;
            case 6: put(pb, iv, optr, IC<2>()); break;
            case 8: put(pb, iv, optr, IC<3>()); break;
            case 10: put(pb, iv, optr, IC<4>()); break;
            case 12: put(pb, iv, optr, IC<5>()); break;
            case 14: put(pb, iv, optr, IC<6>()); break;
            case 16: put(pb, iv, optr, IC<7>()); break;
            default: break;
          }
        }
        wg_wait<0>();
        reg_fence(acc);
      } else {
        Ring r2 = r;
        auto first = [&](int ks) {
          if (ks == 0) { TR(640); TG(144); }
          if (gemm) { mbar_wait(sb + BAR_RFULL + 8 * r2.slot, r2.phase); mbar_wait(sb + BAR_BFULL + 16 * ks, 0); }
          wg_fence();
          const uint32_t a = (((sb & 0x3FFFF) + r2.slot * RING_BYTES) >> 4) + wg * 512;
          const uint32_t bd = (((sb & 0x3FFFF) + OFF_Q + 2 * ks * BB) >> 4) | ((4096u >> 4) << 16);
#pragma unroll
          for (int k = 0; k < 4; k++) wgmma_n160<1, 1>(acc, a + k * 128, HI128, bd + k * 64, HI64, k + ks != 0);
          wg_commit();
          if (ks > 0) {
            wg_wait<1>();
            if (gemm && lane == 0) mbar_arrive_cl(mapa(sb + BAR_BEMPTY + 16 * (ks - 1), 0));
          }
          r2.next();
        };
        first(0);
        load_inv(iv, (it + 1) & 1);
        put(pb, iv, optr, IC<0>()); put(pb, iv, optr, IC<1>());
        first(1);
        put(pb, iv, optr, IC<2>()); put(pb, iv, optr, IC<3>()); put(pb, iv, optr, IC<4>());
        first(2);
        put(pb, iv, optr, IC<5>()); put(pb, iv, optr, IC<6>()); put(pb, iv, optr, IC<7>());
        wg_wait<0>();
        reg_fence(acc);
      }
      if (unsafe(t == id)) slow_path(P, unit_batch(u), unit_head(u, rank), wg, w, lane);
      if (t == id) publish();
      if (!tile) {
        if (gemm) {
          float ac1[80];
          auto half = [&](float (&ac)[80], bool rel, int accf) {
            mbar_wait(sb + BAR_BFULL + 8 * bslot, bphase);
            wg_fence();
            const uint32_t a = ring_addr() + wg * 512, bd = (((sb & 0x3FFFF) + OFF_Q + bslot * BB) >> 4) | ((4096u >> 4) << 16);
#pragma unroll
            for (int k = 0; k < 4; k++) wgmma_n160<1, 1>(ac, a + k * 128, HI128, bd + k * 64, HI64, k == 0 ? accf : 1);
            wg_commit();
            wg_wait<1>();
            if (lane == 0 && rel) mbar_arrive_cl(mapa(sb + BAR_BEMPTY + 8 * bprev, bprev & 1));
            bprev = bslot;
          };
          bprev = 4; bslot = 1;
          half(ac1, true, 0);
          prev = r.slot; r.next(); bslot = 3;
          half(ac1, true, 1);
          release(prev); prev = r.slot; r.next(); bslot = 5;
          half(ac1, true, 1);
          release(prev); prev = r.slot; r.next(); bslot = 0; bphase = 1;
#pragma unroll 1
          for (int ks = 3; ks < 64; ks++) {
            if (wg == 1 && ks == 62) turn_wait();
            if (!(ks & 3)) TR(640 + ks / 2); if ((ks & 7) == 0) TG(144 + (ks >> 3));
            ring_wait();
            if (!(ks & 3)) TR(641 + ks / 2);
            half(acc, ks < 62, 1);
            release(prev);
            bslot++;
            half(ac1, ks < 61, 1);
            if (++bslot == 6) { bslot = 0; bphase ^= 1; }
            prev = r.slot; r.next();
          }
          if (wg == 0) turn_pass();
          wg_wait<0>();
          reg_fence(acc); reg_fence(ac1);
          TR(158); TG(156);
          bar_sync(wg);
          out_tile(acc, 2 * id - 72);
          out_tile(ac1, 2 * id - 71);
        }
        break;
      }
#pragma unroll 1
      for (int ks = 17; ks < 64; ks++) {
        if (END_SKEW && wg == 1 && ks == 64 - END_SKEW) turn_wait();
        bstep(ks, 1);
      }
      if (END_SKEW && wg == 0) turn_pass();
      wg_wait<0>();
      reg_fence(acc);
      release(prev);
      if (lane == 0 && !last) mbar_arrive_cl(mapa(sb + BAR_BEMPTY + 8 * bprev, bprev & 1));
      TR(158); TG(156);
      const int pos0 = row_block(t) * 256 + rank * 128 + wg * 64 + w * 16;
      if (last) {
        bar_sync(wg);
        out_tile(acc, t);
      } else {
        __nv_bfloat16* op0 = P.out + (size_t)o_row(pos0 + (lane >> 2)) * DM + (t & 3) * 160 + (lane & 3) * 2;
        __nv_bfloat16* op1 = P.out + (size_t)o_row(pos0 + (lane >> 2) + 8) * DM + (t & 3) * 160 + (lane & 3) * 2;
#pragma unroll
        for (int j = 0; j < 20; j++) {
          *reinterpret_cast<uint32_t*>(op0 + j * 8) = pack(acc[4 * j], acc[4 * j + 1]);
          *reinterpret_cast<uint32_t*>(op1 + j * 8) = pack(acc[4 * j + 2], acc[4 * j + 3]);
        }
      }
#pragma unroll
      for (int i = 0; i < 60; i++) pb[i] = 0;
    }
    TR(159);
  }
}

typedef CUresult (*EncodeFn)(CUtensorMap*, CUtensorMapDataType, cuuint32_t, void*, const cuuint64_t*, const cuuint64_t*,
                             const cuuint32_t*, const cuuint32_t*, CUtensorMapInterleave, CUtensorMapSwizzle,
                             CUtensorMapL2promotion, CUtensorMapFloatOOBfill);

void make_map(EncodeFn enc, CUtensorMap* m, const void* p, int rank, const cuuint64_t* dims, const cuuint64_t* strides,
              const cuuint32_t* box, CUtensorMapSwizzle sw, CUtensorMapL2promotion promo) {
  cuuint32_t es[3] = {1, 1, 1};
  enc(m, CU_TENSOR_MAP_DATA_TYPE_BFLOAT16, rank, const_cast<void*>(p), dims, strides, box, es, CU_TENSOR_MAP_INTERLEAVE_NONE, sw,
      promo, CU_TENSOR_MAP_FLOAT_OOB_FILL_NONE);
}

}

extern "C" void kernel_launch(void* const* d_in, const int* in_sizes, int n_in, void* d_out, int out_size) {
  static EncodeFn enc = nullptr;
  static int nclusters = 0;
  static void* o_ptr = nullptr;
  if (!enc) {
    cudaDriverEntryPointQueryResult qr;
    cudaGetDriverEntryPoint("cuTensorMapEncodeTiled", (void**)&enc, cudaEnableDefault, &qr);
    cudaFuncSetAttribute(fused_attn_kernel, cudaFuncAttributeMaxDynamicSharedMemorySize, SMEM_BYTES);
    cudaGetSymbolAddress(&o_ptr, g_o);
    cudaLaunchConfig_t cfg = {};
    cfg.gridDim = 128; cfg.blockDim = 384; cfg.dynamicSmemBytes = SMEM_BYTES;
    cudaLaunchAttribute at; at.id = cudaLaunchAttributeClusterDimension;
    at.val.clusterDim.x = 2; at.val.clusterDim.y = 1; at.val.clusterDim.z = 1;
    cfg.attrs = &at; cfg.numAttrs = 1;
    int n = 0;
    cudaOccupancyMaxActiveClusters(&n, fused_attn_kernel, &cfg);
    nclusters = n >= 66 ? MAXCL : (n >= 64 || n <= 0 ? 64 : n);
  }
  const __nv_bfloat16* x = (const __nv_bfloat16*)d_in[0];
  const __nv_bfloat16* k = (const __nv_bfloat16*)d_in[1];
  const __nv_bfloat16* v = (const __nv_bfloat16*)d_in[2];
  const __nv_bfloat16* wq = (const __nv_bfloat16*)d_in[3];
  const __nv_bfloat16* wo = (const __nv_bfloat16*)d_in[4];
  CUtensorMap tm_x, tm_wq, tm_k, tm_v, tm_o, tm_wo;
  const auto S128 = CU_TENSOR_MAP_SWIZZLE_128B;
  const auto P128 = CU_TENSOR_MAP_L2_PROMOTION_L2_128B, P256 = CU_TENSOR_MAP_L2_PROMOTION_L2_256B;
  { cuuint64_t d[2] = {DM, NB * SQ}, s[1] = {DM * 2}; cuuint32_t b[2] = {64, 120}; make_map(enc, &tm_x, x, 2, d, s, b, S128, X_PROMO); }
  { cuuint64_t d[3] = {64, DM, HD / 64}, s[2] = {HD * 2, 128}; cuuint32_t b[3] = {64, 64, 2}; make_map(enc, &tm_wq, wq, 3, d, s, b, S128, P256); }
  { cuuint64_t d[3] = {64, NB * NH * SK, 2}, s[2] = {DH * 2, 128}; cuuint32_t b[3] = {64, 64, 2};
    make_map(enc, &tm_k, k, 3, d, s, b, S128, P128); make_map(enc, &tm_v, v, 3, d, s, b, S128, P128); }
  { cuuint64_t d[3] = {64, HD, NROWS / 64}, s[2] = {NROWS * 2, 128}; cuuint32_t b[3] = {64, 64, 2}; make_map(enc, &tm_o, o_ptr, 3, d, s, b, S128, P256); }
  { cuuint64_t d[3] = {32, HD, DM / 32}, s[2] = {DM * 2, 64}; cuuint32_t b[3] = {32, 64, 5};
    make_map(enc, &tm_wo, wo, 3, d, s, b, CU_TENSOR_MAP_SWIZZLE_64B, P128); }
  Params P{x, k, v, wq, (__nv_bfloat16*)d_out, (__nv_bfloat16*)o_ptr};
  fused_attn_kernel<<<2 * nclusters, 384, SMEM_BYTES>>>(tm_x, tm_wq, tm_k, tm_v, tm_o, tm_wo, P);
}
```

```cpp
#include <cuda_runtime.h>
#include <cuda.h>
#include <cuda_bf16.h>
#include <stdint.h>

namespace {

constexpr int NB = 16, SQ = 240, DM = 640, NH = 32, SK = 1024, DH = 128, HD = NH * DH;
constexpr int NROWS = NB * SQ;
constexpr int NUNITS = 256;
#define DPRO 1
#define LATE_AT 2
#define ALT_FROM 5
#define MERGE89 1
#define END_SKEW 5
#define VREL 8
#define PF_HOLD 6
#define PF_N 4
#define PF_J0 3
#define PF_STEP 3
#define ROT 0
#define O_EF 1
#define B_ORDER 1
#define WO_PF 6
#define ROLE_AT 0
#define PAUSE_NS 11000
#define PAUSE_AT 2
#define EARLY 1
#define EARLY_X 2
#define EARLY_W 2
#define X_PROMO P128
#define PAUSE_J -1
#define PAUSE_SPREAD 0
#define LATE_SUM 0
#define PUT_FROM 1
#define PINLANE 0
#define MAXCL 66
#define SMID_TOP 88
constexpr int NOTILES = 60;
constexpr float QSCALE = 0.08838834764831845f * 1.4426950408889634f;
constexpr float L_MIN = 9.5367431640625e-07f;
constexpr float L_MAX = 1.152921504606846976e18f;

constexpr uint32_t RING_SLOTS = 6, RING_BYTES = 16384;
constexpr uint32_t XB = 15360;
constexpr uint32_t BB = 20480;
constexpr uint32_t OFF_Q = RING_SLOTS * RING_BYTES;
constexpr uint32_t OFF_P = OFF_Q + 4 * XB;
constexpr uint32_t OFF_INV = OFF_P + 4 * XB;
constexpr uint32_t OFF_L2 = OFF_INV + 1280;
constexpr uint32_t OFF_BAR = OFF_L2 + 4096;
constexpr uint32_t BAR_RFULL = OFF_BAR, BAR_REMPTY = BAR_RFULL + 48, BAR_XFULL = BAR_REMPTY + 48,
    BAR_XEMPTY = BAR_XFULL + 64, BAR_BFULL = BAR_XEMPTY + 32, BAR_BEMPTY = BAR_BFULL + 48, BAR_STAGE = BAR_BEMPTY + 48;
constexpr uint32_t BAR_ROLE = BAR_STAGE + 16, BAR_LSUM = BAR_ROLE + 24, BAR_INV = BAR_LSUM + 16;
constexpr uint32_t OFF_TR = BAR_INV + 16;
constexpr uint32_t SMEM_BYTES = OFF_TR + 1024;

constexpr uint32_t HI128 = (1u << 30) | (1024 >> 4);
constexpr uint32_t HI64 = (2u << 30) | (512 >> 4);

__device__ __nv_bfloat16 g_o[HD * NROWS];
__device__ unsigned g_cnt[67 * 8];
#define TS(i)
#define TRL(i)
#define TR(i)
#define TG(i)

struct Params {
  const __nv_bfloat16 *x, *k, *v, *wq;
  __nv_bfloat16 *out, *o;
};

__device__ __forceinline__ void wg_fence() { asm volatile("wgmma.fence.sync.aligned;" ::: "memory"); }
__device__ __forceinline__ void wg_commit() { asm volatile("wgmma.commit_group.sync.aligned;" ::: "memory"); }
template <int N> __device__ __forceinline__ void wg_wait() { asm volatile("wgmma.wait_group.sync.aligned %0;" ::"n"(N) : "memory"); }
template <int N> __device__ __forceinline__ void reg_fence(float (&r)[N]) {
#pragma unroll
  for (int i = 0; i < N; i++) asm volatile("" : "+f"(r[i])::"memory");
}
template <int TA, int TB>
__device__ __forceinline__ void wgmma_n120(float (&d)[60], uint32_t a_lo, uint32_t a_hi, uint32_t b_lo, uint32_t b_hi, int acc) {
  asm volatile(
      "{\n.reg .pred p;\n.reg .b64 da, db;\nsetp.ne.b32 p, %64, 0;\n"
      "mov.b64 da, {%60, %61};\nmov.b64 db, {%62, %63};\n"
      "wgmma.mma_async.sync.aligned.m64n120k16.f32.bf16.bf16 {"
      "%0, %1, %2, %3, %4, %5, %6, %7, %8, %9, %10, %11, %12, %13, %14, %15, %16, %17, %18, %19, %20, %21, %22, %23, "
      "%24, %25, %26, %27, %28, %29, %30, %31, %32, %33, %34, %35, %36, %37, %38, %39, %40, %41, %42, %43, %44, %45, "
      "%46, %47, %48, %49, %50, %51, %52, %53, %54, %55, %56, %57, %58, %59"
      "}, da, db, p, 1, 1, %65, %66;\n}\n"
      : "+f"(d[0]), "+f"(d[1]), "+f"(d[2]), "+f"(d[3]), "+f"(d[4]), "+f"(d[5]), "+f"(d[6]), "+f"(d[7]), "+f"(d[8]),
        "+f"(d[9]), "+f"(d[10]), "+f"(d[11]), "+f"(d[12]), "+f"(d[13]), "+f"(d[14]), "+f"(d[15]), "+f"(d[16]),
        "+f"(d[17]), "+f"(d[18]), "+f"(d[19]), "+f"(d[20]), "+f"(d[21]), "+f"(d[22]), "+f"(d[23]), "+f"(d[24]),
        "+f"(d[25]), "+f"(d[26]), "+f"(d[27]), "+f"(d[28]), "+f"(d[29]), "+f"(d[30]), "+f"(d[31]), "+f"(d[32]),
        "+f"(d[33]), "+f"(d[34]), "+f"(d[35]), "+f"(d[36]), "+f"(d[37]), "+f"(d[38]), "+f"(d[39]), "+f"(d[40]),
        "+f"(d[41]), "+f"(d[42]), "+f"(d[43]), "+f"(d[44]), "+f"(d[45]), "+f"(d[46]), "+f"(d[47]), "+f"(d[48]),
        "+f"(d[49]), "+f"(d[50]), "+f"(d[51]), "+f"(d[52]), "+f"(d[53]), "+f"(d[54]), "+f"(d[55]), "+f"(d[56]),
        "+f"(d[57]), "+f"(d[58]), "+f"(d[59])
      : "r"(a_lo), "r"(a_hi), "r"(b_lo), "r"(b_hi), "r"(acc), "n"(TA), "n"(TB));
}

template <int TA, int TB>
__device__ __forceinline__ void wgmma_n160(float (&d)[80], uint32_t a_lo, uint32_t a_hi, uint32_t b_lo, uint32_t b_hi, int acc) {
  asm volatile(
      "{\n.reg .pred p;\n.reg .b64 da, db;\nsetp.ne.b32 p, %84, 0;\n"
      "mov.b64 da, {%80, %81};\nmov.b64 db, {%82, %83};\n"
      "wgmma.mma_async.sync.aligned.m64n160k16.f32.bf16.bf16 {"
      "%0, %1, %2, %3, %4, %5, %6, %7, %8, %9, %10, %11, %12, %13, %14, %15, %16, %17, %18, %19, %20, %21, %22, %23, "
      "%24, %25, %26, %27, %28, %29, %30, %31, %32, %33, %34, %35, %36, %37, %38, %39, %40, %41, %42, %43, %44, %45, "
      "%46, %47, %48, %49, %50, %51, %52, %53, %54, %55, %56, %57, %58, %59, %60, %61, %62, %63, %64, %65, %66, %67, "
      "%68, %69, %70, %71, %72, %73, %74, %75, %76, %77, %78, %79"
      "}, da, db, p, 1, 1, %85, %86;\n}\n"
      : "+f"(d[0]), "+f"(d[1]), "+f"(d[2]), "+f"(d[3]), "+f"(d[4]), "+f"(d[5]), "+f"(d[6]), "+f"(d[7]), "+f"(d[8]),
        "+f"(d[9]), "+f"(d[10]), "+f"(d[11]), "+f"(d[12]), "+f"(d[13]), "+f"(d[14]), "+f"(d[15]), "+f"(d[16]),
        "+f"(d[17]), "+f"(d[18]), "+f"(d[19]), "+f"(d[20]), "+f"(d[21]), "+f"(d[22]), "+f"(d[23]), "+f"(d[24]),
        "+f"(d[25]), "+f"(d[26]), "+f"(d[27]), "+f"(d[28]), "+f"(d[29]), "+f"(d[30]), "+f"(d[31]), "+f"(d[32]),
        "+f"(d[33]), "+f"(d[34]), "+f"(d[35]), "+f"(d[36]), "+f"(d[37]), "+f"(d[38]), "+f"(d[39]), "+f"(d[40]),
        "+f"(d[41]), "+f"(d[42]), "+f"(d[43]), "+f"(d[44]), "+f"(d[45]), "+f"(d[46]), "+f"(d[47]), "+f"(d[48]),
        "+f"(d[49]), "+f"(d[50]), "+f"(d[51]), "+f"(d[52]), "+f"(d[53]), "+f"(d[54]), "+f"(d[55]), "+f"(d[56]),
        "+f"(d[57]), "+f"(d[58]), "+f"(d[59]), "+f"(d[60]), "+f"(d[61]), "+f"(d[62]), "+f"(d[63]), "+f"(d[64]),
        "+f"(d[65]), "+f"(d[66]), "+f"(d[67]), "+f"(d[68]), "+f"(d[69]), "+f"(d[70]), "+f"(d[71]), "+f"(d[72]),
        "+f"(d[73]), "+f"(d[74]), "+f"(d[75]), "+f"(d[76]), "+f"(d[77]), "+f"(d[78]), "+f"(d[79])
      : "r"(a_lo), "r"(a_hi), "r"(b_lo), "r"(b_hi), "r"(acc), "n"(TA), "n"(TB));
}
__device__ __forceinline__ void mbar_init(uint32_t bar, int cnt) { asm volatile("mbarrier.init.shared::cta.b64 [%0], %1;" ::"r"(bar), "r"(cnt)); }
__device__ __forceinline__ void mbar_expect(uint32_t bar, uint32_t bytes) {
  asm volatile("mbarrier.arrive.expect_tx.shared::cta.b64 _, [%0], %1;" ::"r"(bar), "r"(bytes) : "memory");
}
__device__ __forceinline__ uint32_t mapa(uint32_t addr, uint32_t cta) {
  uint32_t r; asm("mapa.shared::cluster.u32 %0, %1, %2;" : "=r"(r) : "r"(addr), "r"(cta)); return r;
}
__device__ __forceinline__ void mbar_expect_cl(uint32_t cbar, uint32_t bytes) {
  asm volatile("mbarrier.arrive.expect_tx.shared::cluster.b64 _, [%0], %1;" ::"r"(cbar), "r"(bytes) : "memory");
}
__device__ __forceinline__ void mbar_arrive(uint32_t bar) { asm volatile("mbarrier.arrive.shared::cta.b64 _, [%0];" ::"r"(bar) : "memory"); }
__device__ __forceinline__ void mbar_arrive_cl(uint32_t cbar) { asm volatile("mbarrier.arrive.shared::cluster.b64 _, [%0];" ::"r"(cbar) : "memory"); }
__device__ __forceinline__ void mbar_wait(uint32_t bar, uint32_t parity) {
  asm volatile(
      "{\n.reg .pred p;\n.reg .u32 n;\n"
      "mbarrier.try_wait.parity.shared::cta.b64 p, [%0], %1;\n@p bra WAIT_DONE;\n"
      "mov.u32 n, 0;\n"
      "WAIT_LOOP:\n"
      "mbarrier.try_wait.parity.shared::cta.b64 p, [%0], %1;\n@p bra WAIT_DONE;\n"
      "add.u32 n, n, 1;\nsetp.lt.u32 p, n, 0x4000000;\n@p bra WAIT_LOOP;\ntrap;\n"
      "WAIT_DONE:\n}\n" ::"r"(bar), "r"(parity) : "memory");
}
__device__ __forceinline__ void mbar_wait_cl(uint32_t bar, uint32_t parity) {
  asm volatile(
      "{\n.reg .pred p;\n.reg .u32 n;\nmov.u32 n, 0;\n"
      "WAIT_LOOP:\n"
      "mbarrier.try_wait.parity.acquire.cluster.shared::cta.b64 p, [%0], %1;\n@p bra WAIT_DONE;\n"
      "add.u32 n, n, 1;\nsetp.lt.u32 p, n, 0x4000000;\n@p bra WAIT_LOOP;\ntrap;\n"
      "WAIT_DONE:\n}\n" ::"r"(bar), "r"(parity) : "memory");
}
__device__ __forceinline__ void tma3d(uint32_t dst, const CUtensorMap* m, int c0, int c1, int c2, uint32_t bar) {
  asm volatile("cp.async.bulk.tensor.3d.shared::cluster.global.mbarrier::complete_tx::bytes [%0], [%1, {%3, %4, %5}], [%2];"
               ::"r"(dst), "l"(m), "r"(bar), "r"(c0), "r"(c1), "r"(c2) : "memory");
}
__device__ __forceinline__ void tma3d_hint(uint32_t dst, const CUtensorMap* m, int c0, int c1, int c2, uint32_t bar, uint64_t pol) {
  asm volatile("cp.async.bulk.tensor.3d.shared::cluster.global.mbarrier::complete_tx::bytes.L2::cache_hint [%0], [%1, {%3, %4, %5}], [%2], %6;"
               ::"r"(dst), "l"(m), "r"(bar), "r"(c0), "r"(c1), "r"(c2), "l"(pol) : "memory");
}
__device__ __forceinline__ void tma2d_mc(uint32_t dst, const CUtensorMap* m, int c0, int c1, uint32_t bar) {
  asm volatile("cp.async.bulk.tensor.2d.shared::cluster.global.mbarrier::complete_tx::bytes.multicast::cluster [%0], [%1, {%3, %4}], [%2], %5;"
               ::"r"(dst), "l"(m), "r"(bar), "r"(c0), "r"(c1), "h"((uint16_t)3) : "memory");
}
__device__ __forceinline__ void tma3d_mc(uint32_t dst, const CUtensorMap* m, int c0, int c1, int c2, uint32_t bar) {
  asm volatile("cp.async.bulk.tensor.3d.shared::cluster.global.mbarrier::complete_tx::bytes.multicast::cluster [%0], [%1, {%3, %4, %5}], [%2], %6;"
               ::"r"(dst), "l"(m), "r"(bar), "r"(c0), "r"(c1), "r"(c2), "h"((uint16_t)3) : "memory");
}
__device__ __forceinline__ void l2_prefetch(const void* p, uint32_t bytes) {
  asm volatile("cp.async.bulk.prefetch.L2.global [%0], %1;" ::"l"(p), "r"(bytes) : "memory");
}
__device__ __forceinline__ void fence_async_smem() { asm volatile("fence.proxy.async.shared::cta;" ::: "memory"); }
__device__ __forceinline__ void bar_sync(int wg) {
  if (wg == 0) asm volatile("bar.sync 1, 128;" ::: "memory");
  else asm volatile("bar.sync 2, 128;" ::: "memory");
}
__device__ __forceinline__ bool bar_red_or(int id, bool v) {
  uint32_t r;
  asm volatile("{\n.reg .pred p, q;\nsetp.ne.u32 p, %2, 0;\nbar.red.or.pred q, %1, 128, p;\nselp.u32 %0, 1, 0, q;\n}\n"
               : "=r"(r) : "r"(1 + id), "r"((uint32_t)v) : "memory");
  return r != 0;
}
__device__ __forceinline__ uint32_t hfma2(uint32_t a, uint32_t b, uint32_t c) { uint32_t r; asm("fma.rn.bf16x2 %0, %1, %2, %3;" : "=r"(r) : "r"(a), "r"(b), "r"(c)); return r; }
__device__ __forceinline__ float ex2(float x) { float y; asm("ex2.approx.ftz.f32 %0, %1;" : "=f"(y) : "f"(x)); return y; }
__device__ __forceinline__ uint32_t pack(float lo, float hi) { uint32_t r; asm("cvt.rn.bf16x2.f32 %0, %1, %2;" : "=r"(r) : "f"(hi), "f"(lo)); return r; }
__device__ __forceinline__ void stsm4t(uint32_t a, uint32_t r0, uint32_t r1, uint32_t r2, uint32_t r3) {
  asm volatile("stmatrix.sync.aligned.m8n8.x4.trans.shared.b16 [%0], {%1,%2,%3,%4};" ::"r"(a), "r"(r0), "r"(r1), "r"(r2), "r"(r3) : "memory");
}
__device__ __forceinline__ void stsm2t(uint32_t a, uint32_t r0, uint32_t r1) {
  asm volatile("stmatrix.sync.aligned.m8n8.x2.trans.shared.b16 [%0], {%1,%2};" ::"r"(a), "r"(r0), "r"(r1) : "memory");
}
__device__ __forceinline__ void mma16816(float (&d)[4], const uint32_t (&a)[4], uint32_t b0, uint32_t b1) {
  asm volatile("mma.sync.aligned.m16n8k16.row.col.f32.bf16.bf16.f32 {%0,%1,%2,%3}, {%4,%5,%6,%7}, {%8,%9}, {%0,%1,%2,%3};"
               : "+f"(d[0]), "+f"(d[1]), "+f"(d[2]), "+f"(d[3]) : "r"(a[0]), "r"(a[1]), "r"(a[2]), "r"(a[3]), "r"(b0), "r"(b1));
}

template <int V> struct IC { static constexpr int value = V; };

struct Ring {
  uint32_t slot = 0, phase = 0;
  __device__ __forceinline__ void next() { if (++slot == RING_SLOTS) { slot = 0; phase ^= 1; } }
};

__device__ __forceinline__ void mma_tn(float (&o0)[60], float (&o1)[60], uint32_t a, uint32_t b, int acc) {
#pragma unroll
  for (int k = 0; k < 4; k++) {
    wgmma_n120<1, 0>(o0, a + k * 128, HI128, b + k * 2, HI128, k == 0 ? acc : 1);
    wgmma_n120<1, 0>(o1, a + 512 + k * 128, HI128, b + k * 2, HI128, k == 0 ? acc : 1);
  }
}
__device__ __forceinline__ void mma_tn_split(float (&o0)[60], float (&o1)[60], uint32_t a, uint32_t b) {
#pragma unroll
  for (int k = 0; k < 4; k++) wgmma_n120<1, 0>(o0, a + k * 128, HI128, b + k * 2, HI128, 1);
  wg_commit();
#pragma unroll
  for (int k = 0; k < 4; k++) wgmma_n120<1, 0>(o1, a + 512 + k * 128, HI128, b + k * 2, HI128, 1);
  wg_commit();
}
__device__ __forceinline__ void mma_qk(float (&s)[60], uint32_t a, uint32_t q) {
#pragma unroll
  for (int k = 0; k < 8; k++)
    wgmma_n120<0, 0>(s, a + (k >> 2) * 512 + (k & 3) * 2, HI128, q + (k >> 2) * (XB >> 4) + (k & 3) * 2, HI128, k != 0);
}
template <int J0, int J1, bool FIRST = false>
__device__ __forceinline__ void exp_store(const float (&s)[60], float (&l)[30], uint32_t dst) {
#pragma unroll
  for (int j = J0; j < J1; j += 2) {
    uint32_t p[4];
#pragma unroll
    for (int jj = 0; jj < 2; jj++) {
      if (j + jj < 15) {
        const int c = j + jj;
        float e0 = ex2(s[4 * c]), e1 = ex2(s[4 * c + 1]), e2 = ex2(s[4 * c + 2]), e3 = ex2(s[4 * c + 3]);
        if (FIRST) { l[2 * c] = e0 + e2; l[2 * c + 1] = e1 + e3; }
        else { l[2 * c] += e0; l[2 * c + 1] += e1; l[2 * c] += e2; l[2 * c + 1] += e3; }
        p[2 * jj] = pack(e0, e1); p[2 * jj + 1] = pack(e2, e3);
      }
    }
    if (j + 1 < 15) stsm4t(dst + j * 1024, p[0], p[1], p[2], p[3]);
    else stsm2t(dst + j * 1024, p[0], p[1]);
  }
}

__device__ __forceinline__ int o_pos(int wg, int r) {
  const int j = r >> 3, q = (r >> 1) & 3, c = r & 1;
  if (j < 12) return (wg ? 144 : 0) + (j >> 2) * 32 + q * 8 + (j & 3) * 2 + c;
  if (j < 14) return (wg ? 128 : 96) + q * 4 + (j - 12) * 2 + c;
  return (wg ? 120 : 112) + q * 2 + c;
}
__device__ __forceinline__ int o_row(int p) {
  const int b = p / SQ, r = p - b * SQ, wg = r >= 120, c = r & 1;
  const int a = r - (wg ? 144 : 0), m = r - (wg ? 128 : 96), e = r - (wg ? 120 : 112);
  int row;
  if (a >= 0 && a < 96) row = ((a >> 5) * 4 + ((a >> 1) & 3)) * 8 + ((a >> 3) & 3) * 2 + c;
  else if (m >= 0 && m < 16) row = (12 + ((m >> 1) & 1)) * 8 + (m >> 2) * 2 + c;
  else row = 112 + e;
  return b * SQ + wg * 120 + row;
}

__device__ __forceinline__ void slow_path(const Params& P, int b, int h, int wg, int w, int lane) {
  const int g = lane >> 2, q = lane & 3, row0 = wg * 120;
  const uint16_t* wq = reinterpret_cast<const uint16_t*>(P.wq) + h * DH + g;
  const __nv_bfloat16* kp = P.k + (size_t)(b * NH + h) * SK * DH;
  const uint16_t* vp = reinterpret_cast<const uint16_t*>(P.v) + (size_t)(b * NH + h) * SK * DH + g;
#pragma unroll 1
  for (int t = w; t < 8; t += 4) {
    const int r0 = 16 * t + g, r1 = r0 + 8;
    const __nv_bfloat16* x0 = P.x + (size_t)(b * SQ + row0 + r0) * DM + 2 * q;
    const __nv_bfloat16* x1 = P.x + (size_t)(b * SQ + row0 + min(r1, 119)) * DM + 2 * q;
    float o[16][4];
#pragma unroll
    for (int n = 0; n < 16; n++) o[n][0] = o[n][1] = o[n][2] = o[n][3] = 0.f;
#pragma unroll 1
    for (int k0 = 0; k0 < DM; k0 += 16) {
      uint32_t a[4] = {*(const uint32_t*)(x0 + k0), *(const uint32_t*)(x1 + k0), *(const uint32_t*)(x0 + k0 + 8), *(const uint32_t*)(x1 + k0 + 8)};
      const uint16_t* wr = wq + (size_t)(k0 + 2 * q) * HD;
#pragma unroll
      for (int n = 0; n < 16; n++) {
        if ((n & 3) == 0) __syncwarp();
        mma16816(o[n], a, wr[8 * n] | ((uint32_t)wr[8 * n + HD] << 16), wr[8 * n + 8 * HD] | ((uint32_t)wr[8 * n + 9 * HD] << 16));
      }
    }
    uint32_t qa[8][4];
#pragma unroll
    for (int k = 0; k < 8; k++) {
      qa[k][0] = pack(o[2 * k][0] * QSCALE, o[2 * k][1] * QSCALE);
      qa[k][1] = pack(o[2 * k][2] * QSCALE, o[2 * k][3] * QSCALE);
      qa[k][2] = pack(o[2 * k + 1][0] * QSCALE, o[2 * k + 1][1] * QSCALE);
      qa[k][3] = pack(o[2 * k + 1][2] * QSCALE, o[2 * k + 1][3] * QSCALE);
    }
#pragma unroll
    for (int n = 0; n < 16; n++) o[n][0] = o[n][1] = o[n][2] = o[n][3] = 0.f;
    float m0 = -INFINITY, m1 = -INFINITY, l0 = 0.f, l1 = 0.f;
#pragma unroll 1
    for (int key0 = 0; key0 < SK; key0 += 16) {
      float s[2][4];
#pragma unroll
      for (int nt = 0; nt < 2; nt++) {
        s[nt][0] = s[nt][1] = s[nt][2] = s[nt][3] = 0.f;
        const __nv_bfloat16* kr = kp + (size_t)(key0 + 8 * nt + g) * DH + 2 * q;
#pragma unroll
        for (int k = 0; k < 8; k++) mma16816(s[nt], qa[k], *(const uint32_t*)(kr + 16 * k), *(const uint32_t*)(kr + 16 * k + 8));
      }
      float n0 = fmaxf(fmaxf(s[0][0], s[0][1]), fmaxf(s[1][0], s[1][1])), n1 = fmaxf(fmaxf(s[0][2], s[0][3]), fmaxf(s[1][2], s[1][3]));
      n0 = fmaxf(n0, __shfl_xor_sync(~0u, n0, 1)); n1 = fmaxf(n1, __shfl_xor_sync(~0u, n1, 1));
      n0 = fmaxf(n0, __shfl_xor_sync(~0u, n0, 2)); n1 = fmaxf(n1, __shfl_xor_sync(~0u, n1, 2));
      n0 = fmaxf(n0, m0); n1 = fmaxf(n1, m1);
      const float z0 = n0 == -INFINITY ? 0.f : n0, z1 = n1 == -INFINITY ? 0.f : n1;
      const float c0 = ex2(m0 - z0), c1 = ex2(m1 - z1);
      m0 = n0; m1 = n1;
#pragma unroll
      for (int nt = 0; nt < 2; nt++) {
        s[nt][0] = ex2(s[nt][0] - z0); s[nt][1] = ex2(s[nt][1] - z0);
        s[nt][2] = ex2(s[nt][2] - z1); s[nt][3] = ex2(s[nt][3] - z1);
      }
      l0 = l0 * c0 + s[0][0] + s[0][1] + s[1][0] + s[1][1];
      l1 = l1 * c1 + s[0][2] + s[0][3] + s[1][2] + s[1][3];
      uint32_t pa[4] = {pack(s[0][0], s[0][1]), pack(s[0][2], s[0][3]), pack(s[1][0], s[1][1]), pack(s[1][2], s[1][3])};
      const uint16_t* vr = vp + (size_t)(key0 + 2 * q) * DH;
#pragma unroll
      for (int n = 0; n < 16; n++) {
        if ((n & 3) == 0) __syncwarp();
        o[n][0] *= c0; o[n][1] *= c0; o[n][2] *= c1; o[n][3] *= c1;
        mma16816(o[n], pa, vr[8 * n] | ((uint32_t)vr[8 * n + DH] << 16), vr[8 * n + 8 * DH] | ((uint32_t)vr[8 * n + 9 * DH] << 16));
      }
    }
    l0 += __shfl_xor_sync(~0u, l0, 1); l1 += __shfl_xor_sync(~0u, l1, 1);
    l0 += __shfl_xor_sync(~0u, l0, 2); l1 += __shfl_xor_sync(~0u, l1, 2);
    const float i0 = 1.f / l0, i1 = 1.f / l1;
    __nv_bfloat16* oc = P.o + (size_t)(h * DH + 2 * q) * NROWS + b * SQ;
    const int p0 = o_pos(wg, r0), p1 = o_pos(wg, min(r1, 119));
#pragma unroll
    for (int n = 0; n < 16; n++) {
      oc[(size_t)(8 * n) * NROWS + p0] = __float2bfloat16(o[n][0] * i0);
      oc[(size_t)(8 * n + 1) * NROWS + p0] = __float2bfloat16(o[n][1] * i0);
      if (r1 < 120) {
        oc[(size_t)(8 * n) * NROWS + p1] = __float2bfloat16(o[n][2] * i1);
        oc[(size_t)(8 * n + 1) * NROWS + p1] = __float2bfloat16(o[n][3] * i1);
      }
    }
  }
}

__device__ __forceinline__ int bk(int ks) { return B_ORDER && ks < 48 ? 32 - (ks & 48) + (ks & 15) : ks; }
__device__ __forceinline__ uint32_t x_slot(uint32_t wg, uint32_t j) { return j < 2 ? (2 * wg + j) * XB : (2 * j + wg) * XB; }
__device__ __forceinline__ int row_block(int t) { return t >= 44 ? (t >> 2) - 11 : (t >> 2) + 4; }
__device__ __forceinline__ int unit_batch(int u) { return (u & 63) >> 2; }
__device__ __forceinline__ int unit_head(int u, int rank) { return (u >> 6) * 8 + (u & 3) * 2 + rank; }

template <int NCL>
__global__ void __cluster_dims__(2, 1, 1) __launch_bounds__(384, 1)
fused_attn_kernel(const __grid_constant__ CUtensorMap tm_x, const __grid_constant__ CUtensorMap tm_wq,
                  const __grid_constant__ CUtensorMap tm_k, const __grid_constant__ CUtensorMap tm_v,
                  const __grid_constant__ CUtensorMap tm_o, const __grid_constant__ CUtensorMap tm_wo,
                  const __grid_constant__ Params P) {
  extern __shared__ uint8_t smem_raw[];
  const uint32_t sb = ((uint32_t)__cvta_generic_to_shared(smem_raw) + 1023) & ~1023u;
  if (threadIdx.x == 0) TS(152);
  const int warp = __shfl_sync(~0u, threadIdx.x >> 5, 0);
  int lane = threadIdx.x & 31;
  const int rank = blockIdx.x & 1, cl = blockIdx.x >> 1, ncl = NCL ? NCL : gridDim.x >> 1;

  const int nsingle = NCL == 66 ? 44 : NOTILES;
  auto role = [&]() {
    mbar_wait(sb + BAR_ROLE + 16, 0);
    int id;
    asm volatile("ld.shared.u32 %0, [%1];" : "=r"(id) : "r"(sb + BAR_ROLE + 8) : "memory");
    return id;
  };

  if (EARLY && threadIdx.x == 128) asm volatile("prefetch.tensormap [%0];" ::"l"(&tm_x) : "memory");
  if (threadIdx.x == 0) {
    if (EARLY) asm volatile("prefetch.tensormap [%0];" ::"l"(&tm_wq) : "memory");
    for (int i = 0; i < 6; i++) {
      mbar_init(sb + BAR_RFULL + 8 * i, 1); mbar_init(sb + BAR_REMPTY + 8 * i, 8);
      mbar_init(sb + BAR_BFULL + 8 * i, 1); mbar_init(sb + BAR_BEMPTY + 8 * i, 16);
    }
    for (int i = 0; i < 8; i++) mbar_init(sb + BAR_XFULL + 8 * i, 1);
    for (int i = 0; i < 4; i++) mbar_init(sb + BAR_XEMPTY + 8 * i, 8);
    for (int i = 0; i < 2; i++) { mbar_init(sb + BAR_STAGE + 8 * i, 4); mbar_init(sb + BAR_LSUM + 8 * i, 4); mbar_init(sb + BAR_INV + 8 * i, 1); }
    mbar_init(sb + BAR_ROLE, 1); mbar_init(sb + BAR_ROLE + 16, 1);
    asm volatile("fence.mbarrier_init.release.cluster;" ::: "memory");
  }
  __syncwarp();
  asm volatile("barrier.cluster.arrive.relaxed.aligned;" ::: "memory");
  auto first_w = [&](int s) {
    mbar_expect(sb + BAR_RFULL + 8 * s, RING_BYTES);
    tma3d(sb + s * RING_BYTES, &tm_wq, 0, s * 64, 2 * unit_head(cl, rank), sb + BAR_RFULL + 8 * s);
  };
  if (EARLY && threadIdx.x == 0) first_w(0);
  __syncwarp();
  asm volatile("barrier.cluster.wait.aligned;" ::: "memory");
  if (EARLY && threadIdx.x == 128) {
#pragma unroll 1
    for (int s = 0; s < EARLY_X; s++) {
      const uint32_t fb = sb + BAR_XFULL + 32 * rank + 8 * s;
      mbar_expect(fb, XB);
      mbar_expect_cl(mapa(fb, rank ^ 1), XB);
      tma2d_mc(sb + OFF_Q + x_slot(rank, s), &tm_x, s * 64, unit_batch(cl) * SQ + rank * 120, fb);
      if (s + 1 < EARLY_W) first_w(s + 1);
    }
  }
  __syncwarp();
  if (threadIdx.x == 0) TS(153);

  if (warp >= 8) {
    asm volatile("setmaxnreg.dec.sync.aligned.u32 24;");
    if (warp == 8) {
      uint64_t pol;
      asm volatile("createpolicy.fractional.L2::evict_first.b64 %0, 1.0;" : "=l"(pol));
      Ring r;
      if (EARLY) r.slot = EARLY_W;
      auto load = [&](const CUtensorMap* m, int c1, int c2, bool ef) {
        mbar_wait(sb + BAR_REMPTY + 8 * r.slot, r.phase ^ 1);
        if (lane == 0) {
          mbar_expect(sb + BAR_RFULL + 8 * r.slot, RING_BYTES);
          if (ef) tma3d_hint(sb + r.slot * RING_BYTES, m, 0, c1, c2, sb + BAR_RFULL + 8 * r.slot, pol);
          else tma3d(sb + r.slot * RING_BYTES, m, 0, c1, c2, sb + BAR_RFULL + 8 * r.slot);
        }
        r.next();
      };
      const int rot = ROT * (blockIdx.x * 5 + (blockIdx.x >> 4));
      auto pause = [&](int u0) {
        if (PAUSE_NS && NCL == 66 && u0 == PAUSE_AT * 66) {
          const int id = role();
          if (id >= 44 && id < 58) {
            unsigned t0, t1;
            asm volatile("mov.u32 %0, %globaltimer_lo;" : "=r"(t0));
            do { __nanosleep(200); asm volatile("mov.u32 %0, %globaltimer_lo;" : "=r"(t1)); } while (t1 - t0 < PAUSE_NS + (id - 44) * PAUSE_SPREAD);
          }
        }
      };
      for (int u0 = 0;; u0 += ncl) {
        const int u = __shfl_sync(~0u, (u0 >= 3 * ncl ? role() : cl) + u0, 0);
        if (u >= NUNITS) break;
        if (PAUSE_J < 0) pause(u0);
        const int h = unit_head(u, rank);
        const int krow = (unit_batch(u) * NH + h) * SK;
#pragma unroll 1
        for (int s = EARLY && u0 == 0 ? EARLY_W : 0; s < 10; s++) {
          if (u0 == 0 && s == 0 && lane == 0) TS(154);
          load(&tm_wq, s * 64, 2 * h, false);
          if (u0 == 0 && s == 0 && lane == 0) TS(155);
          const int sp = u0 == 0 ? s - PF_HOLD : s;
          if (sp >= 0 && sp < PF_N && lane == 0) l2_prefetch(P.v + (size_t)(krow + ((PF_J0 + sp * PF_STEP + rot) & 15) * 64) * DH, 16384);
        }
#pragma unroll 1
        for (int j = 0; j <= 16; j++) {
          if (j == PAUSE_J) pause(u0);
          if (j < 16) load(&tm_k, krow + ((j + rot) & 15) * 64, 0, true);
          if (j == 1 + DPRO) load(&tm_v, krow + (rot & 15) * 64, 0, true);
          if (j > 1) load(&tm_v, krow + ((j - 1 + rot) & 15) * 64, 0, true);
        }
      }
      const int id = __shfl_sync(~0u, role(), 0);
      const bool dbl = NCL == 66 && id >= 58;
      for (int t = dbl ? 2 * id - 72 : id; t < (dbl ? NOTILES : nsingle); t += ncl) {
        const int row0 = row_block(t) * 256 + rank * 128;
        const int b0 = row0 / SQ, b1 = (row0 + 127) / SQ;
#pragma unroll 1
        for (int ks = 0; ks < 64; ks++) {
          if (dbl ? (ks & 15) == 0 : ks == 0 || ks == 48) {
            const unsigned* c = &g_cnt[((lane & 1 ? b1 : b0) * 4 + (ks || dbl ? ks >> 4 : min(lane >> 1, 2))) * 8];
            unsigned v, n = 0;
            do {
              asm volatile("ld.acquire.gpu.global.u32 %0, [%1];" : "=r"(v) : "l"(c) : "memory");
              if (++n > (1u << 26)) __trap();
            } while (v < 16);
            __syncwarp();
            asm volatile("fence.proxy.async.global;" ::: "memory");
          }
          load(&tm_o, (dbl ? ks : bk(ks)) * 64, row0 >> 6, O_EF);
        }
      }
      if (lane == 0 && atomicAdd(&g_cnt[64 * 8], 1) == gridDim.x - 1) {
        for (int i = 0; i < 67; i++) g_cnt[i * 8] = 0;
      }
    } else if (warp == 9) {
      if (lane == 0) {
        uint32_t it = 0;
        for (;; it++) {
          const int u = (it >= 3 ? role() : cl) + it * ncl;
          if (u >= NUNITS) break;
          const int row = unit_batch(u) * SQ + rank * 120;
#pragma unroll 1
          for (int s = EARLY && it == 0 ? EARLY_X : 0; s < 10; s++) {
            const uint32_t j = s & 3, par = ((s >> 2) + (j < 2 ? it : 0)) & 1;
            mbar_wait(sb + BAR_XEMPTY + 8 * j, par ^ 1);
            const uint32_t fb = sb + BAR_XFULL + 32 * rank + 8 * j;
            mbar_expect(fb, XB);
            mbar_expect_cl(mapa(fb, rank ^ 1), XB);
            tma2d_mc(sb + OFF_Q + x_slot(rank, j), &tm_x, s * 64, row, fb);
          }
        }
        const int id = role();
        const bool dbl = NCL == 66 && id >= 58;
        uint32_t slot = rank, phase = 0;
        for (int t = dbl ? 2 * id - 72 + rank : id; t < (dbl ? NOTILES : nsingle); t += ncl) {
#pragma unroll 1
          for (int ks = dbl ? 0 : rank; ks < 64; ks += dbl ? 1 : 2) {
            mbar_wait(sb + BAR_BEMPTY + 8 * slot, phase);
            const uint32_t fb = sb + BAR_BFULL + 8 * slot;
            mbar_expect(fb, BB);
            mbar_expect_cl(mapa(fb, rank ^ 1), BB);
            tma3d_mc(sb + OFF_Q + slot * BB, &tm_wo, 0, (dbl ? ks : bk(ks)) * 64, (t & 3) * 5, fb);
            if (WO_PF && dbl && ks + WO_PF < 64 && (ks & 3) == ((id >> 1) & 3))
              asm volatile("cp.async.bulk.prefetch.tensor.3d.L2.global [%0, {%1, %2, %3}];" ::"l"(&tm_wo), "r"(0), "r"((ks + WO_PF) * 64), "r"((t & 3) * 5) : "memory");
            slot += 2;
            if (slot >= 6) { slot -= 6; phase ^= 1; }
          }
        }
      }
    } else {
      const int wg = warp - 10;
      {
        mbar_wait(sb + BAR_RFULL, 0);
        const __nv_bfloat16* xs = P.x + (size_t)(unit_batch(cl) * SQ + ((cl & 3) * 2 + rank) * 30 + min(lane, 29)) * DM + 256 + wg * 64;
#pragma unroll
        for (int i = 0; i < 3; i++) asm volatile("prefetch.global.L2 [%0];" ::"l"(xs + i * 128));
        if (lane < 16) asm volatile("prefetch.global.L2 [%0];" ::"l"(P.wq + (size_t)(384 + unit_batch(cl) * 16 + lane) * HD + unit_head(cl, rank) * DH + wg * 64));
      }
      auto take_role = [&]() {
          if (wg == 0 && rank == 0 && lane == 0) {
            int id = cl;
            if (NCL == 66) {
              uint32_t smid;
              asm("mov.u32 %0, %smid;" : "=r"(smid));
              id = smid >= SMID_TOP ? 65 - atomicAdd(&g_cnt[65 * 8], 1) : atomicAdd(&g_cnt[66 * 8], 1);
            }
    #pragma unroll
            for (int c = 0; c < 2; c++) {
              const uint32_t a = mapa(sb + BAR_ROLE, c);
              asm volatile("st.shared::cluster.u32 [%0 + 8], %1;\nmbarrier.arrive.release.cluster.shared::cluster.b64 _, [%0];" ::"r"(a), "r"(id) : "memory");
            }
          }
          if (wg == 0 && lane == 0) {
            mbar_wait_cl(sb + BAR_ROLE, 0);
            mbar_arrive(sb + BAR_ROLE + 16);
          }
      };
      if (ROLE_AT < 0) { take_role(); __syncwarp(); }
      for (uint32_t it = 0;; it++) {
        const int u = __shfl_sync(~0u, (it >= 3 ? role() : cl) + it * ncl, 0);
        if (u >= NUNITS) break;
        mbar_wait(sb + BAR_LSUM + 8 * wg, it & 1);
        float l4[4], v[4];
        const uint32_t a = sb + OFF_L2 + wg * 2048 + lane * 16;
        asm volatile("ld.shared.v4.f32 {%0, %1, %2, %3}, [%4];" : "=f"(l4[0]), "=f"(l4[1]), "=f"(l4[2]), "=f"(l4[3]) : "r"(a) : "memory");
#pragma unroll
        for (int g = 1; g < 4; g++) {
          asm volatile("ld.shared.v4.f32 {%0, %1, %2, %3}, [%4];" : "=f"(v[0]), "=f"(v[1]), "=f"(v[2]), "=f"(v[3]) : "r"(a + g * 512) : "memory");
#pragma unroll
          for (int c = 0; c < 4; c++) l4[c] += v[c];
        }
#pragma unroll
        for (int c = 0; c < 4; c++) {
          float inv;
          asm("rcp.approx.ftz.f32 %0, %1;" : "=f"(inv) : "f"(l4[c]));
          l4[c] = l4[c] >= L_MIN && l4[c] <= L_MAX ? inv : __uint_as_float(0x7FFFFFFFu);
        }
        const uint32_t h0 = pack(l4[0], l4[1]), h1 = pack(l4[2], l4[3]);
        const uint32_t e0 = pack(l4[0] - __uint_as_float(h0 << 16), l4[1] - __uint_as_float(h0 & 0xFFFF0000u));
        const uint32_t e1 = pack(l4[2] - __uint_as_float(h1 << 16), l4[3] - __uint_as_float(h1 & 0xFFFF0000u));
        const uint32_t ia = sb + OFF_INV + wg * 640 + (lane & 1) * 288 + (lane >> 1) * 8;
        asm volatile("st.shared.v2.u32 [%0], {%1, %2};\nst.shared.v2.u32 [%0 + 144], {%3, %4};" ::"r"(ia), "r"(h0), "r"(e0), "r"(h1), "r"(e1) : "memory");
        __syncwarp();
        if (lane == 0) {
          mbar_arrive(sb + BAR_INV + 8 * wg);
          if ((int)it == ROLE_AT) {
            take_role();
          }
          mbar_wait(sb + BAR_STAGE + 8 * wg, it & 1);
          __threadfence();
          asm volatile("red.relaxed.gpu.global.add.u32 [%0], 1;" ::"l"(&g_cnt[(unit_batch(u) * 4 + (u >> 6)) * 8]) : "memory");
        }
        __syncwarp();
      }
    }
  } else {
    asm volatile("setmaxnreg.inc.sync.aligned.u32 240;");
    const int wg = warp >> 2, w = warp & 3;
    if (PINLANE) lane = __shfl_sync(~0u, lane, lane);
    const uint32_t qreg = sb + OFF_Q + wg * 2 * XB, preg = sb + OFF_P + (2 + wg) * XB;
    const uint32_t st_off = ((lane >> 4) * 8 + (lane & 7)) * 128 + (((2 * w + ((lane >> 3) & 1)) ^ (lane & 7)) << 4);
    const uint32_t xempty = mapa(sb + BAR_XEMPTY, wg);
    Ring r;
    uint32_t it = 0;
    const uint32_t qd = (qreg & 0x3FFFF) >> 4, pd = (preg & 0x3FFFF) >> 4;
    auto ring_addr = [&]() { return ((sb & 0x3FFFF) + r.slot * RING_BYTES) >> 4; };
    auto ring_wait = [&]() { mbar_wait(sb + BAR_RFULL + 8 * r.slot, r.phase); };
    auto release = [&](uint32_t slot) { if (lane == 0) mbar_arrive(sb + BAR_REMPTY + 8 * slot); };
    auto turn_wait = [&]() {
      if (wg == 0) asm volatile("bar.sync 3, 256;" ::: "memory");
      else asm volatile("bar.sync 4, 256;" ::: "memory");
    };
    auto turn_pass = [&]() {
      if (wg == 0) asm volatile("bar.arrive 4, 256;" ::: "memory");
      else asm volatile("bar.arrive 3, 256;" ::: "memory");
    };

    uint32_t chk = 0;
    auto sum_l = [&]() {
      __syncwarp();
      float lv[8][4];
#pragma unroll
      for (int g = 0; g < 8; g++)
        asm volatile("ld.shared.v4.f32 {%0, %1, %2, %3}, [%4];" : "=f"(lv[g][0]), "=f"(lv[g][1]), "=f"(lv[g][2]), "=f"(lv[g][3])
                     : "r"(preg + (8 * w + g) * 480 + min(lane, 29) * 16) : "memory");
#pragma unroll
      for (int c = 0; c < 4; c++) lv[0][c] = ((lv[0][c] + lv[1][c]) + (lv[2][c] + lv[3][c])) + ((lv[4][c] + lv[5][c]) + (lv[6][c] + lv[7][c]));
      asm volatile("st.shared.v4.f32 [%0], {%1, %2, %3, %4};" ::"r"(sb + OFF_L2 + wg * 2048 + w * 512 + lane * 16), "f"(lv[0][0]), "f"(lv[0][1]),
                   "f"(lv[0][2]), "f"(lv[0][3]) : "memory");
      __syncwarp();
      if (lane == 0) mbar_arrive(sb + BAR_LSUM + 8 * wg);
    };
    auto load_inv = [&](uint32_t (&iv)[30], uint32_t parity) {
      mbar_wait(sb + BAR_INV + 8 * wg, parity);
      chk = 0;
#pragma unroll
      for (int j = 0; j < 7; j++)
        asm volatile("ld.shared.v4.u32 {%0, %1, %2, %3}, [%4];" : "=r"(iv[4 * j]), "=r"(iv[4 * j + 1]), "=r"(iv[4 * j + 2]), "=r"(iv[4 * j + 3])
                     : "r"(sb + OFF_INV + wg * 640 + (lane & 3) * 144 + j * 16) : "memory");
      asm volatile("ld.shared.v2.u32 {%0, %1}, [%2];" : "=r"(iv[28]), "=r"(iv[29]) : "r"(sb + OFF_INV + wg * 640 + (lane & 3) * 144 + 112) : "memory");
    };
    auto norm = [&](uint32_t (&n)[8], const uint32_t (&po)[60], const uint32_t (&iv)[30], auto part) {
      constexpr int k = decltype(part)::value >> 1, j0 = (decltype(part)::value & 1) * 8;
#pragma unroll
      for (int j = 0; j < 8; j++)
        n[j] = j0 + j < 15 ? hfma2(po[15 * k + (j0 + j) % 15], iv[2 * ((j0 + j) % 15)], hfma2(po[15 * k + (j0 + j) % 15], iv[2 * ((j0 + j) % 15) + 1], 0x80008000u)) : 0x3F803F80u;
#pragma unroll
      for (int j = 0; j < 8; j += 2) chk = hfma2(n[j], n[j + 1], chk);
    };
    auto store = [&](const uint32_t (&n)[8], const char* optr, auto part) {
      constexpr int k = decltype(part)::value >> 1;
      const char* o = optr + (size_t)(8 * (k & 1) + 64 * (k >> 1)) * NROWS * 2;
      if ((decltype(part)::value & 1) == 0)
        asm volatile(
            "{\n.reg .pred p;\nsetp.ne.u64 p, %9, 0;\n"
            "@p st.global.v4.u32 [%8], {%0, %1, %2, %3};\n@p st.global.v4.u32 [%8 + 64], {%4, %5, %6, %7};\n}\n"
            ::"r"(n[0]), "r"(n[1]), "r"(n[2]), "r"(n[3]), "r"(n[4]), "r"(n[5]), "r"(n[6]), "r"(n[7]),
            "l"(o + (wg ? 288 : 0) + (lane & 3) * 16), "l"(optr) : "memory");
      else
        asm volatile(
            "{\n.reg .pred p;\nsetp.ne.u64 p, %10, 0;\n"
            "@p st.global.v4.u32 [%7 + 128], {%0, %1, %2, %3};\n@p st.global.v2.u32 [%8], {%4, %5};\n@p st.global.u32 [%9], %6;\n}\n"
            ::"r"(n[0]), "r"(n[1]), "r"(n[2]), "r"(n[3]), "r"(n[4]), "r"(n[5]), "r"(n[6]), "l"(o + (wg ? 288 : 0) + (lane & 3) * 16),
            "l"(o + (wg ? 256 : 192) + (lane & 3) * 8), "l"(o + (wg ? 240 : 224) + (lane & 3) * 4), "l"(optr) : "memory");
    };
    auto put = [&](const uint32_t (&po)[60], const uint32_t (&iv)[30], const char* optr, auto part) {
      uint32_t n[8];
      norm(n, po, iv, part);
      store(n, optr, part);
    };
    auto out_ptr = [&](int u) {
      return reinterpret_cast<const char*>(P.o + (size_t)(unit_head(u, rank) * DH + 16 * w + (lane >> 2)) * NROWS + unit_batch(u) * SQ);
    };
    auto unsafe = [&](bool valid) {
      const bool b = valid && ((chk & 0x7F80u) == 0x7F80u || (chk & 0x7F800000u) == 0x7F800000u);
      return __any_sync(~0u, bar_red_or(wg, b));
    };
    auto publish = [&]() { __syncwarp(); if (lane == 0) mbar_arrive(sb + BAR_STAGE + 8 * wg); };

    uint32_t po[60];
#pragma unroll
    for (int i = 0; i < 60; i++) po[i] = 0;
    int id = 0;
    bool more;
    do {
      float o0[60], o1[60];
      uint32_t prev = 0;
      auto qstep = [&](int s, int acc) {
        const uint32_t j = s & 3, par = ((s >> 2) + (j < 2 ? it : 0)) & 1;
        TR(it * 160 + 3 * s);
        ring_wait();
        TR(it * 160 + 3 * s + 1);
        mbar_wait(sb + BAR_XFULL + 32 * wg + 8 * j, par);
        TR(it * 160 + 3 * s + 2);
        if (s >= ALT_FROM) turn_wait();
        wg_fence();
        mma_tn(o0, o1, ring_addr(), ((sb & 0x3FFFF) + OFF_Q + x_slot(wg, j)) >> 4, acc);
        wg_commit();
        if ((s >= ALT_FROM && !(MERGE89 && s == 8)) || (s == ALT_FROM - 1 && wg == 1)) turn_pass();
        if (s > 0) {
          wg_wait<1>();
          release(prev);
          if (s <= 6 && lane == 0) mbar_arrive_cl(xempty + 8 * ((s - 1) & 3));
        }
        prev = r.slot;
        r.next();
      };
      qstep(0, 0);
      const int up = (it > 3 ? id : cl) + ((int)it - 1) * ncl;
      const char* optr = it > 0 ? out_ptr(up) : nullptr;
      uint32_t n7[8];
      {
        uint32_t iv[30];
        if (LATE_SUM && it > 0) {
          sum_l();
          if (lane == 0) mbar_arrive_cl(xempty + 24);
        }
        if (PUT_FROM == 1) {
          qstep(1, 1); load_inv(iv, (it + 1) & 1); put(po, iv, optr, IC<0>());
          qstep(2, 1); put(po, iv, optr, IC<1>());
          qstep(3, 1); put(po, iv, optr, IC<2>());
          qstep(4, 1); put(po, iv, optr, IC<3>());
          qstep(5, 1); put(po, iv, optr, IC<4>());
          qstep(6, 1); put(po, iv, optr, IC<5>());
          qstep(7, 1); put(po, iv, optr, IC<6>());
          norm(n7, po, iv, IC<7>());
          if (LATE_AT == 3) store(n7, optr, IC<7>());
          qstep(8, 1);
          if (LATE_AT == 2) store(n7, optr, IC<7>());
        } else {
          qstep(1, 1);
          qstep(2, 1); load_inv(iv, (it + 1) & 1); put(po, iv, optr, IC<0>());
          qstep(3, 1); put(po, iv, optr, IC<1>());
          qstep(4, 1); put(po, iv, optr, IC<2>());
          qstep(5, 1); put(po, iv, optr, IC<3>());
          qstep(6, 1); put(po, iv, optr, IC<4>());
          qstep(7, 1); put(po, iv, optr, IC<5>());
          uint32_t n6[8];
          norm(n6, po, iv, IC<6>());
          norm(n7, po, iv, IC<7>());
          qstep(8, 1);
          store(n6, optr, IC<6>());
        }
      }
      TR(it * 160 + 27);
      ring_wait();
      TR(it * 160 + 28);
      mbar_wait(sb + BAR_XFULL + 32 * wg + 8, it & 1);
      TR(it * 160 + 29);
      if (!MERGE89) turn_wait();
      wg_fence();
      mma_tn_split(o0, o1, ring_addr(), qd + (XB >> 4));
      turn_pass();
      if (LATE_AT == 4) store(n7, optr, IC<7>());
      wg_wait<2>();
      release(prev);
      auto put_q = [&](const float (&o)[60], uint32_t dst) {
        bar_sync(wg);
#pragma unroll
        for (int j = 0; j < 14; j += 2)
          stsm4t(dst + j * 1024, pack(o[4 * j] * QSCALE, o[4 * j + 1] * QSCALE), pack(o[4 * j + 2] * QSCALE, o[4 * j + 3] * QSCALE),
                 pack(o[4 * j + 4] * QSCALE, o[4 * j + 5] * QSCALE), pack(o[4 * j + 6] * QSCALE, o[4 * j + 7] * QSCALE));
        stsm2t(dst + 14 * 1024, pack(o[56] * QSCALE, o[57] * QSCALE), pack(o[58] * QSCALE, o[59] * QSCALE));
      };
      wg_wait<1>();
      reg_fence(o0);
      put_q(o0, qreg + st_off);
      wg_wait<0>();
      reg_fence(o1);
      release(r.slot);
      r.next();
      TR(it * 160 + 30);
      put_q(o1, qreg + XB + st_off);
      fence_async_smem();
      if (unsafe(it > 0)) {
        slow_path(P, unit_batch(up), unit_head(up, rank), wg, w, lane);
        optr = nullptr;
        if (!DPRO) {
#pragma unroll
          for (int i = 0; i < 60; i++) o0[i] = o1[i] = 0.f;
        }
      }
      TR(it * 160 + 32); TG(it * 160 + 142);

      float sc[60], l[30];
      uint32_t slot0 = r.slot;
      ring_wait();
      TR(it * 160 + 33);
      turn_wait();
      wg_fence();
      mma_qk(sc, ring_addr(), qd);
      wg_commit();
      r.next();
      uint32_t slot1 = r.slot;
      ring_wait();
      wg_fence();
      mma_qk(o1, ring_addr(), qd);
      wg_commit();
      r.next();
      turn_pass();
      if (LATE_AT == 0) store(n7, optr, IC<7>());
      wg_wait<1>();
      reg_fence(sc);
      TR(it * 160 + 35);
      release(slot0);
      exp_store<0, 15, true>(sc, l, preg + st_off);
      TR(it * 160 + 38); TG(it * 160 + 43);
      slot0 = r.slot;
      ring_wait();
      wg_fence();
      mma_qk(sc, ring_addr(), qd);
      wg_commit();
      r.next();
      wg_wait<1>();
      reg_fence(o1);
      TR(it * 160 + 41);
      release(slot1);
      exp_store<0, 15>(o1, l, preg - 2 * XB + st_off);
      fence_async_smem();
      bar_sync(wg);
      TR(it * 160 + 44);
      slot1 = r.slot;
      ring_wait();
      turn_wait();
      wg_fence();
      mma_tn(o0, o1, ring_addr(), pd, 0);
      wg_commit();
      r.next();
      ring_wait();
      wg_fence();
      mma_tn(o0, o1, ring_addr(), pd - (2 * XB >> 4), 1);
      wg_commit();
      turn_pass();
      if (LATE_AT == 1) store(n7, optr, IC<7>());
      if (it > 0) publish();
      if (it >= 2) id = __shfl_sync(~0u, role(), 0);
      wg_wait<1>();
      reg_fence(sc);
      release(slot0);
      release(slot1);
      bar_sync(wg);
      TR(it * 160 + 47);
      exp_store<0, VREL>(sc, l, preg + st_off);
      wg_wait<0>();
      reg_fence(o0); reg_fence(o1);
      release(r.slot);
      r.next();
      exp_store<VREL, 15>(sc, l, preg + st_off);
      fence_async_smem();
      bar_sync(wg);
      more = id + ((int)it + 1) * ncl < NUNITS;
      const bool gemm = id < nsingle || (NCL == 66 && id >= 58);
#pragma unroll 1
      for (int s = DPRO ? 3 : 1; s < 16; s++) {
        const uint32_t kslot = r.slot;
        TR(it * 160 + 32 + 6 * s); TG(it * 160 + 37 + 6 * s);
        if (s == 8) TRL(it * 160 + 139);
        ring_wait();
        TR(it * 160 + 33 + 6 * s);
        turn_wait();
        wg_fence();
        mma_qk(sc, ring_addr(), qd);
        wg_commit();
        r.next();
        TR(it * 160 + 36 + 6 * s);
        ring_wait();
        TR(it * 160 + 34 + 6 * s);
        wg_fence();
        mma_tn(o0, o1, ring_addr(), pd - ((s - 1) & 1) * (2 * XB >> 4), DPRO || s != 1);
        wg_commit();
        if (wg == 0 || s < 15) turn_pass();
        wg_wait<1>();
        reg_fence(sc);
        TR(it * 160 + 35 + 6 * s);
        release(kslot);
        if (s == 15) {
          if (more) { if (lane < 2) mbar_arrive_cl(xempty + 8 * lane); }
          else if (lane < 3 && gemm) mbar_arrive_cl(mapa(sb + BAR_BEMPTY + 8 * lane, lane & 1));
        }
        exp_store<0, VREL>(sc, l, preg - (s & 1) * 2 * XB + st_off);
        wg_wait<0>();
        reg_fence(o0); reg_fence(o1);
        release(r.slot);
        r.next();
        exp_store<VREL, 15>(sc, l, preg - (s & 1) * 2 * XB + st_off);
        fence_async_smem();
      }
      bar_sync(wg);
      TR(it * 160 + 128);
      ring_wait();
      wg_fence();
      mma_tn_split(o0, o1, ring_addr(), pd - (2 * XB >> 4));
      {
        const uint32_t a = preg + (8 * w + (lane >> 2)) * 480 + (lane & 3) * 8;
#pragma unroll
        for (int j = 0; j < 15; j++) asm volatile("st.shared.v2.f32 [%0], {%1, %2};" ::"r"(a + j * 32), "f"(l[2 * j]), "f"(l[2 * j + 1]) : "memory");
      }
      TR(it * 160 + 132);
      if (!LATE_SUM) sum_l();
      TR(it * 160 + 133);
      wg_wait<1>();
      reg_fence(o0);
      TR(it * 160 + 134);
#pragma unroll
      for (int j = 0; j < 15; j++) { po[j] = pack(o0[4 * j], o0[4 * j + 1]); po[15 + j] = pack(o0[4 * j + 2], o0[4 * j + 3]); }
      wg_wait<0>();
      reg_fence(o1);
      release(r.slot);
      r.next();
      if (LATE_SUM && !more) sum_l();
      if (more) { if (lane < 2 - LATE_SUM) mbar_arrive_cl(xempty + 16 + 8 * lane); }
      else if (gemm && lane < 3) mbar_arrive_cl(mapa(sb + BAR_BEMPTY + 24 + 8 * lane, (lane + 1) & 1));
      TR(it * 160 + 130);
#pragma unroll
      for (int j = 0; j < 15; j++) { po[30 + j] = pack(o1[4 * j], o1[4 * j + 1]); po[45 + j] = pack(o1[4 * j + 2], o1[4 * j + 3]); }
      TR(it * 160 + 131); TG(it * 160 + 143);
      it++;
    } while (more);
    const bool gemm = id < nsingle || (NCL == 66 && id >= 58);
    const int u = (it > 3 ? id : cl) + ((int)it - 1) * ncl;
    if (NCL != 66) lane = __shfl_sync(~0u, lane, lane);
    uint32_t pb[60];
#pragma unroll
    for (int i = 0; i < 60; i++) pb[i] = NCL != 66 ? po[i] ^ (gridDim.y - 1) : po[i];

    uint32_t bslot = 0, bphase = 0;
    auto out_tile = [&](const float (&acc)[80], int t) {
      const uint32_t st = sb + w * RING_BYTES + wg * 8192;
      const uint32_t sa = st + (lane & 15) * 336 + (lane >> 4) * 16;
#pragma unroll
      for (int j = 0; j < 20; j += 2)
        asm volatile("stmatrix.sync.aligned.m8n8.x4.shared.b16 [%0], {%1,%2,%3,%4};" ::"r"(sa + j * 16), "r"(pack(acc[4 * j], acc[4 * j + 1])),
                     "r"(pack(acc[4 * j + 2], acc[4 * j + 3])), "r"(pack(acc[4 * j + 4], acc[4 * j + 5])), "r"(pack(acc[4 * j + 6], acc[4 * j + 7])) : "memory");
      fence_async_smem();
      __syncwarp();
      if (lane < 16) {
        __nv_bfloat16* dst = P.out + (size_t)o_row(row_block(t) * 256 + rank * 128 + wg * 64 + w * 16 + lane) * DM + (t & 3) * 160;
        asm volatile("cp.async.bulk.global.shared::cta.bulk_group [%0], [%1], 320;" ::"l"(dst), "r"(st + lane * 336) : "memory");
        asm volatile("cp.async.bulk.commit_group;" ::: "memory");
        asm volatile("cp.async.bulk.wait_group.read 0;" ::: "memory");
      }
      __syncwarp();
    };
    for (int t = id; t == id || (NCL != 66 && t < nsingle); t += ncl) {
      float acc[80];
      uint32_t prev = 0, bprev = 0;
      const bool tile = t < nsingle;
      const bool last = NCL == 66 || t + ncl >= nsingle;
      auto bstep = [&](int ks, int accf) {
        if (!(ks & 3)) TR(640 + ks / 2); if ((ks & 7) == 0) TG(144 + (ks >> 3));
        ring_wait();
        mbar_wait(sb + BAR_BFULL + 8 * bslot, bphase);
        if (!(ks & 3)) TR(641 + ks / 2);
        wg_fence();
        const uint32_t a = ring_addr() + wg * 512, bd = (((sb & 0x3FFFF) + OFF_Q + bslot * BB) >> 4) | ((4096u >> 4) << 16);
#pragma unroll
        for (int k = 0; k < 4; k++) wgmma_n160<1, 1>(acc, a + k * 128, HI128, bd + k * 64, HI64, k == 0 ? accf : 1);
        wg_commit();
        if (ks > 0) {
          wg_wait<1>();
          release(prev);
          if (lane == 0 && (ks < 59 || !last)) mbar_arrive_cl(mapa(sb + BAR_BEMPTY + 8 * bprev, bprev & 1));
        }
        prev = r.slot; bprev = bslot;
        r.next();
        if (++bslot == 6) { bslot = 0; bphase ^= 1; }
      };
      const char* optr = t == id ? out_ptr(u) : nullptr;
      uint32_t iv[30];
      if (tile) {
        bstep(0, 0);
        bstep(1, 1);
        load_inv(iv, (it + 1) & 1);
#pragma unroll 1
        for (int ks = 2; ks < 17; ks++) {
          bstep(ks, 1);
          switch (ks) {
            case 2: put(pb, iv, optr, IC<0>()); break;
            case 4: put(pb, iv, optr, IC<1>()); break;
            case 6: put(pb, iv, optr, IC<2>()); break;
            case 8: put(pb, iv, optr, IC<3>()); break;
            case 10: put(pb, iv, optr, IC<4>()); break;
            case 12: put(pb, iv, optr, IC<5>()); break;
            case 14: put(pb, iv, optr, IC<6>()); break;
            case 16: put(pb, iv, optr, IC<7>()); break;
            default: break;
          }
        }
        wg_wait<0>();
        reg_fence(acc);
      } else {
        Ring r2 = r;
        auto first = [&](int ks) {
          if (ks == 0) { TR(640); TG(144); }
          if (gemm) { mbar_wait(sb + BAR_RFULL + 8 * r2.slot, r2.phase); mbar_wait(sb + BAR_BFULL + 16 * ks, 0); }
          wg_fence();
          const uint32_t a = (((sb & 0x3FFFF) + r2.slot * RING_BYTES) >> 4) + wg * 512;
          const uint32_t bd = (((sb & 0x3FFFF) + OFF_Q + 2 * ks * BB) >> 4) | ((4096u >> 4) << 16);
#pragma unroll
          for (int k = 0; k < 4; k++) wgmma_n160<1, 1>(acc, a + k * 128, HI128, bd + k * 64, HI64, k + ks != 0);
          wg_commit();
          if (ks > 0) {
            wg_wait<1>();
            if (gemm && lane == 0) mbar_arrive_cl(mapa(sb + BAR_BEMPTY + 16 * (ks - 1), 0));
          }
          r2.next();
        };
        first(0);
        load_inv(iv, (it + 1) & 1);
        put(pb, iv, optr, IC<0>()); put(pb, iv, optr, IC<1>());
        first(1);
        put(pb, iv, optr, IC<2>()); put(pb, iv, optr, IC<3>()); put(pb, iv, optr, IC<4>());
        first(2);
        put(pb, iv, optr, IC<5>()); put(pb, iv, optr, IC<6>()); put(pb, iv, optr, IC<7>());
        wg_wait<0>();
        reg_fence(acc);
      }
      if (unsafe(t == id)) slow_path(P, unit_batch(u), unit_head(u, rank), wg, w, lane);
      if (t == id) publish();
      if (!tile) {
        if (gemm) {
          float ac1[80];
          auto half = [&](float (&ac)[80], bool rel, int accf) {
            mbar_wait(sb + BAR_BFULL + 8 * bslot, bphase);
            wg_fence();
            const uint32_t a = ring_addr() + wg * 512, bd = (((sb & 0x3FFFF) + OFF_Q + bslot * BB) >> 4) | ((4096u >> 4) << 16);
#pragma unroll
            for (int k = 0; k < 4; k++) wgmma_n160<1, 1>(ac, a + k * 128, HI128, bd + k * 64, HI64, k == 0 ? accf : 1);
            wg_commit();
            wg_wait<1>();
            if (lane == 0 && rel) mbar_arrive_cl(mapa(sb + BAR_BEMPTY + 8 * bprev, bprev & 1));
            bprev = bslot;
          };
          bprev = 4; bslot = 1;
          half(ac1, true, 0);
          prev = r.slot; r.next(); bslot = 3;
          half(ac1, true, 1);
          release(prev); prev = r.slot; r.next(); bslot = 5;
          half(ac1, true, 1);
          release(prev); prev = r.slot; r.next(); bslot = 0; bphase = 1;
#pragma unroll 1
          for (int ks = 3; ks < 64; ks++) {
            if (wg == 1 && ks == 62) turn_wait();
            if (!(ks & 3)) TR(640 + ks / 2); if ((ks & 7) == 0) TG(144 + (ks >> 3));
            ring_wait();
            if (!(ks & 3)) TR(641 + ks / 2);
            half(acc, ks < 62, 1);
            release(prev);
            bslot++;
            half(ac1, ks < 61, 1);
            if (++bslot == 6) { bslot = 0; bphase ^= 1; }
            prev = r.slot; r.next();
          }
          if (wg == 0) turn_pass();
          wg_wait<0>();
          reg_fence(acc); reg_fence(ac1);
          TRL(158); TG(156);
          bar_sync(wg);
          out_tile(acc, 2 * id - 72);
          out_tile(ac1, 2 * id - 71);
        }
        break;
      }
#pragma unroll 1
      for (int ks = 17; ks < 64; ks++) {
        if (END_SKEW && wg == 1 && ks == 64 - END_SKEW) turn_wait();
        bstep(ks, 1);
      }
      if (END_SKEW && wg == 0) turn_pass();
      wg_wait<0>();
      reg_fence(acc);
      release(prev);
      if (lane == 0 && !last) mbar_arrive_cl(mapa(sb + BAR_BEMPTY + 8 * bprev, bprev & 1));
      TRL(158); TG(156);
      const int pos0 = row_block(t) * 256 + rank * 128 + wg * 64 + w * 16;
      if (last) {
        bar_sync(wg);
        out_tile(acc, t);
      } else {
        __nv_bfloat16* op0 = P.out + (size_t)o_row(pos0 + (lane >> 2)) * DM + (t & 3) * 160 + (lane & 3) * 2;
        __nv_bfloat16* op1 = P.out + (size_t)o_row(pos0 + (lane >> 2) + 8) * DM + (t & 3) * 160 + (lane & 3) * 2;
#pragma unroll
        for (int j = 0; j < 20; j++) {
          *reinterpret_cast<uint32_t*>(op0 + j * 8) = pack(acc[4 * j], acc[4 * j + 1]);
          *reinterpret_cast<uint32_t*>(op1 + j * 8) = pack(acc[4 * j + 2], acc[4 * j + 3]);
        }
      }
#pragma unroll
      for (int i = 0; i < 60; i++) pb[i] = 0;
    }
    TRL(159);
  }
}

typedef CUresult (*EncodeFn)(CUtensorMap*, CUtensorMapDataType, cuuint32_t, void*, const cuuint64_t*, const cuuint64_t*,
                             const cuuint32_t*, const cuuint32_t*, CUtensorMapInterleave, CUtensorMapSwizzle,
                             CUtensorMapL2promotion, CUtensorMapFloatOOBfill);

void make_map(EncodeFn enc, CUtensorMap* m, const void* p, int rank, const cuuint64_t* dims, const cuuint64_t* strides,
              const cuuint32_t* box, CUtensorMapSwizzle sw, CUtensorMapL2promotion promo) {
  cuuint32_t es[3] = {1, 1, 1};
  enc(m, CU_TENSOR_MAP_DATA_TYPE_BFLOAT16, rank, const_cast<void*>(p), dims, strides, box, es, CU_TENSOR_MAP_INTERLEAVE_NONE, sw,
      promo, CU_TENSOR_MAP_FLOAT_OOB_FILL_NONE);
}

}

extern "C" void kernel_launch(void* const* d_in, const int* in_sizes, int n_in, void* d_out, int out_size) {
  static EncodeFn enc = nullptr;
  static int nclusters = 0;
  static void* o_ptr = nullptr;
  if (!enc) {
    cudaDriverEntryPointQueryResult qr;
    cudaGetDriverEntryPoint("cuTensorMapEncodeTiled", (void**)&enc, cudaEnableDefault, &qr);
    cudaFuncSetAttribute(fused_attn_kernel<66>, cudaFuncAttributeMaxDynamicSharedMemorySize, SMEM_BYTES);
    cudaFuncSetAttribute(fused_attn_kernel<0>, cudaFuncAttributeMaxDynamicSharedMemorySize, SMEM_BYTES);
    cudaGetSymbolAddress(&o_ptr, g_o);
    cudaLaunchConfig_t cfg = {};
    cfg.gridDim = 128; cfg.blockDim = 384; cfg.dynamicSmemBytes = SMEM_BYTES;
    cudaLaunchAttribute at; at.id = cudaLaunchAttributeClusterDimension;
    at.val.clusterDim.x = 2; at.val.clusterDim.y = 1; at.val.clusterDim.z = 1;
    cfg.attrs = &at; cfg.numAttrs = 1;
    int n = 0;
    cudaOccupancyMaxActiveClusters(&n, fused_attn_kernel<66>, &cfg);
    nclusters = n >= 66 ? MAXCL : (n >= 64 || n <= 0 ? 64 : n);
  }
  const __nv_bfloat16* x = (const __nv_bfloat16*)d_in[0];
  const __nv_bfloat16* k = (const __nv_bfloat16*)d_in[1];
  const __nv_bfloat16* v = (const __nv_bfloat16*)d_in[2];
  const __nv_bfloat16* wq = (const __nv_bfloat16*)d_in[3];
  const __nv_bfloat16* wo = (const __nv_bfloat16*)d_in[4];
  CUtensorMap tm_x, tm_wq, tm_k, tm_v, tm_o, tm_wo;
  const auto S128 = CU_TENSOR_MAP_SWIZZLE_128B;
  const auto P128 = CU_TENSOR_MAP_L2_PROMOTION_L2_128B, P256 = CU_TENSOR_MAP_L2_PROMOTION_L2_256B;
  { cuuint64_t d[2] = {DM, NB * SQ}, s[1] = {DM * 2}; cuuint32_t b[2] = {64, 120}; make_map(enc, &tm_x, x, 2, d, s, b, S128, X_PROMO); }
  { cuuint64_t d[3] = {64, DM, HD / 64}, s[2] = {HD * 2, 128}; cuuint32_t b[3] = {64, 64, 2}; make_map(enc, &tm_wq, wq, 3, d, s, b, S128, P256); }
  { cuuint64_t d[3] = {64, NB * NH * SK, 2}, s[2] = {DH * 2, 128}; cuuint32_t b[3] = {64, 64, 2};
    make_map(enc, &tm_k, k, 3, d, s, b, S128, P128); make_map(enc, &tm_v, v, 3, d, s, b, S128, P128); }
  { cuuint64_t d[3] = {64, HD, NROWS / 64}, s[2] = {NROWS * 2, 128}; cuuint32_t b[3] = {64, 64, 2}; make_map(enc, &tm_o, o_ptr, 3, d, s, b, S128, P256); }
  { cuuint64_t d[3] = {32, HD, DM / 32}, s[2] = {DM * 2, 64}; cuuint32_t b[3] = {32, 64, 5};
    make_map(enc, &tm_wo, wo, 3, d, s, b, CU_TENSOR_MAP_SWIZZLE_64B, P128); }
  Params P{x, k, v, wq, (__nv_bfloat16*)d_out, (__nv_bfloat16*)o_ptr};
  if (nclusters == 66) fused_attn_kernel<66><<<132, 384, SMEM_BYTES>>>(tm_x, tm_wq, tm_k, tm_v, tm_o, tm_wo, P);
  else fused_attn_kernel<0><<<2 * nclusters, 384, SMEM_BYTES>>>(tm_x, tm_wq, tm_k, tm_v, tm_o, tm_wo, P);
}
```

```cpp
#include <cuda_runtime.h>
#include <cuda.h>
#include <cuda_bf16.h>
#include <stdint.h>

namespace {

constexpr int NB = 16, SQ = 240, DM = 640, NH = 32, SK = 1024, DH = 128, HD = NH * DH;
constexpr int NROWS = NB * SQ;
constexpr int NUNITS = 256;
#define DPRO 1
#define LATE_AT 2
#define ALT_FROM 5
#define MERGE89 1
#define END_SKEW 5
#define VREL 8
#define PF_HOLD 6
#define PF_N 4
#define PF_J0 3
#define PF_STEP 3
#define ROT 0
#define O_EF 1
#define B_ORDER 1
#define WO_PF 6
#define ROLE_AT 0
#define PAUSE_NS 11000
#define PAUSE_AT 2
#define EARLY 1
#define EARLY_X 2
#define EARLY_W 2
#define X_PROMO P128
#define PAUSE_J -1
#define PAUSE_SPREAD 0
#define WO_PF0 1
#define LATE_SUM 0
#define PUT_FROM 1
#define PINLANE 0
#define MAXCL 66
#define SMID_TOP 88
constexpr int NOTILES = 60;
constexpr float QSCALE = 0.08838834764831845f * 1.4426950408889634f;
constexpr float L_MIN = 9.5367431640625e-07f;
constexpr float L_MAX = 1.152921504606846976e18f;

constexpr uint32_t RING_SLOTS = 6, RING_BYTES = 16384;
constexpr uint32_t XB = 15360;
constexpr uint32_t BB = 20480;
constexpr uint32_t OFF_Q = RING_SLOTS * RING_BYTES;
constexpr uint32_t OFF_P = OFF_Q + 4 * XB;
constexpr uint32_t OFF_INV = OFF_P + 4 * XB;
constexpr uint32_t OFF_L2 = OFF_INV + 1280;
constexpr uint32_t OFF_BAR = OFF_L2 + 4096;
constexpr uint32_t BAR_RFULL = OFF_BAR, BAR_REMPTY = BAR_RFULL + 48, BAR_XFULL = BAR_REMPTY + 48,
    BAR_XEMPTY = BAR_XFULL + 64, BAR_BFULL = BAR_XEMPTY + 32, BAR_BEMPTY = BAR_BFULL + 48, BAR_STAGE = BAR_BEMPTY + 48;
constexpr uint32_t BAR_ROLE = BAR_STAGE + 16, BAR_LSUM = BAR_ROLE + 24, BAR_INV = BAR_LSUM + 16;
constexpr uint32_t OFF_TR = BAR_INV + 16;
constexpr uint32_t SMEM_BYTES = OFF_TR + 1024;

constexpr uint32_t HI128 = (1u << 30) | (1024 >> 4);
constexpr uint32_t HI64 = (2u << 30) | (512 >> 4);

__device__ __nv_bfloat16 g_o[HD * NROWS];
__device__ unsigned g_cnt[67 * 8];
#define TS(i)
#define TRL(i)
#define TR(i)
#define TG(i)

struct Params {
  const __nv_bfloat16 *x, *k, *v, *wq;
  __nv_bfloat16 *out, *o;
};

__device__ __forceinline__ void wg_fence() { asm volatile("wgmma.fence.sync.aligned;" ::: "memory"); }
__device__ __forceinline__ void wg_commit() { asm volatile("wgmma.commit_group.sync.aligned;" ::: "memory"); }
template <int N> __device__ __forceinline__ void wg_wait() { asm volatile("wgmma.wait_group.sync.aligned %0;" ::"n"(N) : "memory"); }
template <int N> __device__ __forceinline__ void reg_fence(float (&r)[N]) {
#pragma unroll
  for (int i = 0; i < N; i++) asm volatile("" : "+f"(r[i])::"memory");
}
template <int TA, int TB>
__device__ __forceinline__ void wgmma_n120(float (&d)[60], uint32_t a_lo, uint32_t a_hi, uint32_t b_lo, uint32_t b_hi, int acc) {
  asm volatile(
      "{\n.reg .pred p;\n.reg .b64 da, db;\nsetp.ne.b32 p, %64, 0;\n"
      "mov.b64 da, {%60, %61};\nmov.b64 db, {%62, %63};\n"
      "wgmma.mma_async.sync.aligned.m64n120k16.f32.bf16.bf16 {"
      "%0, %1, %2, %3, %4, %5, %6, %7, %8, %9, %10, %11, %12, %13, %14, %15, %16, %17, %18, %19, %20, %21, %22, %23, "
      "%24, %25, %26, %27, %28, %29, %30, %31, %32, %33, %34, %35, %36, %37, %38, %39, %40, %41, %42, %43, %44, %45, "
      "%46, %47, %48, %49, %50, %51, %52, %53, %54, %55, %56, %57, %58, %59"
      "}, da, db, p, 1, 1, %65, %66;\n}\n"
      : "+f"(d[0]), "+f"(d[1]), "+f"(d[2]), "+f"(d[3]), "+f"(d[4]), "+f"(d[5]), "+f"(d[6]), "+f"(d[7]), "+f"(d[8]),
        "+f"(d[9]), "+f"(d[10]), "+f"(d[11]), "+f"(d[12]), "+f"(d[13]), "+f"(d[14]), "+f"(d[15]), "+f"(d[16]),
        "+f"(d[17]), "+f"(d[18]), "+f"(d[19]), "+f"(d[20]), "+f"(d[21]), "+f"(d[22]), "+f"(d[23]), "+f"(d[24]),
        "+f"(d[25]), "+f"(d[26]), "+f"(d[27]), "+f"(d[28]), "+f"(d[29]), "+f"(d[30]), "+f"(d[31]), "+f"(d[32]),
        "+f"(d[33]), "+f"(d[34]), "+f"(d[35]), "+f"(d[36]), "+f"(d[37]), "+f"(d[38]), "+f"(d[39]), "+f"(d[40]),
        "+f"(d[41]), "+f"(d[42]), "+f"(d[43]), "+f"(d[44]), "+f"(d[45]), "+f"(d[46]), "+f"(d[47]), "+f"(d[48]),
        "+f"(d[49]), "+f"(d[50]), "+f"(d[51]), "+f"(d[52]), "+f"(d[53]), "+f"(d[54]), "+f"(d[55]), "+f"(d[56]),
        "+f"(d[57]), "+f"(d[58]), "+f"(d[59])
      : "r"(a_lo), "r"(a_hi), "r"(b_lo), "r"(b_hi), "r"(acc), "n"(TA), "n"(TB));
}

template <int TA, int TB>
__device__ __forceinline__ void wgmma_n160(float (&d)[80], uint32_t a_lo, uint32_t a_hi, uint32_t b_lo, uint32_t b_hi, int acc) {
  asm volatile(
      "{\n.reg .pred p;\n.reg .b64 da, db;\nsetp.ne.b32 p, %84, 0;\n"
      "mov.b64 da, {%80, %81};\nmov.b64 db, {%82, %83};\n"
      "wgmma.mma_async.sync.aligned.m64n160k16.f32.bf16.bf16 {"
      "%0, %1, %2, %3, %4, %5, %6, %7, %8, %9, %10, %11, %12, %13, %14, %15, %16, %17, %18, %19, %20, %21, %22, %23, "
      "%24, %25, %26, %27, %28, %29, %30, %31, %32, %33, %34, %35, %36, %37, %38, %39, %40, %41, %42, %43, %44, %45, "
      "%46, %47, %48, %49, %50, %51, %52, %53, %54, %55, %56, %57, %58, %59, %60, %61, %62, %63, %64, %65, %66, %67, "
      "%68, %69, %70, %71, %72, %73, %74, %75, %76, %77, %78, %79"
      "}, da, db, p, 1, 1, %85, %86;\n}\n"
      : "+f"(d[0]), "+f"(d[1]), "+f"(d[2]), "+f"(d[3]), "+f"(d[4]), "+f"(d[5]), "+f"(d[6]), "+f"(d[7]), "+f"(d[8]),
        "+f"(d[9]), "+f"(d[10]), "+f"(d[11]), "+f"(d[12]), "+f"(d[13]), "+f"(d[14]), "+f"(d[15]), "+f"(d[16]),
        "+f"(d[17]), "+f"(d[18]), "+f"(d[19]), "+f"(d[20]), "+f"(d[21]), "+f"(d[22]), "+f"(d[23]), "+f"(d[24]),
        "+f"(d[25]), "+f"(d[26]), "+f"(d[27]), "+f"(d[28]), "+f"(d[29]), "+f"(d[30]), "+f"(d[31]), "+f"(d[32]),
        "+f"(d[33]), "+f"(d[34]), "+f"(d[35]), "+f"(d[36]), "+f"(d[37]), "+f"(d[38]), "+f"(d[39]), "+f"(d[40]),
        "+f"(d[41]), "+f"(d[42]), "+f"(d[43]), "+f"(d[44]), "+f"(d[45]), "+f"(d[46]), "+f"(d[47]), "+f"(d[48]),
        "+f"(d[49]), "+f"(d[50]), "+f"(d[51]), "+f"(d[52]), "+f"(d[53]), "+f"(d[54]), "+f"(d[55]), "+f"(d[56]),
        "+f"(d[57]), "+f"(d[58]), "+f"(d[59]), "+f"(d[60]), "+f"(d[61]), "+f"(d[62]), "+f"(d[63]), "+f"(d[64]),
        "+f"(d[65]), "+f"(d[66]), "+f"(d[67]), "+f"(d[68]), "+f"(d[69]), "+f"(d[70]), "+f"(d[71]), "+f"(d[72]),
        "+f"(d[73]), "+f"(d[74]), "+f"(d[75]), "+f"(d[76]), "+f"(d[77]), "+f"(d[78]), "+f"(d[79])
      : "r"(a_lo), "r"(a_hi), "r"(b_lo), "r"(b_hi), "r"(acc), "n"(TA), "n"(TB));
}
__device__ __forceinline__ void mbar_init(uint32_t bar, int cnt) { asm volatile("mbarrier.init.shared::cta.b64 [%0], %1;" ::"r"(bar), "r"(cnt)); }
__device__ __forceinline__ void mbar_expect(uint32_t bar, uint32_t bytes) {
  asm volatile("mbarrier.arrive.expect_tx.shared::cta.b64 _, [%0], %1;" ::"r"(bar), "r"(bytes) : "memory");
}
__device__ __forceinline__ uint32_t mapa(uint32_t addr, uint32_t cta) {
  uint32_t r; asm("mapa.shared::cluster.u32 %0, %1, %2;" : "=r"(r) : "r"(addr), "r"(cta)); return r;
}
__device__ __forceinline__ void mbar_expect_cl(uint32_t cbar, uint32_t bytes) {
  asm volatile("mbarrier.arrive.expect_tx.shared::cluster.b64 _, [%0], %1;" ::"r"(cbar), "r"(bytes) : "memory");
}
__device__ __forceinline__ void mbar_arrive(uint32_t bar) { asm volatile("mbarrier.arrive.shared::cta.b64 _, [%0];" ::"r"(bar) : "memory"); }
__device__ __forceinline__ void mbar_arrive_cl(uint32_t cbar) { asm volatile("mbarrier.arrive.shared::cluster.b64 _, [%0];" ::"r"(cbar) : "memory"); }
__device__ __forceinline__ void mbar_wait(uint32_t bar, uint32_t parity) {
  asm volatile(
      "{\n.reg .pred p;\n.reg .u32 n;\n"
      "mbarrier.try_wait.parity.shared::cta.b64 p, [%0], %1;\n@p bra WAIT_DONE;\n"
      "mov.u32 n, 0;\n"
      "WAIT_LOOP:\n"
      "mbarrier.try_wait.parity.shared::cta.b64 p, [%0], %1;\n@p bra WAIT_DONE;\n"
      "add.u32 n, n, 1;\nsetp.lt.u32 p, n, 0x4000000;\n@p bra WAIT_LOOP;\ntrap;\n"
      "WAIT_DONE:\n}\n" ::"r"(bar), "r"(parity) : "memory");
}
__device__ __forceinline__ void mbar_wait_cl(uint32_t bar, uint32_t parity) {
  asm volatile(
      "{\n.reg .pred p;\n.reg .u32 n;\nmov.u32 n, 0;\n"
      "WAIT_LOOP:\n"
      "mbarrier.try_wait.parity.acquire.cluster.shared::cta.b64 p, [%0], %1;\n@p bra WAIT_DONE;\n"
      "add.u32 n, n, 1;\nsetp.lt.u32 p, n, 0x4000000;\n@p bra WAIT_LOOP;\ntrap;\n"
      "WAIT_DONE:\n}\n" ::"r"(bar), "r"(parity) : "memory");
}
__device__ __forceinline__ void tma3d(uint32_t dst, const CUtensorMap* m, int c0, int c1, int c2, uint32_t bar) {
  asm volatile("cp.async.bulk.tensor.3d.shared::cluster.global.mbarrier::complete_tx::bytes [%0], [%1, {%3, %4, %5}], [%2];"
               ::"r"(dst), "l"(m), "r"(bar), "r"(c0), "r"(c1), "r"(c2) : "memory");
}
__device__ __forceinline__ void tma3d_hint(uint32_t dst, const CUtensorMap* m, int c0, int c1, int c2, uint32_t bar, uint64_t pol) {
  asm volatile("cp.async.bulk.tensor.3d.shared::cluster.global.mbarrier::complete_tx::bytes.L2::cache_hint [%0], [%1, {%3, %4, %5}], [%2], %6;"
               ::"r"(dst), "l"(m), "r"(bar), "r"(c0), "r"(c1), "r"(c2), "l"(pol) : "memory");
}
__device__ __forceinline__ void tma2d_mc(uint32_t dst, const CUtensorMap* m, int c0, int c1, uint32_t bar) {
  asm volatile("cp.async.bulk.tensor.2d.shared::cluster.global.mbarrier::complete_tx::bytes.multicast::cluster [%0], [%1, {%3, %4}], [%2], %5;"
               ::"r"(dst), "l"(m), "r"(bar), "r"(c0), "r"(c1), "h"((uint16_t)3) : "memory");
}
__device__ __forceinline__ void tma3d_mc(uint32_t dst, const CUtensorMap* m, int c0, int c1, int c2, uint32_t bar) {
  asm volatile("cp.async.bulk.tensor.3d.shared::cluster.global.mbarrier::complete_tx::bytes.multicast::cluster [%0], [%1, {%3, %4, %5}], [%2], %6;"
               ::"r"(dst), "l"(m), "r"(bar), "r"(c0), "r"(c1), "r"(c2), "h"((uint16_t)3) : "memory");
}
__device__ __forceinline__ void l2_prefetch(const void* p, uint32_t bytes) {
  asm volatile("cp.async.bulk.prefetch.L2.global [%0], %1;" ::"l"(p), "r"(bytes) : "memory");
}
__device__ __forceinline__ void fence_async_smem() { asm volatile("fence.proxy.async.shared::cta;" ::: "memory"); }
__device__ __forceinline__ void bar_sync(int wg) {
  if (wg == 0) asm volatile("bar.sync 1, 128;" ::: "memory");
  else asm volatile("bar.sync 2, 128;" ::: "memory");
}
__device__ __forceinline__ bool bar_red_or(int id, bool v) {
  uint32_t r;
  asm volatile("{\n.reg .pred p, q;\nsetp.ne.u32 p, %2, 0;\nbar.red.or.pred q, %1, 128, p;\nselp.u32 %0, 1, 0, q;\n}\n"
               : "=r"(r) : "r"(1 + id), "r"((uint32_t)v) : "memory");
  return r != 0;
}
__device__ __forceinline__ uint32_t hfma2(uint32_t a, uint32_t b, uint32_t c) { uint32_t r; asm("fma.rn.bf16x2 %0, %1, %2, %3;" : "=r"(r) : "r"(a), "r"(b), "r"(c)); return r; }
__device__ __forceinline__ float ex2(float x) { float y; asm("ex2.approx.ftz.f32 %0, %1;" : "=f"(y) : "f"(x)); return y; }
__device__ __forceinline__ uint32_t pack(float lo, float hi) { uint32_t r; asm("cvt.rn.bf16x2.f32 %0, %1, %2;" : "=r"(r) : "f"(hi), "f"(lo)); return r; }
__device__ __forceinline__ void stsm4t(uint32_t a, uint32_t r0, uint32_t r1, uint32_t r2, uint32_t r3) {
  asm volatile("stmatrix.sync.aligned.m8n8.x4.trans.shared.b16 [%0], {%1,%2,%3,%4};" ::"r"(a), "r"(r0), "r"(r1), "r"(r2), "r"(r3) : "memory");
}
__device__ __forceinline__ void stsm2t(uint32_t a, uint32_t r0, uint32_t r1) {
  asm volatile("stmatrix.sync.aligned.m8n8.x2.trans.shared.b16 [%0], {%1,%2};" ::"r"(a), "r"(r0), "r"(r1) : "memory");
}
__device__ __forceinline__ void mma16816(float (&d)[4], const uint32_t (&a)[4], uint32_t b0, uint32_t b1) {
  asm volatile("mma.sync.aligned.m16n8k16.row.col.f32.bf16.bf16.f32 {%0,%1,%2,%3}, {%4,%5,%6,%7}, {%8,%9}, {%0,%1,%2,%3};"
               : "+f"(d[0]), "+f"(d[1]), "+f"(d[2]), "+f"(d[3]) : "r"(a[0]), "r"(a[1]), "r"(a[2]), "r"(a[3]), "r"(b0), "r"(b1));
}

template <int V> struct IC { static constexpr int value = V; };

struct Ring {
  uint32_t slot = 0, phase = 0;
  __device__ __forceinline__ void next() { if (++slot == RING_SLOTS) { slot = 0; phase ^= 1; } }
};

__device__ __forceinline__ void mma_tn(float (&o0)[60], float (&o1)[60], uint32_t a, uint32_t b, int acc) {
#pragma unroll
  for (int k = 0; k < 4; k++) {
    wgmma_n120<1, 0>(o0, a + k * 128, HI128, b + k * 2, HI128, k == 0 ? acc : 1);
    wgmma_n120<1, 0>(o1, a + 512 + k * 128, HI128, b + k * 2, HI128, k == 0 ? acc : 1);
  }
}
__device__ __forceinline__ void mma_tn_split(float (&o0)[60], float (&o1)[60], uint32_t a, uint32_t b) {
#pragma unroll
  for (int k = 0; k < 4; k++) wgmma_n120<1, 0>(o0, a + k * 128, HI128, b + k * 2, HI128, 1);
  wg_commit();
#pragma unroll
  for (int k = 0; k < 4; k++) wgmma_n120<1, 0>(o1, a + 512 + k * 128, HI128, b + k * 2, HI128, 1);
  wg_commit();
}
__device__ __forceinline__ void mma_qk(float (&s)[60], uint32_t a, uint32_t q) {
#pragma unroll
  for (int k = 0; k < 8; k++)
    wgmma_n120<0, 0>(s, a + (k >> 2) * 512 + (k & 3) * 2, HI128, q + (k >> 2) * (XB >> 4) + (k & 3) * 2, HI128, k != 0);
}
template <int J0, int J1, bool FIRST = false>
__device__ __forceinline__ void exp_store(const float (&s)[60], float (&l)[30], uint32_t dst) {
#pragma unroll
  for (int j = J0; j < J1; j += 2) {
    uint32_t p[4];
#pragma unroll
    for (int jj = 0; jj < 2; jj++) {
      if (j + jj < 15) {
        const int c = j + jj;
        float e0 = ex2(s[4 * c]), e1 = ex2(s[4 * c + 1]), e2 = ex2(s[4 * c + 2]), e3 = ex2(s[4 * c + 3]);
        if (FIRST) { l[2 * c] = e0 + e2; l[2 * c + 1] = e1 + e3; }
        else { l[2 * c] += e0; l[2 * c + 1] += e1; l[2 * c] += e2; l[2 * c + 1] += e3; }
        p[2 * jj] = pack(e0, e1); p[2 * jj + 1] = pack(e2, e3);
      }
    }
    if (j + 1 < 15) stsm4t(dst + j * 1024, p[0], p[1], p[2], p[3]);
    else stsm2t(dst + j * 1024, p[0], p[1]);
  }
}

__device__ __forceinline__ int o_pos(int wg, int r) {
  const int j = r >> 3, q = (r >> 1) & 3, c = r & 1;
  if (j < 12) return (wg ? 144 : 0) + (j >> 2) * 32 + q * 8 + (j & 3) * 2 + c;
  if (j < 14) return (wg ? 128 : 96) + q * 4 + (j - 12) * 2 + c;
  return (wg ? 120 : 112) + q * 2 + c;
}
__device__ __forceinline__ int o_row(int p) {
  const int b = p / SQ, r = p - b * SQ, wg = r >= 120, c = r & 1;
  const int a = r - (wg ? 144 : 0), m = r - (wg ? 128 : 96), e = r - (wg ? 120 : 112);
  int row;
  if (a >= 0 && a < 96) row = ((a >> 5) * 4 + ((a >> 1) & 3)) * 8 + ((a >> 3) & 3) * 2 + c;
  else if (m >= 0 && m < 16) row = (12 + ((m >> 1) & 1)) * 8 + (m >> 2) * 2 + c;
  else row = 112 + e;
  return b * SQ + wg * 120 + row;
}

__device__ __forceinline__ void slow_path(const Params& P, int b, int h, int wg, int w, int lane) {
  const int g = lane >> 2, q = lane & 3, row0 = wg * 120;
  const uint16_t* wq = reinterpret_cast<const uint16_t*>(P.wq) + h * DH + g;
  const __nv_bfloat16* kp = P.k + (size_t)(b * NH + h) * SK * DH;
  const uint16_t* vp = reinterpret_cast<const uint16_t*>(P.v) + (size_t)(b * NH + h) * SK * DH + g;
#pragma unroll 1
  for (int t = w; t < 8; t += 4) {
    const int r0 = 16 * t + g, r1 = r0 + 8;
    const __nv_bfloat16* x0 = P.x + (size_t)(b * SQ + row0 + r0) * DM + 2 * q;
    const __nv_bfloat16* x1 = P.x + (size_t)(b * SQ + row0 + min(r1, 119)) * DM + 2 * q;
    float o[16][4];
#pragma unroll
    for (int n = 0; n < 16; n++) o[n][0] = o[n][1] = o[n][2] = o[n][3] = 0.f;
#pragma unroll 1
    for (int k0 = 0; k0 < DM; k0 += 16) {
      uint32_t a[4] = {*(const uint32_t*)(x0 + k0), *(const uint32_t*)(x1 + k0), *(const uint32_t*)(x0 + k0 + 8), *(const uint32_t*)(x1 + k0 + 8)};
      const uint16_t* wr = wq + (size_t)(k0 + 2 * q) * HD;
#pragma unroll
      for (int n = 0; n < 16; n++) {
        if ((n & 3) == 0) __syncwarp();
        mma16816(o[n], a, wr[8 * n] | ((uint32_t)wr[8 * n + HD] << 16), wr[8 * n + 8 * HD] | ((uint32_t)wr[8 * n + 9 * HD] << 16));
      }
    }
    uint32_t qa[8][4];
#pragma unroll
    for (int k = 0; k < 8; k++) {
      qa[k][0] = pack(o[2 * k][0] * QSCALE, o[2 * k][1] * QSCALE);
      qa[k][1] = pack(o[2 * k][2] * QSCALE, o[2 * k][3] * QSCALE);
      qa[k][2] = pack(o[2 * k + 1][0] * QSCALE, o[2 * k + 1][1] * QSCALE);
      qa[k][3] = pack(o[2 * k + 1][2] * QSCALE, o[2 * k + 1][3] * QSCALE);
    }
#pragma unroll
    for (int n = 0; n < 16; n++) o[n][0] = o[n][1] = o[n][2] = o[n][3] = 0.f;
    float m0 = -INFINITY, m1 = -INFINITY, l0 = 0.f, l1 = 0.f;
#pragma unroll 1
    for (int key0 = 0; key0 < SK; key0 += 16) {
      float s[2][4];
#pragma unroll
      for (int nt = 0; nt < 2; nt++) {
        s[nt][0] = s[nt][1] = s[nt][2] = s[nt][3] = 0.f;
        const __nv_bfloat16* kr = kp + (size_t)(key0 + 8 * nt + g) * DH + 2 * q;
#pragma unroll
        for (int k = 0; k < 8; k++) mma16816(s[nt], qa[k], *(const uint32_t*)(kr + 16 * k), *(const uint32_t*)(kr + 16 * k + 8));
      }
      float n0 = fmaxf(fmaxf(s[0][0], s[0][1]), fmaxf(s[1][0], s[1][1])), n1 = fmaxf(fmaxf(s[0][2], s[0][3]), fmaxf(s[1][2], s[1][3]));
      n0 = fmaxf(n0, __shfl_xor_sync(~0u, n0, 1)); n1 = fmaxf(n1, __shfl_xor_sync(~0u, n1, 1));
      n0 = fmaxf(n0, __shfl_xor_sync(~0u, n0, 2)); n1 = fmaxf(n1, __shfl_xor_sync(~0u, n1, 2));
      n0 = fmaxf(n0, m0); n1 = fmaxf(n1, m1);
      const float z0 = n0 == -INFINITY ? 0.f : n0, z1 = n1 == -INFINITY ? 0.f : n1;
      const float c0 = ex2(m0 - z0), c1 = ex2(m1 - z1);
      m0 = n0; m1 = n1;
#pragma unroll
      for (int nt = 0; nt < 2; nt++) {
        s[nt][0] = ex2(s[nt][0] - z0); s[nt][1] = ex2(s[nt][1] - z0);
        s[nt][2] = ex2(s[nt][2] - z1); s[nt][3] = ex2(s[nt][3] - z1);
      }
      l0 = l0 * c0 + s[0][0] + s[0][1] + s[1][0] + s[1][1];
      l1 = l1 * c1 + s[0][2] + s[0][3] + s[1][2] + s[1][3];
      uint32_t pa[4] = {pack(s[0][0], s[0][1]), pack(s[0][2], s[0][3]), pack(s[1][0], s[1][1]), pack(s[1][2], s[1][3])};
      const uint16_t* vr = vp + (size_t)(key0 + 2 * q) * DH;
#pragma unroll
      for (int n = 0; n < 16; n++) {
        if ((n & 3) == 0) __syncwarp();
        o[n][0] *= c0; o[n][1] *= c0; o[n][2] *= c1; o[n][3] *= c1;
        mma16816(o[n], pa, vr[8 * n] | ((uint32_t)vr[8 * n + DH] << 16), vr[8 * n + 8 * DH] | ((uint32_t)vr[8 * n + 9 * DH] << 16));
      }
    }
    l0 += __shfl_xor_sync(~0u, l0, 1); l1 += __shfl_xor_sync(~0u, l1, 1);
    l0 += __shfl_xor_sync(~0u, l0, 2); l1 += __shfl_xor_sync(~0u, l1, 2);
    const float i0 = 1.f / l0, i1 = 1.f / l1;
    __nv_bfloat16* oc = P.o + (size_t)(h * DH + 2 * q) * NROWS + b * SQ;
    const int p0 = o_pos(wg, r0), p1 = o_pos(wg, min(r1, 119));
#pragma unroll
    for (int n = 0; n < 16; n++) {
      oc[(size_t)(8 * n) * NROWS + p0] = __float2bfloat16(o[n][0] * i0);
      oc[(size_t)(8 * n + 1) * NROWS + p0] = __float2bfloat16(o[n][1] * i0);
      if (r1 < 120) {
        oc[(size_t)(8 * n) * NROWS + p1] = __float2bfloat16(o[n][2] * i1);
        oc[(size_t)(8 * n + 1) * NROWS + p1] = __float2bfloat16(o[n][3] * i1);
      }
    }
  }
}

__device__ __forceinline__ int bk(int ks) { return B_ORDER && ks < 48 ? 32 - (ks & 48) + (ks & 15) : ks; }
__device__ __forceinline__ uint32_t x_slot(uint32_t wg, uint32_t j) { return j < 2 ? (2 * wg + j) * XB : (2 * j + wg) * XB; }
__device__ __forceinline__ int row_block(int t) { return t >= 44 ? (t >> 2) - 11 : (t >> 2) + 4; }
__device__ __forceinline__ int unit_batch(int u) { return (u & 63) >> 2; }
__device__ __forceinline__ int unit_head(int u, int rank) { return (u >> 6) * 8 + (u & 3) * 2 + rank; }

template <int NCL>
__global__ void __cluster_dims__(2, 1, 1) __launch_bounds__(384, 1)
fused_attn_kernel(const __grid_constant__ CUtensorMap tm_x, const __grid_constant__ CUtensorMap tm_wq,
                  const __grid_constant__ CUtensorMap tm_k, const __grid_constant__ CUtensorMap tm_v,
                  const __grid_constant__ CUtensorMap tm_o, const __grid_constant__ CUtensorMap tm_wo,
                  const __grid_constant__ Params P) {
  extern __shared__ uint8_t smem_raw[];
  const uint32_t sb = ((uint32_t)__cvta_generic_to_shared(smem_raw) + 1023) & ~1023u;
  if (threadIdx.x == 0) TS(152);
  const int warp = __shfl_sync(~0u, threadIdx.x >> 5, 0);
  int lane = threadIdx.x & 31;
  const int rank = blockIdx.x & 1, cl = blockIdx.x >> 1, ncl = NCL ? NCL : gridDim.x >> 1;

  const int nsingle = NCL == 66 ? 44 : NOTILES;
  auto role = [&]() {
    mbar_wait(sb + BAR_ROLE + 16, 0);
    int id;
    asm volatile("ld.shared.u32 %0, [%1];" : "=r"(id) : "r"(sb + BAR_ROLE + 8) : "memory");
    return id;
  };

  if (EARLY && threadIdx.x == 128) asm volatile("prefetch.tensormap [%0];" ::"l"(&tm_x) : "memory");
  if (threadIdx.x == 0) {
    if (EARLY) asm volatile("prefetch.tensormap [%0];" ::"l"(&tm_wq) : "memory");
    for (int i = 0; i < 6; i++) {
      mbar_init(sb + BAR_RFULL + 8 * i, 1); mbar_init(sb + BAR_REMPTY + 8 * i, 8);
      mbar_init(sb + BAR_BFULL + 8 * i, 1); mbar_init(sb + BAR_BEMPTY + 8 * i, 16);
    }
    for (int i = 0; i < 8; i++) mbar_init(sb + BAR_XFULL + 8 * i, 1);
    for (int i = 0; i < 4; i++) mbar_init(sb + BAR_XEMPTY + 8 * i, 8);
    for (int i = 0; i < 2; i++) { mbar_init(sb + BAR_STAGE + 8 * i, 4); mbar_init(sb + BAR_LSUM + 8 * i, 4); mbar_init(sb + BAR_INV + 8 * i, 1); }
    mbar_init(sb + BAR_ROLE, 1); mbar_init(sb + BAR_ROLE + 16, 1);
    asm volatile("fence.mbarrier_init.release.cluster;" ::: "memory");
  }
  __syncwarp();
  asm volatile("barrier.cluster.arrive.relaxed.aligned;" ::: "memory");
  auto first_w = [&](int s) {
    mbar_expect(sb + BAR_RFULL + 8 * s, RING_BYTES);
    tma3d(sb + s * RING_BYTES, &tm_wq, 0, s * 64, 2 * unit_head(cl, rank), sb + BAR_RFULL + 8 * s);
  };
  if (EARLY && threadIdx.x == 0) first_w(0);
  __syncwarp();
  asm volatile("barrier.cluster.wait.aligned;" ::: "memory");
  if (EARLY && threadIdx.x == 128) {
#pragma unroll 1
    for (int s = 0; s < EARLY_X; s++) {
      const uint32_t fb = sb + BAR_XFULL + 32 * rank + 8 * s;
      mbar_expect(fb, XB);
      mbar_expect_cl(mapa(fb, rank ^ 1), XB);
      tma2d_mc(sb + OFF_Q + x_slot(rank, s), &tm_x, s * 64, unit_batch(cl) * SQ + rank * 120, fb);
      if (s + 1 < EARLY_W) first_w(s + 1);
    }
  }
  __syncwarp();
  if (threadIdx.x == 0) TS(153);

  if (warp >= 8) {
    asm volatile("setmaxnreg.dec.sync.aligned.u32 24;");
    if (warp == 8) {
      uint64_t pol;
      asm volatile("createpolicy.fractional.L2::evict_first.b64 %0, 1.0;" : "=l"(pol));
      Ring r;
      if (EARLY) r.slot = EARLY_W;
      auto load = [&](const CUtensorMap* m, int c1, int c2, bool ef) {
        mbar_wait(sb + BAR_REMPTY + 8 * r.slot, r.phase ^ 1);
        if (lane == 0) {
          mbar_expect(sb + BAR_RFULL + 8 * r.slot, RING_BYTES);
          if (ef) tma3d_hint(sb + r.slot * RING_BYTES, m, 0, c1, c2, sb + BAR_RFULL + 8 * r.slot, pol);
          else tma3d(sb + r.slot * RING_BYTES, m, 0, c1, c2, sb + BAR_RFULL + 8 * r.slot);
        }
        r.next();
      };
      const int rot = ROT * (blockIdx.x * 5 + (blockIdx.x >> 4));
      auto pause = [&](int u0) {
        if (PAUSE_NS && NCL == 66 && u0 == PAUSE_AT * 66) {
          const int id = role();
          if (id >= 44 && id < 58) {
            unsigned t0, t1;
            asm volatile("mov.u32 %0, %globaltimer_lo;" : "=r"(t0));
            do { __nanosleep(200); asm volatile("mov.u32 %0, %globaltimer_lo;" : "=r"(t1)); } while (t1 - t0 < PAUSE_NS + (id - 44) * PAUSE_SPREAD);
          }
        }
      };
      for (int u0 = 0;; u0 += ncl) {
        const int u = __shfl_sync(~0u, (u0 >= 3 * ncl ? role() : cl) + u0, 0);
        if (u >= NUNITS) break;
        if (PAUSE_J < 0) pause(u0);
        const int h = unit_head(u, rank);
        const int krow = (unit_batch(u) * NH + h) * SK;
#pragma unroll 1
        for (int s = EARLY && u0 == 0 ? EARLY_W : 0; s < 10; s++) {
          if (u0 == 0 && s == 0 && lane == 0) TS(154);
          load(&tm_wq, s * 64, 2 * h, false);
          if (u0 == 0 && s == 0 && lane == 0) TS(155);
          const int sp = u0 == 0 ? s - PF_HOLD : s;
          if (sp >= 0 && sp < PF_N && lane == 0) l2_prefetch(P.v + (size_t)(krow + ((PF_J0 + sp * PF_STEP + rot) & 15) * 64) * DH, 16384);
        }
#pragma unroll 1
        for (int j = 0; j <= 16; j++) {
          if (j == PAUSE_J) pause(u0);
          if (j < 16) load(&tm_k, krow + ((j + rot) & 15) * 64, 0, true);
          if (j == 1 + DPRO) load(&tm_v, krow + (rot & 15) * 64, 0, true);
          if (j > 1) load(&tm_v, krow + ((j - 1 + rot) & 15) * 64, 0, true);
        }
      }
      const int id = __shfl_sync(~0u, role(), 0);
      const bool dbl = NCL == 66 && id >= 58;
      for (int t = dbl ? 2 * id - 72 : id; t < (dbl ? NOTILES : nsingle); t += ncl) {
        const int row0 = row_block(t) * 256 + rank * 128;
        const int b0 = row0 / SQ, b1 = (row0 + 127) / SQ;
#pragma unroll 1
        for (int ks = 0; ks < 64; ks++) {
          if (dbl ? (ks & 15) == 0 : ks == 0 || ks == 48) {
            const unsigned* c = &g_cnt[((lane & 1 ? b1 : b0) * 4 + (ks || dbl ? ks >> 4 : min(lane >> 1, 2))) * 8];
            unsigned v, n = 0;
            do {
              asm volatile("ld.acquire.gpu.global.u32 %0, [%1];" : "=r"(v) : "l"(c) : "memory");
              if (++n > (1u << 26)) __trap();
            } while (v < 16);
            __syncwarp();
            asm volatile("fence.proxy.async.global;" ::: "memory");
          }
          load(&tm_o, (dbl ? ks : bk(ks)) * 64, row0 >> 6, O_EF);
        }
      }
      if (lane == 0 && atomicAdd(&g_cnt[64 * 8], 1) == gridDim.x - 1) {
        for (int i = 0; i < 67; i++) g_cnt[i * 8] = 0;
      }
    } else if (warp == 9) {
      if (lane == 0) {
        uint32_t it = 0;
        for (;; it++) {
          const int u = (it >= 3 ? role() : cl) + it * ncl;
          if (u >= NUNITS) break;
          const int row = unit_batch(u) * SQ + rank * 120;
#pragma unroll 1
          for (int s = EARLY && it == 0 ? EARLY_X : 0; s < 10; s++) {
            const uint32_t j = s & 3, par = ((s >> 2) + (j < 2 ? it : 0)) & 1;
            mbar_wait(sb + BAR_XEMPTY + 8 * j, par ^ 1);
            const uint32_t fb = sb + BAR_XFULL + 32 * rank + 8 * j;
            mbar_expect(fb, XB);
            mbar_expect_cl(mapa(fb, rank ^ 1), XB);
            tma2d_mc(sb + OFF_Q + x_slot(rank, j), &tm_x, s * 64, row, fb);
          }
        }
        const int id = role();
        const bool dbl = NCL == 66 && id >= 58;
        uint32_t slot = rank, phase = 0;
        if (WO_PF0 && dbl)
          asm volatile("cp.async.bulk.prefetch.tensor.3d.L2.global [%0, {%1, %2, %3}];" ::"l"(&tm_wo), "r"(0), "r"((2 + ((id >> 1) & 3)) * 64), "r"(((2 * id - 72 + rank) & 3) * 5) : "memory");
        for (int t = dbl ? 2 * id - 72 + rank : id; t < (dbl ? NOTILES : nsingle); t += ncl) {
#pragma unroll 1
          for (int ks = dbl ? 0 : rank; ks < 64; ks += dbl ? 1 : 2) {
            mbar_wait(sb + BAR_BEMPTY + 8 * slot, phase);
            const uint32_t fb = sb + BAR_BFULL + 8 * slot;
            mbar_expect(fb, BB);
            mbar_expect_cl(mapa(fb, rank ^ 1), BB);
            tma3d_mc(sb + OFF_Q + slot * BB, &tm_wo, 0, (dbl ? ks : bk(ks)) * 64, (t & 3) * 5, fb);
            if (WO_PF && dbl && ks + WO_PF < 64 && (ks & 3) == ((id >> 1) & 3))
              asm volatile("cp.async.bulk.prefetch.tensor.3d.L2.global [%0, {%1, %2, %3}];" ::"l"(&tm_wo), "r"(0), "r"((ks + WO_PF) * 64), "r"((t & 3) * 5) : "memory");
            slot += 2;
            if (slot >= 6) { slot -= 6; phase ^= 1; }
          }
        }
      }
    } else {
      const int wg = warp - 10;
      {
        mbar_wait(sb + BAR_RFULL, 0);
        const __nv_bfloat16* xs = P.x + (size_t)(unit_batch(cl) * SQ + ((cl & 3) * 2 + rank) * 30 + min(lane, 29)) * DM + 256 + wg * 64;
#pragma unroll
        for (int i = 0; i < 3; i++) asm volatile("prefetch.global.L2 [%0];" ::"l"(xs + i * 128));
        if (lane < 16) asm volatile("prefetch.global.L2 [%0];" ::"l"(P.wq + (size_t)(384 + unit_batch(cl) * 16 + lane) * HD + unit_head(cl, rank) * DH + wg * 64));
      }
      auto take_role = [&]() {
          if (wg == 0 && rank == 0 && lane == 0) {
            int id = cl;
            if (NCL == 66) {
              uint32_t smid;
              asm("mov.u32 %0, %smid;" : "=r"(smid));
              id = smid >= SMID_TOP ? 65 - atomicAdd(&g_cnt[65 * 8], 1) : atomicAdd(&g_cnt[66 * 8], 1);
            }
    #pragma unroll
            for (int c = 0; c < 2; c++) {
              const uint32_t a = mapa(sb + BAR_ROLE, c);
              asm volatile("st.shared::cluster.u32 [%0 + 8], %1;\nmbarrier.arrive.release.cluster.shared::cluster.b64 _, [%0];" ::"r"(a), "r"(id) : "memory");
            }
          }
          if (wg == 0 && lane == 0) {
            mbar_wait_cl(sb + BAR_ROLE, 0);
            mbar_arrive(sb + BAR_ROLE + 16);
          }
      };
      if (ROLE_AT < 0) { take_role(); __syncwarp(); }
      for (uint32_t it = 0;; it++) {
        const int u = __shfl_sync(~0u, (it >= 3 ? role() : cl) + it * ncl, 0);
        if (u >= NUNITS) break;
        mbar_wait(sb + BAR_LSUM + 8 * wg, it & 1);
        float l4[4], v[4];
        const uint32_t a = sb + OFF_L2 + wg * 2048 + lane * 16;
        asm volatile("ld.shared.v4.f32 {%0, %1, %2, %3}, [%4];" : "=f"(l4[0]), "=f"(l4[1]), "=f"(l4[2]), "=f"(l4[3]) : "r"(a) : "memory");
#pragma unroll
        for (int g = 1; g < 4; g++) {
          asm volatile("ld.shared.v4.f32 {%0, %1, %2, %3}, [%4];" : "=f"(v[0]), "=f"(v[1]), "=f"(v[2]), "=f"(v[3]) : "r"(a + g * 512) : "memory");
#pragma unroll
          for (int c = 0; c < 4; c++) l4[c] += v[c];
        }
#pragma unroll
        for (int c = 0; c < 4; c++) {
          float inv;
          asm("rcp.approx.ftz.f32 %0, %1;" : "=f"(inv) : "f"(l4[c]));
          l4[c] = l4[c] >= L_MIN && l4[c] <= L_MAX ? inv : __uint_as_float(0x7FFFFFFFu);
        }
        const uint32_t h0 = pack(l4[0], l4[1]), h1 = pack(l4[2], l4[3]);
        const uint32_t e0 = pack(l4[0] - __uint_as_float(h0 << 16), l4[1] - __uint_as_float(h0 & 0xFFFF0000u));
        const uint32_t e1 = pack(l4[2] - __uint_as_float(h1 << 16), l4[3] - __uint_as_float(h1 & 0xFFFF0000u));
        const uint32_t ia = sb + OFF_INV + wg * 640 + (lane & 1) * 288 + (lane >> 1) * 8;
        asm volatile("st.shared.v2.u32 [%0], {%1, %2};\nst.shared.v2.u32 [%0 + 144], {%3, %4};" ::"r"(ia), "r"(h0), "r"(e0), "r"(h1), "r"(e1) : "memory");
        __syncwarp();
        if (lane == 0) {
          mbar_arrive(sb + BAR_INV + 8 * wg);
          if ((int)it == ROLE_AT) {
            take_role();
          }
          mbar_wait(sb + BAR_STAGE + 8 * wg, it & 1);
          __threadfence();
          asm volatile("red.relaxed.gpu.global.add.u32 [%0], 1;" ::"l"(&g_cnt[(unit_batch(u) * 4 + (u >> 6)) * 8]) : "memory");
        }
        __syncwarp();
      }
    }
  } else {
    asm volatile("setmaxnreg.inc.sync.aligned.u32 240;");
    const int wg = warp >> 2, w = warp & 3;
    if (PINLANE) lane = __shfl_sync(~0u, lane, lane);
    const uint32_t qreg = sb + OFF_Q + wg * 2 * XB, preg = sb + OFF_P + (2 + wg) * XB;
    const uint32_t st_off = ((lane >> 4) * 8 + (lane & 7)) * 128 + (((2 * w + ((lane >> 3) & 1)) ^ (lane & 7)) << 4);
    const uint32_t xempty = mapa(sb + BAR_XEMPTY, wg);
    Ring r;
    uint32_t it = 0;
    const uint32_t qd = (qreg & 0x3FFFF) >> 4, pd = (preg & 0x3FFFF) >> 4;
    auto ring_addr = [&]() { return ((sb & 0x3FFFF) + r.slot * RING_BYTES) >> 4; };
    auto ring_wait = [&]() { mbar_wait(sb + BAR_RFULL + 8 * r.slot, r.phase); };
    auto release = [&](uint32_t slot) { if (lane == 0) mbar_arrive(sb + BAR_REMPTY + 8 * slot); };
    auto turn_wait = [&]() {
      if (wg == 0) asm volatile("bar.sync 3, 256;" ::: "memory");
      else asm volatile("bar.sync 4, 256;" ::: "memory");
    };
    auto turn_pass = [&]() {
      if (wg == 0) asm volatile("bar.arrive 4, 256;" ::: "memory");
      else asm volatile("bar.arrive 3, 256;" ::: "memory");
    };

    uint32_t chk = 0;
    auto sum_l = [&]() {
      __syncwarp();
      float lv[8][4];
#pragma unroll
      for (int g = 0; g < 8; g++)
        asm volatile("ld.shared.v4.f32 {%0, %1, %2, %3}, [%4];" : "=f"(lv[g][0]), "=f"(lv[g][1]), "=f"(lv[g][2]), "=f"(lv[g][3])
                     : "r"(preg + (8 * w + g) * 480 + min(lane, 29) * 16) : "memory");
#pragma unroll
      for (int c = 0; c < 4; c++) lv[0][c] = ((lv[0][c] + lv[1][c]) + (lv[2][c] + lv[3][c])) + ((lv[4][c] + lv[5][c]) + (lv[6][c] + lv[7][c]));
      asm volatile("st.shared.v4.f32 [%0], {%1, %2, %3, %4};" ::"r"(sb + OFF_L2 + wg * 2048 + w * 512 + lane * 16), "f"(lv[0][0]), "f"(lv[0][1]),
                   "f"(lv[0][2]), "f"(lv[0][3]) : "memory");
      __syncwarp();
      if (lane == 0) mbar_arrive(sb + BAR_LSUM + 8 * wg);
    };
    auto load_inv = [&](uint32_t (&iv)[30], uint32_t parity) {
      mbar_wait(sb + BAR_INV + 8 * wg, parity);
      chk = 0;
#pragma unroll
      for (int j = 0; j < 7; j++)
        asm volatile("ld.shared.v4.u32 {%0, %1, %2, %3}, [%4];" : "=r"(iv[4 * j]), "=r"(iv[4 * j + 1]), "=r"(iv[4 * j + 2]), "=r"(iv[4 * j + 3])
                     : "r"(sb + OFF_INV + wg * 640 + (lane & 3) * 144 + j * 16) : "memory");
      asm volatile("ld.shared.v2.u32 {%0, %1}, [%2];" : "=r"(iv[28]), "=r"(iv[29]) : "r"(sb + OFF_INV + wg * 640 + (lane & 3) * 144 + 112) : "memory");
    };
    auto norm = [&](uint32_t (&n)[8], const uint32_t (&po)[60], const uint32_t (&iv)[30], auto part) {
      constexpr int k = decltype(part)::value >> 1, j0 = (decltype(part)::value & 1) * 8;
#pragma unroll
      for (int j = 0; j < 8; j++)
        n[j] = j0 + j < 15 ? hfma2(po[15 * k + (j0 + j) % 15], iv[2 * ((j0 + j) % 15)], hfma2(po[15 * k + (j0 + j) % 15], iv[2 * ((j0 + j) % 15) + 1], 0x80008000u)) : 0x3F803F80u;
#pragma unroll
      for (int j = 0; j < 8; j += 2) chk = hfma2(n[j], n[j + 1], chk);
    };
    auto store = [&](const uint32_t (&n)[8], const char* optr, auto part) {
      constexpr int k = decltype(part)::value >> 1, off = (8 * (k & 1) + 64 * (k >> 1)) * NROWS * 2;
      if ((decltype(part)::value & 1) == 0)
        asm volatile(
            "{\n.reg .pred p;\nsetp.ne.u64 p, %8, 0;\n"
            "@p st.global.v4.u32 [%8 + %9], {%0, %1, %2, %3};\n@p st.global.v4.u32 [%8 + %9 + 64], {%4, %5, %6, %7};\n}\n"
            ::"r"(n[0]), "r"(n[1]), "r"(n[2]), "r"(n[3]), "r"(n[4]), "r"(n[5]), "r"(n[6]), "r"(n[7]), "l"(optr), "n"(off) : "memory");
      else
        asm volatile(
            "{\n.reg .pred p;\n.reg .b64 b, c;\nsetp.ne.u64 p, %7, 0;\nmad.wide.s32 b, %9, 8, %7;\nmad.wide.s32 c, %10, 4, %7;\n"
            "@p st.global.v4.u32 [%7 + %8 + 128], {%0, %1, %2, %3};\n@p st.global.v2.u32 [b + %8], {%4, %5};\n@p st.global.u32 [c + %8], %6;\n}\n"
            ::"r"(n[0]), "r"(n[1]), "r"(n[2]), "r"(n[3]), "r"(n[4]), "r"(n[5]), "r"(n[6]), "l"(optr), "n"(off),
            "r"((wg ? -4 : 24) - (lane & 3)), "r"((wg ? -12 : 56) - 3 * (lane & 3)) : "memory");
    };
    auto put = [&](const uint32_t (&po)[60], const uint32_t (&iv)[30], const char* optr, auto part) {
      uint32_t n[8];
      norm(n, po, iv, part);
      store(n, optr, part);
    };
    auto out_ptr = [&](int u) {
      return reinterpret_cast<const char*>(P.o + (uint32_t)((unit_head(u, rank) * DH + 16 * w + (lane >> 2)) * NROWS + unit_batch(u) * SQ + wg * 144 + (lane & 3) * 8));
    };
    auto unsafe = [&](bool valid) {
      const bool b = valid && ((chk & 0x7F80u) == 0x7F80u || (chk & 0x7F800000u) == 0x7F800000u);
      return __any_sync(~0u, bar_red_or(wg, b));
    };
    auto publish = [&]() { __syncwarp(); if (lane == 0) mbar_arrive(sb + BAR_STAGE + 8 * wg); };

    uint32_t po[60];
#pragma unroll
    for (int i = 0; i < 60; i++) po[i] = 0;
    int id = 0;
    bool more;
    do {
      float o0[60], o1[60];
      uint32_t prev = 0;
      auto qstep = [&](int s, int acc) {
        const uint32_t j = s & 3, par = ((s >> 2) + (j < 2 ? it : 0)) & 1;
        TR(it * 160 + 3 * s);
        ring_wait();
        TR(it * 160 + 3 * s + 1);
        mbar_wait(sb + BAR_XFULL + 32 * wg + 8 * j, par);
        TR(it * 160 + 3 * s + 2);
        if (s >= ALT_FROM) turn_wait();
        wg_fence();
        mma_tn(o0, o1, ring_addr(), ((sb & 0x3FFFF) + OFF_Q + x_slot(wg, j)) >> 4, acc);
        wg_commit();
        if ((s >= ALT_FROM && !(MERGE89 && s == 8)) || (s == ALT_FROM - 1 && wg == 1)) turn_pass();
        if (s > 0) {
          wg_wait<1>();
          release(prev);
          if (s <= 6 && lane == 0) mbar_arrive_cl(xempty + 8 * ((s - 1) & 3));
        }
        prev = r.slot;
        r.next();
      };
      qstep(0, 0);
      const int up = (it > 3 ? id : cl) + ((int)it - 1) * ncl;
      const char* optr = it > 0 ? out_ptr(up) : nullptr;
      uint32_t n7[8];
      {
        uint32_t iv[30];
        if (LATE_SUM && it > 0) {
          sum_l();
          if (lane == 0) mbar_arrive_cl(xempty + 24);
        }
        if (PUT_FROM == 1) {
          qstep(1, 1); load_inv(iv, (it + 1) & 1); put(po, iv, optr, IC<0>());
          qstep(2, 1); put(po, iv, optr, IC<1>());
          qstep(3, 1); put(po, iv, optr, IC<2>());
          qstep(4, 1); put(po, iv, optr, IC<3>());
          qstep(5, 1); put(po, iv, optr, IC<4>());
          qstep(6, 1); put(po, iv, optr, IC<5>());
          qstep(7, 1); put(po, iv, optr, IC<6>());
          norm(n7, po, iv, IC<7>());
          if (LATE_AT == 3) store(n7, optr, IC<7>());
          qstep(8, 1);
          if (LATE_AT == 2) store(n7, optr, IC<7>());
        } else {
          qstep(1, 1);
          qstep(2, 1); load_inv(iv, (it + 1) & 1); put(po, iv, optr, IC<0>());
          qstep(3, 1); put(po, iv, optr, IC<1>());
          qstep(4, 1); put(po, iv, optr, IC<2>());
          qstep(5, 1); put(po, iv, optr, IC<3>());
          qstep(6, 1); put(po, iv, optr, IC<4>());
          qstep(7, 1); put(po, iv, optr, IC<5>());
          uint32_t n6[8];
          norm(n6, po, iv, IC<6>());
          norm(n7, po, iv, IC<7>());
          qstep(8, 1);
          store(n6, optr, IC<6>());
        }
      }
      TR(it * 160 + 27);
      ring_wait();
      TR(it * 160 + 28);
      mbar_wait(sb + BAR_XFULL + 32 * wg + 8, it & 1);
      TR(it * 160 + 29);
      if (!MERGE89) turn_wait();
      wg_fence();
      mma_tn_split(o0, o1, ring_addr(), qd + (XB >> 4));
      turn_pass();
      if (LATE_AT == 4) store(n7, optr, IC<7>());
      wg_wait<2>();
      release(prev);
      auto put_q = [&](const float (&o)[60], uint32_t dst) {
        bar_sync(wg);
#pragma unroll
        for (int j = 0; j < 14; j += 2)
          stsm4t(dst + j * 1024, pack(o[4 * j] * QSCALE, o[4 * j + 1] * QSCALE), pack(o[4 * j + 2] * QSCALE, o[4 * j + 3] * QSCALE),
                 pack(o[4 * j + 4] * QSCALE, o[4 * j + 5] * QSCALE), pack(o[4 * j + 6] * QSCALE, o[4 * j + 7] * QSCALE));
        stsm2t(dst + 14 * 1024, pack(o[56] * QSCALE, o[57] * QSCALE), pack(o[58] * QSCALE, o[59] * QSCALE));
      };
      wg_wait<1>();
      reg_fence(o0);
      put_q(o0, qreg + st_off);
      wg_wait<0>();
      reg_fence(o1);
      release(r.slot);
      r.next();
      TR(it * 160 + 30);
      put_q(o1, qreg + XB + st_off);
      fence_async_smem();
      if (unsafe(it > 0)) {
        slow_path(P, unit_batch(up), unit_head(up, rank), wg, w, lane);
        optr = nullptr;
        if (!DPRO) {
#pragma unroll
          for (int i = 0; i < 60; i++) o0[i] = o1[i] = 0.f;
        }
      }
      TR(it * 160 + 32); TG(it * 160 + 142);

      float sc[60], l[30];
      uint32_t slot0 = r.slot;
      ring_wait();
      TR(it * 160 + 33);
      turn_wait();
      wg_fence();
      mma_qk(sc, ring_addr(), qd);
      wg_commit();
      r.next();
      uint32_t slot1 = r.slot;
      ring_wait();
      wg_fence();
      mma_qk(o1, ring_addr(), qd);
      wg_commit();
      r.next();
      turn_pass();
      if (LATE_AT == 0) store(n7, optr, IC<7>());
      wg_wait<1>();
      reg_fence(sc);
      TR(it * 160 + 35);
      release(slot0);
      exp_store<0, 15, true>(sc, l, preg + st_off);
      TR(it * 160 + 38); TG(it * 160 + 43);
      slot0 = r.slot;
      ring_wait();
      wg_fence();
      mma_qk(sc, ring_addr(), qd);
      wg_commit();
      r.next();
      wg_wait<1>();
      reg_fence(o1);
      TR(it * 160 + 41);
      release(slot1);
      exp_store<0, 15>(o1, l, preg - 2 * XB + st_off);
      fence_async_smem();
      bar_sync(wg);
      TR(it * 160 + 44);
      slot1 = r.slot;
      ring_wait();
      turn_wait();
      wg_fence();
      mma_tn(o0, o1, ring_addr(), pd, 0);
      wg_commit();
      r.next();
      ring_wait();
      wg_fence();
      mma_tn(o0, o1, ring_addr(), pd - (2 * XB >> 4), 1);
      wg_commit();
      turn_pass();
      if (LATE_AT == 1) store(n7, optr, IC<7>());
      if (it > 0) publish();
      if (it >= 2) id = __shfl_sync(~0u, role(), 0);
      wg_wait<1>();
      reg_fence(sc);
      release(slot0);
      release(slot1);
      bar_sync(wg);
      TR(it * 160 + 47);
      exp_store<0, VREL>(sc, l, preg + st_off);
      wg_wait<0>();
      reg_fence(o0); reg_fence(o1);
      release(r.slot);
      r.next();
      exp_store<VREL, 15>(sc, l, preg + st_off);
      fence_async_smem();
      bar_sync(wg);
      more = id + ((int)it + 1) * ncl < NUNITS;
      const bool gemm = id < nsingle || (NCL == 66 && id >= 58);
#pragma unroll 1
      for (int s = DPRO ? 3 : 1; s < 16; s++) {
        const uint32_t kslot = r.slot;
        TR(it * 160 + 32 + 6 * s); TG(it * 160 + 37 + 6 * s);
        if (s == 8) TRL(it * 160 + 139);
        ring_wait();
        TR(it * 160 + 33 + 6 * s);
        turn_wait();
        wg_fence();
        mma_qk(sc, ring_addr(), qd);
        wg_commit();
        r.next();
        TR(it * 160 + 36 + 6 * s);
        ring_wait();
        TR(it * 160 + 34 + 6 * s);
        wg_fence();
        mma_tn(o0, o1, ring_addr(), pd - ((s - 1) & 1) * (2 * XB >> 4), DPRO || s != 1);
        wg_commit();
        if (wg == 0 || s < 15) turn_pass();
        wg_wait<1>();
        reg_fence(sc);
        TR(it * 160 + 35 + 6 * s);
        release(kslot);
        if (s == 15) {
          if (more) { if (lane < 2) mbar_arrive_cl(xempty + 8 * lane); }
          else if (lane < 3 && gemm) mbar_arrive_cl(mapa(sb + BAR_BEMPTY + 8 * lane, lane & 1));
        }
        exp_store<0, VREL>(sc, l, preg - (s & 1) * 2 * XB + st_off);
        wg_wait<0>();
        reg_fence(o0); reg_fence(o1);
        release(r.slot);
        r.next();
        exp_store<VREL, 15>(sc, l, preg - (s & 1) * 2 * XB + st_off);
        fence_async_smem();
      }
      bar_sync(wg);
      TR(it * 160 + 128);
      ring_wait();
      wg_fence();
      mma_tn_split(o0, o1, ring_addr(), pd - (2 * XB >> 4));
      {
        const uint32_t a = preg + (8 * w + (lane >> 2)) * 480 + (lane & 3) * 8;
#pragma unroll
        for (int j = 0; j < 15; j++) asm volatile("st.shared.v2.f32 [%0], {%1, %2};" ::"r"(a + j * 32), "f"(l[2 * j]), "f"(l[2 * j + 1]) : "memory");
      }
      TR(it * 160 + 132);
      if (!LATE_SUM) sum_l();
      TR(it * 160 + 133);
      wg_wait<1>();
      reg_fence(o0);
      TR(it * 160 + 134);
#pragma unroll
      for (int j = 0; j < 15; j++) { po[j] = pack(o0[4 * j], o0[4 * j + 1]); po[15 + j] = pack(o0[4 * j + 2], o0[4 * j + 3]); }
      wg_wait<0>();
      reg_fence(o1);
      release(r.slot);
      r.next();
      if (LATE_SUM && !more) sum_l();
      if (more) { if (lane < 2 - LATE_SUM) mbar_arrive_cl(xempty + 16 + 8 * lane); }
      else if (gemm && lane < 3) mbar_arrive_cl(mapa(sb + BAR_BEMPTY + 24 + 8 * lane, (lane + 1) & 1));
      TR(it * 160 + 130);
#pragma unroll
      for (int j = 0; j < 15; j++) { po[30 + j] = pack(o1[4 * j], o1[4 * j + 1]); po[45 + j] = pack(o1[4 * j + 2], o1[4 * j + 3]); }
      TR(it * 160 + 131); TG(it * 160 + 143);
      it++;
    } while (more);
    const bool gemm = id < nsingle || (NCL == 66 && id >= 58);
    const int u = (it > 3 ? id : cl) + ((int)it - 1) * ncl;
    if (NCL != 66) lane = __shfl_sync(~0u, lane, lane);
    uint32_t pb[60];
#pragma unroll
    for (int i = 0; i < 60; i++) pb[i] = NCL != 66 ? po[i] ^ (gridDim.y - 1) : po[i];

    uint32_t bslot = 0, bphase = 0;
    auto out_tile = [&](const float (&acc)[80], int t) {
      const uint32_t st = sb + w * RING_BYTES + wg * 8192;
      const uint32_t sa = st + (lane & 15) * 336 + (lane >> 4) * 16;
#pragma unroll
      for (int j = 0; j < 20; j += 2)
        asm volatile("stmatrix.sync.aligned.m8n8.x4.shared.b16 [%0], {%1,%2,%3,%4};" ::"r"(sa + j * 16), "r"(pack(acc[4 * j], acc[4 * j + 1])),
                     "r"(pack(acc[4 * j + 2], acc[4 * j + 3])), "r"(pack(acc[4 * j + 4], acc[4 * j + 5])), "r"(pack(acc[4 * j + 6], acc[4 * j + 7])) : "memory");
      fence_async_smem();
      __syncwarp();
      if (lane < 16) {
        __nv_bfloat16* dst = P.out + (size_t)o_row(row_block(t) * 256 + rank * 128 + wg * 64 + w * 16 + lane) * DM + (t & 3) * 160;
        asm volatile("cp.async.bulk.global.shared::cta.bulk_group [%0], [%1], 320;" ::"l"(dst), "r"(st + lane * 336) : "memory");
        asm volatile("cp.async.bulk.commit_group;" ::: "memory");
        asm volatile("cp.async.bulk.wait_group.read 0;" ::: "memory");
      }
      __syncwarp();
    };
    for (int t = id; t == id || (NCL != 66 && t < nsingle); t += ncl) {
      float acc[80];
      uint32_t prev = 0, bprev = 0;
      const bool tile = t < nsingle;
      const bool last = NCL == 66 || t + ncl >= nsingle;
      auto bstep = [&](int ks, int accf) {
        if (!(ks & 3)) TR(640 + ks / 2); if ((ks & 7) == 0) TG(144 + (ks >> 3));
        ring_wait();
        mbar_wait(sb + BAR_BFULL + 8 * bslot, bphase);
        if (!(ks & 3)) TR(641 + ks / 2);
        wg_fence();
        const uint32_t a = ring_addr() + wg * 512, bd = (((sb & 0x3FFFF) + OFF_Q + bslot * BB) >> 4) | ((4096u >> 4) << 16);
#pragma unroll
        for (int k = 0; k < 4; k++) wgmma_n160<1, 1>(acc, a + k * 128, HI128, bd + k * 64, HI64, k == 0 ? accf : 1);
        wg_commit();
        if (ks > 0) {
          wg_wait<1>();
          release(prev);
          if (lane == 0 && (ks < 59 || !last)) mbar_arrive_cl(mapa(sb + BAR_BEMPTY + 8 * bprev, bprev & 1));
        }
        prev = r.slot; bprev = bslot;
        r.next();
        if (++bslot == 6) { bslot = 0; bphase ^= 1; }
      };
      const char* optr = t == id ? out_ptr(u) : nullptr;
      uint32_t iv[30], n3[8], n4[8], n5[8], n6[8], n7[8];
      if (tile) {
        bstep(0, 0);
        bstep(1, 1);
        load_inv(iv, (it + 1) & 1);
#pragma unroll 1
        for (int ks = 2; ks < 17; ks++) {
          bstep(ks, 1);
          switch (ks) {
            case 2: put(pb, iv, optr, IC<0>()); break;
            case 4: put(pb, iv, optr, IC<1>()); break;
            case 6: put(pb, iv, optr, IC<2>()); break;
            case 8: put(pb, iv, optr, IC<3>()); break;
            case 10: put(pb, iv, optr, IC<4>()); break;
            case 12: put(pb, iv, optr, IC<5>()); break;
            case 14: put(pb, iv, optr, IC<6>()); break;
            case 16: put(pb, iv, optr, IC<7>()); break;
            default: break;
          }
        }
        wg_wait<0>();
        reg_fence(acc);
#pragma unroll
        for (int i = 0; i < 8; i++) n3[i] = n4[i] = n5[i] = n6[i] = n7[i] = 0;
      } else {
        Ring r2 = r;
        auto first = [&](int ks) {
          if (ks == 0) { TR(640); TG(144); }
          if (gemm) { mbar_wait(sb + BAR_RFULL + 8 * r2.slot, r2.phase); mbar_wait(sb + BAR_BFULL + 16 * ks, 0); }
          wg_fence();
          const uint32_t a = (((sb & 0x3FFFF) + r2.slot * RING_BYTES) >> 4) + wg * 512;
          const uint32_t bd = (((sb & 0x3FFFF) + OFF_Q + 2 * ks * BB) >> 4) | ((4096u >> 4) << 16);
#pragma unroll
          for (int k = 0; k < 4; k++) wgmma_n160<1, 1>(acc, a + k * 128, HI128, bd + k * 64, HI64, k + ks != 0);
          wg_commit();
          if (ks > 0) {
            wg_wait<1>();
            if (gemm && lane == 0) mbar_arrive_cl(mapa(sb + BAR_BEMPTY + 16 * (ks - 1), 0));
          }
          r2.next();
        };
        first(0);
        load_inv(iv, (it + 1) & 1);
        put(pb, iv, optr, IC<0>());
        first(1);
        put(pb, iv, optr, IC<1>());
        norm(n3, pb, iv, IC<3>()); norm(n4, pb, iv, IC<4>());
        first(2);
        put(pb, iv, optr, IC<2>());
        norm(n5, pb, iv, IC<5>()); norm(n6, pb, iv, IC<6>()); norm(n7, pb, iv, IC<7>());
        wg_wait<0>();
        reg_fence(acc);
      }
      if (unsafe(t == id)) {
        slow_path(P, unit_batch(u), unit_head(u, rank), wg, w, lane);
        optr = nullptr;
#pragma unroll
        for (int i = 0; i < 8; i++) n3[i] = n4[i] = n5[i] = n6[i] = n7[i] = 0;
      }
      if (tile && t == id) publish();
      if (!tile) {
        if (gemm) {
          float ac1[80];
          auto half = [&](float (&ac)[80], bool rel, int accf) {
            mbar_wait(sb + BAR_BFULL + 8 * bslot, bphase);
            wg_fence();
            const uint32_t a = ring_addr() + wg * 512, bd = (((sb & 0x3FFFF) + OFF_Q + bslot * BB) >> 4) | ((4096u >> 4) << 16);
#pragma unroll
            for (int k = 0; k < 4; k++) wgmma_n160<1, 1>(ac, a + k * 128, HI128, bd + k * 64, HI64, k == 0 ? accf : 1);
            wg_commit();
            wg_wait<1>();
            if (lane == 0 && rel) mbar_arrive_cl(mapa(sb + BAR_BEMPTY + 8 * bprev, bprev & 1));
            bprev = bslot;
          };
          auto dstep = [&](int ks) {
            if (!(ks & 3)) TR(640 + ks / 2); if ((ks & 7) == 0) TG(144 + (ks >> 3));
            ring_wait();
            if (!(ks & 3)) TR(641 + ks / 2);
            half(acc, ks < 62, 1);
            release(prev);
            bslot++;
            half(ac1, ks < 61, 1);
            if (++bslot == 6) { bslot = 0; bphase ^= 1; }
            prev = r.slot; r.next();
          };
          bprev = 4; bslot = 1;
          half(ac1, true, 0);
          prev = r.slot; r.next(); bslot = 3;
          half(ac1, true, 1);
          release(prev); prev = r.slot; r.next(); bslot = 5;
          store(n3, optr, IC<3>());
          half(ac1, true, 1);
          release(prev); prev = r.slot; r.next(); bslot = 0; bphase = 1;
#pragma unroll 1
          for (int ks = 3; ks < 7; ks++) {
            dstep(ks);
            switch (ks) {
              case 3: store(n4, optr, IC<4>()); break;
              case 4: store(n5, optr, IC<5>()); break;
              case 5: store(n6, optr, IC<6>()); break;
              default: store(n7, optr, IC<7>()); break;
            }
          }
          publish();
#pragma unroll 1
          for (int ks = 7; ks < 64; ks++) {
            if (wg == 1 && ks == 62) turn_wait();
            dstep(ks);
          }
          if (wg == 0) turn_pass();
          wg_wait<0>();
          reg_fence(acc); reg_fence(ac1);
          TRL(158); TG(156);
          bar_sync(wg);
          out_tile(acc, 2 * id - 72);
          out_tile(ac1, 2 * id - 71);
        } else {
          store(n3, optr, IC<3>()); store(n4, optr, IC<4>()); store(n5, optr, IC<5>()); store(n6, optr, IC<6>()); store(n7, optr, IC<7>());
          publish();
        }
        break;
      }
#pragma unroll 1
      for (int ks = 17; ks < 64; ks++) {
        if (END_SKEW && wg == 1 && ks == 64 - END_SKEW) turn_wait();
        bstep(ks, 1);
      }
      if (END_SKEW && wg == 0) turn_pass();
      wg_wait<0>();
      reg_fence(acc);
      release(prev);
      if (lane == 0 && !last) mbar_arrive_cl(mapa(sb + BAR_BEMPTY + 8 * bprev, bprev & 1));
      TRL(158); TG(156);
      const int pos0 = row_block(t) * 256 + rank * 128 + wg * 64 + w * 16;
      if (last) {
        bar_sync(wg);
        out_tile(acc, t);
      } else {
        __nv_bfloat16* op0 = P.out + (size_t)o_row(pos0 + (lane >> 2)) * DM + (t & 3) * 160 + (lane & 3) * 2;
        __nv_bfloat16* op1 = P.out + (size_t)o_row(pos0 + (lane >> 2) + 8) * DM + (t & 3) * 160 + (lane & 3) * 2;
#pragma unroll
        for (int j = 0; j < 20; j++) {
          *reinterpret_cast<uint32_t*>(op0 + j * 8) = pack(acc[4 * j], acc[4 * j + 1]);
          *reinterpret_cast<uint32_t*>(op1 + j * 8) = pack(acc[4 * j + 2], acc[4 * j + 3]);
        }
      }
#pragma unroll
      for (int i = 0; i < 60; i++) pb[i] = 0;
    }
    TRL(159);
  }
}

typedef CUresult (*EncodeFn)(CUtensorMap*, CUtensorMapDataType, cuuint32_t, void*, const cuuint64_t*, const cuuint64_t*,
                             const cuuint32_t*, const cuuint32_t*, CUtensorMapInterleave, CUtensorMapSwizzle,
                             CUtensorMapL2promotion, CUtensorMapFloatOOBfill);

void make_map(EncodeFn enc, CUtensorMap* m, const void* p, int rank, const cuuint64_t* dims, const cuuint64_t* strides,
              const cuuint32_t* box, CUtensorMapSwizzle sw, CUtensorMapL2promotion promo) {
  cuuint32_t es[3] = {1, 1, 1};
  enc(m, CU_TENSOR_MAP_DATA_TYPE_BFLOAT16, rank, const_cast<void*>(p), dims, strides, box, es, CU_TENSOR_MAP_INTERLEAVE_NONE, sw,
      promo, CU_TENSOR_MAP_FLOAT_OOB_FILL_NONE);
}

}

extern "C" void kernel_launch(void* const* d_in, const int* in_sizes, int n_in, void* d_out, int out_size) {
  static EncodeFn enc = nullptr;
  static int nclusters = 0;
  static void* o_ptr = nullptr;
  if (!enc) {
    cudaDriverEntryPointQueryResult qr;
    cudaGetDriverEntryPoint("cuTensorMapEncodeTiled", (void**)&enc, cudaEnableDefault, &qr);
    cudaFuncSetAttribute(fused_attn_kernel<66>, cudaFuncAttributeMaxDynamicSharedMemorySize, SMEM_BYTES);
    cudaFuncSetAttribute(fused_attn_kernel<0>, cudaFuncAttributeMaxDynamicSharedMemorySize, SMEM_BYTES);
    cudaGetSymbolAddress(&o_ptr, g_o);
    cudaLaunchConfig_t cfg = {};
    cfg.gridDim = 128; cfg.blockDim = 384; cfg.dynamicSmemBytes = SMEM_BYTES;
    cudaLaunchAttribute at; at.id = cudaLaunchAttributeClusterDimension;
    at.val.clusterDim.x = 2; at.val.clusterDim.y = 1; at.val.clusterDim.z = 1;
    cfg.attrs = &at; cfg.numAttrs = 1;
    int n = 0;
    cudaOccupancyMaxActiveClusters(&n, fused_attn_kernel<66>, &cfg);
    nclusters = n >= 66 ? MAXCL : (n >= 64 || n <= 0 ? 64 : n);
  }
  const __nv_bfloat16* x = (const __nv_bfloat16*)d_in[0];
  const __nv_bfloat16* k = (const __nv_bfloat16*)d_in[1];
  const __nv_bfloat16* v = (const __nv_bfloat16*)d_in[2];
  const __nv_bfloat16* wq = (const __nv_bfloat16*)d_in[3];
  const __nv_bfloat16* wo = (const __nv_bfloat16*)d_in[4];
  CUtensorMap tm_x, tm_wq, tm_k, tm_v, tm_o, tm_wo;
  const auto S128 = CU_TENSOR_MAP_SWIZZLE_128B;
  const auto P128 = CU_TENSOR_MAP_L2_PROMOTION_L2_128B, P256 = CU_TENSOR_MAP_L2_PROMOTION_L2_256B;
  { cuuint64_t d[2] = {DM, NB * SQ}, s[1] = {DM * 2}; cuuint32_t b[2] = {64, 120}; make_map(enc, &tm_x, x, 2, d, s, b, S128, X_PROMO); }
  { cuuint64_t d[3] = {64, DM, HD / 64}, s[2] = {HD * 2, 128}; cuuint32_t b[3] = {64, 64, 2}; make_map(enc, &tm_wq, wq, 3, d, s, b, S128, P256); }
  { cuuint64_t d[3] = {64, NB * NH * SK, 2}, s[2] = {DH * 2, 128}; cuuint32_t b[3] = {64, 64, 2};
    make_map(enc, &tm_k, k, 3, d, s, b, S128, P128); make_map(enc, &tm_v, v, 3, d, s, b, S128, P128); }
  { cuuint64_t d[3] = {64, HD, NROWS / 64}, s[2] = {NROWS * 2, 128}; cuuint32_t b[3] = {64, 64, 2}; make_map(enc, &tm_o, o_ptr, 3, d, s, b, S128, P256); }
  { cuuint64_t d[3] = {32, HD, DM / 32}, s[2] = {DM * 2, 64}; cuuint32_t b[3] = {32, 64, 5};
    make_map(enc, &tm_wo, wo, 3, d, s, b, CU_TENSOR_MAP_SWIZZLE_64B, P128); }
  Params P{x, k, v, wq, (__nv_bfloat16*)d_out, (__nv_bfloat16*)o_ptr};
  if (nclusters == 66) fused_attn_kernel<66><<<132, 384, SMEM_BYTES>>>(tm_x, tm_wq, tm_k, tm_v, tm_o, tm_wo, P);
  else fused_attn_kernel<0><<<2 * nclusters, 384, SMEM_BYTES>>>(tm_x, tm_wq, tm_k, tm_v, tm_o, tm_wo, P);
}
```

```cpp
#include <cuda_runtime.h>
#include <cuda.h>
#include <cuda_bf16.h>
#include <stdint.h>

namespace {

constexpr int NB = 16, SQ = 240, DM = 640, NH = 32, SK = 1024, DH = 128, HD = NH * DH;
constexpr int NROWS = NB * SQ;
constexpr int NUNITS = 256;
#define DPRO 1
#define LATE_AT 4
#define ALT_FROM 4
#define MERGE89 1
#define END_SKEW 5
#define VREL 8
#define PF_HOLD 6
#define PF_N 4
#define PF_J0 3
#define PF_STEP 3
#define ROT 0
#define O_EF 1
#define B_ORDER 1
#define WO_PF 6
#define ROLE_AT 0
#define PAUSE_NS 11000
#define PAUSE_AT 2
#define EARLY 1
#define EARLY_X 2
#define EARLY_W 2
#define X_PROMO P128
#define PAUSE_J -1
#define PAUSE_SPREAD 0
#define WO_PF0 1
#define EREL_FROM 4
#define PRE9 0
#define LATE_SUM 0
#define PUT_FROM 1
#define PINLANE 0
#define MAXCL 66
#define SMID_TOP 88
constexpr int NOTILES = 60;
constexpr float QSCALE = 0.08838834764831845f * 1.4426950408889634f;
constexpr float L_MIN = 9.5367431640625e-07f;
constexpr float L_MAX = 1.152921504606846976e18f;

constexpr uint32_t RING_SLOTS = 6, RING_BYTES = 16384;
constexpr uint32_t XB = 15360;
constexpr uint32_t BB = 20480;
constexpr uint32_t OFF_Q = RING_SLOTS * RING_BYTES;
constexpr uint32_t OFF_P = OFF_Q + 4 * XB;
constexpr uint32_t OFF_INV = OFF_P + 4 * XB;
constexpr uint32_t OFF_L2 = OFF_INV + 1280;
constexpr uint32_t OFF_BAR = OFF_L2 + 4096;
constexpr uint32_t BAR_RFULL = OFF_BAR, BAR_REMPTY = BAR_RFULL + 48, BAR_XFULL = BAR_REMPTY + 48,
    BAR_XEMPTY = BAR_XFULL + 64, BAR_BFULL = BAR_XEMPTY + 32, BAR_BEMPTY = BAR_BFULL + 48, BAR_STAGE = BAR_BEMPTY + 48;
constexpr uint32_t BAR_ROLE = BAR_STAGE + 16, BAR_LSUM = BAR_ROLE + 24, BAR_INV = BAR_LSUM + 16;
constexpr uint32_t OFF_TR = BAR_INV + 16;
constexpr uint32_t SMEM_BYTES = OFF_TR + 1024;

constexpr uint32_t HI128 = (1u << 30) | (1024 >> 4);
constexpr uint32_t HI64 = (2u << 30) | (512 >> 4);

__device__ __nv_bfloat16 g_o[HD * NROWS];
__device__ unsigned g_cnt[67 * 8];
#define TS(i)
#define TRL(i)
#define TR(i)
#define TG(i)

struct Params {
  const __nv_bfloat16 *x, *k, *v, *wq;
  __nv_bfloat16 *out, *o;
};

__device__ __forceinline__ void wg_fence() { asm volatile("wgmma.fence.sync.aligned;" ::: "memory"); }
__device__ __forceinline__ void wg_commit() { asm volatile("wgmma.commit_group.sync.aligned;" ::: "memory"); }
template <int N> __device__ __forceinline__ void wg_wait() { asm volatile("wgmma.wait_group.sync.aligned %0;" ::"n"(N) : "memory"); }
template <int N> __device__ __forceinline__ void reg_fence(float (&r)[N]) {
#pragma unroll
  for (int i = 0; i < N; i++) asm volatile("" : "+f"(r[i])::"memory");
}
template <int TA, int TB>
__device__ __forceinline__ void wgmma_n120(float (&d)[60], uint32_t a_lo, uint32_t a_hi, uint32_t b_lo, uint32_t b_hi, int acc) {
  asm volatile(
      "{\n.reg .pred p;\n.reg .b64 da, db;\nsetp.ne.b32 p, %64, 0;\n"
      "mov.b64 da, {%60, %61};\nmov.b64 db, {%62, %63};\n"
      "wgmma.mma_async.sync.aligned.m64n120k16.f32.bf16.bf16 {"
      "%0, %1, %2, %3, %4, %5, %6, %7, %8, %9, %10, %11, %12, %13, %14, %15, %16, %17, %18, %19, %20, %21, %22, %23, "
      "%24, %25, %26, %27, %28, %29, %30, %31, %32, %33, %34, %35, %36, %37, %38, %39, %40, %41, %42, %43, %44, %45, "
      "%46, %47, %48, %49, %50, %51, %52, %53, %54, %55, %56, %57, %58, %59"
      "}, da, db, p, 1, 1, %65, %66;\n}\n"
      : "+f"(d[0]), "+f"(d[1]), "+f"(d[2]), "+f"(d[3]), "+f"(d[4]), "+f"(d[5]), "+f"(d[6]), "+f"(d[7]), "+f"(d[8]),
        "+f"(d[9]), "+f"(d[10]), "+f"(d[11]), "+f"(d[12]), "+f"(d[13]), "+f"(d[14]), "+f"(d[15]), "+f"(d[16]),
        "+f"(d[17]), "+f"(d[18]), "+f"(d[19]), "+f"(d[20]), "+f"(d[21]), "+f"(d[22]), "+f"(d[23]), "+f"(d[24]),
        "+f"(d[25]), "+f"(d[26]), "+f"(d[27]), "+f"(d[28]), "+f"(d[29]), "+f"(d[30]), "+f"(d[31]), "+f"(d[32]),
        "+f"(d[33]), "+f"(d[34]), "+f"(d[35]), "+f"(d[36]), "+f"(d[37]), "+f"(d[38]), "+f"(d[39]), "+f"(d[40]),
        "+f"(d[41]), "+f"(d[42]), "+f"(d[43]), "+f"(d[44]), "+f"(d[45]), "+f"(d[46]), "+f"(d[47]), "+f"(d[48]),
        "+f"(d[49]), "+f"(d[50]), "+f"(d[51]), "+f"(d[52]), "+f"(d[53]), "+f"(d[54]), "+f"(d[55]), "+f"(d[56]),
        "+f"(d[57]), "+f"(d[58]), "+f"(d[59])
      : "r"(a_lo), "r"(a_hi), "r"(b_lo), "r"(b_hi), "r"(acc), "n"(TA), "n"(TB));
}

template <int TA, int TB>
__device__ __forceinline__ void wgmma_n160(float (&d)[80], uint32_t a_lo, uint32_t a_hi, uint32_t b_lo, uint32_t b_hi, int acc) {
  asm volatile(
      "{\n.reg .pred p;\n.reg .b64 da, db;\nsetp.ne.b32 p, %84, 0;\n"
      "mov.b64 da, {%80, %81};\nmov.b64 db, {%82, %83};\n"
      "wgmma.mma_async.sync.aligned.m64n160k16.f32.bf16.bf16 {"
      "%0, %1, %2, %3, %4, %5, %6, %7, %8, %9, %10, %11, %12, %13, %14, %15, %16, %17, %18, %19, %20, %21, %22, %23, "
      "%24, %25, %26, %27, %28, %29, %30, %31, %32, %33, %34, %35, %36, %37, %38, %39, %40, %41, %42, %43, %44, %45, "
      "%46, %47, %48, %49, %50, %51, %52, %53, %54, %55, %56, %57, %58, %59, %60, %61, %62, %63, %64, %65, %66, %67, "
      "%68, %69, %70, %71, %72, %73, %74, %75, %76, %77, %78, %79"
      "}, da, db, p, 1, 1, %85, %86;\n}\n"
      : "+f"(d[0]), "+f"(d[1]), "+f"(d[2]), "+f"(d[3]), "+f"(d[4]), "+f"(d[5]), "+f"(d[6]), "+f"(d[7]), "+f"(d[8]),
        "+f"(d[9]), "+f"(d[10]), "+f"(d[11]), "+f"(d[12]), "+f"(d[13]), "+f"(d[14]), "+f"(d[15]), "+f"(d[16]),
        "+f"(d[17]), "+f"(d[18]), "+f"(d[19]), "+f"(d[20]), "+f"(d[21]), "+f"(d[22]), "+f"(d[23]), "+f"(d[24]),
        "+f"(d[25]), "+f"(d[26]), "+f"(d[27]), "+f"(d[28]), "+f"(d[29]), "+f"(d[30]), "+f"(d[31]), "+f"(d[32]),
        "+f"(d[33]), "+f"(d[34]), "+f"(d[35]), "+f"(d[36]), "+f"(d[37]), "+f"(d[38]), "+f"(d[39]), "+f"(d[40]),
        "+f"(d[41]), "+f"(d[42]), "+f"(d[43]), "+f"(d[44]), "+f"(d[45]), "+f"(d[46]), "+f"(d[47]), "+f"(d[48]),
        "+f"(d[49]), "+f"(d[50]), "+f"(d[51]), "+f"(d[52]), "+f"(d[53]), "+f"(d[54]), "+f"(d[55]), "+f"(d[56]),
        "+f"(d[57]), "+f"(d[58]), "+f"(d[59]), "+f"(d[60]), "+f"(d[61]), "+f"(d[62]), "+f"(d[63]), "+f"(d[64]),
        "+f"(d[65]), "+f"(d[66]), "+f"(d[67]), "+f"(d[68]), "+f"(d[69]), "+f"(d[70]), "+f"(d[71]), "+f"(d[72]),
        "+f"(d[73]), "+f"(d[74]), "+f"(d[75]), "+f"(d[76]), "+f"(d[77]), "+f"(d[78]), "+f"(d[79])
      : "r"(a_lo), "r"(a_hi), "r"(b_lo), "r"(b_hi), "r"(acc), "n"(TA), "n"(TB));
}
__device__ __forceinline__ void mbar_init(uint32_t bar, int cnt) { asm volatile("mbarrier.init.shared::cta.b64 [%0], %1;" ::"r"(bar), "r"(cnt)); }
__device__ __forceinline__ void mbar_expect(uint32_t bar, uint32_t bytes) {
  asm volatile("mbarrier.arrive.expect_tx.shared::cta.b64 _, [%0], %1;" ::"r"(bar), "r"(bytes) : "memory");
}
__device__ __forceinline__ uint32_t mapa(uint32_t addr, uint32_t cta) {
  uint32_t r; asm("mapa.shared::cluster.u32 %0, %1, %2;" : "=r"(r) : "r"(addr), "r"(cta)); return r;
}
__device__ __forceinline__ void mbar_expect_cl(uint32_t cbar, uint32_t bytes) {
  asm volatile("mbarrier.arrive.expect_tx.shared::cluster.b64 _, [%0], %1;" ::"r"(cbar), "r"(bytes) : "memory");
}
__device__ __forceinline__ void mbar_arrive(uint32_t bar) { asm volatile("mbarrier.arrive.shared::cta.b64 _, [%0];" ::"r"(bar) : "memory"); }
__device__ __forceinline__ void mbar_arrive_cl(uint32_t cbar) { asm volatile("mbarrier.arrive.shared::cluster.b64 _, [%0];" ::"r"(cbar) : "memory"); }
__device__ __forceinline__ void mbar_wait(uint32_t bar, uint32_t parity) {
  asm volatile(
      "{\n.reg .pred p;\n.reg .u32 n;\n"
      "mbarrier.try_wait.parity.shared::cta.b64 p, [%0], %1;\n@p bra WAIT_DONE;\n"
      "mov.u32 n, 0;\n"
      "WAIT_LOOP:\n"
      "mbarrier.try_wait.parity.shared::cta.b64 p, [%0], %1;\n@p bra WAIT_DONE;\n"
      "add.u32 n, n, 1;\nsetp.lt.u32 p, n, 0x4000000;\n@p bra WAIT_LOOP;\ntrap;\n"
      "WAIT_DONE:\n}\n" ::"r"(bar), "r"(parity) : "memory");
}
__device__ __forceinline__ void mbar_wait_cl(uint32_t bar, uint32_t parity) {
  asm volatile(
      "{\n.reg .pred p;\n.reg .u32 n;\nmov.u32 n, 0;\n"
      "WAIT_LOOP:\n"
      "mbarrier.try_wait.parity.acquire.cluster.shared::cta.b64 p, [%0], %1;\n@p bra WAIT_DONE;\n"
      "add.u32 n, n, 1;\nsetp.lt.u32 p, n, 0x4000000;\n@p bra WAIT_LOOP;\ntrap;\n"
      "WAIT_DONE:\n}\n" ::"r"(bar), "r"(parity) : "memory");
}
__device__ __forceinline__ void tma3d(uint32_t dst, const CUtensorMap* m, int c0, int c1, int c2, uint32_t bar) {
  asm volatile("cp.async.bulk.tensor.3d.shared::cluster.global.mbarrier::complete_tx::bytes [%0], [%1, {%3, %4, %5}], [%2];"
               ::"r"(dst), "l"(m), "r"(bar), "r"(c0), "r"(c1), "r"(c2) : "memory");
}
__device__ __forceinline__ void tma3d_hint(uint32_t dst, const CUtensorMap* m, int c0, int c1, int c2, uint32_t bar, uint64_t pol) {
  asm volatile("cp.async.bulk.tensor.3d.shared::cluster.global.mbarrier::complete_tx::bytes.L2::cache_hint [%0], [%1, {%3, %4, %5}], [%2], %6;"
               ::"r"(dst), "l"(m), "r"(bar), "r"(c0), "r"(c1), "r"(c2), "l"(pol) : "memory");
}
__device__ __forceinline__ void tma2d_mc(uint32_t dst, const CUtensorMap* m, int c0, int c1, uint32_t bar) {
  asm volatile("cp.async.bulk.tensor.2d.shared::cluster.global.mbarrier::complete_tx::bytes.multicast::cluster [%0], [%1, {%3, %4}], [%2], %5;"
               ::"r"(dst), "l"(m), "r"(bar), "r"(c0), "r"(c1), "h"((uint16_t)3) : "memory");
}
__device__ __forceinline__ void tma3d_mc(uint32_t dst, const CUtensorMap* m, int c0, int c1, int c2, uint32_t bar) {
  asm volatile("cp.async.bulk.tensor.3d.shared::cluster.global.mbarrier::complete_tx::bytes.multicast::cluster [%0], [%1, {%3, %4, %5}], [%2], %6;"
               ::"r"(dst), "l"(m), "r"(bar), "r"(c0), "r"(c1), "r"(c2), "h"((uint16_t)3) : "memory");
}
__device__ __forceinline__ void l2_prefetch(const void* p, uint32_t bytes) {
  asm volatile("cp.async.bulk.prefetch.L2.global [%0], %1;" ::"l"(p), "r"(bytes) : "memory");
}
__device__ __forceinline__ void fence_async_smem() { asm volatile("fence.proxy.async.shared::cta;" ::: "memory"); }
__device__ __forceinline__ void bar_sync(int wg) {
  if (wg == 0) asm volatile("bar.sync 1, 128;" ::: "memory");
  else asm volatile("bar.sync 2, 128;" ::: "memory");
}
__device__ __forceinline__ bool bar_red_or(int id, bool v) {
  uint32_t r;
  asm volatile("{\n.reg .pred p, q;\nsetp.ne.u32 p, %2, 0;\nbar.red.or.pred q, %1, 128, p;\nselp.u32 %0, 1, 0, q;\n}\n"
               : "=r"(r) : "r"(1 + id), "r"((uint32_t)v) : "memory");
  return r != 0;
}
__device__ __forceinline__ uint32_t hfma2(uint32_t a, uint32_t b, uint32_t c) { uint32_t r; asm("fma.rn.bf16x2 %0, %1, %2, %3;" : "=r"(r) : "r"(a), "r"(b), "r"(c)); return r; }
__device__ __forceinline__ float ex2(float x) { float y; asm("ex2.approx.ftz.f32 %0, %1;" : "=f"(y) : "f"(x)); return y; }
__device__ __forceinline__ uint32_t pack(float lo, float hi) { uint32_t r; asm("cvt.rn.bf16x2.f32 %0, %1, %2;" : "=r"(r) : "f"(hi), "f"(lo)); return r; }
__device__ __forceinline__ void stsm4t(uint32_t a, uint32_t r0, uint32_t r1, uint32_t r2, uint32_t r3) {
  asm volatile("stmatrix.sync.aligned.m8n8.x4.trans.shared.b16 [%0], {%1,%2,%3,%4};" ::"r"(a), "r"(r0), "r"(r1), "r"(r2), "r"(r3) : "memory");
}
__device__ __forceinline__ void stsm2t(uint32_t a, uint32_t r0, uint32_t r1) {
  asm volatile("stmatrix.sync.aligned.m8n8.x2.trans.shared.b16 [%0], {%1,%2};" ::"r"(a), "r"(r0), "r"(r1) : "memory");
}
__device__ __forceinline__ void mma16816(float (&d)[4], const uint32_t (&a)[4], uint32_t b0, uint32_t b1) {
  asm volatile("mma.sync.aligned.m16n8k16.row.col.f32.bf16.bf16.f32 {%0,%1,%2,%3}, {%4,%5,%6,%7}, {%8,%9}, {%0,%1,%2,%3};"
               : "+f"(d[0]), "+f"(d[1]), "+f"(d[2]), "+f"(d[3]) : "r"(a[0]), "r"(a[1]), "r"(a[2]), "r"(a[3]), "r"(b0), "r"(b1));
}

template <int V> struct IC { static constexpr int value = V; };

struct Ring {
  uint32_t slot = 0, phase = 0;
  __device__ __forceinline__ void next() { if (++slot == RING_SLOTS) { slot = 0; phase ^= 1; } }
};

__device__ __forceinline__ void mma_tn(float (&o0)[60], float (&o1)[60], uint32_t a, uint32_t b, int acc) {
#pragma unroll
  for (int k = 0; k < 4; k++) {
    wgmma_n120<1, 0>(o0, a + k * 128, HI128, b + k * 2, HI128, k == 0 ? acc : 1);
    wgmma_n120<1, 0>(o1, a + 512 + k * 128, HI128, b + k * 2, HI128, k == 0 ? acc : 1);
  }
}
__device__ __forceinline__ void mma_tn_split(float (&o0)[60], float (&o1)[60], uint32_t a, uint32_t b) {
#pragma unroll
  for (int k = 0; k < 4; k++) wgmma_n120<1, 0>(o0, a + k * 128, HI128, b + k * 2, HI128, 1);
  wg_commit();
#pragma unroll
  for (int k = 0; k < 4; k++) wgmma_n120<1, 0>(o1, a + 512 + k * 128, HI128, b + k * 2, HI128, 1);
  wg_commit();
}
__device__ __forceinline__ void mma_qk(float (&s)[60], uint32_t a, uint32_t q) {
#pragma unroll
  for (int k = 0; k < 8; k++)
    wgmma_n120<0, 0>(s, a + (k >> 2) * 512 + (k & 3) * 2, HI128, q + (k >> 2) * (XB >> 4) + (k & 3) * 2, HI128, k != 0);
}
template <int J0, int J1, bool FIRST = false>
__device__ __forceinline__ void exp_store(const float (&s)[60], float (&l)[30], uint32_t dst) {
#pragma unroll
  for (int j = J0; j < J1; j += 2) {
    uint32_t p[4];
#pragma unroll
    for (int jj = 0; jj < 2; jj++) {
      if (j + jj < 15) {
        const int c = j + jj;
        float e0 = ex2(s[4 * c]), e1 = ex2(s[4 * c + 1]), e2 = ex2(s[4 * c + 2]), e3 = ex2(s[4 * c + 3]);
        if (FIRST) { l[2 * c] = e0 + e2; l[2 * c + 1] = e1 + e3; }
        else { l[2 * c] += e0; l[2 * c + 1] += e1; l[2 * c] += e2; l[2 * c + 1] += e3; }
        p[2 * jj] = pack(e0, e1); p[2 * jj + 1] = pack(e2, e3);
      }
    }
    if (j + 1 < 15) stsm4t(dst + j * 1024, p[0], p[1], p[2], p[3]);
    else stsm2t(dst + j * 1024, p[0], p[1]);
  }
}

__device__ __forceinline__ int o_pos(int wg, int r) {
  const int j = r >> 3, q = (r >> 1) & 3, c = r & 1;
  if (j < 12) return (wg ? 144 : 0) + (j >> 2) * 32 + q * 8 + (j & 3) * 2 + c;
  if (j < 14) return (wg ? 128 : 96) + q * 4 + (j - 12) * 2 + c;
  return (wg ? 120 : 112) + q * 2 + c;
}
__device__ __forceinline__ int o_row(int p) {
  const int b = p / SQ, r = p - b * SQ, wg = r >= 120, c = r & 1;
  const int a = r - (wg ? 144 : 0), m = r - (wg ? 128 : 96), e = r - (wg ? 120 : 112);
  int row;
  if (a >= 0 && a < 96) row = ((a >> 5) * 4 + ((a >> 1) & 3)) * 8 + ((a >> 3) & 3) * 2 + c;
  else if (m >= 0 && m < 16) row = (12 + ((m >> 1) & 1)) * 8 + (m >> 2) * 2 + c;
  else row = 112 + e;
  return b * SQ + wg * 120 + row;
}

__device__ __forceinline__ void slow_path(const Params& P, int b, int h, int wg, int w, int lane) {
  const int g = lane >> 2, q = lane & 3, row0 = wg * 120;
  const uint16_t* wq = reinterpret_cast<const uint16_t*>(P.wq) + h * DH + g;
  const __nv_bfloat16* kp = P.k + (size_t)(b * NH + h) * SK * DH;
  const uint16_t* vp = reinterpret_cast<const uint16_t*>(P.v) + (size_t)(b * NH + h) * SK * DH + g;
#pragma unroll 1
  for (int t = w; t < 8; t += 4) {
    const int r0 = 16 * t + g, r1 = r0 + 8;
    const __nv_bfloat16* x0 = P.x + (size_t)(b * SQ + row0 + r0) * DM + 2 * q;
    const __nv_bfloat16* x1 = P.x + (size_t)(b * SQ + row0 + min(r1, 119)) * DM + 2 * q;
    float o[16][4];
#pragma unroll
    for (int n = 0; n < 16; n++) o[n][0] = o[n][1] = o[n][2] = o[n][3] = 0.f;
#pragma unroll 1
    for (int k0 = 0; k0 < DM; k0 += 16) {
      uint32_t a[4] = {*(const uint32_t*)(x0 + k0), *(const uint32_t*)(x1 + k0), *(const uint32_t*)(x0 + k0 + 8), *(const uint32_t*)(x1 + k0 + 8)};
      const uint16_t* wr = wq + (size_t)(k0 + 2 * q) * HD;
#pragma unroll
      for (int n = 0; n < 16; n++) {
        if ((n & 3) == 0) __syncwarp();
        mma16816(o[n], a, wr[8 * n] | ((uint32_t)wr[8 * n + HD] << 16), wr[8 * n + 8 * HD] | ((uint32_t)wr[8 * n + 9 * HD] << 16));
      }
    }
    uint32_t qa[8][4];
#pragma unroll
    for (int k = 0; k < 8; k++) {
      qa[k][0] = pack(o[2 * k][0] * QSCALE, o[2 * k][1] * QSCALE);
      qa[k][1] = pack(o[2 * k][2] * QSCALE, o[2 * k][3] * QSCALE);
      qa[k][2] = pack(o[2 * k + 1][0] * QSCALE, o[2 * k + 1][1] * QSCALE);
      qa[k][3] = pack(o[2 * k + 1][2] * QSCALE, o[2 * k + 1][3] * QSCALE);
    }
#pragma unroll
    for (int n = 0; n < 16; n++) o[n][0] = o[n][1] = o[n][2] = o[n][3] = 0.f;
    float m0 = -INFINITY, m1 = -INFINITY, l0 = 0.f, l1 = 0.f;
#pragma unroll 1
    for (int key0 = 0; key0 < SK; key0 += 16) {
      float s[2][4];
#pragma unroll
      for (int nt = 0; nt < 2; nt++) {
        s[nt][0] = s[nt][1] = s[nt][2] = s[nt][3] = 0.f;
        const __nv_bfloat16* kr = kp + (size_t)(key0 + 8 * nt + g) * DH + 2 * q;
#pragma unroll
        for (int k = 0; k < 8; k++) mma16816(s[nt], qa[k], *(const uint32_t*)(kr + 16 * k), *(const uint32_t*)(kr + 16 * k + 8));
      }
      float n0 = fmaxf(fmaxf(s[0][0], s[0][1]), fmaxf(s[1][0], s[1][1])), n1 = fmaxf(fmaxf(s[0][2], s[0][3]), fmaxf(s[1][2], s[1][3]));
      n0 = fmaxf(n0, __shfl_xor_sync(~0u, n0, 1)); n1 = fmaxf(n1, __shfl_xor_sync(~0u, n1, 1));
      n0 = fmaxf(n0, __shfl_xor_sync(~0u, n0, 2)); n1 = fmaxf(n1, __shfl_xor_sync(~0u, n1, 2));
      n0 = fmaxf(n0, m0); n1 = fmaxf(n1, m1);
      const float z0 = n0 == -INFINITY ? 0.f : n0, z1 = n1 == -INFINITY ? 0.f : n1;
      const float c0 = ex2(m0 - z0), c1 = ex2(m1 - z1);
      m0 = n0; m1 = n1;
#pragma unroll
      for (int nt = 0; nt < 2; nt++) {
        s[nt][0] = ex2(s[nt][0] - z0); s[nt][1] = ex2(s[nt][1] - z0);
        s[nt][2] = ex2(s[nt][2] - z1); s[nt][3] = ex2(s[nt][3] - z1);
      }
      l0 = l0 * c0 + s[0][0] + s[0][1] + s[1][0] + s[1][1];
      l1 = l1 * c1 + s[0][2] + s[0][3] + s[1][2] + s[1][3];
      uint32_t pa[4] = {pack(s[0][0], s[0][1]), pack(s[0][2], s[0][3]), pack(s[1][0], s[1][1]), pack(s[1][2], s[1][3])};
      const uint16_t* vr = vp + (size_t)(key0 + 2 * q) * DH;
#pragma unroll
      for (int n = 0; n < 16; n++) {
        if ((n & 3) == 0) __syncwarp();
        o[n][0] *= c0; o[n][1] *= c0; o[n][2] *= c1; o[n][3] *= c1;
        mma16816(o[n], pa, vr[8 * n] | ((uint32_t)vr[8 * n + DH] << 16), vr[8 * n + 8 * DH] | ((uint32_t)vr[8 * n + 9 * DH] << 16));
      }
    }
    l0 += __shfl_xor_sync(~0u, l0, 1); l1 += __shfl_xor_sync(~0u, l1, 1);
    l0 += __shfl_xor_sync(~0u, l0, 2); l1 += __shfl_xor_sync(~0u, l1, 2);
    const float i0 = 1.f / l0, i1 = 1.f / l1;
    __nv_bfloat16* oc = P.o + (size_t)(h * DH + 2 * q) * NROWS + b * SQ;
    const int p0 = o_pos(wg, r0), p1 = o_pos(wg, min(r1, 119));
#pragma unroll
    for (int n = 0; n < 16; n++) {
      oc[(size_t)(8 * n) * NROWS + p0] = __float2bfloat16(o[n][0] * i0);
      oc[(size_t)(8 * n + 1) * NROWS + p0] = __float2bfloat16(o[n][1] * i0);
      if (r1 < 120) {
        oc[(size_t)(8 * n) * NROWS + p1] = __float2bfloat16(o[n][2] * i1);
        oc[(size_t)(8 * n + 1) * NROWS + p1] = __float2bfloat16(o[n][3] * i1);
      }
    }
  }
}

__device__ __forceinline__ int bk(int ks) { return B_ORDER && ks < 48 ? 32 - (ks & 48) + (ks & 15) : ks; }
__device__ __forceinline__ uint32_t x_slot(uint32_t wg, uint32_t j) { return j < 2 ? (2 * wg + j) * XB : (2 * j + wg) * XB; }
__device__ __forceinline__ int row_block(int t) { return t >= 44 ? (t >> 2) - 11 : (t >> 2) + 4; }
__device__ __forceinline__ int unit_batch(int u) { return (u & 63) >> 2; }
__device__ __forceinline__ int unit_head(int u, int rank) { return (u >> 6) * 8 + (u & 3) * 2 + rank; }

template <int NCL>
__global__ void __cluster_dims__(2, 1, 1) __launch_bounds__(384, 1)
fused_attn_kernel(const __grid_constant__ CUtensorMap tm_x, const __grid_constant__ CUtensorMap tm_wq,
                  const __grid_constant__ CUtensorMap tm_k, const __grid_constant__ CUtensorMap tm_v,
                  const __grid_constant__ CUtensorMap tm_o, const __grid_constant__ CUtensorMap tm_wo,
                  const __grid_constant__ Params P) {
  extern __shared__ uint8_t smem_raw[];
  const uint32_t sb = ((uint32_t)__cvta_generic_to_shared(smem_raw) + 1023) & ~1023u;
  if (threadIdx.x == 0) TS(152);
  const int warp = __shfl_sync(~0u, threadIdx.x >> 5, 0);
  int lane = threadIdx.x & 31;
  const int rank = blockIdx.x & 1, cl = blockIdx.x >> 1, ncl = NCL ? NCL : gridDim.x >> 1;

  const int nsingle = NCL == 66 ? 44 : NOTILES;
  auto role = [&]() {
    mbar_wait(sb + BAR_ROLE + 16, 0);
    int id;
    asm volatile("ld.shared.u32 %0, [%1];" : "=r"(id) : "r"(sb + BAR_ROLE + 8) : "memory");
    return id;
  };

  if (EARLY && threadIdx.x == 128) asm volatile("prefetch.tensormap [%0];" ::"l"(&tm_x) : "memory");
  if (threadIdx.x == 0) {
    if (EARLY) asm volatile("prefetch.tensormap [%0];" ::"l"(&tm_wq) : "memory");
    for (int i = 0; i < 6; i++) {
      mbar_init(sb + BAR_RFULL + 8 * i, 1); mbar_init(sb + BAR_REMPTY + 8 * i, 8);
      mbar_init(sb + BAR_BFULL + 8 * i, 1); mbar_init(sb + BAR_BEMPTY + 8 * i, 16);
    }
    for (int i = 0; i < 8; i++) mbar_init(sb + BAR_XFULL + 8 * i, 1);
    for (int i = 0; i < 4; i++) mbar_init(sb + BAR_XEMPTY + 8 * i, 8);
    for (int i = 0; i < 2; i++) { mbar_init(sb + BAR_STAGE + 8 * i, 4); mbar_init(sb + BAR_LSUM + 8 * i, 4); mbar_init(sb + BAR_INV + 8 * i, 1); }
    mbar_init(sb + BAR_ROLE, 1); mbar_init(sb + BAR_ROLE + 16, 1);
    asm volatile("fence.mbarrier_init.release.cluster;" ::: "memory");
  }
  __syncwarp();
  asm volatile("barrier.cluster.arrive.relaxed.aligned;" ::: "memory");
  auto first_w = [&](int s) {
    mbar_expect(sb + BAR_RFULL + 8 * s, RING_BYTES);
    tma3d(sb + s * RING_BYTES, &tm_wq, 0, s * 64, 2 * unit_head(cl, rank), sb + BAR_RFULL + 8 * s);
  };
  if (EARLY && threadIdx.x == 0) first_w(0);
  __syncwarp();
  asm volatile("barrier.cluster.wait.aligned;" ::: "memory");
  if (EARLY && threadIdx.x == 128) {
#pragma unroll 1
    for (int s = 0; s < EARLY_X; s++) {
      const uint32_t fb = sb + BAR_XFULL + 32 * rank + 8 * s;
      mbar_expect(fb, XB);
      mbar_expect_cl(mapa(fb, rank ^ 1), XB);
      tma2d_mc(sb + OFF_Q + x_slot(rank, s), &tm_x, s * 64, unit_batch(cl) * SQ + rank * 120, fb);
      if (s + 1 < EARLY_W) first_w(s + 1);
    }
  }
  __syncwarp();
  if (threadIdx.x == 0) TS(153);

  if (warp >= 8) {
    asm volatile("setmaxnreg.dec.sync.aligned.u32 24;");
    if (warp == 8) {
      uint64_t pol;
      asm volatile("createpolicy.fractional.L2::evict_first.b64 %0, 1.0;" : "=l"(pol));
      Ring r;
      if (EARLY) r.slot = EARLY_W;
      auto load = [&](const CUtensorMap* m, int c1, int c2, bool ef) {
        mbar_wait(sb + BAR_REMPTY + 8 * r.slot, r.phase ^ 1);
        if (lane == 0) {
          mbar_expect(sb + BAR_RFULL + 8 * r.slot, RING_BYTES);
          if (ef) tma3d_hint(sb + r.slot * RING_BYTES, m, 0, c1, c2, sb + BAR_RFULL + 8 * r.slot, pol);
          else tma3d(sb + r.slot * RING_BYTES, m, 0, c1, c2, sb + BAR_RFULL + 8 * r.slot);
        }
        r.next();
      };
      const int rot = ROT * (blockIdx.x * 5 + (blockIdx.x >> 4));
      auto pause = [&](int u0) {
        if (PAUSE_NS && NCL == 66 && u0 == PAUSE_AT * 66) {
          const int id = role();
          if (id >= 44 && id < 58) {
            unsigned t0, t1;
            asm volatile("mov.u32 %0, %globaltimer_lo;" : "=r"(t0));
            do { __nanosleep(200); asm volatile("mov.u32 %0, %globaltimer_lo;" : "=r"(t1)); } while (t1 - t0 < PAUSE_NS + (id - 44) * PAUSE_SPREAD);
          }
        }
      };
      for (int u0 = 0;; u0 += ncl) {
        const int u = __shfl_sync(~0u, (u0 >= 3 * ncl ? role() : cl) + u0, 0);
        if (u >= NUNITS) break;
        if (PAUSE_J < 0) pause(u0);
        const int h = unit_head(u, rank);
        const int krow = (unit_batch(u) * NH + h) * SK;
#pragma unroll 1
        for (int s = EARLY && u0 == 0 ? EARLY_W : 0; s < 10; s++) {
          if (u0 == 0 && s == 0 && lane == 0) TS(154);
          load(&tm_wq, s * 64, 2 * h, false);
          if (u0 == 0 && s == 0 && lane == 0) TS(155);
          const int sp = u0 == 0 ? s - PF_HOLD : s;
          if (sp >= 0 && sp < PF_N && lane == 0) l2_prefetch(P.v + (size_t)(krow + ((PF_J0 + sp * PF_STEP + rot) & 15) * 64) * DH, 16384);
        }
#pragma unroll 1
        for (int j = 0; j <= 16; j++) {
          if (j == PAUSE_J) pause(u0);
          if (j < 16) load(&tm_k, krow + ((j + rot) & 15) * 64, 0, true);
          if (j == 1 + DPRO) load(&tm_v, krow + (rot & 15) * 64, 0, true);
          if (j > 1) load(&tm_v, krow + ((j - 1 + rot) & 15) * 64, 0, true);
        }
      }
      const int id = __shfl_sync(~0u, role(), 0);
      const bool dbl = NCL == 66 && id >= 58;
      for (int t = dbl ? 2 * id - 72 : id; t < (dbl ? NOTILES : nsingle); t += ncl) {
        const int row0 = row_block(t) * 256 + rank * 128;
        const int b0 = row0 / SQ, b1 = (row0 + 127) / SQ;
#pragma unroll 1
        for (int ks = 0; ks < 64; ks++) {
          if (dbl ? (ks & 15) == 0 : ks == 0 || ks == 48) {
            const unsigned* c = &g_cnt[((lane & 1 ? b1 : b0) * 4 + (ks || dbl ? ks >> 4 : min(lane >> 1, 2))) * 8];
            unsigned v, n = 0;
            do {
              asm volatile("ld.acquire.gpu.global.u32 %0, [%1];" : "=r"(v) : "l"(c) : "memory");
              if (++n > (1u << 26)) __trap();
            } while (v < 16);
            __syncwarp();
            asm volatile("fence.proxy.async.global;" ::: "memory");
          }
          load(&tm_o, (dbl ? ks : bk(ks)) * 64, row0 >> 6, O_EF);
        }
      }
      if (lane == 0 && atomicAdd(&g_cnt[64 * 8], 1) == gridDim.x - 1) {
        for (int i = 0; i < 67; i++) g_cnt[i * 8] = 0;
      }
    } else if (warp == 9) {
      if (lane == 0) {
        uint32_t it = 0;
        for (;; it++) {
          const int u = (it >= 3 ? role() : cl) + it * ncl;
          if (u >= NUNITS) break;
          const int row = unit_batch(u) * SQ + rank * 120;
#pragma unroll 1
          for (int s = EARLY && it == 0 ? EARLY_X : 0; s < 10; s++) {
            const uint32_t j = s & 3, par = ((s >> 2) + (j < 2 ? it : 0)) & 1;
            mbar_wait(sb + BAR_XEMPTY + 8 * j, par ^ 1);
            const uint32_t fb = sb + BAR_XFULL + 32 * rank + 8 * j;
            mbar_expect(fb, XB);
            mbar_expect_cl(mapa(fb, rank ^ 1), XB);
            tma2d_mc(sb + OFF_Q + x_slot(rank, j), &tm_x, s * 64, row, fb);
          }
        }
        const int id = role();
        const bool dbl = NCL == 66 && id >= 58;
        uint32_t slot = rank, phase = 0;
        if (WO_PF0 && dbl)
          asm volatile("cp.async.bulk.prefetch.tensor.3d.L2.global [%0, {%1, %2, %3}];" ::"l"(&tm_wo), "r"(0), "r"((2 + ((id >> 1) & 3)) * 64), "r"(((2 * id - 72 + rank) & 3) * 5) : "memory");
        for (int t = dbl ? 2 * id - 72 + rank : id; t < (dbl ? NOTILES : nsingle); t += ncl) {
#pragma unroll 1
          for (int ks = dbl ? 0 : rank; ks < 64; ks += dbl ? 1 : 2) {
            mbar_wait(sb + BAR_BEMPTY + 8 * slot, phase);
            const uint32_t fb = sb + BAR_BFULL + 8 * slot;
            mbar_expect(fb, BB);
            mbar_expect_cl(mapa(fb, rank ^ 1), BB);
            tma3d_mc(sb + OFF_Q + slot * BB, &tm_wo, 0, (dbl ? ks : bk(ks)) * 64, (t & 3) * 5, fb);
            if (WO_PF && dbl && ks + WO_PF < 64 && (ks & 3) == ((id >> 1) & 3))
              asm volatile("cp.async.bulk.prefetch.tensor.3d.L2.global [%0, {%1, %2, %3}];" ::"l"(&tm_wo), "r"(0), "r"((ks + WO_PF) * 64), "r"((t & 3) * 5) : "memory");
            slot += 2;
            if (slot >= 6) { slot -= 6; phase ^= 1; }
          }
        }
      }
    } else {
      const int wg = warp - 10;
      {
        mbar_wait(sb + BAR_RFULL, 0);
        const __nv_bfloat16* xs = P.x + (size_t)(unit_batch(cl) * SQ + ((cl & 3) * 2 + rank) * 30 + min(lane, 29)) * DM + 256 + wg * 64;
#pragma unroll
        for (int i = 0; i < 3; i++) asm volatile("prefetch.global.L2 [%0];" ::"l"(xs + i * 128));
        if (lane < 16) asm volatile("prefetch.global.L2 [%0];" ::"l"(P.wq + (size_t)(384 + unit_batch(cl) * 16 + lane) * HD + unit_head(cl, rank) * DH + wg * 64));
      }
      auto take_role = [&]() {
          if (wg == 0 && rank == 0 && lane == 0) {
            int id = cl;
            if (NCL == 66) {
              uint32_t smid;
              asm("mov.u32 %0, %smid;" : "=r"(smid));
              id = smid >= SMID_TOP ? 65 - atomicAdd(&g_cnt[65 * 8], 1) : atomicAdd(&g_cnt[66 * 8], 1);
            }
    #pragma unroll
            for (int c = 0; c < 2; c++) {
              const uint32_t a = mapa(sb + BAR_ROLE, c);
              asm volatile("st.shared::cluster.u32 [%0 + 8], %1;\nmbarrier.arrive.release.cluster.shared::cluster.b64 _, [%0];" ::"r"(a), "r"(id) : "memory");
            }
          }
          if (wg == 0 && lane == 0) {
            mbar_wait_cl(sb + BAR_ROLE, 0);
            mbar_arrive(sb + BAR_ROLE + 16);
          }
      };
      if (ROLE_AT < 0) { take_role(); __syncwarp(); }
      for (uint32_t it = 0;; it++) {
        const int u = __shfl_sync(~0u, (it >= 3 ? role() : cl) + it * ncl, 0);
        if (u >= NUNITS) break;
        mbar_wait(sb + BAR_LSUM + 8 * wg, it & 1);
        float l4[4], v[4];
        const uint32_t a = sb + OFF_L2 + wg * 2048 + lane * 16;
        asm volatile("ld.shared.v4.f32 {%0, %1, %2, %3}, [%4];" : "=f"(l4[0]), "=f"(l4[1]), "=f"(l4[2]), "=f"(l4[3]) : "r"(a) : "memory");
#pragma unroll
        for (int g = 1; g < 4; g++) {
          asm volatile("ld.shared.v4.f32 {%0, %1, %2, %3}, [%4];" : "=f"(v[0]), "=f"(v[1]), "=f"(v[2]), "=f"(v[3]) : "r"(a + g * 512) : "memory");
#pragma unroll
          for (int c = 0; c < 4; c++) l4[c] += v[c];
        }
#pragma unroll
        for (int c = 0; c < 4; c++) {
          float inv;
          asm("rcp.approx.ftz.f32 %0, %1;" : "=f"(inv) : "f"(l4[c]));
          l4[c] = l4[c] >= L_MIN && l4[c] <= L_MAX ? inv : __uint_as_float(0x7FFFFFFFu);
        }
        const uint32_t h0 = pack(l4[0], l4[1]), h1 = pack(l4[2], l4[3]);
        const uint32_t e0 = pack(l4[0] - __uint_as_float(h0 << 16), l4[1] - __uint_as_float(h0 & 0xFFFF0000u));
        const uint32_t e1 = pack(l4[2] - __uint_as_float(h1 << 16), l4[3] - __uint_as_float(h1 & 0xFFFF0000u));
        const uint32_t ia = sb + OFF_INV + wg * 640 + (lane & 1) * 288 + (lane >> 1) * 8;
        asm volatile("st.shared.v2.u32 [%0], {%1, %2};\nst.shared.v2.u32 [%0 + 144], {%3, %4};" ::"r"(ia), "r"(h0), "r"(e0), "r"(h1), "r"(e1) : "memory");
        __syncwarp();
        if (lane == 0) {
          mbar_arrive(sb + BAR_INV + 8 * wg);
          if ((int)it == ROLE_AT) {
            take_role();
          }
          mbar_wait(sb + BAR_STAGE + 8 * wg, it & 1);
          __threadfence();
          asm volatile("red.relaxed.gpu.global.add.u32 [%0], 1;" ::"l"(&g_cnt[(unit_batch(u) * 4 + (u >> 6)) * 8]) : "memory");
        }
        __syncwarp();
      }
    }
  } else {
    asm volatile("setmaxnreg.inc.sync.aligned.u32 240;");
    const int wg = warp >> 2, w = warp & 3;
    if (PINLANE) lane = __shfl_sync(~0u, lane, lane);
    const uint32_t qreg = sb + OFF_Q + wg * 2 * XB, preg = sb + OFF_P + (2 + wg) * XB;
    const uint32_t st_off = ((lane >> 4) * 8 + (lane & 7)) * 128 + (((2 * w + ((lane >> 3) & 1)) ^ (lane & 7)) << 4);
    const uint32_t xempty = mapa(sb + BAR_XEMPTY, wg);
    Ring r;
    uint32_t it = 0;
    const uint32_t qd = (qreg & 0x3FFFF) >> 4, pd = (preg & 0x3FFFF) >> 4;
    auto ring_addr = [&]() { return ((sb & 0x3FFFF) + r.slot * RING_BYTES) >> 4; };
    auto ring_wait = [&]() { mbar_wait(sb + BAR_RFULL + 8 * r.slot, r.phase); };
    auto release = [&](uint32_t slot) { if (lane == 0) mbar_arrive(sb + BAR_REMPTY + 8 * slot); };
    auto turn_wait = [&]() {
      if (wg == 0) asm volatile("bar.sync 3, 256;" ::: "memory");
      else asm volatile("bar.sync 4, 256;" ::: "memory");
    };
    auto turn_pass = [&]() {
      if (wg == 0) asm volatile("bar.arrive 4, 256;" ::: "memory");
      else asm volatile("bar.arrive 3, 256;" ::: "memory");
    };

    uint32_t chk = 0;
    auto sum_l = [&]() {
      __syncwarp();
      float lv[8][4];
#pragma unroll
      for (int g = 0; g < 8; g++)
        asm volatile("ld.shared.v4.f32 {%0, %1, %2, %3}, [%4];" : "=f"(lv[g][0]), "=f"(lv[g][1]), "=f"(lv[g][2]), "=f"(lv[g][3])
                     : "r"(preg + (8 * w + g) * 480 + min(lane, 29) * 16) : "memory");
#pragma unroll
      for (int c = 0; c < 4; c++) lv[0][c] = ((lv[0][c] + lv[1][c]) + (lv[2][c] + lv[3][c])) + ((lv[4][c] + lv[5][c]) + (lv[6][c] + lv[7][c]));
      asm volatile("st.shared.v4.f32 [%0], {%1, %2, %3, %4};" ::"r"(sb + OFF_L2 + wg * 2048 + w * 512 + lane * 16), "f"(lv[0][0]), "f"(lv[0][1]),
                   "f"(lv[0][2]), "f"(lv[0][3]) : "memory");
      __syncwarp();
      if (lane == 0) mbar_arrive(sb + BAR_LSUM + 8 * wg);
    };
    auto load_inv = [&](uint32_t (&iv)[30], uint32_t parity) {
      mbar_wait(sb + BAR_INV + 8 * wg, parity);
      chk = 0;
#pragma unroll
      for (int j = 0; j < 7; j++)
        asm volatile("ld.shared.v4.u32 {%0, %1, %2, %3}, [%4];" : "=r"(iv[4 * j]), "=r"(iv[4 * j + 1]), "=r"(iv[4 * j + 2]), "=r"(iv[4 * j + 3])
                     : "r"(sb + OFF_INV + wg * 640 + (lane & 3) * 144 + j * 16) : "memory");
      asm volatile("ld.shared.v2.u32 {%0, %1}, [%2];" : "=r"(iv[28]), "=r"(iv[29]) : "r"(sb + OFF_INV + wg * 640 + (lane & 3) * 144 + 112) : "memory");
    };
    auto norm = [&](uint32_t (&n)[8], const uint32_t (&po)[60], const uint32_t (&iv)[30], auto part) {
      constexpr int k = decltype(part)::value >> 1, j0 = (decltype(part)::value & 1) * 8;
#pragma unroll
      for (int j = 0; j < 8; j++)
        n[j] = j0 + j < 15 ? hfma2(po[15 * k + (j0 + j) % 15], iv[2 * ((j0 + j) % 15)], hfma2(po[15 * k + (j0 + j) % 15], iv[2 * ((j0 + j) % 15) + 1], 0x80008000u)) : 0x3F803F80u;
#pragma unroll
      for (int j = 0; j < 8; j += 2) chk = hfma2(n[j], n[j + 1], chk);
    };
    auto store = [&](const uint32_t (&n)[8], const char* optr, auto part) {
      constexpr int k = decltype(part)::value >> 1, off = (8 * (k & 1) + 64 * (k >> 1)) * NROWS * 2;
      if ((decltype(part)::value & 1) == 0)
        asm volatile(
            "{\n.reg .pred p;\nsetp.ne.u64 p, %8, 0;\n"
            "@p st.global.v4.u32 [%8 + %9], {%0, %1, %2, %3};\n@p st.global.v4.u32 [%8 + %9 + 64], {%4, %5, %6, %7};\n}\n"
            ::"r"(n[0]), "r"(n[1]), "r"(n[2]), "r"(n[3]), "r"(n[4]), "r"(n[5]), "r"(n[6]), "r"(n[7]), "l"(optr), "n"(off) : "memory");
      else
        asm volatile(
            "{\n.reg .pred p;\n.reg .b64 b, c;\nsetp.ne.u64 p, %7, 0;\nmad.wide.s32 b, %9, 8, %7;\nmad.wide.s32 c, %10, 4, %7;\n"
            "@p st.global.v4.u32 [%7 + %8 + 128], {%0, %1, %2, %3};\n@p st.global.v2.u32 [b + %8], {%4, %5};\n@p st.global.u32 [c + %8], %6;\n}\n"
            ::"r"(n[0]), "r"(n[1]), "r"(n[2]), "r"(n[3]), "r"(n[4]), "r"(n[5]), "r"(n[6]), "l"(optr), "n"(off),
            "r"((wg ? -4 : 24) - (lane & 3)), "r"((wg ? -12 : 56) - 3 * (lane & 3)) : "memory");
    };
    auto put = [&](const uint32_t (&po)[60], const uint32_t (&iv)[30], const char* optr, auto part) {
      uint32_t n[8];
      norm(n, po, iv, part);
      store(n, optr, part);
    };
    auto out_ptr = [&](int u) {
      return reinterpret_cast<const char*>(P.o + (uint32_t)((unit_head(u, rank) * DH + 16 * w + (lane >> 2)) * NROWS + unit_batch(u) * SQ + wg * 144 + (lane & 3) * 8));
    };
    auto unsafe = [&](bool valid) {
      const bool b = valid && ((chk & 0x7F80u) == 0x7F80u || (chk & 0x7F800000u) == 0x7F800000u);
      return __any_sync(~0u, bar_red_or(wg, b));
    };
    auto publish = [&]() { __syncwarp(); if (lane == 0) mbar_arrive(sb + BAR_STAGE + 8 * wg); };

    uint32_t po[60];
#pragma unroll
    for (int i = 0; i < 60; i++) po[i] = 0;
    int id = 0;
    bool more;
    do {
      float o0[60], o1[60];
      uint32_t prev = 0;
      auto qstep = [&](int s, int acc) {
        const uint32_t j = s & 3, par = ((s >> 2) + (j < 2 ? it : 0)) & 1;
        TR(it * 160 + 3 * s);
        ring_wait();
        TR(it * 160 + 3 * s + 1);
        mbar_wait(sb + BAR_XFULL + 32 * wg + 8 * j, par);
        TR(it * 160 + 3 * s + 2);
        if (s >= ALT_FROM) turn_wait();
        wg_fence();
        mma_tn(o0, o1, ring_addr(), ((sb & 0x3FFFF) + OFF_Q + x_slot(wg, j)) >> 4, acc);
        wg_commit();
        if (s >= ALT_FROM || (s == ALT_FROM - 1 && wg == 1)) turn_pass();
        if (s > 0 && s <= EREL_FROM) {
          wg_wait<1>();
          release(prev);
          if (s <= 6 && lane == 0) mbar_arrive_cl(xempty + 8 * ((s - 1) & 3));
        }
        prev = r.slot;
        r.next();
      };
      auto qdone = [&](int s) {
        if (s >= EREL_FROM) {
          wg_wait<0>();
          release(prev);
          if (s <= 5 && lane == 0) mbar_arrive_cl(xempty + 8 * (s & 3));
        }
      };
      qstep(0, 0);
      const int up = (it > 3 ? id : cl) + ((int)it - 1) * ncl;
      const char* optr = it > 0 ? out_ptr(up) : nullptr;
      uint32_t n7[8];
      {
        uint32_t iv[30];
        qstep(1, 1); load_inv(iv, (it + 1) & 1); put(po, iv, optr, IC<0>());
        qstep(2, 1); put(po, iv, optr, IC<1>()); qdone(2);
        qstep(3, 1); put(po, iv, optr, IC<2>()); qdone(3);
        qstep(4, 1); put(po, iv, optr, IC<3>()); qdone(4);
        qstep(5, 1); put(po, iv, optr, IC<4>()); qdone(5);
        qstep(6, 1); put(po, iv, optr, IC<5>()); qdone(6);
        qstep(7, 1); put(po, iv, optr, IC<6>());
        norm(n7, po, iv, IC<7>());
        qdone(7);
        if (LATE_AT == 3 || (LATE_AT == 5 && wg == 1)) store(n7, optr, IC<7>());
      }
      TR(it * 160 + 24);
      const uint32_t a8 = ring_addr(), slot8 = r.slot;
      ring_wait();
      r.next();
      TR(it * 160 + 25);
      mbar_wait(sb + BAR_XFULL + 32 * wg, it & 1);
      TR(it * 160 + 26);
      auto wait9 = [&]() {
        TR(it * 160 + 27);
        ring_wait();
        TR(it * 160 + 28);
        mbar_wait(sb + BAR_XFULL + 32 * wg + 8, it & 1);
        TR(it * 160 + 29);
      };
      if (PRE9) wait9();
      turn_wait();
      wg_fence();
      mma_tn(o0, o1, a8, qd, 1);
      wg_commit();
      if (!PRE9) { wait9(); wg_fence(); }
      mma_tn_split(o0, o1, ring_addr(), qd + (XB >> 4));
      turn_pass();
      wg_wait<2>();
      if (EREL_FROM > 7) release(prev);
      release(slot8);
      if (LATE_AT == 4 || (LATE_AT == 5 && wg == 0)) store(n7, optr, IC<7>());
      auto put_q = [&](const float (&o)[60], uint32_t dst) {
        bar_sync(wg);
#pragma unroll
        for (int j = 0; j < 14; j += 2)
          stsm4t(dst + j * 1024, pack(o[4 * j] * QSCALE, o[4 * j + 1] * QSCALE), pack(o[4 * j + 2] * QSCALE, o[4 * j + 3] * QSCALE),
                 pack(o[4 * j + 4] * QSCALE, o[4 * j + 5] * QSCALE), pack(o[4 * j + 6] * QSCALE, o[4 * j + 7] * QSCALE));
        stsm2t(dst + 14 * 1024, pack(o[56] * QSCALE, o[57] * QSCALE), pack(o[58] * QSCALE, o[59] * QSCALE));
      };
      wg_wait<1>();
      reg_fence(o0);
      put_q(o0, qreg + st_off);
      wg_wait<0>();
      reg_fence(o1);
      release(r.slot);
      r.next();
      TR(it * 160 + 30);
      put_q(o1, qreg + XB + st_off);
      fence_async_smem();
      if (unsafe(it > 0)) {
        slow_path(P, unit_batch(up), unit_head(up, rank), wg, w, lane);
        optr = nullptr;
        if (!DPRO) {
#pragma unroll
          for (int i = 0; i < 60; i++) o0[i] = o1[i] = 0.f;
        }
      }
      TR(it * 160 + 32); TG(it * 160 + 142);

      float sc[60], l[30];
      uint32_t slot0 = r.slot;
      ring_wait();
      TR(it * 160 + 33);
      turn_wait();
      wg_fence();
      mma_qk(sc, ring_addr(), qd);
      wg_commit();
      r.next();
      uint32_t slot1 = r.slot;
      ring_wait();
      wg_fence();
      mma_qk(o1, ring_addr(), qd);
      wg_commit();
      r.next();
      turn_pass();
      if (LATE_AT == 0) store(n7, optr, IC<7>());
      wg_wait<1>();
      reg_fence(sc);
      TR(it * 160 + 35);
      release(slot0);
      exp_store<0, 15, true>(sc, l, preg + st_off);
      TR(it * 160 + 38); TG(it * 160 + 43);
      slot0 = r.slot;
      ring_wait();
      wg_fence();
      mma_qk(sc, ring_addr(), qd);
      wg_commit();
      r.next();
      wg_wait<1>();
      reg_fence(o1);
      TR(it * 160 + 41);
      release(slot1);
      exp_store<0, 15>(o1, l, preg - 2 * XB + st_off);
      fence_async_smem();
      bar_sync(wg);
      TR(it * 160 + 44);
      slot1 = r.slot;
      ring_wait();
      turn_wait();
      wg_fence();
      mma_tn(o0, o1, ring_addr(), pd, 0);
      wg_commit();
      r.next();
      ring_wait();
      wg_fence();
      mma_tn(o0, o1, ring_addr(), pd - (2 * XB >> 4), 1);
      wg_commit();
      turn_pass();
      if (LATE_AT == 1) store(n7, optr, IC<7>());
      if (it > 0) publish();
      if (it >= 2) id = __shfl_sync(~0u, role(), 0);
      wg_wait<1>();
      reg_fence(sc);
      release(slot0);
      release(slot1);
      bar_sync(wg);
      TR(it * 160 + 47);
      exp_store<0, VREL>(sc, l, preg + st_off);
      wg_wait<0>();
      reg_fence(o0); reg_fence(o1);
      release(r.slot);
      r.next();
      exp_store<VREL, 15>(sc, l, preg + st_off);
      fence_async_smem();
      bar_sync(wg);
      more = id + ((int)it + 1) * ncl < NUNITS;
      const bool gemm = id < nsingle || (NCL == 66 && id >= 58);
#pragma unroll 1
      for (int s = DPRO ? 3 : 1; s < 16; s++) {
        const uint32_t kslot = r.slot;
        TR(it * 160 + 32 + 6 * s); TG(it * 160 + 37 + 6 * s);
        if (s == 8) TRL(it * 160 + 139);
        ring_wait();
        TR(it * 160 + 33 + 6 * s);
        turn_wait();
        wg_fence();
        mma_qk(sc, ring_addr(), qd);
        wg_commit();
        r.next();
        TR(it * 160 + 36 + 6 * s);
        ring_wait();
        TR(it * 160 + 34 + 6 * s);
        wg_fence();
        mma_tn(o0, o1, ring_addr(), pd - ((s - 1) & 1) * (2 * XB >> 4), DPRO || s != 1);
        wg_commit();
        if (wg == 0 || s < 15) turn_pass();
        wg_wait<1>();
        reg_fence(sc);
        TR(it * 160 + 35 + 6 * s);
        release(kslot);
        if (s == 15) {
          if (more) { if (lane < 2) mbar_arrive_cl(xempty + 8 * lane); }
          else if (lane < 3 && gemm) mbar_arrive_cl(mapa(sb + BAR_BEMPTY + 8 * lane, lane & 1));
        }
        exp_store<0, VREL>(sc, l, preg - (s & 1) * 2 * XB + st_off);
        wg_wait<0>();
        reg_fence(o0); reg_fence(o1);
        release(r.slot);
        r.next();
        exp_store<VREL, 15>(sc, l, preg - (s & 1) * 2 * XB + st_off);
        fence_async_smem();
      }
      bar_sync(wg);
      TR(it * 160 + 128);
      ring_wait();
      wg_fence();
      mma_tn_split(o0, o1, ring_addr(), pd - (2 * XB >> 4));
      {
        const uint32_t a = preg + (8 * w + (lane >> 2)) * 480 + (lane & 3) * 8;
#pragma unroll
        for (int j = 0; j < 15; j++) asm volatile("st.shared.v2.f32 [%0], {%1, %2};" ::"r"(a + j * 32), "f"(l[2 * j]), "f"(l[2 * j + 1]) : "memory");
      }
      TR(it * 160 + 132);
      sum_l();
      TR(it * 160 + 133);
      wg_wait<1>();
      reg_fence(o0);
      TR(it * 160 + 134);
#pragma unroll
      for (int j = 0; j < 15; j++) { po[j] = pack(o0[4 * j], o0[4 * j + 1]); po[15 + j] = pack(o0[4 * j + 2], o0[4 * j + 3]); }
      wg_wait<0>();
      reg_fence(o1);
      release(r.slot);
      r.next();
      if (more) { if (lane < 2) mbar_arrive_cl(xempty + 16 + 8 * lane); }
      else if (gemm && lane < 3) mbar_arrive_cl(mapa(sb + BAR_BEMPTY + 24 + 8 * lane, (lane + 1) & 1));
      TR(it * 160 + 130);
#pragma unroll
      for (int j = 0; j < 15; j++) { po[30 + j] = pack(o1[4 * j], o1[4 * j + 1]); po[45 + j] = pack(o1[4 * j + 2], o1[4 * j + 3]); }
      TR(it * 160 + 131); TG(it * 160 + 143);
      it++;
    } while (more);
    const bool gemm = id < nsingle || (NCL == 66 && id >= 58);
    const int u = (it > 3 ? id : cl) + ((int)it - 1) * ncl;
    if (NCL != 66) lane = __shfl_sync(~0u, lane, lane);
    uint32_t pb[60];
#pragma unroll
    for (int i = 0; i < 60; i++) pb[i] = NCL != 66 ? po[i] ^ (gridDim.y - 1) : po[i];

    uint32_t bslot = 0, bphase = 0;
    auto out_tile = [&](const float (&acc)[80], int t) {
      const uint32_t st = sb + w * RING_BYTES + wg * 8192;
      const uint32_t sa = st + (lane & 15) * 336 + (lane >> 4) * 16;
#pragma unroll
      for (int j = 0; j < 20; j += 2)
        asm volatile("stmatrix.sync.aligned.m8n8.x4.shared.b16 [%0], {%1,%2,%3,%4};" ::"r"(sa + j * 16), "r"(pack(acc[4 * j], acc[4 * j + 1])),
                     "r"(pack(acc[4 * j + 2], acc[4 * j + 3])), "r"(pack(acc[4 * j + 4], acc[4 * j + 5])), "r"(pack(acc[4 * j + 6], acc[4 * j + 7])) : "memory");
      fence_async_smem();
      __syncwarp();
      if (lane < 16) {
        __nv_bfloat16* dst = P.out + (size_t)o_row(row_block(t) * 256 + rank * 128 + wg * 64 + w * 16 + lane) * DM + (t & 3) * 160;
        asm volatile("cp.async.bulk.global.shared::cta.bulk_group [%0], [%1], 320;" ::"l"(dst), "r"(st + lane * 336) : "memory");
        asm volatile("cp.async.bulk.commit_group;" ::: "memory");
        asm volatile("cp.async.bulk.wait_group.read 0;" ::: "memory");
      }
      __syncwarp();
    };
    for (int t = id; t == id || (NCL != 66 && t < nsingle); t += ncl) {
      float acc[80];
      uint32_t prev = 0, bprev = 0;
      const bool tile = t < nsingle;
      const bool last = NCL == 66 || t + ncl >= nsingle;
      auto bstep = [&](int ks, int accf) {
        if (!(ks & 3)) TR(640 + ks / 2); if ((ks & 7) == 0) TG(144 + (ks >> 3));
        ring_wait();
        mbar_wait(sb + BAR_BFULL + 8 * bslot, bphase);
        if (!(ks & 3)) TR(641 + ks / 2);
        wg_fence();
        const uint32_t a = ring_addr() + wg * 512, bd = (((sb & 0x3FFFF) + OFF_Q + bslot * BB) >> 4) | ((4096u >> 4) << 16);
#pragma unroll
        for (int k = 0; k < 4; k++) wgmma_n160<1, 1>(acc, a + k * 128, HI128, bd + k * 64, HI64, k == 0 ? accf : 1);
        wg_commit();
        if (ks > 0) {
          wg_wait<1>();
          release(prev);
          if (lane == 0 && (ks < 59 || !last)) mbar_arrive_cl(mapa(sb + BAR_BEMPTY + 8 * bprev, bprev & 1));
        }
        prev = r.slot; bprev = bslot;
        r.next();
        if (++bslot == 6) { bslot = 0; bphase ^= 1; }
      };
      const char* optr = t == id ? out_ptr(u) : nullptr;
      uint32_t iv[30], n3[8], n4[8], n5[8], n6[8], n7[8];
      if (tile) {
        bstep(0, 0);
        bstep(1, 1);
        load_inv(iv, (it + 1) & 1);
#pragma unroll 1
        for (int ks = 2; ks < 17; ks++) {
          bstep(ks, 1);
          switch (ks) {
            case 2: put(pb, iv, optr, IC<0>()); break;
            case 4: put(pb, iv, optr, IC<1>()); break;
            case 6: put(pb, iv, optr, IC<2>()); break;
            case 8: put(pb, iv, optr, IC<3>()); break;
            case 10: put(pb, iv, optr, IC<4>()); break;
            case 12: put(pb, iv, optr, IC<5>()); break;
            case 14: put(pb, iv, optr, IC<6>()); break;
            case 16: put(pb, iv, optr, IC<7>()); break;
            default: break;
          }
        }
        wg_wait<0>();
        reg_fence(acc);
#pragma unroll
        for (int i = 0; i < 8; i++) n3[i] = n4[i] = n5[i] = n6[i] = n7[i] = 0;
      } else {
        Ring r2 = r;
        auto first = [&](int ks) {
          if (ks == 0) { TR(640); TG(144); }
          if (gemm) { mbar_wait(sb + BAR_RFULL + 8 * r2.slot, r2.phase); mbar_wait(sb + BAR_BFULL + 16 * ks, 0); }
          wg_fence();
          const uint32_t a = (((sb & 0x3FFFF) + r2.slot * RING_BYTES) >> 4) + wg * 512;
          const uint32_t bd = (((sb & 0x3FFFF) + OFF_Q + 2 * ks * BB) >> 4) | ((4096u >> 4) << 16);
#pragma unroll
          for (int k = 0; k < 4; k++) wgmma_n160<1, 1>(acc, a + k * 128, HI128, bd + k * 64, HI64, k + ks != 0);
          wg_commit();
          if (ks > 0) {
            wg_wait<1>();
            if (gemm && lane == 0) mbar_arrive_cl(mapa(sb + BAR_BEMPTY + 16 * (ks - 1), 0));
          }
          r2.next();
        };
        first(0);
        load_inv(iv, (it + 1) & 1);
        put(pb, iv, optr, IC<0>());
        first(1);
        put(pb, iv, optr, IC<1>());
        norm(n3, pb, iv, IC<3>()); norm(n4, pb, iv, IC<4>());
        first(2);
        put(pb, iv, optr, IC<2>());
        norm(n5, pb, iv, IC<5>()); norm(n6, pb, iv, IC<6>()); norm(n7, pb, iv, IC<7>());
        wg_wait<0>();
        reg_fence(acc);
      }
      if (unsafe(t == id)) {
        slow_path(P, unit_batch(u), unit_head(u, rank), wg, w, lane);
        optr = nullptr;
#pragma unroll
        for (int i = 0; i < 8; i++) n3[i] = n4[i] = n5[i] = n6[i] = n7[i] = 0;
      }
      if (tile && t == id) publish();
      if (!tile) {
        if (gemm) {
          float ac1[80];
          auto half = [&](float (&ac)[80], bool rel, int accf) {
            mbar_wait(sb + BAR_BFULL + 8 * bslot, bphase);
            wg_fence();
            const uint32_t a = ring_addr() + wg * 512, bd = (((sb & 0x3FFFF) + OFF_Q + bslot * BB) >> 4) | ((4096u >> 4) << 16);
#pragma unroll
            for (int k = 0; k < 4; k++) wgmma_n160<1, 1>(ac, a + k * 128, HI128, bd + k * 64, HI64, k == 0 ? accf : 1);
            wg_commit();
            wg_wait<1>();
            if (lane == 0 && rel) mbar_arrive_cl(mapa(sb + BAR_BEMPTY + 8 * bprev, bprev & 1));
            bprev = bslot;
          };
          auto dstep = [&](int ks) {
            if (!(ks & 3)) TR(640 + ks / 2); if ((ks & 7) == 0) TG(144 + (ks >> 3));
            ring_wait();
            if (!(ks & 3)) TR(641 + ks / 2);
            half(acc, ks < 62, 1);
            release(prev);
            bslot++;
            half(ac1, ks < 61, 1);
            if (++bslot == 6) { bslot = 0; bphase ^= 1; }
            prev = r.slot; r.next();
          };
          bprev = 4; bslot = 1;
          half(ac1, true, 0);
          prev = r.slot; r.next(); bslot = 3;
          half(ac1, true, 1);
          release(prev); prev = r.slot; r.next(); bslot = 5;
          store(n3, optr, IC<3>());
          half(ac1, true, 1);
          release(prev); prev = r.slot; r.next(); bslot = 0; bphase = 1;
#pragma unroll 1
          for (int ks = 3; ks < 7; ks++) {
            dstep(ks);
            switch (ks) {
              case 3: store(n4, optr, IC<4>()); break;
              case 4: store(n5, optr, IC<5>()); break;
              case 5: store(n6, optr, IC<6>()); break;
              default: store(n7, optr, IC<7>()); break;
            }
          }
          publish();
#pragma unroll 1
          for (int ks = 7; ks < 64; ks++) {
            if (wg == 1 && ks == 62) turn_wait();
            dstep(ks);
          }
          if (wg == 0) turn_pass();
          wg_wait<0>();
          reg_fence(acc); reg_fence(ac1);
          TRL(158); TG(156);
          bar_sync(wg);
          out_tile(acc, 2 * id - 72);
          out_tile(ac1, 2 * id - 71);
        } else {
          store(n3, optr, IC<3>()); store(n4, optr, IC<4>()); store(n5, optr, IC<5>()); store(n6, optr, IC<6>()); store(n7, optr, IC<7>());
          publish();
        }
        break;
      }
#pragma unroll 1
      for (int ks = 17; ks < 64; ks++) {
        if (END_SKEW && wg == 1 && ks == 64 - END_SKEW) turn_wait();
        bstep(ks, 1);
      }
      if (END_SKEW && wg == 0) turn_pass();
      wg_wait<0>();
      reg_fence(acc);
      release(prev);
      if (lane == 0 && !last) mbar_arrive_cl(mapa(sb + BAR_BEMPTY + 8 * bprev, bprev & 1));
      TRL(158); TG(156);
      const int pos0 = row_block(t) * 256 + rank * 128 + wg * 64 + w * 16;
      if (last) {
        bar_sync(wg);
        out_tile(acc, t);
      } else {
        __nv_bfloat16* op0 = P.out + (size_t)o_row(pos0 + (lane >> 2)) * DM + (t & 3) * 160 + (lane & 3) * 2;
        __nv_bfloat16* op1 = P.out + (size_t)o_row(pos0 + (lane >> 2) + 8) * DM + (t & 3) * 160 + (lane & 3) * 2;
#pragma unroll
        for (int j = 0; j < 20; j++) {
          *reinterpret_cast<uint32_t*>(op0 + j * 8) = pack(acc[4 * j], acc[4 * j + 1]);
          *reinterpret_cast<uint32_t*>(op1 + j * 8) = pack(acc[4 * j + 2], acc[4 * j + 3]);
        }
      }
#pragma unroll
      for (int i = 0; i < 60; i++) pb[i] = 0;
    }
    TRL(159);
  }
}

typedef CUresult (*EncodeFn)(CUtensorMap*, CUtensorMapDataType, cuuint32_t, void*, const cuuint64_t*, const cuuint64_t*,
                             const cuuint32_t*, const cuuint32_t*, CUtensorMapInterleave, CUtensorMapSwizzle,
                             CUtensorMapL2promotion, CUtensorMapFloatOOBfill);

void make_map(EncodeFn enc, CUtensorMap* m, const void* p, int rank, const cuuint64_t* dims, const cuuint64_t* strides,
              const cuuint32_t* box, CUtensorMapSwizzle sw, CUtensorMapL2promotion promo) {
  cuuint32_t es[3] = {1, 1, 1};
  enc(m, CU_TENSOR_MAP_DATA_TYPE_BFLOAT16, rank, const_cast<void*>(p), dims, strides, box, es, CU_TENSOR_MAP_INTERLEAVE_NONE, sw,
      promo, CU_TENSOR_MAP_FLOAT_OOB_FILL_NONE);
}

}

extern "C" void kernel_launch(void* const* d_in, const int* in_sizes, int n_in, void* d_out, int out_size) {
  static EncodeFn enc = nullptr;
  static int nclusters = 0;
  static void* o_ptr = nullptr;
  if (!enc) {
    cudaDriverEntryPointQueryResult qr;
    cudaGetDriverEntryPoint("cuTensorMapEncodeTiled", (void**)&enc, cudaEnableDefault, &qr);
    cudaFuncSetAttribute(fused_attn_kernel<66>, cudaFuncAttributeMaxDynamicSharedMemorySize, SMEM_BYTES);
    cudaFuncSetAttribute(fused_attn_kernel<0>, cudaFuncAttributeMaxDynamicSharedMemorySize, SMEM_BYTES);
    cudaGetSymbolAddress(&o_ptr, g_o);
    cudaLaunchConfig_t cfg = {};
    cfg.gridDim = 128; cfg.blockDim = 384; cfg.dynamicSmemBytes = SMEM_BYTES;
    cudaLaunchAttribute at; at.id = cudaLaunchAttributeClusterDimension;
    at.val.clusterDim.x = 2; at.val.clusterDim.y = 1; at.val.clusterDim.z = 1;
    cfg.attrs = &at; cfg.numAttrs = 1;
    int n = 0;
    cudaOccupancyMaxActiveClusters(&n, fused_attn_kernel<66>, &cfg);
    nclusters = n >= 66 ? MAXCL : (n >= 64 || n <= 0 ? 64 : n);
  }
  const __nv_bfloat16* x = (const __nv_bfloat16*)d_in[0];
  const __nv_bfloat16* k = (const __nv_bfloat16*)d_in[1];
  const __nv_bfloat16* v = (const __nv_bfloat16*)d_in[2];
  const __nv_bfloat16* wq = (const __nv_bfloat16*)d_in[3];
  const __nv_bfloat16* wo = (const __nv_bfloat16*)d_in[4];
  CUtensorMap tm_x, tm_wq, tm_k, tm_v, tm_o, tm_wo;
  const auto S128 = CU_TENSOR_MAP_SWIZZLE_128B;
  const auto P128 = CU_TENSOR_MAP_L2_PROMOTION_L2_128B, P256 = CU_TENSOR_MAP_L2_PROMOTION_L2_256B;
  { cuuint64_t d[2] = {DM, NB * SQ}, s[1] = {DM * 2}; cuuint32_t b[2] = {64, 120}; make_map(enc, &tm_x, x, 2, d, s, b, S128, X_PROMO); }
  { cuuint64_t d[3] = {64, DM, HD / 64}, s[2] = {HD * 2, 128}; cuuint32_t b[3] = {64, 64, 2}; make_map(enc, &tm_wq, wq, 3, d, s, b, S128, P256); }
  { cuuint64_t d[3] = {64, NB * NH * SK, 2}, s[2] = {DH * 2, 128}; cuuint32_t b[3] = {64, 64, 2};
    make_map(enc, &tm_k, k, 3, d, s, b, S128, P128); make_map(enc, &tm_v, v, 3, d, s, b, S128, P128); }
  { cuuint64_t d[3] = {64, HD, NROWS / 64}, s[2] = {NROWS * 2, 128}; cuuint32_t b[3] = {64, 64, 2}; make_map(enc, &tm_o, o_ptr, 3, d, s, b, S128, P256); }
  { cuuint64_t d[3] = {32, HD, DM / 32}, s[2] = {DM * 2, 64}; cuuint32_t b[3] = {32, 64, 5};
    make_map(enc, &tm_wo, wo, 3, d, s, b, CU_TENSOR_MAP_SWIZZLE_64B, P128); }
  Params P{x, k, v, wq, (__nv_bfloat16*)d_out, (__nv_bfloat16*)o_ptr};
  if (nclusters == 66) fused_attn_kernel<66><<<132, 384, SMEM_BYTES>>>(tm_x, tm_wq, tm_k, tm_v, tm_o, tm_wo, P);
  else fused_attn_kernel<0><<<2 * nclusters, 384, SMEM_BYTES>>>(tm_x, tm_wq, tm_k, tm_v, tm_o, tm_wo, P);
}
```

```cpp
#include <cuda_runtime.h>
#include <cuda.h>
#include <cuda_bf16.h>
#include <stdint.h>

namespace {

constexpr int NB = 16, SQ = 240, DM = 640, NH = 32, SK = 1024, DH = 128, HD = NH * DH;
constexpr int NROWS = NB * SQ;
constexpr int NUNITS = 256;
#define DPRO 1
#define LATE_AT 4
#define ALT_FROM 4
#define MERGE89 1
#define END_SKEW 5
#define VREL 8
#define PF_HOLD 6
#define PF_N 4
#define PF_J0 3
#define PF_STEP 3
#define ROT 0
#define O_EF 1
#define B_ORDER 1
#define WO_PF 6
#define ROLE_AT 0
#define PAUSE_NS 11000
#define PAUSE_AT 2
#define EARLY 1
#define EARLY_X 2
#define EARLY_W 2
#define X_PROMO P128
#define PAUSE_J -1
#define PAUSE_SPREAD 0
#define WO_PF0 1
#define EREL_FROM 4
#define PRE9 0
#define LATE_SUM 0
#define PUT_FROM 1
#define PINLANE 0
#define MAXCL 66
#define SMID_TOP 88
constexpr int NOTILES = 60;
constexpr float QSCALE = 0.08838834764831845f * 1.4426950408889634f;
constexpr float L_MIN = 9.5367431640625e-07f;
constexpr float L_MAX = 1.152921504606846976e18f;

constexpr uint32_t RING_SLOTS = 6, RING_BYTES = 16384;
constexpr uint32_t XB = 15360;
constexpr uint32_t BB = 20480;
constexpr uint32_t OFF_Q = RING_SLOTS * RING_BYTES;
constexpr uint32_t OFF_P = OFF_Q + 4 * XB;
constexpr uint32_t OFF_INV = OFF_P + 4 * XB;
constexpr uint32_t OFF_L2 = OFF_INV + 1280;
constexpr uint32_t OFF_BAR = OFF_L2 + 4096;
constexpr uint32_t BAR_RFULL = OFF_BAR, BAR_REMPTY = BAR_RFULL + 48, BAR_XFULL = BAR_REMPTY + 48,
    BAR_XEMPTY = BAR_XFULL + 64, BAR_BFULL = BAR_XEMPTY + 32, BAR_BEMPTY = BAR_BFULL + 48, BAR_STAGE = BAR_BEMPTY + 48;
constexpr uint32_t BAR_ROLE = BAR_STAGE + 16, BAR_LSUM = BAR_ROLE + 24, BAR_INV = BAR_LSUM + 16;
constexpr uint32_t OFF_TR = BAR_INV + 16;
constexpr uint32_t SMEM_BYTES = OFF_TR + 1024;

constexpr uint32_t HI128 = (1u << 30) | (1024 >> 4);
constexpr uint32_t HI64 = (2u << 30) | (512 >> 4);
constexpr uint32_t HI64A = (2u << 30) | (1024 >> 4), LBO64A = (512u >> 4) << 16;

__device__ __nv_bfloat16 g_o[HD * NROWS];
__device__ unsigned g_cnt[67 * 8];
#define TS(i)
#define TRL(i)
#define TR(i)
#define TG(i)

struct Params {
  const __nv_bfloat16 *x, *k, *v, *wq;
  __nv_bfloat16 *out, *o;
};

__device__ __forceinline__ void wg_fence() { asm volatile("wgmma.fence.sync.aligned;" ::: "memory"); }
__device__ __forceinline__ void wg_commit() { asm volatile("wgmma.commit_group.sync.aligned;" ::: "memory"); }
template <int N> __device__ __forceinline__ void wg_wait() { asm volatile("wgmma.wait_group.sync.aligned %0;" ::"n"(N) : "memory"); }
template <int N> __device__ __forceinline__ void reg_fence(float (&r)[N]) {
#pragma unroll
  for (int i = 0; i < N; i++) asm volatile("" : "+f"(r[i])::"memory");
}
template <int TA, int TB>
__device__ __forceinline__ void wgmma_n120(float (&d)[60], uint32_t a_lo, uint32_t a_hi, uint32_t b_lo, uint32_t b_hi, int acc) {
  asm volatile(
      "{\n.reg .pred p;\n.reg .b64 da, db;\nsetp.ne.b32 p, %64, 0;\n"
      "mov.b64 da, {%60, %61};\nmov.b64 db, {%62, %63};\n"
      "wgmma.mma_async.sync.aligned.m64n120k16.f32.bf16.bf16 {"
      "%0, %1, %2, %3, %4, %5, %6, %7, %8, %9, %10, %11, %12, %13, %14, %15, %16, %17, %18, %19, %20, %21, %22, %23, "
      "%24, %25, %26, %27, %28, %29, %30, %31, %32, %33, %34, %35, %36, %37, %38, %39, %40, %41, %42, %43, %44, %45, "
      "%46, %47, %48, %49, %50, %51, %52, %53, %54, %55, %56, %57, %58, %59"
      "}, da, db, p, 1, 1, %65, %66;\n}\n"
      : "+f"(d[0]), "+f"(d[1]), "+f"(d[2]), "+f"(d[3]), "+f"(d[4]), "+f"(d[5]), "+f"(d[6]), "+f"(d[7]), "+f"(d[8]),
        "+f"(d[9]), "+f"(d[10]), "+f"(d[11]), "+f"(d[12]), "+f"(d[13]), "+f"(d[14]), "+f"(d[15]), "+f"(d[16]),
        "+f"(d[17]), "+f"(d[18]), "+f"(d[19]), "+f"(d[20]), "+f"(d[21]), "+f"(d[22]), "+f"(d[23]), "+f"(d[24]),
        "+f"(d[25]), "+f"(d[26]), "+f"(d[27]), "+f"(d[28]), "+f"(d[29]), "+f"(d[30]), "+f"(d[31]), "+f"(d[32]),
        "+f"(d[33]), "+f"(d[34]), "+f"(d[35]), "+f"(d[36]), "+f"(d[37]), "+f"(d[38]), "+f"(d[39]), "+f"(d[40]),
        "+f"(d[41]), "+f"(d[42]), "+f"(d[43]), "+f"(d[44]), "+f"(d[45]), "+f"(d[46]), "+f"(d[47]), "+f"(d[48]),
        "+f"(d[49]), "+f"(d[50]), "+f"(d[51]), "+f"(d[52]), "+f"(d[53]), "+f"(d[54]), "+f"(d[55]), "+f"(d[56]),
        "+f"(d[57]), "+f"(d[58]), "+f"(d[59])
      : "r"(a_lo), "r"(a_hi), "r"(b_lo), "r"(b_hi), "r"(acc), "n"(TA), "n"(TB));
}

template <int TA, int TB>
__device__ __forceinline__ void wgmma_n160(float (&d)[80], uint32_t a_lo, uint32_t a_hi, uint32_t b_lo, uint32_t b_hi, int acc) {
  asm volatile(
      "{\n.reg .pred p;\n.reg .b64 da, db;\nsetp.ne.b32 p, %84, 0;\n"
      "mov.b64 da, {%80, %81};\nmov.b64 db, {%82, %83};\n"
      "wgmma.mma_async.sync.aligned.m64n160k16.f32.bf16.bf16 {"
      "%0, %1, %2, %3, %4, %5, %6, %7, %8, %9, %10, %11, %12, %13, %14, %15, %16, %17, %18, %19, %20, %21, %22, %23, "
      "%24, %25, %26, %27, %28, %29, %30, %31, %32, %33, %34, %35, %36, %37, %38, %39, %40, %41, %42, %43, %44, %45, "
      "%46, %47, %48, %49, %50, %51, %52, %53, %54, %55, %56, %57, %58, %59, %60, %61, %62, %63, %64, %65, %66, %67, "
      "%68, %69, %70, %71, %72, %73, %74, %75, %76, %77, %78, %79"
      "}, da, db, p, 1, 1, %85, %86;\n}\n"
      : "+f"(d[0]), "+f"(d[1]), "+f"(d[2]), "+f"(d[3]), "+f"(d[4]), "+f"(d[5]), "+f"(d[6]), "+f"(d[7]), "+f"(d[8]),
        "+f"(d[9]), "+f"(d[10]), "+f"(d[11]), "+f"(d[12]), "+f"(d[13]), "+f"(d[14]), "+f"(d[15]), "+f"(d[16]),
        "+f"(d[17]), "+f"(d[18]), "+f"(d[19]), "+f"(d[20]), "+f"(d[21]), "+f"(d[22]), "+f"(d[23]), "+f"(d[24]),
        "+f"(d[25]), "+f"(d[26]), "+f"(d[27]), "+f"(d[28]), "+f"(d[29]), "+f"(d[30]), "+f"(d[31]), "+f"(d[32]),
        "+f"(d[33]), "+f"(d[34]), "+f"(d[35]), "+f"(d[36]), "+f"(d[37]), "+f"(d[38]), "+f"(d[39]), "+f"(d[40]),
        "+f"(d[41]), "+f"(d[42]), "+f"(d[43]), "+f"(d[44]), "+f"(d[45]), "+f"(d[46]), "+f"(d[47]), "+f"(d[48]),
        "+f"(d[49]), "+f"(d[50]), "+f"(d[51]), "+f"(d[52]), "+f"(d[53]), "+f"(d[54]), "+f"(d[55]), "+f"(d[56]),
        "+f"(d[57]), "+f"(d[58]), "+f"(d[59]), "+f"(d[60]), "+f"(d[61]), "+f"(d[62]), "+f"(d[63]), "+f"(d[64]),
        "+f"(d[65]), "+f"(d[66]), "+f"(d[67]), "+f"(d[68]), "+f"(d[69]), "+f"(d[70]), "+f"(d[71]), "+f"(d[72]),
        "+f"(d[73]), "+f"(d[74]), "+f"(d[75]), "+f"(d[76]), "+f"(d[77]), "+f"(d[78]), "+f"(d[79])
      : "r"(a_lo), "r"(a_hi), "r"(b_lo), "r"(b_hi), "r"(acc), "n"(TA), "n"(TB));
}
__device__ __forceinline__ void mbar_init(uint32_t bar, int cnt) { asm volatile("mbarrier.init.shared::cta.b64 [%0], %1;" ::"r"(bar), "r"(cnt)); }
__device__ __forceinline__ void mbar_expect(uint32_t bar, uint32_t bytes) {
  asm volatile("mbarrier.arrive.expect_tx.shared::cta.b64 _, [%0], %1;" ::"r"(bar), "r"(bytes) : "memory");
}
__device__ __forceinline__ uint32_t mapa(uint32_t addr, uint32_t cta) {
  uint32_t r; asm("mapa.shared::cluster.u32 %0, %1, %2;" : "=r"(r) : "r"(addr), "r"(cta)); return r;
}
__device__ __forceinline__ void mbar_expect_cl(uint32_t cbar, uint32_t bytes) {
  asm volatile("mbarrier.arrive.expect_tx.shared::cluster.b64 _, [%0], %1;" ::"r"(cbar), "r"(bytes) : "memory");
}
__device__ __forceinline__ void mbar_arrive(uint32_t bar) { asm volatile("mbarrier.arrive.shared::cta.b64 _, [%0];" ::"r"(bar) : "memory"); }
__device__ __forceinline__ void mbar_arrive_cl(uint32_t cbar) { asm volatile("mbarrier.arrive.shared::cluster.b64 _, [%0];" ::"r"(cbar) : "memory"); }
__device__ __forceinline__ void mbar_wait(uint32_t bar, uint32_t parity) {
  asm volatile(
      "{\n.reg .pred p;\n.reg .u32 n;\n"
      "mbarrier.try_wait.parity.shared::cta.b64 p, [%0], %1;\n@p bra WAIT_DONE;\n"
      "mov.u32 n, 0;\n"
      "WAIT_LOOP:\n"
      "mbarrier.try_wait.parity.shared::cta.b64 p, [%0], %1;\n@p bra WAIT_DONE;\n"
      "add.u32 n, n, 1;\nsetp.lt.u32 p, n, 0x4000000;\n@p bra WAIT_LOOP;\ntrap;\n"
      "WAIT_DONE:\n}\n" ::"r"(bar), "r"(parity) : "memory");
}
__device__ __forceinline__ void mbar_wait_cl(uint32_t bar, uint32_t parity) {
  asm volatile(
      "{\n.reg .pred p;\n.reg .u32 n;\nmov.u32 n, 0;\n"
      "WAIT_LOOP:\n"
      "mbarrier.try_wait.parity.acquire.cluster.shared::cta.b64 p, [%0], %1;\n@p bra WAIT_DONE;\n"
      "add.u32 n, n, 1;\nsetp.lt.u32 p, n, 0x4000000;\n@p bra WAIT_LOOP;\ntrap;\n"
      "WAIT_DONE:\n}\n" ::"r"(bar), "r"(parity) : "memory");
}
__device__ __forceinline__ void tma3d(uint32_t dst, const CUtensorMap* m, int c0, int c1, int c2, uint32_t bar) {
  asm volatile("cp.async.bulk.tensor.3d.shared::cluster.global.mbarrier::complete_tx::bytes [%0], [%1, {%3, %4, %5}], [%2];"
               ::"r"(dst), "l"(m), "r"(bar), "r"(c0), "r"(c1), "r"(c2) : "memory");
}
__device__ __forceinline__ void tma3d_hint(uint32_t dst, const CUtensorMap* m, int c0, int c1, int c2, uint32_t bar, uint64_t pol) {
  asm volatile("cp.async.bulk.tensor.3d.shared::cluster.global.mbarrier::complete_tx::bytes.L2::cache_hint [%0], [%1, {%3, %4, %5}], [%2], %6;"
               ::"r"(dst), "l"(m), "r"(bar), "r"(c0), "r"(c1), "r"(c2), "l"(pol) : "memory");
}
__device__ __forceinline__ void tma2d_mc(uint32_t dst, const CUtensorMap* m, int c0, int c1, uint32_t bar) {
  asm volatile("cp.async.bulk.tensor.2d.shared::cluster.global.mbarrier::complete_tx::bytes.multicast::cluster [%0], [%1, {%3, %4}], [%2], %5;"
               ::"r"(dst), "l"(m), "r"(bar), "r"(c0), "r"(c1), "h"((uint16_t)3) : "memory");
}
__device__ __forceinline__ void tma3d_mc(uint32_t dst, const CUtensorMap* m, int c0, int c1, int c2, uint32_t bar) {
  asm volatile("cp.async.bulk.tensor.3d.shared::cluster.global.mbarrier::complete_tx::bytes.multicast::cluster [%0], [%1, {%3, %4, %5}], [%2], %6;"
               ::"r"(dst), "l"(m), "r"(bar), "r"(c0), "r"(c1), "r"(c2), "h"((uint16_t)3) : "memory");
}
__device__ __forceinline__ void l2_prefetch(const void* p, uint32_t bytes) {
  asm volatile("cp.async.bulk.prefetch.L2.global [%0], %1;" ::"l"(p), "r"(bytes) : "memory");
}
__device__ __forceinline__ void fence_async_smem() { asm volatile("fence.proxy.async.shared::cta;" ::: "memory"); }
__device__ __forceinline__ void bar_sync(int wg) {
  if (wg == 0) asm volatile("bar.sync 1, 128;" ::: "memory");
  else asm volatile("bar.sync 2, 128;" ::: "memory");
}
__device__ __forceinline__ bool bar_red_or(int id, bool v) {
  uint32_t r;
  asm volatile("{\n.reg .pred p, q;\nsetp.ne.u32 p, %2, 0;\nbar.red.or.pred q, %1, 128, p;\nselp.u32 %0, 1, 0, q;\n}\n"
               : "=r"(r) : "r"(1 + id), "r"((uint32_t)v) : "memory");
  return r != 0;
}
__device__ __forceinline__ uint32_t hfma2(uint32_t a, uint32_t b, uint32_t c) { uint32_t r; asm("fma.rn.bf16x2 %0, %1, %2, %3;" : "=r"(r) : "r"(a), "r"(b), "r"(c)); return r; }
__device__ __forceinline__ float ex2(float x) { float y; asm("ex2.approx.ftz.f32 %0, %1;" : "=f"(y) : "f"(x)); return y; }
__device__ __forceinline__ uint32_t pack(float lo, float hi) { uint32_t r; asm("cvt.rn.bf16x2.f32 %0, %1, %2;" : "=r"(r) : "f"(hi), "f"(lo)); return r; }
__device__ __forceinline__ void stsm4t(uint32_t a, uint32_t r0, uint32_t r1, uint32_t r2, uint32_t r3) {
  asm volatile("stmatrix.sync.aligned.m8n8.x4.trans.shared.b16 [%0], {%1,%2,%3,%4};" ::"r"(a), "r"(r0), "r"(r1), "r"(r2), "r"(r3) : "memory");
}
__device__ __forceinline__ void stsm2t(uint32_t a, uint32_t r0, uint32_t r1) {
  asm volatile("stmatrix.sync.aligned.m8n8.x2.trans.shared.b16 [%0], {%1,%2};" ::"r"(a), "r"(r0), "r"(r1) : "memory");
}
__device__ __forceinline__ void mma16816(float (&d)[4], const uint32_t (&a)[4], uint32_t b0, uint32_t b1) {
  asm volatile("mma.sync.aligned.m16n8k16.row.col.f32.bf16.bf16.f32 {%0,%1,%2,%3}, {%4,%5,%6,%7}, {%8,%9}, {%0,%1,%2,%3};"
               : "+f"(d[0]), "+f"(d[1]), "+f"(d[2]), "+f"(d[3]) : "r"(a[0]), "r"(a[1]), "r"(a[2]), "r"(a[3]), "r"(b0), "r"(b1));
}

template <int V> struct IC { static constexpr int value = V; };

struct Ring {
  uint32_t slot = 0, phase = 0;
  __device__ __forceinline__ void next() { if (++slot == RING_SLOTS) { slot = 0; phase ^= 1; } }
};

__device__ __forceinline__ void mma_tn(float (&o0)[60], float (&o1)[60], uint32_t a, uint32_t b, int acc) {
#pragma unroll
  for (int k = 0; k < 4; k++) {
    wgmma_n120<1, 0>(o0, a + k * 128, HI128, b + k * 2, HI128, k == 0 ? acc : 1);
    wgmma_n120<1, 0>(o1, a + 512 + k * 128, HI128, b + k * 2, HI128, k == 0 ? acc : 1);
  }
}
__device__ __forceinline__ void mma_tn_split(float (&o0)[60], float (&o1)[60], uint32_t a, uint32_t b) {
#pragma unroll
  for (int k = 0; k < 4; k++) wgmma_n120<1, 0>(o0, a + k * 128, HI128, b + k * 2, HI128, 1);
  wg_commit();
#pragma unroll
  for (int k = 0; k < 4; k++) wgmma_n120<1, 0>(o1, a + 512 + k * 128, HI128, b + k * 2, HI128, 1);
  wg_commit();
}
__device__ __forceinline__ void mma_qk(float (&s)[60], uint32_t a, uint32_t q) {
#pragma unroll
  for (int k = 0; k < 8; k++)
    wgmma_n120<0, 0>(s, a + (k >> 2) * 512 + (k & 3) * 2, HI128, q + (k >> 2) * (XB >> 4) + (k & 3) * 2, HI128, k != 0);
}
template <int J0, int J1, bool FIRST = false>
__device__ __forceinline__ void exp_store(const float (&s)[60], float (&l)[30], uint32_t dst) {
#pragma unroll
  for (int j = J0; j < J1; j += 2) {
    uint32_t p[4];
#pragma unroll
    for (int jj = 0; jj < 2; jj++) {
      if (j + jj < 15) {
        const int c = j + jj;
        float e0 = ex2(s[4 * c]), e1 = ex2(s[4 * c + 1]), e2 = ex2(s[4 * c + 2]), e3 = ex2(s[4 * c + 3]);
        if (FIRST) { l[2 * c] = e0 + e2; l[2 * c + 1] = e1 + e3; }
        else { l[2 * c] += e0; l[2 * c + 1] += e1; l[2 * c] += e2; l[2 * c + 1] += e3; }
        p[2 * jj] = pack(e0, e1); p[2 * jj + 1] = pack(e2, e3);
      }
    }
    if (j + 1 < 15) stsm4t(dst + j * 1024, p[0], p[1], p[2], p[3]);
    else stsm2t(dst + j * 1024, p[0], p[1]);
  }
}

__device__ __forceinline__ int o_pos(int b, int wg, int r) {
  const int j = r >> 3, q = (r >> 1) & 3, c = r & 1, o = b & 1, base = (b >> 1) * 480;
  if (j < 12) return base + (o * 9 + wg * 3 + (j >> 2)) * 32 + q * 8 + (j & 3) * 2 + c;
  if (j < 14) return base + (6 + 2 * o) * 32 + wg * 16 + q * 4 + (j - 12) * 2 + c;
  return base + 7 * 32 + (o * 2 + wg) * 8 + q * 2 + c;
}
__device__ __forceinline__ int o_row(int p) {
  const int pair = p / 480, a = (p - pair * 480) >> 5, in = p & 31, c = p & 1;
  int tile, row;
  if (a == 7) { tile = in >> 3; row = 112 + (in & 7); }
  else if (a == 6 || a == 8) { tile = a - 6 + (in >> 4); row = (12 + ((in >> 1) & 1)) * 8 + ((in >> 2) & 3) * 2 + c; }
  else { const int f = a > 8 ? a - 3 : a; tile = f / 3; row = ((f - tile * 3) * 4 + ((in >> 1) & 3)) * 8 + (in >> 3) * 2 + c; }
  return pair * 480 + tile * 120 + row;
}
__device__ __forceinline__ uint32_t o_idx(int k, int p) {
  return ((k >> 3) * (NROWS / 32) + (p >> 5)) * 256 + (k & 7) * 32 + ((((p >> 3) & 3) ^ ((k & 7) >> 1)) << 3) + (p & 7);
}

__device__ __forceinline__ void slow_path(const Params& P, int b, int h, int wg, int w, int lane) {
  const int g = lane >> 2, q = lane & 3, row0 = wg * 120;
  const uint16_t* wq = reinterpret_cast<const uint16_t*>(P.wq) + h * DH + g;
  const __nv_bfloat16* kp = P.k + (size_t)(b * NH + h) * SK * DH;
  const uint16_t* vp = reinterpret_cast<const uint16_t*>(P.v) + (size_t)(b * NH + h) * SK * DH + g;
#pragma unroll 1
  for (int t = w; t < 8; t += 4) {
    const int r0 = 16 * t + g, r1 = r0 + 8;
    const __nv_bfloat16* x0 = P.x + (size_t)(b * SQ + row0 + r0) * DM + 2 * q;
    const __nv_bfloat16* x1 = P.x + (size_t)(b * SQ + row0 + min(r1, 119)) * DM + 2 * q;
    float o[16][4];
#pragma unroll
    for (int n = 0; n < 16; n++) o[n][0] = o[n][1] = o[n][2] = o[n][3] = 0.f;
#pragma unroll 1
    for (int k0 = 0; k0 < DM; k0 += 16) {
      uint32_t a[4] = {*(const uint32_t*)(x0 + k0), *(const uint32_t*)(x1 + k0), *(const uint32_t*)(x0 + k0 + 8), *(const uint32_t*)(x1 + k0 + 8)};
      const uint16_t* wr = wq + (size_t)(k0 + 2 * q) * HD;
#pragma unroll
      for (int n = 0; n < 16; n++) {
        if ((n & 3) == 0) __syncwarp();
        mma16816(o[n], a, wr[8 * n] | ((uint32_t)wr[8 * n + HD] << 16), wr[8 * n + 8 * HD] | ((uint32_t)wr[8 * n + 9 * HD] << 16));
      }
    }
    uint32_t qa[8][4];
#pragma unroll
    for (int k = 0; k < 8; k++) {
      qa[k][0] = pack(o[2 * k][0] * QSCALE, o[2 * k][1] * QSCALE);
      qa[k][1] = pack(o[2 * k][2] * QSCALE, o[2 * k][3] * QSCALE);
      qa[k][2] = pack(o[2 * k + 1][0] * QSCALE, o[2 * k + 1][1] * QSCALE);
      qa[k][3] = pack(o[2 * k + 1][2] * QSCALE, o[2 * k + 1][3] * QSCALE);
    }
#pragma unroll
    for (int n = 0; n < 16; n++) o[n][0] = o[n][1] = o[n][2] = o[n][3] = 0.f;
    float m0 = -INFINITY, m1 = -INFINITY, l0 = 0.f, l1 = 0.f;
#pragma unroll 1
    for (int key0 = 0; key0 < SK; key0 += 16) {
      float s[2][4];
#pragma unroll
      for (int nt = 0; nt < 2; nt++) {
        s[nt][0] = s[nt][1] = s[nt][2] = s[nt][3] = 0.f;
        const __nv_bfloat16* kr = kp + (size_t)(key0 + 8 * nt + g) * DH + 2 * q;
#pragma unroll
        for (int k = 0; k < 8; k++) mma16816(s[nt], qa[k], *(const uint32_t*)(kr + 16 * k), *(const uint32_t*)(kr + 16 * k + 8));
      }
      float n0 = fmaxf(fmaxf(s[0][0], s[0][1]), fmaxf(s[1][0], s[1][1])), n1 = fmaxf(fmaxf(s[0][2], s[0][3]), fmaxf(s[1][2], s[1][3]));
      n0 = fmaxf(n0, __shfl_xor_sync(~0u, n0, 1)); n1 = fmaxf(n1, __shfl_xor_sync(~0u, n1, 1));
      n0 = fmaxf(n0, __shfl_xor_sync(~0u, n0, 2)); n1 = fmaxf(n1, __shfl_xor_sync(~0u, n1, 2));
      n0 = fmaxf(n0, m0); n1 = fmaxf(n1, m1);
      const float z0 = n0 == -INFINITY ? 0.f : n0, z1 = n1 == -INFINITY ? 0.f : n1;
      const float c0 = ex2(m0 - z0), c1 = ex2(m1 - z1);
      m0 = n0; m1 = n1;
#pragma unroll
      for (int nt = 0; nt < 2; nt++) {
        s[nt][0] = ex2(s[nt][0] - z0); s[nt][1] = ex2(s[nt][1] - z0);
        s[nt][2] = ex2(s[nt][2] - z1); s[nt][3] = ex2(s[nt][3] - z1);
      }
      l0 = l0 * c0 + s[0][0] + s[0][1] + s[1][0] + s[1][1];
      l1 = l1 * c1 + s[0][2] + s[0][3] + s[1][2] + s[1][3];
      uint32_t pa[4] = {pack(s[0][0], s[0][1]), pack(s[0][2], s[0][3]), pack(s[1][0], s[1][1]), pack(s[1][2], s[1][3])};
      const uint16_t* vr = vp + (size_t)(key0 + 2 * q) * DH;
#pragma unroll
      for (int n = 0; n < 16; n++) {
        if ((n & 3) == 0) __syncwarp();
        o[n][0] *= c0; o[n][1] *= c0; o[n][2] *= c1; o[n][3] *= c1;
        mma16816(o[n], pa, vr[8 * n] | ((uint32_t)vr[8 * n + DH] << 16), vr[8 * n + 8 * DH] | ((uint32_t)vr[8 * n + 9 * DH] << 16));
      }
    }
    l0 += __shfl_xor_sync(~0u, l0, 1); l1 += __shfl_xor_sync(~0u, l1, 1);
    l0 += __shfl_xor_sync(~0u, l0, 2); l1 += __shfl_xor_sync(~0u, l1, 2);
    const float i0 = 1.f / l0, i1 = 1.f / l1;
    __nv_bfloat16* oc0 = P.o + o_idx(h * DH + 2 * q, o_pos(b, wg, r0));
    __nv_bfloat16* oc1 = P.o + o_idx(h * DH + 2 * q, o_pos(b, wg, min(r1, 119)));
#pragma unroll
    for (int n = 0; n < 16; n++) {
      oc0[8 * n * NROWS] = __float2bfloat16(o[n][0] * i0);
      oc0[8 * n * NROWS + 32] = __float2bfloat16(o[n][1] * i0);
      if (r1 < 120) {
        oc1[8 * n * NROWS] = __float2bfloat16(o[n][2] * i1);
        oc1[8 * n * NROWS + 32] = __float2bfloat16(o[n][3] * i1);
      }
    }
  }
}

__device__ __forceinline__ int bk(int ks) { return B_ORDER && ks < 48 ? 32 - (ks & 48) + (ks & 15) : ks; }
__device__ __forceinline__ uint32_t x_slot(uint32_t wg, uint32_t j) { return j < 2 ? (2 * wg + j) * XB : (2 * j + wg) * XB; }
__device__ __forceinline__ int row_block(int t) { return t >= 44 ? (t >> 2) - 11 : (t >> 2) + 4; }
__device__ __forceinline__ int unit_batch(int u) { return (u & 63) >> 2; }
__device__ __forceinline__ int unit_head(int u, int rank) { return (u >> 6) * 8 + (u & 3) * 2 + rank; }

template <int NCL>
__global__ void __cluster_dims__(2, 1, 1) __launch_bounds__(384, 1)
fused_attn_kernel(const __grid_constant__ CUtensorMap tm_x, const __grid_constant__ CUtensorMap tm_wq,
                  const __grid_constant__ CUtensorMap tm_k, const __grid_constant__ CUtensorMap tm_v,
                  const __grid_constant__ CUtensorMap tm_o, const __grid_constant__ CUtensorMap tm_wo,
                  const __grid_constant__ Params P) {
  extern __shared__ uint8_t smem_raw[];
  const uint32_t sb = ((uint32_t)__cvta_generic_to_shared(smem_raw) + 1023) & ~1023u;
  if (threadIdx.x == 0) TS(152);
  const int warp = __shfl_sync(~0u, threadIdx.x >> 5, 0);
  int lane = threadIdx.x & 31;
  const int rank = blockIdx.x & 1, cl = blockIdx.x >> 1, ncl = NCL ? NCL : gridDim.x >> 1;

  const int nsingle = NCL == 66 ? 44 : NOTILES;
  auto role = [&]() {
    mbar_wait(sb + BAR_ROLE + 16, 0);
    int id;
    asm volatile("ld.shared.u32 %0, [%1];" : "=r"(id) : "r"(sb + BAR_ROLE + 8) : "memory");
    return id;
  };

  if (EARLY && threadIdx.x == 128) asm volatile("prefetch.tensormap [%0];" ::"l"(&tm_x) : "memory");
  if (threadIdx.x == 0) {
    if (EARLY) asm volatile("prefetch.tensormap [%0];" ::"l"(&tm_wq) : "memory");
    for (int i = 0; i < 6; i++) {
      mbar_init(sb + BAR_RFULL + 8 * i, 1); mbar_init(sb + BAR_REMPTY + 8 * i, 8);
      mbar_init(sb + BAR_BFULL + 8 * i, 1); mbar_init(sb + BAR_BEMPTY + 8 * i, 16);
    }
    for (int i = 0; i < 8; i++) mbar_init(sb + BAR_XFULL + 8 * i, 1);
    for (int i = 0; i < 4; i++) mbar_init(sb + BAR_XEMPTY + 8 * i, 8);
    for (int i = 0; i < 2; i++) { mbar_init(sb + BAR_STAGE + 8 * i, 4); mbar_init(sb + BAR_LSUM + 8 * i, 4); mbar_init(sb + BAR_INV + 8 * i, 1); }
    mbar_init(sb + BAR_ROLE, 1); mbar_init(sb + BAR_ROLE + 16, 1);
    asm volatile("fence.mbarrier_init.release.cluster;" ::: "memory");
  }
  __syncwarp();
  asm volatile("barrier.cluster.arrive.relaxed.aligned;" ::: "memory");
  auto first_w = [&](int s) {
    mbar_expect(sb + BAR_RFULL + 8 * s, RING_BYTES);
    tma3d(sb + s * RING_BYTES, &tm_wq, 0, s * 64, 2 * unit_head(cl, rank), sb + BAR_RFULL + 8 * s);
  };
  if (EARLY && threadIdx.x == 0) first_w(0);
  __syncwarp();
  asm volatile("barrier.cluster.wait.aligned;" ::: "memory");
  if (EARLY && threadIdx.x == 128) {
#pragma unroll 1
    for (int s = 0; s < EARLY_X; s++) {
      const uint32_t fb = sb + BAR_XFULL + 32 * rank + 8 * s;
      mbar_expect(fb, XB);
      mbar_expect_cl(mapa(fb, rank ^ 1), XB);
      tma2d_mc(sb + OFF_Q + x_slot(rank, s), &tm_x, s * 64, unit_batch(cl) * SQ + rank * 120, fb);
      if (s + 1 < EARLY_W) first_w(s + 1);
    }
  }
  __syncwarp();
  if (threadIdx.x == 0) TS(153);

  if (warp >= 8) {
    asm volatile("setmaxnreg.dec.sync.aligned.u32 24;");
    if (warp == 8) {
      uint64_t pol;
      asm volatile("createpolicy.fractional.L2::evict_first.b64 %0, 1.0;" : "=l"(pol));
      Ring r;
      if (EARLY) r.slot = EARLY_W;
      auto load = [&](const CUtensorMap* m, int c1, int c2, bool ef) {
        mbar_wait(sb + BAR_REMPTY + 8 * r.slot, r.phase ^ 1);
        if (lane == 0) {
          mbar_expect(sb + BAR_RFULL + 8 * r.slot, RING_BYTES);
          if (ef) tma3d_hint(sb + r.slot * RING_BYTES, m, 0, c1, c2, sb + BAR_RFULL + 8 * r.slot, pol);
          else tma3d(sb + r.slot * RING_BYTES, m, 0, c1, c2, sb + BAR_RFULL + 8 * r.slot);
        }
        r.next();
      };
      const int rot = ROT * (blockIdx.x * 5 + (blockIdx.x >> 4));
      auto pause = [&](int u0) {
        if (PAUSE_NS && NCL == 66 && u0 == PAUSE_AT * 66) {
          const int id = role();
          if (id >= 44 && id < 58) {
            unsigned t0, t1;
            asm volatile("mov.u32 %0, %globaltimer_lo;" : "=r"(t0));
            do { __nanosleep(200); asm volatile("mov.u32 %0, %globaltimer_lo;" : "=r"(t1)); } while (t1 - t0 < PAUSE_NS + (id - 44) * PAUSE_SPREAD);
          }
        }
      };
      for (int u0 = 0;; u0 += ncl) {
        const int u = __shfl_sync(~0u, (u0 >= 3 * ncl ? role() : cl) + u0, 0);
        if (u >= NUNITS) break;
        if (PAUSE_J < 0) pause(u0);
        const int h = unit_head(u, rank);
        const int krow = (unit_batch(u) * NH + h) * SK;
#pragma unroll 1
        for (int s = EARLY && u0 == 0 ? EARLY_W : 0; s < 10; s++) {
          if (u0 == 0 && s == 0 && lane == 0) TS(154);
          load(&tm_wq, s * 64, 2 * h, false);
          if (u0 == 0 && s == 0 && lane == 0) TS(155);
          const int sp = u0 == 0 ? s - PF_HOLD : s;
          if (sp >= 0 && sp < PF_N && lane == 0) l2_prefetch(P.v + (size_t)(krow + ((PF_J0 + sp * PF_STEP + rot) & 15) * 64) * DH, 16384);
        }
#pragma unroll 1
        for (int j = 0; j <= 16; j++) {
          if (j == PAUSE_J) pause(u0);
          if (j < 16) load(&tm_k, krow + ((j + rot) & 15) * 64, 0, true);
          if (j == 1 + DPRO) load(&tm_v, krow + (rot & 15) * 64, 0, true);
          if (j > 1) load(&tm_v, krow + ((j - 1 + rot) & 15) * 64, 0, true);
        }
      }
      const int id = __shfl_sync(~0u, role(), 0);
      const bool dbl = NCL == 66 && id >= 58;
      for (int t = dbl ? 2 * id - 72 : id; t < (dbl ? NOTILES : nsingle); t += ncl) {
        const int row0 = row_block(t) * 256 + rank * 128;
        const int b0 = (row0 & ~31) / SQ, b1 = (row0 + 127) / SQ;
#pragma unroll 1
        for (int ks = 0; ks < 64; ks++) {
          if (dbl ? (ks & 15) == 0 : ks == 0 || ks == 48) {
            const unsigned* c = &g_cnt[((lane & 1 ? b1 : b0) * 4 + (ks || dbl ? ks >> 4 : min(lane >> 1, 2))) * 8];
            unsigned v, n = 0;
            do {
              asm volatile("ld.acquire.gpu.global.u32 %0, [%1];" : "=r"(v) : "l"(c) : "memory");
              if (++n > (1u << 26)) __trap();
            } while (v < 16);
            __syncwarp();
            asm volatile("fence.proxy.async.global;" ::: "memory");
          }
          mbar_wait(sb + BAR_REMPTY + 8 * r.slot, r.phase ^ 1);
          if (lane == 0) {
            mbar_expect(sb + BAR_RFULL + 8 * r.slot, RING_BYTES);
            asm volatile("cp.async.bulk.tensor.4d.shared::cluster.global.mbarrier::complete_tx::bytes.L2::cache_hint [%0], [%1, {%3, %3, %4, %5}], [%2], %6;"
                         ::"r"(sb + r.slot * RING_BYTES), "l"(&tm_o), "r"(sb + BAR_RFULL + 8 * r.slot), "r"(0), "r"((dbl ? ks : bk(ks)) * 8), "r"(row0 >> 6), "l"(pol) : "memory");
          }
          r.next();
        }
      }
      if (lane == 0 && atomicAdd(&g_cnt[64 * 8], 1) == gridDim.x - 1) {
        for (int i = 0; i < 67; i++) g_cnt[i * 8] = 0;
      }
    } else if (warp == 9) {
      if (lane == 0) {
        uint32_t it = 0;
        for (;; it++) {
          const int u = (it >= 3 ? role() : cl) + it * ncl;
          if (u >= NUNITS) break;
          const int row = unit_batch(u) * SQ + rank * 120;
#pragma unroll 1
          for (int s = EARLY && it == 0 ? EARLY_X : 0; s < 10; s++) {
            const uint32_t j = s & 3, par = ((s >> 2) + (j < 2 ? it : 0)) & 1;
            mbar_wait(sb + BAR_XEMPTY + 8 * j, par ^ 1);
            const uint32_t fb = sb + BAR_XFULL + 32 * rank + 8 * j;
            mbar_expect(fb, XB);
            mbar_expect_cl(mapa(fb, rank ^ 1), XB);
            tma2d_mc(sb + OFF_Q + x_slot(rank, j), &tm_x, s * 64, row, fb);
          }
        }
        const int id = role();
        const bool dbl = NCL == 66 && id >= 58;
        uint32_t slot = rank, phase = 0;
        if (WO_PF0 && dbl)
          asm volatile("cp.async.bulk.prefetch.tensor.3d.L2.global [%0, {%1, %2, %3}];" ::"l"(&tm_wo), "r"(0), "r"((2 + ((id >> 1) & 3)) * 64), "r"(((2 * id - 72 + rank) & 3) * 5) : "memory");
        for (int t = dbl ? 2 * id - 72 + rank : id; t < (dbl ? NOTILES : nsingle); t += ncl) {
#pragma unroll 1
          for (int ks = dbl ? 0 : rank; ks < 64; ks += dbl ? 1 : 2) {
            mbar_wait(sb + BAR_BEMPTY + 8 * slot, phase);
            const uint32_t fb = sb + BAR_BFULL + 8 * slot;
            mbar_expect(fb, BB);
            mbar_expect_cl(mapa(fb, rank ^ 1), BB);
            tma3d_mc(sb + OFF_Q + slot * BB, &tm_wo, 0, (dbl ? ks : bk(ks)) * 64, (t & 3) * 5, fb);
            if (WO_PF && dbl && ks + WO_PF < 64 && (ks & 3) == ((id >> 1) & 3))
              asm volatile("cp.async.bulk.prefetch.tensor.3d.L2.global [%0, {%1, %2, %3}];" ::"l"(&tm_wo), "r"(0), "r"((ks + WO_PF) * 64), "r"((t & 3) * 5) : "memory");
            slot += 2;
            if (slot >= 6) { slot -= 6; phase ^= 1; }
          }
        }
      }
    } else {
      const int wg = warp - 10;
      {
        mbar_wait(sb + BAR_RFULL, 0);
        const __nv_bfloat16* xs = P.x + (size_t)(unit_batch(cl) * SQ + ((cl & 3) * 2 + rank) * 30 + min(lane, 29)) * DM + 256 + wg * 64;
#pragma unroll
        for (int i = 0; i < 3; i++) asm volatile("prefetch.global.L2 [%0];" ::"l"(xs + i * 128));
        if (lane < 16) asm volatile("prefetch.global.L2 [%0];" ::"l"(P.wq + (size_t)(384 + unit_batch(cl) * 16 + lane) * HD + unit_head(cl, rank) * DH + wg * 64));
      }
      auto take_role = [&]() {
          if (wg == 0 && rank == 0 && lane == 0) {
            int id = cl;
            if (NCL == 66) {
              uint32_t smid;
              asm("mov.u32 %0, %smid;" : "=r"(smid));
              id = smid >= SMID_TOP ? 65 - atomicAdd(&g_cnt[65 * 8], 1) : atomicAdd(&g_cnt[66 * 8], 1);
            }
    #pragma unroll
            for (int c = 0; c < 2; c++) {
              const uint32_t a = mapa(sb + BAR_ROLE, c);
              asm volatile("st.shared::cluster.u32 [%0 + 8], %1;\nmbarrier.arrive.release.cluster.shared::cluster.b64 _, [%0];" ::"r"(a), "r"(id) : "memory");
            }
          }
          if (wg == 0 && lane == 0) {
            mbar_wait_cl(sb + BAR_ROLE, 0);
            mbar_arrive(sb + BAR_ROLE + 16);
          }
      };
      if (ROLE_AT < 0) { take_role(); __syncwarp(); }
      for (uint32_t it = 0;; it++) {
        const int u = __shfl_sync(~0u, (it >= 3 ? role() : cl) + it * ncl, 0);
        if (u >= NUNITS) break;
        mbar_wait(sb + BAR_LSUM + 8 * wg, it & 1);
        float l4[4], v[4];
        const uint32_t a = sb + OFF_L2 + wg * 2048 + lane * 16;
        asm volatile("ld.shared.v4.f32 {%0, %1, %2, %3}, [%4];" : "=f"(l4[0]), "=f"(l4[1]), "=f"(l4[2]), "=f"(l4[3]) : "r"(a) : "memory");
#pragma unroll
        for (int g = 1; g < 4; g++) {
          asm volatile("ld.shared.v4.f32 {%0, %1, %2, %3}, [%4];" : "=f"(v[0]), "=f"(v[1]), "=f"(v[2]), "=f"(v[3]) : "r"(a + g * 512) : "memory");
#pragma unroll
          for (int c = 0; c < 4; c++) l4[c] += v[c];
        }
#pragma unroll
        for (int c = 0; c < 4; c++) {
          float inv;
          asm("rcp.approx.ftz.f32 %0, %1;" : "=f"(inv) : "f"(l4[c]));
          l4[c] = l4[c] >= L_MIN && l4[c] <= L_MAX ? inv : __uint_as_float(0x7FFFFFFFu);
        }
        const uint32_t h0 = pack(l4[0], l4[1]), h1 = pack(l4[2], l4[3]);
        const uint32_t e0 = pack(l4[0] - __uint_as_float(h0 << 16), l4[1] - __uint_as_float(h0 & 0xFFFF0000u));
        const uint32_t e1 = pack(l4[2] - __uint_as_float(h1 << 16), l4[3] - __uint_as_float(h1 & 0xFFFF0000u));
        const uint32_t ia = sb + OFF_INV + wg * 640 + (lane & 1) * 288 + (lane >> 1) * 8;
        asm volatile("st.shared.v2.u32 [%0], {%1, %2};\nst.shared.v2.u32 [%0 + 144], {%3, %4};" ::"r"(ia), "r"(h0), "r"(e0), "r"(h1), "r"(e1) : "memory");
        __syncwarp();
        if (lane == 0) {
          mbar_arrive(sb + BAR_INV + 8 * wg);
          if ((int)it == ROLE_AT) {
            take_role();
          }
          mbar_wait(sb + BAR_STAGE + 8 * wg, it & 1);
          __threadfence();
          asm volatile("red.relaxed.gpu.global.add.u32 [%0], 1;" ::"l"(&g_cnt[(unit_batch(u) * 4 + (u >> 6)) * 8]) : "memory");
        }
        __syncwarp();
      }
    }
  } else {
    asm volatile("setmaxnreg.inc.sync.aligned.u32 240;");
    const int wg = warp >> 2, w = warp & 3;
    if (PINLANE) lane = __shfl_sync(~0u, lane, lane);
    const uint32_t qreg = sb + OFF_Q + wg * 2 * XB, preg = sb + OFF_P + (2 + wg) * XB;
    const uint32_t st_off = ((lane >> 4) * 8 + (lane & 7)) * 128 + (((2 * w + ((lane >> 3) & 1)) ^ (lane & 7)) << 4);
    const uint32_t xempty = mapa(sb + BAR_XEMPTY, wg);
    Ring r;
    uint32_t it = 0;
    const uint32_t qd = (qreg & 0x3FFFF) >> 4, pd = (preg & 0x3FFFF) >> 4;
    auto ring_addr = [&]() { return ((sb & 0x3FFFF) + r.slot * RING_BYTES) >> 4; };
    auto ring_wait = [&]() { mbar_wait(sb + BAR_RFULL + 8 * r.slot, r.phase); };
    auto release = [&](uint32_t slot) { if (lane == 0) mbar_arrive(sb + BAR_REMPTY + 8 * slot); };
    auto turn_wait = [&]() {
      if (wg == 0) asm volatile("bar.sync 3, 256;" ::: "memory");
      else asm volatile("bar.sync 4, 256;" ::: "memory");
    };
    auto turn_pass = [&]() {
      if (wg == 0) asm volatile("bar.arrive 4, 256;" ::: "memory");
      else asm volatile("bar.arrive 3, 256;" ::: "memory");
    };

    uint32_t chk = 0;
    auto sum_l = [&]() {
      __syncwarp();
      float lv[8][4];
#pragma unroll
      for (int g = 0; g < 8; g++)
        asm volatile("ld.shared.v4.f32 {%0, %1, %2, %3}, [%4];" : "=f"(lv[g][0]), "=f"(lv[g][1]), "=f"(lv[g][2]), "=f"(lv[g][3])
                     : "r"(preg + (8 * w + g) * 480 + min(lane, 29) * 16) : "memory");
#pragma unroll
      for (int c = 0; c < 4; c++) lv[0][c] = ((lv[0][c] + lv[1][c]) + (lv[2][c] + lv[3][c])) + ((lv[4][c] + lv[5][c]) + (lv[6][c] + lv[7][c]));
      asm volatile("st.shared.v4.f32 [%0], {%1, %2, %3, %4};" ::"r"(sb + OFF_L2 + wg * 2048 + w * 512 + lane * 16), "f"(lv[0][0]), "f"(lv[0][1]),
                   "f"(lv[0][2]), "f"(lv[0][3]) : "memory");
      __syncwarp();
      if (lane == 0) mbar_arrive(sb + BAR_LSUM + 8 * wg);
    };
    auto load_inv = [&](uint32_t (&iv)[30], uint32_t parity) {
      mbar_wait(sb + BAR_INV + 8 * wg, parity);
      chk = 0;
#pragma unroll
      for (int j = 0; j < 7; j++)
        asm volatile("ld.shared.v4.u32 {%0, %1, %2, %3}, [%4];" : "=r"(iv[4 * j]), "=r"(iv[4 * j + 1]), "=r"(iv[4 * j + 2]), "=r"(iv[4 * j + 3])
                     : "r"(sb + OFF_INV + wg * 640 + (lane & 3) * 144 + j * 16) : "memory");
      asm volatile("ld.shared.v2.u32 {%0, %1}, [%2];" : "=r"(iv[28]), "=r"(iv[29]) : "r"(sb + OFF_INV + wg * 640 + (lane & 3) * 144 + 112) : "memory");
    };
    auto norm = [&](uint32_t (&n)[8], const uint32_t (&po)[60], const uint32_t (&iv)[30], auto part) {
      constexpr int k = decltype(part)::value >> 1, j0 = (decltype(part)::value & 1) * 8;
#pragma unroll
      for (int j = 0; j < 8; j++)
        n[j] = j0 + j < 15 ? hfma2(po[15 * k + (j0 + j) % 15], iv[2 * ((j0 + j) % 15)], hfma2(po[15 * k + (j0 + j) % 15], iv[2 * ((j0 + j) % 15) + 1], 0x80008000u)) : 0x3F803F80u;
#pragma unroll
      for (int j = 0; j < 8; j += 2) chk = hfma2(n[j], n[j + 1], chk);
    };
    int od1, od2;
    auto store = [&](const uint32_t (&n)[8], const char* optr, auto part) {
      constexpr int k = decltype(part)::value >> 1, off = (8 * (k & 1) + 64 * (k >> 1)) * NROWS * 2;
      if ((decltype(part)::value & 1) == 0)
        asm volatile(
            "{\n.reg .pred p;\nsetp.ne.u64 p, %8, 0;\n"
            "@p st.global.v4.u32 [%8 + %9], {%0, %1, %2, %3};\n@p st.global.v4.u32 [%8 + %9 + 512], {%4, %5, %6, %7};\n}\n"
            ::"r"(n[0]), "r"(n[1]), "r"(n[2]), "r"(n[3]), "r"(n[4]), "r"(n[5]), "r"(n[6]), "r"(n[7]), "l"(optr), "n"(off) : "memory");
      else
        asm volatile(
            "{\n.reg .pred p;\n.reg .b64 b, c;\nsetp.ne.u64 p, %7, 0;\nmad.wide.s32 b, %9, 1, %7;\nmad.wide.s32 c, %10, 1, %7;\n"
            "@p st.global.v4.u32 [%7 + %8 + 1024], {%0, %1, %2, %3};\n@p st.global.v2.u32 [b + %8], {%4, %5};\n@p st.global.u32 [c + %8], %6;\n}\n"
            ::"r"(n[0]), "r"(n[1]), "r"(n[2]), "r"(n[3]), "r"(n[4]), "r"(n[5]), "r"(n[6]), "l"(optr), "n"(off), "r"(od1), "r"(od2) : "memory");
    };
    auto put = [&](const uint32_t (&po)[60], const uint32_t (&iv)[30], const char* optr, auto part) {
      uint32_t n[8];
      norm(n, po, iv, part);
      store(n, optr, part);
    };
    auto out_ptr = [&](int u) {
      const int k = unit_head(u, rank) * DH + 16 * w + (lane >> 2), b = unit_batch(u), q = lane & 3;
      const uint32_t i0 = o_idx(k, o_pos(b, wg, 2 * q));
      od1 = 2 * (int)(o_idx(k, o_pos(b, wg, 96 + 2 * q)) - i0);
      od2 = 2 * (int)(o_idx(k, o_pos(b, wg, 112 + 2 * q)) - i0);
      return reinterpret_cast<const char*>(P.o + i0);
    };
    auto unsafe = [&](bool valid) {
      const bool b = valid && ((chk & 0x7F80u) == 0x7F80u || (chk & 0x7F800000u) == 0x7F800000u);
      return __any_sync(~0u, bar_red_or(wg, b));
    };
    auto publish = [&]() { __syncwarp(); if (lane == 0) mbar_arrive(sb + BAR_STAGE + 8 * wg); };

    uint32_t po[60];
#pragma unroll
    for (int i = 0; i < 60; i++) po[i] = 0;
    int id = 0;
    bool more;
    do {
      float o0[60], o1[60];
      uint32_t prev = 0;
      auto qstep = [&](int s, int acc) {
        const uint32_t j = s & 3, par = ((s >> 2) + (j < 2 ? it : 0)) & 1;
        TR(it * 160 + 3 * s);
        ring_wait();
        TR(it * 160 + 3 * s + 1);
        mbar_wait(sb + BAR_XFULL + 32 * wg + 8 * j, par);
        TR(it * 160 + 3 * s + 2);
        if (s >= ALT_FROM) turn_wait();
        wg_fence();
        mma_tn(o0, o1, ring_addr(), ((sb & 0x3FFFF) + OFF_Q + x_slot(wg, j)) >> 4, acc);
        wg_commit();
        if (s >= ALT_FROM || (s == ALT_FROM - 1 && wg == 1)) turn_pass();
        if (s > 0 && s <= EREL_FROM) {
          wg_wait<1>();
          release(prev);
          if (s <= 6 && lane == 0) mbar_arrive_cl(xempty + 8 * ((s - 1) & 3));
        }
        prev = r.slot;
        r.next();
      };
      auto qdone = [&](int s) {
        if (s >= EREL_FROM) {
          wg_wait<0>();
          release(prev);
          if (s <= 5 && lane == 0) mbar_arrive_cl(xempty + 8 * (s & 3));
        }
      };
      qstep(0, 0);
      const int up = (it > 3 ? id : cl) + ((int)it - 1) * ncl;
      const char* optr = out_ptr(up);
      if (it == 0) optr = nullptr;
      uint32_t n7[8];
      {
        uint32_t iv[30];
        qstep(1, 1); load_inv(iv, (it + 1) & 1); put(po, iv, optr, IC<0>());
        qstep(2, 1); put(po, iv, optr, IC<1>()); qdone(2);
        qstep(3, 1); put(po, iv, optr, IC<2>()); qdone(3);
        qstep(4, 1); put(po, iv, optr, IC<3>()); qdone(4);
        qstep(5, 1); put(po, iv, optr, IC<4>()); qdone(5);
        qstep(6, 1); put(po, iv, optr, IC<5>()); qdone(6);
        qstep(7, 1); put(po, iv, optr, IC<6>());
        norm(n7, po, iv, IC<7>());
        qdone(7);
        if (LATE_AT == 3 || (LATE_AT == 5 && wg == 1)) store(n7, optr, IC<7>());
      }
      TR(it * 160 + 24);
      const uint32_t a8 = ring_addr(), slot8 = r.slot;
      ring_wait();
      r.next();
      TR(it * 160 + 25);
      mbar_wait(sb + BAR_XFULL + 32 * wg, it & 1);
      TR(it * 160 + 26);
      auto wait9 = [&]() {
        TR(it * 160 + 27);
        ring_wait();
        TR(it * 160 + 28);
        mbar_wait(sb + BAR_XFULL + 32 * wg + 8, it & 1);
        TR(it * 160 + 29);
      };
      if (PRE9) wait9();
      turn_wait();
      wg_fence();
      mma_tn(o0, o1, a8, qd, 1);
      wg_commit();
      if (!PRE9) { wait9(); wg_fence(); }
      mma_tn_split(o0, o1, ring_addr(), qd + (XB >> 4));
      turn_pass();
      wg_wait<2>();
      if (EREL_FROM > 7) release(prev);
      release(slot8);
      if (LATE_AT == 4 || (LATE_AT == 5 && wg == 0)) store(n7, optr, IC<7>());
      auto put_q = [&](const float (&o)[60], uint32_t dst) {
        bar_sync(wg);
#pragma unroll
        for (int j = 0; j < 14; j += 2)
          stsm4t(dst + j * 1024, pack(o[4 * j] * QSCALE, o[4 * j + 1] * QSCALE), pack(o[4 * j + 2] * QSCALE, o[4 * j + 3] * QSCALE),
                 pack(o[4 * j + 4] * QSCALE, o[4 * j + 5] * QSCALE), pack(o[4 * j + 6] * QSCALE, o[4 * j + 7] * QSCALE));
        stsm2t(dst + 14 * 1024, pack(o[56] * QSCALE, o[57] * QSCALE), pack(o[58] * QSCALE, o[59] * QSCALE));
      };
      wg_wait<1>();
      reg_fence(o0);
      put_q(o0, qreg + st_off);
      wg_wait<0>();
      reg_fence(o1);
      release(r.slot);
      r.next();
      TR(it * 160 + 30);
      put_q(o1, qreg + XB + st_off);
      fence_async_smem();
      if (unsafe(it > 0)) {
        slow_path(P, unit_batch(up), unit_head(up, rank), wg, w, lane);
        optr = nullptr;
        if (!DPRO) {
#pragma unroll
          for (int i = 0; i < 60; i++) o0[i] = o1[i] = 0.f;
        }
      }
      TR(it * 160 + 32); TG(it * 160 + 142);

      float sc[60], l[30];
      uint32_t slot0 = r.slot;
      ring_wait();
      TR(it * 160 + 33);
      turn_wait();
      wg_fence();
      mma_qk(sc, ring_addr(), qd);
      wg_commit();
      r.next();
      uint32_t slot1 = r.slot;
      ring_wait();
      wg_fence();
      mma_qk(o1, ring_addr(), qd);
      wg_commit();
      r.next();
      turn_pass();
      if (LATE_AT == 0) store(n7, optr, IC<7>());
      wg_wait<1>();
      reg_fence(sc);
      TR(it * 160 + 35);
      release(slot0);
      exp_store<0, 15, true>(sc, l, preg + st_off);
      TR(it * 160 + 38); TG(it * 160 + 43);
      slot0 = r.slot;
      ring_wait();
      wg_fence();
      mma_qk(sc, ring_addr(), qd);
      wg_commit();
      r.next();
      wg_wait<1>();
      reg_fence(o1);
      TR(it * 160 + 41);
      release(slot1);
      exp_store<0, 15>(o1, l, preg - 2 * XB + st_off);
      fence_async_smem();
      bar_sync(wg);
      TR(it * 160 + 44);
      slot1 = r.slot;
      ring_wait();
      turn_wait();
      wg_fence();
      mma_tn(o0, o1, ring_addr(), pd, 0);
      wg_commit();
      r.next();
      ring_wait();
      wg_fence();
      mma_tn(o0, o1, ring_addr(), pd - (2 * XB >> 4), 1);
      wg_commit();
      turn_pass();
      if (LATE_AT == 1) store(n7, optr, IC<7>());
      if (it > 0) publish();
      if (it >= 2) id = __shfl_sync(~0u, role(), 0);
      wg_wait<1>();
      reg_fence(sc);
      release(slot0);
      release(slot1);
      bar_sync(wg);
      TR(it * 160 + 47);
      exp_store<0, VREL>(sc, l, preg + st_off);
      wg_wait<0>();
      reg_fence(o0); reg_fence(o1);
      release(r.slot);
      r.next();
      exp_store<VREL, 15>(sc, l, preg + st_off);
      fence_async_smem();
      bar_sync(wg);
      more = id + ((int)it + 1) * ncl < NUNITS;
      const bool gemm = id < nsingle || (NCL == 66 && id >= 58);
#pragma unroll 1
      for (int s = DPRO ? 3 : 1; s < 16; s++) {
        const uint32_t kslot = r.slot;
        TR(it * 160 + 32 + 6 * s); TG(it * 160 + 37 + 6 * s);
        if (s == 8) TRL(it * 160 + 139);
        ring_wait();
        TR(it * 160 + 33 + 6 * s);
        turn_wait();
        wg_fence();
        mma_qk(sc, ring_addr(), qd);
        wg_commit();
        r.next();
        TR(it * 160 + 36 + 6 * s);
        ring_wait();
        TR(it * 160 + 34 + 6 * s);
        wg_fence();
        mma_tn(o0, o1, ring_addr(), pd - ((s - 1) & 1) * (2 * XB >> 4), DPRO || s != 1);
        wg_commit();
        if (wg == 0 || s < 15) turn_pass();
        wg_wait<1>();
        reg_fence(sc);
        TR(it * 160 + 35 + 6 * s);
        release(kslot);
        if (s == 15) {
          if (more) { if (lane < 2) mbar_arrive_cl(xempty + 8 * lane); }
          else if (lane < 3 && gemm) mbar_arrive_cl(mapa(sb + BAR_BEMPTY + 8 * lane, lane & 1));
        }
        exp_store<0, VREL>(sc, l, preg - (s & 1) * 2 * XB + st_off);
        wg_wait<0>();
        reg_fence(o0); reg_fence(o1);
        release(r.slot);
        r.next();
        exp_store<VREL, 15>(sc, l, preg - (s & 1) * 2 * XB + st_off);
        fence_async_smem();
      }
      bar_sync(wg);
      TR(it * 160 + 128);
      ring_wait();
      wg_fence();
      mma_tn_split(o0, o1, ring_addr(), pd - (2 * XB >> 4));
      {
        const uint32_t a = preg + (8 * w + (lane >> 2)) * 480 + (lane & 3) * 8;
#pragma unroll
        for (int j = 0; j < 15; j++) asm volatile("st.shared.v2.f32 [%0], {%1, %2};" ::"r"(a + j * 32), "f"(l[2 * j]), "f"(l[2 * j + 1]) : "memory");
      }
      TR(it * 160 + 132);
      sum_l();
      TR(it * 160 + 133);
      wg_wait<1>();
      reg_fence(o0);
      TR(it * 160 + 134);
#pragma unroll
      for (int j = 0; j < 15; j++) { po[j] = pack(o0[4 * j], o0[4 * j + 1]); po[15 + j] = pack(o0[4 * j + 2], o0[4 * j + 3]); }
      wg_wait<0>();
      reg_fence(o1);
      release(r.slot);
      r.next();
      if (more) { if (lane < 2) mbar_arrive_cl(xempty + 16 + 8 * lane); }
      else if (gemm && lane < 3) mbar_arrive_cl(mapa(sb + BAR_BEMPTY + 24 + 8 * lane, (lane + 1) & 1));
      TR(it * 160 + 130);
#pragma unroll
      for (int j = 0; j < 15; j++) { po[30 + j] = pack(o1[4 * j], o1[4 * j + 1]); po[45 + j] = pack(o1[4 * j + 2], o1[4 * j + 3]); }
      TR(it * 160 + 131); TG(it * 160 + 143);
      it++;
    } while (more);
    const bool gemm = id < nsingle || (NCL == 66 && id >= 58);
    const int u = (it > 3 ? id : cl) + ((int)it - 1) * ncl;
    if (NCL != 66) lane = __shfl_sync(~0u, lane, lane);
    uint32_t pb[60];
#pragma unroll
    for (int i = 0; i < 60; i++) pb[i] = NCL != 66 ? po[i] ^ (gridDim.y - 1) : po[i];

    uint32_t bslot = 0, bphase = 0;
    auto out_tile = [&](const float (&acc)[80], int t) {
      const uint32_t st = sb + w * RING_BYTES + wg * 8192;
      const uint32_t sa = st + (lane & 15) * 336 + (lane >> 4) * 16;
#pragma unroll
      for (int j = 0; j < 20; j += 2)
        asm volatile("stmatrix.sync.aligned.m8n8.x4.shared.b16 [%0], {%1,%2,%3,%4};" ::"r"(sa + j * 16), "r"(pack(acc[4 * j], acc[4 * j + 1])),
                     "r"(pack(acc[4 * j + 2], acc[4 * j + 3])), "r"(pack(acc[4 * j + 4], acc[4 * j + 5])), "r"(pack(acc[4 * j + 6], acc[4 * j + 7])) : "memory");
      fence_async_smem();
      __syncwarp();
      if (lane < 16) {
        __nv_bfloat16* dst = P.out + (size_t)o_row(row_block(t) * 256 + rank * 128 + wg * 64 + w * 16 + lane) * DM + (t & 3) * 160;
        asm volatile("cp.async.bulk.global.shared::cta.bulk_group [%0], [%1], 320;" ::"l"(dst), "r"(st + lane * 336) : "memory");
        asm volatile("cp.async.bulk.commit_group;" ::: "memory");
        asm volatile("cp.async.bulk.wait_group.read 0;" ::: "memory");
      }
      __syncwarp();
    };
    for (int t = id; t == id || (NCL != 66 && t < nsingle); t += ncl) {
      float acc[80];
      uint32_t prev = 0, bprev = 0;
      const bool tile = t < nsingle;
      const bool last = NCL == 66 || t + ncl >= nsingle;
      auto bstep = [&](int ks, int accf) {
        if (!(ks & 3)) TR(640 + ks / 2); if ((ks & 7) == 0) TG(144 + (ks >> 3));
        ring_wait();
        mbar_wait(sb + BAR_BFULL + 8 * bslot, bphase);
        if (!(ks & 3)) TR(641 + ks / 2);
        wg_fence();
        const uint32_t a = ring_addr() + wg * 512, bd = (((sb & 0x3FFFF) + OFF_Q + bslot * BB) >> 4) | ((4096u >> 4) << 16);
#pragma unroll
        for (int k = 0; k < 4; k++) wgmma_n160<1, 1>(acc, a + LBO64A + k * 128, HI64A, bd + k * 64, HI64, k == 0 ? accf : 1);
        wg_commit();
        if (ks > 0) {
          wg_wait<1>();
          release(prev);
          if (lane == 0 && (ks < 59 || !last)) mbar_arrive_cl(mapa(sb + BAR_BEMPTY + 8 * bprev, bprev & 1));
        }
        prev = r.slot; bprev = bslot;
        r.next();
        if (++bslot == 6) { bslot = 0; bphase ^= 1; }
      };
      const char* optr = out_ptr(u);
      if (t != id) optr = nullptr;
      uint32_t iv[30], n3[8], n4[8], n5[8], n6[8], n7[8];
      if (tile) {
        bstep(0, 0);
        bstep(1, 1);
        load_inv(iv, (it + 1) & 1);
#pragma unroll 1
        for (int ks = 2; ks < 17; ks++) {
          bstep(ks, 1);
          switch (ks) {
            case 2: put(pb, iv, optr, IC<0>()); break;
            case 4: put(pb, iv, optr, IC<1>()); break;
            case 6: put(pb, iv, optr, IC<2>()); break;
            case 8: put(pb, iv, optr, IC<3>()); break;
            case 10: put(pb, iv, optr, IC<4>()); break;
            case 12: put(pb, iv, optr, IC<5>()); break;
            case 14: put(pb, iv, optr, IC<6>()); break;
            case 16: put(pb, iv, optr, IC<7>()); break;
            default: break;
          }
        }
        wg_wait<0>();
        reg_fence(acc);
#pragma unroll
        for (int i = 0; i < 8; i++) n3[i] = n4[i] = n5[i] = n6[i] = n7[i] = 0;
      } else {
        Ring r2 = r;
        auto first = [&](int ks) {
          if (ks == 0) { TR(640); TG(144); }
          if (gemm) { mbar_wait(sb + BAR_RFULL + 8 * r2.slot, r2.phase); mbar_wait(sb + BAR_BFULL + 16 * ks, 0); }
          wg_fence();
          const uint32_t a = (((sb & 0x3FFFF) + r2.slot * RING_BYTES) >> 4) + wg * 512;
          const uint32_t bd = (((sb & 0x3FFFF) + OFF_Q + 2 * ks * BB) >> 4) | ((4096u >> 4) << 16);
#pragma unroll
          for (int k = 0; k < 4; k++) wgmma_n160<1, 1>(acc, a + LBO64A + k * 128, HI64A, bd + k * 64, HI64, k + ks != 0);
          wg_commit();
          if (ks > 0) {
            wg_wait<1>();
            if (gemm && lane == 0) mbar_arrive_cl(mapa(sb + BAR_BEMPTY + 16 * (ks - 1), 0));
          }
          r2.next();
        };
        first(0);
        load_inv(iv, (it + 1) & 1);
        put(pb, iv, optr, IC<0>());
        first(1);
        put(pb, iv, optr, IC<1>());
        norm(n3, pb, iv, IC<3>()); norm(n4, pb, iv, IC<4>());
        first(2);
        put(pb, iv, optr, IC<2>());
        norm(n5, pb, iv, IC<5>()); norm(n6, pb, iv, IC<6>()); norm(n7, pb, iv, IC<7>());
        wg_wait<0>();
        reg_fence(acc);
      }
      if (unsafe(t == id)) {
        slow_path(P, unit_batch(u), unit_head(u, rank), wg, w, lane);
        optr = nullptr;
#pragma unroll
        for (int i = 0; i < 8; i++) n3[i] = n4[i] = n5[i] = n6[i] = n7[i] = 0;
      }
      if (tile && t == id) publish();
      if (!tile) {
        if (gemm) {
          float ac1[80];
          auto half = [&](float (&ac)[80], bool rel, int accf) {
            mbar_wait(sb + BAR_BFULL + 8 * bslot, bphase);
            wg_fence();
            const uint32_t a = ring_addr() + wg * 512, bd = (((sb & 0x3FFFF) + OFF_Q + bslot * BB) >> 4) | ((4096u >> 4) << 16);
#pragma unroll
            for (int k = 0; k < 4; k++) wgmma_n160<1, 1>(ac, a + LBO64A + k * 128, HI64A, bd + k * 64, HI64, k == 0 ? accf : 1);
            wg_commit();
            wg_wait<1>();
            if (lane == 0 && rel) mbar_arrive_cl(mapa(sb + BAR_BEMPTY + 8 * bprev, bprev & 1));
            bprev = bslot;
          };
          auto dstep = [&](int ks) {
            if (!(ks & 3)) TR(640 + ks / 2); if ((ks & 7) == 0) TG(144 + (ks >> 3));
            ring_wait();
            if (!(ks & 3)) TR(641 + ks / 2);
            half(acc, ks < 62, 1);
            release(prev);
            bslot++;
            half(ac1, ks < 61, 1);
            if (++bslot == 6) { bslot = 0; bphase ^= 1; }
            prev = r.slot; r.next();
          };
          bprev = 4; bslot = 1;
          half(ac1, true, 0);
          prev = r.slot; r.next(); bslot = 3;
          half(ac1, true, 1);
          release(prev); prev = r.slot; r.next(); bslot = 5;
          store(n3, optr, IC<3>());
          half(ac1, true, 1);
          release(prev); prev = r.slot; r.next(); bslot = 0; bphase = 1;
#pragma unroll 1
          for (int ks = 3; ks < 7; ks++) {
            dstep(ks);
            switch (ks) {
              case 3: store(n4, optr, IC<4>()); break;
              case 4: store(n5, optr, IC<5>()); break;
              case 5: store(n6, optr, IC<6>()); break;
              default: store(n7, optr, IC<7>()); break;
            }
          }
          publish();
#pragma unroll 1
          for (int ks = 7; ks < 64; ks++) {
            if (wg == 1 && ks == 62) turn_wait();
            dstep(ks);
          }
          if (wg == 0) turn_pass();
          wg_wait<0>();
          reg_fence(acc); reg_fence(ac1);
          TRL(158); TG(156);
          bar_sync(wg);
          out_tile(acc, 2 * id - 72);
          out_tile(ac1, 2 * id - 71);
        } else {
          store(n3, optr, IC<3>()); store(n4, optr, IC<4>()); store(n5, optr, IC<5>()); store(n6, optr, IC<6>()); store(n7, optr, IC<7>());
          publish();
        }
        break;
      }
#pragma unroll 1
      for (int ks = 17; ks < 64; ks++) {
        if (END_SKEW && wg == 1 && ks == 64 - END_SKEW) turn_wait();
        bstep(ks, 1);
      }
      if (END_SKEW && wg == 0) turn_pass();
      wg_wait<0>();
      reg_fence(acc);
      release(prev);
      if (lane == 0 && !last) mbar_arrive_cl(mapa(sb + BAR_BEMPTY + 8 * bprev, bprev & 1));
      TRL(158); TG(156);
      const int pos0 = row_block(t) * 256 + rank * 128 + wg * 64 + w * 16;
      if (last) {
        bar_sync(wg);
        out_tile(acc, t);
      } else {
        __nv_bfloat16* op0 = P.out + (size_t)o_row(pos0 + (lane >> 2)) * DM + (t & 3) * 160 + (lane & 3) * 2;
        __nv_bfloat16* op1 = P.out + (size_t)o_row(pos0 + (lane >> 2) + 8) * DM + (t & 3) * 160 + (lane & 3) * 2;
#pragma unroll
        for (int j = 0; j < 20; j++) {
          *reinterpret_cast<uint32_t*>(op0 + j * 8) = pack(acc[4 * j], acc[4 * j + 1]);
          *reinterpret_cast<uint32_t*>(op1 + j * 8) = pack(acc[4 * j + 2], acc[4 * j + 3]);
        }
      }
#pragma unroll
      for (int i = 0; i < 60; i++) pb[i] = 0;
    }
    TRL(159);
  }
}

typedef CUresult (*EncodeFn)(CUtensorMap*, CUtensorMapDataType, cuuint32_t, void*, const cuuint64_t*, const cuuint64_t*,
                             const cuuint32_t*, const cuuint32_t*, CUtensorMapInterleave, CUtensorMapSwizzle,
                             CUtensorMapL2promotion, CUtensorMapFloatOOBfill);

void make_map(EncodeFn enc, CUtensorMap* m, const void* p, int rank, const cuuint64_t* dims, const cuuint64_t* strides,
              const cuuint32_t* box, CUtensorMapSwizzle sw, CUtensorMapL2promotion promo) {
  cuuint32_t es[4] = {1, 1, 1, 1};
  enc(m, CU_TENSOR_MAP_DATA_TYPE_BFLOAT16, rank, const_cast<void*>(p), dims, strides, box, es, CU_TENSOR_MAP_INTERLEAVE_NONE, sw,
      promo, CU_TENSOR_MAP_FLOAT_OOB_FILL_NONE);
}

}

extern "C" void kernel_launch(void* const* d_in, const int* in_sizes, int n_in, void* d_out, int out_size) {
  static EncodeFn enc = nullptr;
  static int nclusters = 0;
  static void* o_ptr = nullptr;
  if (!enc) {
    cudaDriverEntryPointQueryResult qr;
    cudaGetDriverEntryPoint("cuTensorMapEncodeTiled", (void**)&enc, cudaEnableDefault, &qr);
    cudaFuncSetAttribute(fused_attn_kernel<66>, cudaFuncAttributeMaxDynamicSharedMemorySize, SMEM_BYTES);
    cudaFuncSetAttribute(fused_attn_kernel<0>, cudaFuncAttributeMaxDynamicSharedMemorySize, SMEM_BYTES);
    cudaGetSymbolAddress(&o_ptr, g_o);
    cudaLaunchConfig_t cfg = {};
    cfg.gridDim = 128; cfg.blockDim = 384; cfg.dynamicSmemBytes = SMEM_BYTES;
    cudaLaunchAttribute at; at.id = cudaLaunchAttributeClusterDimension;
    at.val.clusterDim.x = 2; at.val.clusterDim.y = 1; at.val.clusterDim.z = 1;
    cfg.attrs = &at; cfg.numAttrs = 1;
    int n = 0;
    cudaOccupancyMaxActiveClusters(&n, fused_attn_kernel<66>, &cfg);
    nclusters = n >= 66 ? MAXCL : (n >= 64 || n <= 0 ? 64 : n);
  }
  const __nv_bfloat16* x = (const __nv_bfloat16*)d_in[0];
  const __nv_bfloat16* k = (const __nv_bfloat16*)d_in[1];
  const __nv_bfloat16* v = (const __nv_bfloat16*)d_in[2];
  const __nv_bfloat16* wq = (const __nv_bfloat16*)d_in[3];
  const __nv_bfloat16* wo = (const __nv_bfloat16*)d_in[4];
  CUtensorMap tm_x, tm_wq, tm_k, tm_v, tm_o, tm_wo;
  const auto S128 = CU_TENSOR_MAP_SWIZZLE_128B;
  const auto P128 = CU_TENSOR_MAP_L2_PROMOTION_L2_128B, P256 = CU_TENSOR_MAP_L2_PROMOTION_L2_256B;
  { cuuint64_t d[2] = {DM, NB * SQ}, s[1] = {DM * 2}; cuuint32_t b[2] = {64, 120}; make_map(enc, &tm_x, x, 2, d, s, b, S128, X_PROMO); }
  { cuuint64_t d[3] = {64, DM, HD / 64}, s[2] = {HD * 2, 128}; cuuint32_t b[3] = {64, 64, 2}; make_map(enc, &tm_wq, wq, 3, d, s, b, S128, P256); }
  { cuuint64_t d[3] = {64, NB * NH * SK, 2}, s[2] = {DH * 2, 128}; cuuint32_t b[3] = {64, 64, 2};
    make_map(enc, &tm_k, k, 3, d, s, b, S128, P128); make_map(enc, &tm_v, v, 3, d, s, b, S128, P128); }
  { cuuint64_t d[4] = {256, 2, HD / 8, NROWS / 64}, s[3] = {512, NROWS * 16, 1024}; cuuint32_t b[4] = {256, 2, 8, 2};
    make_map(enc, &tm_o, o_ptr, 4, d, s, b, CU_TENSOR_MAP_SWIZZLE_NONE, P256); }
  { cuuint64_t d[3] = {32, HD, DM / 32}, s[2] = {DM * 2, 64}; cuuint32_t b[3] = {32, 64, 5};
    make_map(enc, &tm_wo, wo, 3, d, s, b, CU_TENSOR_MAP_SWIZZLE_64B, P128); }
  Params P{x, k, v, wq, (__nv_bfloat16*)d_out, (__nv_bfloat16*)o_ptr};
  if (nclusters == 66) fused_attn_kernel<66><<<132, 384, SMEM_BYTES>>>(tm_x, tm_wq, tm_k, tm_v, tm_o, tm_wo, P);
  else fused_attn_kernel<0><<<2 * nclusters, 384, SMEM_BYTES>>>(tm_x, tm_wq, tm_k, tm_v, tm_o, tm_wo, P);
}
```

```cpp
#include <cuda_runtime.h>
#include <cuda.h>
#include <cuda_bf16.h>
#include <stdint.h>

namespace {

constexpr int NB = 16, SQ = 240, DM = 640, NH = 32, SK = 1024, DH = 128, HD = NH * DH;
constexpr int NROWS = NB * SQ;
constexpr int NUNITS = 256;
#define DPRO 1
#define LATE_AT 4
#define ALT_FROM 4
#define END_SKEW 5
#define VREL 6
#define PF_HOLD 6
#define PF_N 4
#define PF_J0 3
#define PF_STEP 3
#define ROT 0
#define O_EF 1
#define B_ORDER 1
#define WO_PF 6
#define ROLE_AT 0
#define PAUSE_NS 11000
#define PAUSE_AT 2
#define EARLY 1
#define EARLY_X 2
#define EARLY_W 2
#define X_PROMO P128
#define PAUSE_J -1
#define PAUSE_SPREAD 0
#define WO_PF0 1
#define EREL_FROM 4
#define PRE9 0
#define MAXCL 66
#define SMID_TOP 88
constexpr int NOTILES = 60;
constexpr float QSCALE = 0.08838834764831845f * 1.4426950408889634f;
constexpr float L_MIN = 9.5367431640625e-07f;
constexpr float L_MAX = 1.152921504606846976e18f;

constexpr uint32_t RING_SLOTS = 6, RING_BYTES = 16384;
constexpr uint32_t XB = 15360;
constexpr uint32_t BB = 20480;
constexpr uint32_t OFF_Q = RING_SLOTS * RING_BYTES;
constexpr uint32_t OFF_P = OFF_Q + 4 * XB;
constexpr uint32_t OFF_INV = OFF_P + 4 * XB;
constexpr uint32_t OFF_L2 = OFF_INV + 1280;
constexpr uint32_t OFF_BAR = OFF_L2 + 4096;
constexpr uint32_t BAR_RFULL = OFF_BAR, BAR_REMPTY = BAR_RFULL + 48, BAR_XFULL = BAR_REMPTY + 48,
    BAR_XEMPTY = BAR_XFULL + 64, BAR_BFULL = BAR_XEMPTY + 32, BAR_BEMPTY = BAR_BFULL + 48, BAR_STAGE = BAR_BEMPTY + 48;
constexpr uint32_t BAR_ROLE = BAR_STAGE + 16, BAR_LSUM = BAR_ROLE + 24, BAR_INV = BAR_LSUM + 16;
constexpr uint32_t OFF_TR = BAR_INV + 16;
constexpr uint32_t SMEM_BYTES = OFF_TR + 1024;

constexpr uint32_t HI128 = (1u << 30) | (1024 >> 4);
constexpr uint32_t HI64 = (2u << 30) | (512 >> 4);
constexpr uint32_t HI64A = (2u << 30) | (1024 >> 4), LBO64A = (512u >> 4) << 16;

__device__ __nv_bfloat16 g_o[HD * NROWS];
__device__ unsigned g_cnt[67 * 8];
#define TS(i)
#define TRL(i)
#define TR(i)
#define TG(i)

struct Params {
  const __nv_bfloat16 *x, *k, *v, *wq;
  __nv_bfloat16 *out, *o;
};

__device__ __forceinline__ void wg_fence() { asm volatile("wgmma.fence.sync.aligned;" ::: "memory"); }
__device__ __forceinline__ void wg_commit() { asm volatile("wgmma.commit_group.sync.aligned;" ::: "memory"); }
template <int N> __device__ __forceinline__ void wg_wait() { asm volatile("wgmma.wait_group.sync.aligned %0;" ::"n"(N) : "memory"); }
template <int N> __device__ __forceinline__ void reg_fence(float (&r)[N]) {
#pragma unroll
  for (int i = 0; i < N; i++) asm volatile("" : "+f"(r[i])::"memory");
}
template <int TA, int TB>
__device__ __forceinline__ void wgmma_n120(float (&d)[60], uint32_t a_lo, uint32_t a_hi, uint32_t b_lo, uint32_t b_hi, int acc) {
  asm volatile(
      "{\n.reg .pred p;\n.reg .b64 da, db;\nsetp.ne.b32 p, %64, 0;\n"
      "mov.b64 da, {%60, %61};\nmov.b64 db, {%62, %63};\n"
      "wgmma.mma_async.sync.aligned.m64n120k16.f32.bf16.bf16 {"
      "%0, %1, %2, %3, %4, %5, %6, %7, %8, %9, %10, %11, %12, %13, %14, %15, %16, %17, %18, %19, %20, %21, %22, %23, "
      "%24, %25, %26, %27, %28, %29, %30, %31, %32, %33, %34, %35, %36, %37, %38, %39, %40, %41, %42, %43, %44, %45, "
      "%46, %47, %48, %49, %50, %51, %52, %53, %54, %55, %56, %57, %58, %59"
      "}, da, db, p, 1, 1, %65, %66;\n}\n"
      : "+f"(d[0]), "+f"(d[1]), "+f"(d[2]), "+f"(d[3]), "+f"(d[4]), "+f"(d[5]), "+f"(d[6]), "+f"(d[7]), "+f"(d[8]),
        "+f"(d[9]), "+f"(d[10]), "+f"(d[11]), "+f"(d[12]), "+f"(d[13]), "+f"(d[14]), "+f"(d[15]), "+f"(d[16]),
        "+f"(d[17]), "+f"(d[18]), "+f"(d[19]), "+f"(d[20]), "+f"(d[21]), "+f"(d[22]), "+f"(d[23]), "+f"(d[24]),
        "+f"(d[25]), "+f"(d[26]), "+f"(d[27]), "+f"(d[28]), "+f"(d[29]), "+f"(d[30]), "+f"(d[31]), "+f"(d[32]),
        "+f"(d[33]), "+f"(d[34]), "+f"(d[35]), "+f"(d[36]), "+f"(d[37]), "+f"(d[38]), "+f"(d[39]), "+f"(d[40]),
        "+f"(d[41]), "+f"(d[42]), "+f"(d[43]), "+f"(d[44]), "+f"(d[45]), "+f"(d[46]), "+f"(d[47]), "+f"(d[48]),
        "+f"(d[49]), "+f"(d[50]), "+f"(d[51]), "+f"(d[52]), "+f"(d[53]), "+f"(d[54]), "+f"(d[55]), "+f"(d[56]),
        "+f"(d[57]), "+f"(d[58]), "+f"(d[59])
      : "r"(a_lo), "r"(a_hi), "r"(b_lo), "r"(b_hi), "r"(acc), "n"(TA), "n"(TB));
}

template <int TA, int TB>
__device__ __forceinline__ void wgmma_n160(float (&d)[80], uint32_t a_lo, uint32_t a_hi, uint32_t b_lo, uint32_t b_hi, int acc) {
  asm volatile(
      "{\n.reg .pred p;\n.reg .b64 da, db;\nsetp.ne.b32 p, %84, 0;\n"
      "mov.b64 da, {%80, %81};\nmov.b64 db, {%82, %83};\n"
      "wgmma.mma_async.sync.aligned.m64n160k16.f32.bf16.bf16 {"
      "%0, %1, %2, %3, %4, %5, %6, %7, %8, %9, %10, %11, %12, %13, %14, %15, %16, %17, %18, %19, %20, %21, %22, %23, "
      "%24, %25, %26, %27, %28, %29, %30, %31, %32, %33, %34, %35, %36, %37, %38, %39, %40, %41, %42, %43, %44, %45, "
      "%46, %47, %48, %49, %50, %51, %52, %53, %54, %55, %56, %57, %58, %59, %60, %61, %62, %63, %64, %65, %66, %67, "
      "%68, %69, %70, %71, %72, %73, %74, %75, %76, %77, %78, %79"
      "}, da, db, p, 1, 1, %85, %86;\n}\n"
      : "+f"(d[0]), "+f"(d[1]), "+f"(d[2]), "+f"(d[3]), "+f"(d[4]), "+f"(d[5]), "+f"(d[6]), "+f"(d[7]), "+f"(d[8]),
        "+f"(d[9]), "+f"(d[10]), "+f"(d[11]), "+f"(d[12]), "+f"(d[13]), "+f"(d[14]), "+f"(d[15]), "+f"(d[16]),
        "+f"(d[17]), "+f"(d[18]), "+f"(d[19]), "+f"(d[20]), "+f"(d[21]), "+f"(d[22]), "+f"(d[23]), "+f"(d[24]),
        "+f"(d[25]), "+f"(d[26]), "+f"(d[27]), "+f"(d[28]), "+f"(d[29]), "+f"(d[30]), "+f"(d[31]), "+f"(d[32]),
        "+f"(d[33]), "+f"(d[34]), "+f"(d[35]), "+f"(d[36]), "+f"(d[37]), "+f"(d[38]), "+f"(d[39]), "+f"(d[40]),
        "+f"(d[41]), "+f"(d[42]), "+f"(d[43]), "+f"(d[44]), "+f"(d[45]), "+f"(d[46]), "+f"(d[47]), "+f"(d[48]),
        "+f"(d[49]), "+f"(d[50]), "+f"(d[51]), "+f"(d[52]), "+f"(d[53]), "+f"(d[54]), "+f"(d[55]), "+f"(d[56]),
        "+f"(d[57]), "+f"(d[58]), "+f"(d[59]), "+f"(d[60]), "+f"(d[61]), "+f"(d[62]), "+f"(d[63]), "+f"(d[64]),
        "+f"(d[65]), "+f"(d[66]), "+f"(d[67]), "+f"(d[68]), "+f"(d[69]), "+f"(d[70]), "+f"(d[71]), "+f"(d[72]),
        "+f"(d[73]), "+f"(d[74]), "+f"(d[75]), "+f"(d[76]), "+f"(d[77]), "+f"(d[78]), "+f"(d[79])
      : "r"(a_lo), "r"(a_hi), "r"(b_lo), "r"(b_hi), "r"(acc), "n"(TA), "n"(TB));
}
__device__ __forceinline__ void mbar_init(uint32_t bar, int cnt) { asm volatile("mbarrier.init.shared::cta.b64 [%0], %1;" ::"r"(bar), "r"(cnt)); }
__device__ __forceinline__ void mbar_expect(uint32_t bar, uint32_t bytes) {
  asm volatile("mbarrier.arrive.expect_tx.shared::cta.b64 _, [%0], %1;" ::"r"(bar), "r"(bytes) : "memory");
}
__device__ __forceinline__ uint32_t mapa(uint32_t addr, uint32_t cta) {
  uint32_t r; asm("mapa.shared::cluster.u32 %0, %1, %2;" : "=r"(r) : "r"(addr), "r"(cta)); return r;
}
__device__ __forceinline__ void mbar_expect_cl(uint32_t cbar, uint32_t bytes) {
  asm volatile("mbarrier.arrive.expect_tx.shared::cluster.b64 _, [%0], %1;" ::"r"(cbar), "r"(bytes) : "memory");
}
__device__ __forceinline__ void mbar_arrive(uint32_t bar) { asm volatile("mbarrier.arrive.shared::cta.b64 _, [%0];" ::"r"(bar) : "memory"); }
__device__ __forceinline__ void mbar_arrive_cl(uint32_t cbar) { asm volatile("mbarrier.arrive.shared::cluster.b64 _, [%0];" ::"r"(cbar) : "memory"); }
__device__ __forceinline__ void warp_arrive(uint32_t bar) {
  asm volatile("{\n.reg .pred p;\nelect.sync _|p, 0xffffffff;\n@p mbarrier.arrive.shared::cta.b64 _, [%0];\n}\n" ::"r"(bar) : "memory");
}
__device__ __forceinline__ void warp_arrive_cl(uint32_t cbar) {
  asm volatile("{\n.reg .pred p;\nelect.sync _|p, 0xffffffff;\n@p mbarrier.arrive.shared::cluster.b64 _, [%0];\n}\n" ::"r"(cbar) : "memory");
}
__device__ __forceinline__ void mbar_wait(uint32_t bar, uint32_t parity) {
  asm volatile(
      "{\n.reg .pred p;\n.reg .u32 n;\n"
      "mbarrier.try_wait.parity.shared::cta.b64 p, [%0], %1;\n@p bra WAIT_DONE;\n"
      "mov.u32 n, 0;\n"
      "WAIT_LOOP:\n"
      "mbarrier.try_wait.parity.shared::cta.b64 p, [%0], %1;\n@p bra WAIT_DONE;\n"
      "add.u32 n, n, 1;\nsetp.lt.u32 p, n, 0x4000000;\n@p bra WAIT_LOOP;\ntrap;\n"
      "WAIT_DONE:\n}\n" ::"r"(bar), "r"(parity) : "memory");
}
__device__ __forceinline__ void mbar_wait_cl(uint32_t bar, uint32_t parity) {
  asm volatile(
      "{\n.reg .pred p;\n.reg .u32 n;\nmov.u32 n, 0;\n"
      "WAIT_LOOP:\n"
      "mbarrier.try_wait.parity.acquire.cluster.shared::cta.b64 p, [%0], %1;\n@p bra WAIT_DONE;\n"
      "add.u32 n, n, 1;\nsetp.lt.u32 p, n, 0x4000000;\n@p bra WAIT_LOOP;\ntrap;\n"
      "WAIT_DONE:\n}\n" ::"r"(bar), "r"(parity) : "memory");
}
__device__ __forceinline__ void tma3d(uint32_t dst, const CUtensorMap* m, int c0, int c1, int c2, uint32_t bar) {
  asm volatile("cp.async.bulk.tensor.3d.shared::cluster.global.mbarrier::complete_tx::bytes [%0], [%1, {%3, %4, %5}], [%2];"
               ::"r"(dst), "l"(m), "r"(bar), "r"(c0), "r"(c1), "r"(c2) : "memory");
}
__device__ __forceinline__ void tma3d_hint(uint32_t dst, const CUtensorMap* m, int c0, int c1, int c2, uint32_t bar, uint64_t pol) {
  asm volatile("cp.async.bulk.tensor.3d.shared::cluster.global.mbarrier::complete_tx::bytes.L2::cache_hint [%0], [%1, {%3, %4, %5}], [%2], %6;"
               ::"r"(dst), "l"(m), "r"(bar), "r"(c0), "r"(c1), "r"(c2), "l"(pol) : "memory");
}
__device__ __forceinline__ void tma2d_mc(uint32_t dst, const CUtensorMap* m, int c0, int c1, uint32_t bar) {
  asm volatile("cp.async.bulk.tensor.2d.shared::cluster.global.mbarrier::complete_tx::bytes.multicast::cluster [%0], [%1, {%3, %4}], [%2], %5;"
               ::"r"(dst), "l"(m), "r"(bar), "r"(c0), "r"(c1), "h"((uint16_t)3) : "memory");
}
__device__ __forceinline__ void tma3d_mc(uint32_t dst, const CUtensorMap* m, int c0, int c1, int c2, uint32_t bar) {
  asm volatile("cp.async.bulk.tensor.3d.shared::cluster.global.mbarrier::complete_tx::bytes.multicast::cluster [%0], [%1, {%3, %4, %5}], [%2], %6;"
               ::"r"(dst), "l"(m), "r"(bar), "r"(c0), "r"(c1), "r"(c2), "h"((uint16_t)3) : "memory");
}
__device__ __forceinline__ void l2_prefetch(const void* p, uint32_t bytes) {
  asm volatile("cp.async.bulk.prefetch.L2.global [%0], %1;" ::"l"(p), "r"(bytes) : "memory");
}
__device__ __forceinline__ void fence_async_smem() { asm volatile("fence.proxy.async.shared::cta;" ::: "memory"); }
__device__ __forceinline__ void bar_sync(int wg) {
  if (wg == 0) asm volatile("bar.sync 1, 128;" ::: "memory");
  else asm volatile("bar.sync 2, 128;" ::: "memory");
}
__device__ __forceinline__ bool bar_red_or(int id, bool v) {
  uint32_t r;
  asm volatile("{\n.reg .pred p, q;\nsetp.ne.u32 p, %2, 0;\nbar.red.or.pred q, %1, 128, p;\nselp.u32 %0, 1, 0, q;\n}\n"
               : "=r"(r) : "r"(1 + id), "r"((uint32_t)v) : "memory");
  return r != 0;
}
__device__ __forceinline__ uint32_t hfma2(uint32_t a, uint32_t b, uint32_t c) { uint32_t r; asm("fma.rn.bf16x2 %0, %1, %2, %3;" : "=r"(r) : "r"(a), "r"(b), "r"(c)); return r; }
__device__ __forceinline__ float ex2(float x) { float y; asm("ex2.approx.ftz.f32 %0, %1;" : "=f"(y) : "f"(x)); return y; }
__device__ __forceinline__ uint32_t pack(float lo, float hi) { uint32_t r; asm("cvt.rn.bf16x2.f32 %0, %1, %2;" : "=r"(r) : "f"(hi), "f"(lo)); return r; }
__device__ __forceinline__ void stsm4t(uint32_t a, uint32_t r0, uint32_t r1, uint32_t r2, uint32_t r3) {
  asm volatile("stmatrix.sync.aligned.m8n8.x4.trans.shared.b16 [%0], {%1,%2,%3,%4};" ::"r"(a), "r"(r0), "r"(r1), "r"(r2), "r"(r3) : "memory");
}
__device__ __forceinline__ void stsm2t(uint32_t a, uint32_t r0, uint32_t r1) {
  asm volatile("stmatrix.sync.aligned.m8n8.x2.trans.shared.b16 [%0], {%1,%2};" ::"r"(a), "r"(r0), "r"(r1) : "memory");
}
__device__ __forceinline__ void mma16816(float (&d)[4], const uint32_t (&a)[4], uint32_t b0, uint32_t b1) {
  asm volatile("mma.sync.aligned.m16n8k16.row.col.f32.bf16.bf16.f32 {%0,%1,%2,%3}, {%4,%5,%6,%7}, {%8,%9}, {%0,%1,%2,%3};"
               : "+f"(d[0]), "+f"(d[1]), "+f"(d[2]), "+f"(d[3]) : "r"(a[0]), "r"(a[1]), "r"(a[2]), "r"(a[3]), "r"(b0), "r"(b1));
}

__device__ __forceinline__ uint32_t fresh_tid() { uint32_t t; asm volatile("mov.u32 %0, %tid.x;" : "=r"(t)); return t; }

template <int V> struct IC { static constexpr int value = V; };

struct Ring {
  uint32_t slot = 0, phase = 0;
  __device__ __forceinline__ void next() { if (++slot == RING_SLOTS) { slot = 0; phase ^= 1; } }
};

__device__ __forceinline__ void mma_tn(float (&o0)[60], float (&o1)[60], uint32_t a, uint32_t b, int acc) {
#pragma unroll
  for (int k = 0; k < 4; k++) {
    wgmma_n120<1, 0>(o0, a + k * 128, HI128, b + k * 2, HI128, k == 0 ? acc : 1);
    wgmma_n120<1, 0>(o1, a + 512 + k * 128, HI128, b + k * 2, HI128, k == 0 ? acc : 1);
  }
}
__device__ __forceinline__ void mma_tn_split(float (&o0)[60], float (&o1)[60], uint32_t a, uint32_t b) {
#pragma unroll
  for (int k = 0; k < 4; k++) wgmma_n120<1, 0>(o0, a + k * 128, HI128, b + k * 2, HI128, 1);
  wg_commit();
#pragma unroll
  for (int k = 0; k < 4; k++) wgmma_n120<1, 0>(o1, a + 512 + k * 128, HI128, b + k * 2, HI128, 1);
  wg_commit();
}
__device__ __forceinline__ void mma_qk(float (&s)[60], uint32_t a, uint32_t q) {
#pragma unroll
  for (int k = 0; k < 8; k++)
    wgmma_n120<0, 0>(s, a + (k >> 2) * 512 + (k & 3) * 2, HI128, q + (k >> 2) * (XB >> 4) + (k & 3) * 2, HI128, k != 0);
}
template <int J0, int J1, bool FIRST = false>
__device__ __forceinline__ void exp_store(const float (&s)[60], float (&l)[30], uint32_t dst) {
#pragma unroll
  for (int j = J0; j < J1; j += 2) {
    uint32_t p[4];
#pragma unroll
    for (int jj = 0; jj < 2; jj++) {
      if (j + jj < 15) {
        const int c = j + jj;
        float e0 = ex2(s[4 * c]), e1 = ex2(s[4 * c + 1]), e2 = ex2(s[4 * c + 2]), e3 = ex2(s[4 * c + 3]);
        if (FIRST) { l[2 * c] = e0 + e2; l[2 * c + 1] = e1 + e3; }
        else { l[2 * c] += e0; l[2 * c + 1] += e1; l[2 * c] += e2; l[2 * c + 1] += e3; }
        p[2 * jj] = pack(e0, e1); p[2 * jj + 1] = pack(e2, e3);
      }
    }
    if (j + 1 < 15) stsm4t(dst + j * 1024, p[0], p[1], p[2], p[3]);
    else stsm2t(dst + j * 1024, p[0], p[1]);
  }
}

__device__ __forceinline__ int o_pos(int b, int wg, int r) {
  const int j = r >> 3, q = (r >> 1) & 3, c = r & 1, o = b & 1, base = (b >> 1) * 480;
  if (j < 12) return base + (o * 9 + wg * 3 + (j >> 2)) * 32 + q * 8 + (j & 3) * 2 + c;
  if (j < 14) return base + (6 + 2 * o) * 32 + wg * 16 + q * 4 + (j - 12) * 2 + c;
  return base + 7 * 32 + (o * 2 + wg) * 8 + q * 2 + c;
}
__device__ __forceinline__ int o_row(int p) {
  const int pair = p / 480, a = (p - pair * 480) >> 5, in = p & 31, c = p & 1;
  int tile, row;
  if (a == 7) { tile = in >> 3; row = 112 + (in & 7); }
  else if (a == 6 || a == 8) { tile = a - 6 + (in >> 4); row = (12 + ((in >> 1) & 1)) * 8 + ((in >> 2) & 3) * 2 + c; }
  else { const int f = a > 8 ? a - 3 : a; tile = f / 3; row = ((f - tile * 3) * 4 + ((in >> 1) & 3)) * 8 + (in >> 3) * 2 + c; }
  return pair * 480 + tile * 120 + row;
}
__device__ __forceinline__ uint32_t o_idx(int k, int p) {
  return ((k >> 3) * (NROWS / 32) + (p >> 5)) * 256 + (k & 7) * 32 + ((((p >> 3) & 3) ^ ((k & 7) >> 1)) << 3) + (p & 7);
}

__device__ __forceinline__ void slow_path(const Params& P, int b, int h, int wg, int w, int lane) {
  const int g = lane >> 2, q = lane & 3, row0 = wg * 120;
  const uint16_t* wq = reinterpret_cast<const uint16_t*>(P.wq) + h * DH + g;
  const __nv_bfloat16* kp = P.k + (size_t)(b * NH + h) * SK * DH;
  const uint16_t* vp = reinterpret_cast<const uint16_t*>(P.v) + (size_t)(b * NH + h) * SK * DH + g;
#pragma unroll 1
  for (int t = w; t < 8; t += 4) {
    const int r0 = 16 * t + g, r1 = r0 + 8;
    const __nv_bfloat16* x0 = P.x + (size_t)(b * SQ + row0 + r0) * DM + 2 * q;
    const __nv_bfloat16* x1 = P.x + (size_t)(b * SQ + row0 + min(r1, 119)) * DM + 2 * q;
    float o[16][4];
#pragma unroll
    for (int n = 0; n < 16; n++) o[n][0] = o[n][1] = o[n][2] = o[n][3] = 0.f;
#pragma unroll 1
    for (int k0 = 0; k0 < DM; k0 += 16) {
      uint32_t a[4] = {*(const uint32_t*)(x0 + k0), *(const uint32_t*)(x1 + k0), *(const uint32_t*)(x0 + k0 + 8), *(const uint32_t*)(x1 + k0 + 8)};
      const uint16_t* wr = wq + (size_t)(k0 + 2 * q) * HD;
#pragma unroll
      for (int n = 0; n < 16; n++) {
        if ((n & 3) == 0) __syncwarp();
        mma16816(o[n], a, wr[8 * n] | ((uint32_t)wr[8 * n + HD] << 16), wr[8 * n + 8 * HD] | ((uint32_t)wr[8 * n + 9 * HD] << 16));
      }
    }
    uint32_t qa[8][4];
#pragma unroll
    for (int k = 0; k < 8; k++) {
      qa[k][0] = pack(o[2 * k][0] * QSCALE, o[2 * k][1] * QSCALE);
      qa[k][1] = pack(o[2 * k][2] * QSCALE, o[2 * k][3] * QSCALE);
      qa[k][2] = pack(o[2 * k + 1][0] * QSCALE, o[2 * k + 1][1] * QSCALE);
      qa[k][3] = pack(o[2 * k + 1][2] * QSCALE, o[2 * k + 1][3] * QSCALE);
    }
#pragma unroll
    for (int n = 0; n < 16; n++) o[n][0] = o[n][1] = o[n][2] = o[n][3] = 0.f;
    float m0 = -INFINITY, m1 = -INFINITY, l0 = 0.f, l1 = 0.f;
#pragma unroll 1
    for (int key0 = 0; key0 < SK; key0 += 16) {
      float s[2][4];
#pragma unroll
      for (int nt = 0; nt < 2; nt++) {
        s[nt][0] = s[nt][1] = s[nt][2] = s[nt][3] = 0.f;
        const __nv_bfloat16* kr = kp + (size_t)(key0 + 8 * nt + g) * DH + 2 * q;
#pragma unroll
        for (int k = 0; k < 8; k++) mma16816(s[nt], qa[k], *(const uint32_t*)(kr + 16 * k), *(const uint32_t*)(kr + 16 * k + 8));
      }
      float n0 = fmaxf(fmaxf(s[0][0], s[0][1]), fmaxf(s[1][0], s[1][1])), n1 = fmaxf(fmaxf(s[0][2], s[0][3]), fmaxf(s[1][2], s[1][3]));
      n0 = fmaxf(n0, __shfl_xor_sync(~0u, n0, 1)); n1 = fmaxf(n1, __shfl_xor_sync(~0u, n1, 1));
      n0 = fmaxf(n0, __shfl_xor_sync(~0u, n0, 2)); n1 = fmaxf(n1, __shfl_xor_sync(~0u, n1, 2));
      n0 = fmaxf(n0, m0); n1 = fmaxf(n1, m1);
      const float z0 = n0 == -INFINITY ? 0.f : n0, z1 = n1 == -INFINITY ? 0.f : n1;
      const float c0 = ex2(m0 - z0), c1 = ex2(m1 - z1);
      m0 = n0; m1 = n1;
#pragma unroll
      for (int nt = 0; nt < 2; nt++) {
        s[nt][0] = ex2(s[nt][0] - z0); s[nt][1] = ex2(s[nt][1] - z0);
        s[nt][2] = ex2(s[nt][2] - z1); s[nt][3] = ex2(s[nt][3] - z1);
      }
      l0 = l0 * c0 + s[0][0] + s[0][1] + s[1][0] + s[1][1];
      l1 = l1 * c1 + s[0][2] + s[0][3] + s[1][2] + s[1][3];
      uint32_t pa[4] = {pack(s[0][0], s[0][1]), pack(s[0][2], s[0][3]), pack(s[1][0], s[1][1]), pack(s[1][2], s[1][3])};
      const uint16_t* vr = vp + (size_t)(key0 + 2 * q) * DH;
#pragma unroll
      for (int n = 0; n < 16; n++) {
        if ((n & 3) == 0) __syncwarp();
        o[n][0] *= c0; o[n][1] *= c0; o[n][2] *= c1; o[n][3] *= c1;
        mma16816(o[n], pa, vr[8 * n] | ((uint32_t)vr[8 * n + DH] << 16), vr[8 * n + 8 * DH] | ((uint32_t)vr[8 * n + 9 * DH] << 16));
      }
    }
    l0 += __shfl_xor_sync(~0u, l0, 1); l1 += __shfl_xor_sync(~0u, l1, 1);
    l0 += __shfl_xor_sync(~0u, l0, 2); l1 += __shfl_xor_sync(~0u, l1, 2);
    const float i0 = 1.f / l0, i1 = 1.f / l1;
    __nv_bfloat16* oc0 = P.o + o_idx(h * DH + 2 * q, o_pos(b, wg, r0));
    __nv_bfloat16* oc1 = P.o + o_idx(h * DH + 2 * q, o_pos(b, wg, min(r1, 119)));
#pragma unroll
    for (int n = 0; n < 16; n++) {
      oc0[8 * n * NROWS] = __float2bfloat16(o[n][0] * i0);
      oc0[8 * n * NROWS + 32] = __float2bfloat16(o[n][1] * i0);
      if (r1 < 120) {
        oc1[8 * n * NROWS] = __float2bfloat16(o[n][2] * i1);
        oc1[8 * n * NROWS + 32] = __float2bfloat16(o[n][3] * i1);
      }
    }
  }
}

__device__ __forceinline__ int bk(int ks) { return B_ORDER && ks < 48 ? 32 - (ks & 48) + (ks & 15) : ks; }
__device__ __forceinline__ uint32_t x_slot(uint32_t wg, uint32_t j) { return j < 2 ? (2 * wg + j) * XB : (2 * j + wg) * XB; }
__device__ __forceinline__ int row_block(int t) { return t >= 44 ? (t >> 2) - 11 : (t >> 2) + 4; }
__device__ __forceinline__ int unit_batch(int u) { return (u & 63) >> 2; }
__device__ __forceinline__ int unit_head(int u, int rank) { return (u >> 6) * 8 + (u & 3) * 2 + rank; }

template <int NCL>
__global__ void __cluster_dims__(2, 1, 1) __launch_bounds__(384, 1)
fused_attn_kernel(const __grid_constant__ CUtensorMap tm_x, const __grid_constant__ CUtensorMap tm_wq,
                  const __grid_constant__ CUtensorMap tm_k, const __grid_constant__ CUtensorMap tm_v,
                  const __grid_constant__ CUtensorMap tm_o, const __grid_constant__ CUtensorMap tm_wo,
                  const __grid_constant__ Params P) {
  extern __shared__ uint8_t smem_raw[];
  const uint32_t sb = ((uint32_t)__cvta_generic_to_shared(smem_raw) + 1023) & ~1023u;
  if (threadIdx.x == 0) TS(152);
  const int warp = __shfl_sync(~0u, threadIdx.x >> 5, 0);
  const int lane = threadIdx.x & 31;
  const int rank = blockIdx.x & 1, cl = blockIdx.x >> 1, ncl = NCL ? NCL : gridDim.x >> 1;

  const int nsingle = NCL == 66 ? 44 : NOTILES;
  auto role = [&]() {
    mbar_wait(sb + BAR_ROLE + 16, 0);
    int id;
    asm volatile("ld.shared.u32 %0, [%1];" : "=r"(id) : "r"(sb + BAR_ROLE + 8) : "memory");
    return id;
  };

  if (EARLY && threadIdx.x == 128) asm volatile("prefetch.tensormap [%0];" ::"l"(&tm_x) : "memory");
  if (threadIdx.x == 0) {
    if (EARLY) asm volatile("prefetch.tensormap [%0];" ::"l"(&tm_wq) : "memory");
    for (int i = 0; i < 6; i++) {
      mbar_init(sb + BAR_RFULL + 8 * i, 1); mbar_init(sb + BAR_REMPTY + 8 * i, 8);
      mbar_init(sb + BAR_BFULL + 8 * i, 1); mbar_init(sb + BAR_BEMPTY + 8 * i, 16);
    }
    for (int i = 0; i < 8; i++) mbar_init(sb + BAR_XFULL + 8 * i, 1);
    for (int i = 0; i < 4; i++) mbar_init(sb + BAR_XEMPTY + 8 * i, 8);
    for (int i = 0; i < 2; i++) { mbar_init(sb + BAR_STAGE + 8 * i, 4); mbar_init(sb + BAR_LSUM + 8 * i, 4); mbar_init(sb + BAR_INV + 8 * i, 1); }
    mbar_init(sb + BAR_ROLE, 1); mbar_init(sb + BAR_ROLE + 16, 1);
    asm volatile("fence.mbarrier_init.release.cluster;" ::: "memory");
  }
  __syncwarp();
  asm volatile("barrier.cluster.arrive.relaxed.aligned;" ::: "memory");
  auto first_w = [&](int s) {
    mbar_expect(sb + BAR_RFULL + 8 * s, RING_BYTES);
    tma3d(sb + s * RING_BYTES, &tm_wq, 0, s * 64, 2 * unit_head(cl, rank), sb + BAR_RFULL + 8 * s);
  };
  if (EARLY && threadIdx.x == 0) first_w(0);
  __syncwarp();
  asm volatile("barrier.cluster.wait.aligned;" ::: "memory");
  if (EARLY && threadIdx.x == 128) {
#pragma unroll 1
    for (int s = 0; s < EARLY_X; s++) {
      const uint32_t fb = sb + BAR_XFULL + 32 * rank + 8 * s;
      mbar_expect(fb, XB);
      mbar_expect_cl(mapa(fb, rank ^ 1), XB);
      tma2d_mc(sb + OFF_Q + x_slot(rank, s), &tm_x, s * 64, unit_batch(cl) * SQ + rank * 120, fb);
      if (s + 1 < EARLY_W) first_w(s + 1);
    }
  }
  __syncwarp();
  if (threadIdx.x == 0) TS(153);

  if (warp >= 8) {
    asm volatile("setmaxnreg.dec.sync.aligned.u32 24;");
    if (warp == 8) {
      uint64_t pol;
      asm volatile("createpolicy.fractional.L2::evict_first.b64 %0, 1.0;" : "=l"(pol));
      Ring r;
      if (EARLY) r.slot = EARLY_W;
      auto load = [&](const CUtensorMap* m, int c1, int c2, bool ef) {
        mbar_wait(sb + BAR_REMPTY + 8 * r.slot, r.phase ^ 1);
        if (lane == 0) {
          mbar_expect(sb + BAR_RFULL + 8 * r.slot, RING_BYTES);
          if (ef) tma3d_hint(sb + r.slot * RING_BYTES, m, 0, c1, c2, sb + BAR_RFULL + 8 * r.slot, pol);
          else tma3d(sb + r.slot * RING_BYTES, m, 0, c1, c2, sb + BAR_RFULL + 8 * r.slot);
        }
        r.next();
      };
      const int rot = ROT * (blockIdx.x * 5 + (blockIdx.x >> 4));
      auto pause = [&](int u0) {
        if (PAUSE_NS && NCL == 66 && u0 == PAUSE_AT * 66) {
          const int id = role();
          if (id >= 44 && id < 58) {
            unsigned t0, t1;
            asm volatile("mov.u32 %0, %globaltimer_lo;" : "=r"(t0));
            do { __nanosleep(200); asm volatile("mov.u32 %0, %globaltimer_lo;" : "=r"(t1)); } while (t1 - t0 < PAUSE_NS + (id - 44) * PAUSE_SPREAD);
          }
        }
      };
      for (int u0 = 0;; u0 += ncl) {
        const int u = __shfl_sync(~0u, (u0 >= 3 * ncl ? role() : cl) + u0, 0);
        if (u >= NUNITS) break;
        if (PAUSE_J < 0) pause(u0);
        const int h = unit_head(u, rank);
        const int krow = (unit_batch(u) * NH + h) * SK;
#pragma unroll 1
        for (int s = EARLY && u0 == 0 ? EARLY_W : 0; s < 10; s++) {
          if (u0 == 0 && s == 0 && lane == 0) TS(154);
          load(&tm_wq, s * 64, 2 * h, false);
          if (u0 == 0 && s == 0 && lane == 0) TS(155);
          const int sp = u0 == 0 ? s - PF_HOLD : s;
          if (sp >= 0 && sp < PF_N && lane == 0) l2_prefetch(P.v + (size_t)(krow + ((PF_J0 + sp * PF_STEP + rot) & 15) * 64) * DH, 16384);
        }
#pragma unroll 1
        for (int j = 0; j <= 16; j++) {
          if (j == PAUSE_J) pause(u0);
          if (j < 16) load(&tm_k, krow + ((j + rot) & 15) * 64, 0, true);
          if (j == 1 + DPRO) load(&tm_v, krow + (rot & 15) * 64, 0, true);
          if (j > 1) load(&tm_v, krow + ((j - 1 + rot) & 15) * 64, 0, true);
        }
      }
      const int id = __shfl_sync(~0u, role(), 0);
      const bool dbl = NCL == 66 && id >= 58;
      for (int t = dbl ? 2 * id - 72 : id; t < (dbl ? NOTILES : nsingle); t += ncl) {
        const int row0 = row_block(t) * 256 + rank * 128;
        const int b0 = (row0 & ~31) / SQ, b1 = (row0 + 127) / SQ;
#pragma unroll 1
        for (int ks = 0; ks < 64; ks++) {
          if (dbl ? (ks & 15) == 0 : ks == 0 || ks == 48) {
            const unsigned* c = &g_cnt[((lane & 1 ? b1 : b0) * 4 + (ks || dbl ? ks >> 4 : min(lane >> 1, 2))) * 8];
            unsigned v, n = 0;
            do {
              asm volatile("ld.acquire.gpu.global.u32 %0, [%1];" : "=r"(v) : "l"(c) : "memory");
              if (++n > (1u << 26)) __trap();
            } while (v < 16);
            __syncwarp();
            asm volatile("fence.proxy.async.global;" ::: "memory");
          }
          mbar_wait(sb + BAR_REMPTY + 8 * r.slot, r.phase ^ 1);
          if (lane == 0) {
            mbar_expect(sb + BAR_RFULL + 8 * r.slot, RING_BYTES);
            asm volatile("cp.async.bulk.tensor.4d.shared::cluster.global.mbarrier::complete_tx::bytes.L2::cache_hint [%0], [%1, {%3, %3, %4, %5}], [%2], %6;"
                         ::"r"(sb + r.slot * RING_BYTES), "l"(&tm_o), "r"(sb + BAR_RFULL + 8 * r.slot), "r"(0), "r"((dbl ? ks : bk(ks)) * 8), "r"(row0 >> 6), "l"(pol) : "memory");
          }
          r.next();
        }
      }
      if (lane == 0 && atomicAdd(&g_cnt[64 * 8], 1) == gridDim.x - 1) {
        for (int i = 0; i < 67; i++) g_cnt[i * 8] = 0;
      }
    } else if (warp == 9) {
      if (lane == 0) {
        uint32_t it = 0;
        for (;; it++) {
          const int u = (it >= 3 ? role() : cl) + it * ncl;
          if (u >= NUNITS) break;
          const int row = unit_batch(u) * SQ + rank * 120;
#pragma unroll 1
          for (int s = EARLY && it == 0 ? EARLY_X : 0; s < 10; s++) {
            const uint32_t j = s & 3, par = ((s >> 2) + (j < 2 ? it : 0)) & 1;
            mbar_wait(sb + BAR_XEMPTY + 8 * j, par ^ 1);
            const uint32_t fb = sb + BAR_XFULL + 32 * rank + 8 * j;
            mbar_expect(fb, XB);
            mbar_expect_cl(mapa(fb, rank ^ 1), XB);
            tma2d_mc(sb + OFF_Q + x_slot(rank, j), &tm_x, s * 64, row, fb);
          }
        }
        const int id = role();
        const bool dbl = NCL == 66 && id >= 58;
        uint32_t slot = rank, phase = 0;
        if (WO_PF0 && dbl)
          asm volatile("cp.async.bulk.prefetch.tensor.3d.L2.global [%0, {%1, %2, %3}];" ::"l"(&tm_wo), "r"(0), "r"((2 + ((id >> 1) & 3)) * 64), "r"(((2 * id - 72 + rank) & 3) * 5) : "memory");
        for (int t = dbl ? 2 * id - 72 + rank : id; t < (dbl ? NOTILES : nsingle); t += ncl) {
#pragma unroll 1
          for (int ks = dbl ? 0 : rank; ks < 64; ks += dbl ? 1 : 2) {
            mbar_wait(sb + BAR_BEMPTY + 8 * slot, phase);
            const uint32_t fb = sb + BAR_BFULL + 8 * slot;
            mbar_expect(fb, BB);
            mbar_expect_cl(mapa(fb, rank ^ 1), BB);
            tma3d_mc(sb + OFF_Q + slot * BB, &tm_wo, 0, (dbl ? ks : bk(ks)) * 64, (t & 3) * 5, fb);
            if (WO_PF && dbl && ks + WO_PF < 64 && (ks & 3) == ((id >> 1) & 3))
              asm volatile("cp.async.bulk.prefetch.tensor.3d.L2.global [%0, {%1, %2, %3}];" ::"l"(&tm_wo), "r"(0), "r"((ks + WO_PF) * 64), "r"((t & 3) * 5) : "memory");
            slot += 2;
            if (slot >= 6) { slot -= 6; phase ^= 1; }
          }
        }
      }
    } else {
      const int wg = warp - 10;
      {
        mbar_wait(sb + BAR_RFULL, 0);
        const __nv_bfloat16* xs = P.x + (size_t)(unit_batch(cl) * SQ + ((cl & 3) * 2 + rank) * 30 + min(lane, 29)) * DM + 256 + wg * 64;
#pragma unroll
        for (int i = 0; i < 3; i++) asm volatile("prefetch.global.L2 [%0];" ::"l"(xs + i * 128));
        if (lane < 16) asm volatile("prefetch.global.L2 [%0];" ::"l"(P.wq + (size_t)(384 + unit_batch(cl) * 16 + lane) * HD + unit_head(cl, rank) * DH + wg * 64));
      }
      auto take_role = [&]() {
          if (wg == 0 && rank == 0 && lane == 0) {
            int id = cl;
            if (NCL == 66) {
              uint32_t smid;
              asm("mov.u32 %0, %smid;" : "=r"(smid));
              id = smid >= SMID_TOP ? 65 - atomicAdd(&g_cnt[65 * 8], 1) : atomicAdd(&g_cnt[66 * 8], 1);
            }
    #pragma unroll
            for (int c = 0; c < 2; c++) {
              const uint32_t a = mapa(sb + BAR_ROLE, c);
              asm volatile("st.shared::cluster.u32 [%0 + 8], %1;\nmbarrier.arrive.release.cluster.shared::cluster.b64 _, [%0];" ::"r"(a), "r"(id) : "memory");
            }
          }
          if (wg == 0 && lane == 0) {
            mbar_wait_cl(sb + BAR_ROLE, 0);
            mbar_arrive(sb + BAR_ROLE + 16);
          }
      };
      if (ROLE_AT < 0) { take_role(); __syncwarp(); }
      for (uint32_t it = 0;; it++) {
        const int u = __shfl_sync(~0u, (it >= 3 ? role() : cl) + it * ncl, 0);
        if (u >= NUNITS) break;
        mbar_wait(sb + BAR_LSUM + 8 * wg, it & 1);
        float l4[4], v[4];
        const uint32_t a = sb + OFF_L2 + wg * 2048 + lane * 16;
        asm volatile("ld.shared.v4.f32 {%0, %1, %2, %3}, [%4];" : "=f"(l4[0]), "=f"(l4[1]), "=f"(l4[2]), "=f"(l4[3]) : "r"(a) : "memory");
#pragma unroll
        for (int g = 1; g < 4; g++) {
          asm volatile("ld.shared.v4.f32 {%0, %1, %2, %3}, [%4];" : "=f"(v[0]), "=f"(v[1]), "=f"(v[2]), "=f"(v[3]) : "r"(a + g * 512) : "memory");
#pragma unroll
          for (int c = 0; c < 4; c++) l4[c] += v[c];
        }
#pragma unroll
        for (int c = 0; c < 4; c++) {
          float inv;
          asm("rcp.approx.ftz.f32 %0, %1;" : "=f"(inv) : "f"(l4[c]));
          l4[c] = l4[c] >= L_MIN && l4[c] <= L_MAX ? inv : __uint_as_float(0x7FFFFFFFu);
        }
        const uint32_t h0 = pack(l4[0], l4[1]), h1 = pack(l4[2], l4[3]);
        const uint32_t e0 = pack(l4[0] - __uint_as_float(h0 << 16), l4[1] - __uint_as_float(h0 & 0xFFFF0000u));
        const uint32_t e1 = pack(l4[2] - __uint_as_float(h1 << 16), l4[3] - __uint_as_float(h1 & 0xFFFF0000u));
        asm volatile("st.shared.v4.u32 [%0], {%1, %2, %3, %4};" ::"r"(sb + OFF_INV + wg * 640 + (lane & 3) * 144 + (lane >> 2) * 16), "r"(h0), "r"(e0), "r"(h1), "r"(e1) : "memory");
        __syncwarp();
        if (lane == 0) {
          mbar_arrive(sb + BAR_INV + 8 * wg);
          if ((int)it == ROLE_AT) {
            take_role();
          }
          mbar_wait(sb + BAR_STAGE + 8 * wg, it & 1);
          __threadfence();
          asm volatile("red.relaxed.gpu.global.add.u32 [%0], 1;" ::"l"(&g_cnt[(unit_batch(u) * 4 + (u >> 6)) * 8]) : "memory");
        }
        __syncwarp();
      }
    }
  } else {
    asm volatile("setmaxnreg.inc.sync.aligned.u32 240;");
    const int wg = warp >> 2, w = warp & 3;
    const uint32_t qreg = sb + OFF_Q + wg * 2 * XB, preg = sb + OFF_P + (2 + wg) * XB;
    const uint32_t st_off = ((lane >> 4) * 8 + (lane & 7)) * 128 + (((2 * w + ((lane >> 3) & 1)) ^ (lane & 7)) << 4);
    const uint32_t xempty = mapa(sb + BAR_XEMPTY, wg);
    Ring r;
    uint32_t it = 0;
    const uint32_t qd = (qreg & 0x3FFFF) >> 4, pd = (preg & 0x3FFFF) >> 4;
    auto ring_addr = [&]() { return ((sb & 0x3FFFF) + r.slot * RING_BYTES) >> 4; };
    auto ring_wait = [&]() { mbar_wait(sb + BAR_RFULL + 8 * r.slot, r.phase); };
    auto release = [&](uint32_t slot) { warp_arrive(sb + BAR_REMPTY + 8 * slot); };
    auto turn_wait = [&]() {
      if (wg == 0) asm volatile("bar.sync 3, 256;" ::: "memory");
      else asm volatile("bar.sync 4, 256;" ::: "memory");
    };
    auto turn_pass = [&]() {
      if (wg == 0) asm volatile("bar.arrive 4, 256;" ::: "memory");
      else asm volatile("bar.arrive 3, 256;" ::: "memory");
    };

    uint32_t chk = 0;
    auto load_inv = [&](uint32_t (&iv)[30], uint32_t parity) {
      const int lane = fresh_tid() & 31;
      mbar_wait(sb + BAR_INV + 8 * wg, parity);
      chk = 0;
#pragma unroll
      for (int j = 0; j < 7; j++)
        asm volatile("ld.shared.v4.u32 {%0, %1, %2, %3}, [%4];" : "=r"(iv[4 * j]), "=r"(iv[4 * j + 1]), "=r"(iv[4 * j + 2]), "=r"(iv[4 * j + 3])
                     : "r"(sb + OFF_INV + wg * 640 + (lane & 3) * 144 + j * 16) : "memory");
      asm volatile("ld.shared.v2.u32 {%0, %1}, [%2];" : "=r"(iv[28]), "=r"(iv[29]) : "r"(sb + OFF_INV + wg * 640 + (lane & 3) * 144 + 112) : "memory");
    };
    auto norm = [&](uint32_t (&n)[8], const uint32_t (&po)[60], const uint32_t (&iv)[30], auto part) {
      constexpr int k = decltype(part)::value >> 1, j0 = (decltype(part)::value & 1) * 8;
#pragma unroll
      for (int j = 0; j < 8; j++)
        n[j] = j0 + j < 15 ? hfma2(po[15 * k + (j0 + j) % 15], iv[2 * ((j0 + j) % 15)], hfma2(po[15 * k + (j0 + j) % 15], iv[2 * ((j0 + j) % 15) + 1], 0x80008000u)) : 0x3F803F80u;
#pragma unroll
      for (int j = 0; j < 8; j += 2) chk = hfma2(n[j], n[j + 1], chk);
    };
    int od1, od2;
    auto store = [&](const uint32_t (&n)[8], const char* optr, auto part) {
      constexpr int k = decltype(part)::value >> 1, off = (8 * (k & 1) + 64 * (k >> 1)) * NROWS * 2;
      if ((decltype(part)::value & 1) == 0)
        asm volatile(
            "{\n.reg .pred p;\nsetp.ne.u64 p, %8, 0;\n"
            "@p st.global.v4.u32 [%8 + %9], {%0, %1, %2, %3};\n@p st.global.v4.u32 [%8 + %9 + 512], {%4, %5, %6, %7};\n}\n"
            ::"r"(n[0]), "r"(n[1]), "r"(n[2]), "r"(n[3]), "r"(n[4]), "r"(n[5]), "r"(n[6]), "r"(n[7]), "l"(optr), "n"(off) : "memory");
      else
        asm volatile(
            "{\n.reg .pred p;\n.reg .b64 b, c;\nsetp.ne.u64 p, %7, 0;\nmad.wide.s32 b, %9, 1, %7;\nmad.wide.s32 c, %10, 1, %7;\n"
            "@p st.global.v4.u32 [%7 + %8 + 1024], {%0, %1, %2, %3};\n@p st.global.v2.u32 [b + %8], {%4, %5};\n@p st.global.u32 [c + %8], %6;\n}\n"
            ::"r"(n[0]), "r"(n[1]), "r"(n[2]), "r"(n[3]), "r"(n[4]), "r"(n[5]), "r"(n[6]), "l"(optr), "n"(off), "r"(od1), "r"(od2) : "memory");
    };
    auto put = [&](const uint32_t (&po)[60], const uint32_t (&iv)[30], const char* optr, auto part) {
      uint32_t n[8];
      norm(n, po, iv, part);
      store(n, optr, part);
    };
    auto out_ptr = [&](int u) {
      const int lane = fresh_tid() & 31;
      const int k = unit_head(u, rank) * DH + 16 * w + (lane >> 2), b = unit_batch(u), q = lane & 3;
      const uint32_t i0 = o_idx(k, o_pos(b, wg, 2 * q));
      od1 = 2 * (int)(o_idx(k, o_pos(b, wg, 96 + 2 * q)) - i0);
      od2 = 2 * (int)(o_idx(k, o_pos(b, wg, 112 + 2 * q)) - i0);
      return reinterpret_cast<const char*>(P.o + i0);
    };
    auto unsafe = [&](bool valid) {
      const bool b = valid && ((chk & 0x7F80u) == 0x7F80u || (chk & 0x7F800000u) == 0x7F800000u);
      return __any_sync(~0u, bar_red_or(wg, b));
    };
    auto publish = [&]() { __syncwarp(); warp_arrive(sb + BAR_STAGE + 8 * wg); };

    uint32_t po[60];
#pragma unroll
    for (int i = 0; i < 60; i++) po[i] = 0;
    int id = 0;
    bool more;
    do {
      float o0[60], o1[60];
      uint32_t prev = 0;
      auto qstep = [&](int s, int acc) {
        const uint32_t j = s & 3, par = ((s >> 2) + (j < 2 ? it : 0)) & 1;
        TR(it * 160 + 3 * s);
        ring_wait();
        TR(it * 160 + 3 * s + 1);
        mbar_wait(sb + BAR_XFULL + 32 * wg + 8 * j, par);
        TR(it * 160 + 3 * s + 2);
        if (s >= ALT_FROM) turn_wait();
        wg_fence();
        mma_tn(o0, o1, ring_addr(), ((sb & 0x3FFFF) + OFF_Q + x_slot(wg, j)) >> 4, acc);
        wg_commit();
        if (s >= ALT_FROM || (s == ALT_FROM - 1 && wg == 1)) turn_pass();
        if (s > 0 && s <= EREL_FROM) {
          wg_wait<1>();
          release(prev);
          if (s <= 6) warp_arrive_cl(xempty + 8 * ((s - 1) & 3));
        }
        prev = r.slot;
        r.next();
      };
      auto qdone = [&](int s) {
        if (s >= EREL_FROM) {
          wg_wait<0>();
          release(prev);
          if (s <= 5) warp_arrive_cl(xempty + 8 * (s & 3));
        }
      };
      qstep(0, 0);
      qstep(1, 1);
      const int up = (it > 3 ? id : cl) + ((int)it - 1) * ncl;
      const char* optr = out_ptr(up);
      if (it == 0) optr = nullptr;
      uint32_t n7[8];
      {
        uint32_t iv[30];
        load_inv(iv, (it + 1) & 1); put(po, iv, optr, IC<0>());
        qstep(2, 1); put(po, iv, optr, IC<1>()); qdone(2);
        qstep(3, 1); put(po, iv, optr, IC<2>()); qdone(3);
        qstep(4, 1); put(po, iv, optr, IC<3>()); qdone(4);
        qstep(5, 1); put(po, iv, optr, IC<4>()); qdone(5);
        qstep(6, 1); put(po, iv, optr, IC<5>()); qdone(6);
        qstep(7, 1); put(po, iv, optr, IC<6>());
        norm(n7, po, iv, IC<7>());
        qdone(7);
        if (LATE_AT == 3 || (LATE_AT == 5 && wg == 1)) store(n7, optr, IC<7>());
      }
      TR(it * 160 + 24);
      const uint32_t a8 = ring_addr(), slot8 = r.slot;
      ring_wait();
      r.next();
      TR(it * 160 + 25);
      mbar_wait(sb + BAR_XFULL + 32 * wg, it & 1);
      TR(it * 160 + 26);
      auto wait9 = [&]() {
        TR(it * 160 + 27);
        ring_wait();
        TR(it * 160 + 28);
        mbar_wait(sb + BAR_XFULL + 32 * wg + 8, it & 1);
        TR(it * 160 + 29);
      };
      if (PRE9) wait9();
      turn_wait();
      wg_fence();
      mma_tn(o0, o1, a8, qd, 1);
      wg_commit();
      if (!PRE9) { wait9(); wg_fence(); }
      mma_tn_split(o0, o1, ring_addr(), qd + (XB >> 4));
      turn_pass();
      wg_wait<2>();
      if (EREL_FROM > 7) release(prev);
      release(slot8);
      if (LATE_AT == 4 || (LATE_AT == 5 && wg == 0)) store(n7, optr, IC<7>());
      auto put_q = [&](const float (&o)[60], uint32_t dst) {
        bar_sync(wg);
#pragma unroll
        for (int j = 0; j < 14; j += 2)
          stsm4t(dst + j * 1024, pack(o[4 * j] * QSCALE, o[4 * j + 1] * QSCALE), pack(o[4 * j + 2] * QSCALE, o[4 * j + 3] * QSCALE),
                 pack(o[4 * j + 4] * QSCALE, o[4 * j + 5] * QSCALE), pack(o[4 * j + 6] * QSCALE, o[4 * j + 7] * QSCALE));
        stsm2t(dst + 14 * 1024, pack(o[56] * QSCALE, o[57] * QSCALE), pack(o[58] * QSCALE, o[59] * QSCALE));
      };
      wg_wait<1>();
      reg_fence(o0);
      put_q(o0, qreg + st_off);
      wg_wait<0>();
      reg_fence(o1);
      release(r.slot);
      r.next();
      TR(it * 160 + 30);
      put_q(o1, qreg + XB + st_off);
      fence_async_smem();
      if (unsafe(it > 0)) {
        slow_path(P, unit_batch(up), unit_head(up, rank), wg, w, fresh_tid() & 31);
        optr = nullptr;
        if (!DPRO) {
#pragma unroll
          for (int i = 0; i < 60; i++) o0[i] = o1[i] = 0.f;
        }
      }
      TR(it * 160 + 32); TG(it * 160 + 142);

      float sc[60], l[30];
      uint32_t slot0 = r.slot;
      ring_wait();
      TR(it * 160 + 33);
      turn_wait();
      wg_fence();
      mma_qk(sc, ring_addr(), qd);
      wg_commit();
      r.next();
      uint32_t slot1 = r.slot;
      ring_wait();
      wg_fence();
      mma_qk(o1, ring_addr(), qd);
      wg_commit();
      r.next();
      turn_pass();
      if (LATE_AT == 0) store(n7, optr, IC<7>());
      wg_wait<1>();
      reg_fence(sc);
      TR(it * 160 + 35);
      release(slot0);
      exp_store<0, 15, true>(sc, l, preg + st_off);
      TR(it * 160 + 38); TG(it * 160 + 43);
      slot0 = r.slot;
      ring_wait();
      wg_fence();
      mma_qk(sc, ring_addr(), qd);
      wg_commit();
      r.next();
      wg_wait<1>();
      reg_fence(o1);
      TR(it * 160 + 41);
      release(slot1);
      exp_store<0, 15>(o1, l, preg - 2 * XB + st_off);
      fence_async_smem();
      bar_sync(wg);
      TR(it * 160 + 44);
      slot1 = r.slot;
      ring_wait();
      turn_wait();
      wg_fence();
      mma_tn(o0, o1, ring_addr(), pd, 0);
      wg_commit();
      r.next();
      ring_wait();
      wg_fence();
      mma_tn(o0, o1, ring_addr(), pd - (2 * XB >> 4), 1);
      wg_commit();
      turn_pass();
      if (LATE_AT == 1) store(n7, optr, IC<7>());
      if (it > 0) publish();
      if (it >= 2) id = __shfl_sync(~0u, role(), 0);
      wg_wait<1>();
      reg_fence(sc);
      release(slot0);
      release(slot1);
      bar_sync(wg);
      TR(it * 160 + 47);
      exp_store<0, VREL>(sc, l, preg + st_off);
      wg_wait<0>();
      reg_fence(o0); reg_fence(o1);
      release(r.slot);
      r.next();
      exp_store<VREL, 15>(sc, l, preg + st_off);
      fence_async_smem();
      bar_sync(wg);
      more = id + ((int)it + 1) * ncl < NUNITS;
      const bool gemm = id < nsingle || (NCL == 66 && id >= 58);
#pragma unroll 1
      for (int s = DPRO ? 3 : 1; s < 16; s++) {
        const uint32_t kslot = r.slot;
        TR(it * 160 + 32 + 6 * s); TG(it * 160 + 37 + 6 * s);
        if (s == 8) TRL(it * 160 + 139);
        ring_wait();
        TR(it * 160 + 33 + 6 * s);
        turn_wait();
        wg_fence();
        mma_qk(sc, ring_addr(), qd);
        wg_commit();
        r.next();
        TR(it * 160 + 36 + 6 * s);
        ring_wait();
        TR(it * 160 + 34 + 6 * s);
        wg_fence();
        mma_tn(o0, o1, ring_addr(), pd - ((s - 1) & 1) * (2 * XB >> 4), DPRO || s != 1);
        wg_commit();
        if (wg == 0 || s < 15) turn_pass();
        wg_wait<1>();
        reg_fence(sc);
        TR(it * 160 + 35 + 6 * s);
        release(kslot);
        if (s == 15) {
          if (more) { warp_arrive_cl(xempty); warp_arrive_cl(xempty + 8); }
          else if (gemm) for (int i = 0; i < 3; i++) warp_arrive_cl(mapa(sb + BAR_BEMPTY + 8 * i, i & 1));
        }
        exp_store<0, VREL>(sc, l, preg - (s & 1) * 2 * XB + st_off);
        wg_wait<0>();
        reg_fence(o0); reg_fence(o1);
        release(r.slot);
        r.next();
        exp_store<VREL, 15>(sc, l, preg - (s & 1) * 2 * XB + st_off);
        fence_async_smem();
      }
      const uint32_t tid = fresh_tid();
      bar_sync(wg);
      TR(it * 160 + 128);
      ring_wait();
      wg_fence();
      mma_tn_split(o0, o1, ring_addr(), pd - (2 * XB >> 4));
      {
        float a[16], b[8], c[4];
        const bool b4 = tid & 16, b3 = tid & 8, b2 = tid & 4;
#pragma unroll
        for (int i = 0; i < 16; i++) {
          const float hi = i < 14 ? l[(16 + i) % 30] : 1.f;
          a[i] = (b4 ? hi : l[i]) + __shfl_xor_sync(~0u, b4 ? l[i] : hi, 16);
        }
#pragma unroll
        for (int i = 0; i < 8; i++) b[i] = (b3 ? a[8 + i] : a[i]) + __shfl_xor_sync(~0u, b3 ? a[i] : a[8 + i], 8);
#pragma unroll
        for (int i = 0; i < 4; i++) c[i] = (b2 ? b[4 + i] : b[i]) + __shfl_xor_sync(~0u, b2 ? b[i] : b[4 + i], 4);
        asm volatile("st.shared.v4.f32 [%0], {%1, %2, %3, %4};" ::"r"(sb + OFF_L2 + tid * 16), "f"(c[0]), "f"(c[1]),
                     "f"(c[2]), "f"(c[3]) : "memory");
        __syncwarp();
        warp_arrive(sb + BAR_LSUM + 8 * wg);
      }
      TR(it * 160 + 132);
      TR(it * 160 + 133);
      wg_wait<1>();
      reg_fence(o0);
      TR(it * 160 + 134);
#pragma unroll
      for (int j = 0; j < 15; j++) { po[j] = pack(o0[4 * j], o0[4 * j + 1]); po[15 + j] = pack(o0[4 * j + 2], o0[4 * j + 3]); }
      wg_wait<0>();
      reg_fence(o1);
      release(r.slot);
      r.next();
      if (more) { warp_arrive_cl(xempty + 16); warp_arrive_cl(xempty + 24); }
      else if (gemm) for (int i = 3; i < 6; i++) warp_arrive_cl(mapa(sb + BAR_BEMPTY + 8 * i, i & 1));
      TR(it * 160 + 130);
#pragma unroll
      for (int j = 0; j < 15; j++) { po[30 + j] = pack(o1[4 * j], o1[4 * j + 1]); po[45 + j] = pack(o1[4 * j + 2], o1[4 * j + 3]); }
      TR(it * 160 + 131); TG(it * 160 + 143);
      it++;
    } while (more);
    const bool gemm = id < nsingle || (NCL == 66 && id >= 58);
    const int u = (it > 3 ? id : cl) + ((int)it - 1) * ncl;
    uint32_t pb[60];
#pragma unroll
    for (int i = 0; i < 60; i++) pb[i] = NCL != 66 ? po[i] ^ (gridDim.y - 1) : po[i];

    uint32_t bslot = 0, bphase = 0;
    auto out_tile = [&](const float (&acc)[80], int t) {
      const int lane = fresh_tid() & 31;
      const uint32_t st = sb + w * RING_BYTES + wg * 8192;
      const uint32_t sa = st + (lane & 15) * 336 + (lane >> 4) * 16;
#pragma unroll
      for (int j = 0; j < 20; j += 2)
        asm volatile("stmatrix.sync.aligned.m8n8.x4.shared.b16 [%0], {%1,%2,%3,%4};" ::"r"(sa + j * 16), "r"(pack(acc[4 * j], acc[4 * j + 1])),
                     "r"(pack(acc[4 * j + 2], acc[4 * j + 3])), "r"(pack(acc[4 * j + 4], acc[4 * j + 5])), "r"(pack(acc[4 * j + 6], acc[4 * j + 7])) : "memory");
      fence_async_smem();
      __syncwarp();
      if (lane < 16) {
        __nv_bfloat16* dst = P.out + (size_t)o_row(row_block(t) * 256 + rank * 128 + wg * 64 + w * 16 + lane) * DM + (t & 3) * 160;
        asm volatile("cp.async.bulk.global.shared::cta.bulk_group [%0], [%1], 320;" ::"l"(dst), "r"(st + lane * 336) : "memory");
        asm volatile("cp.async.bulk.commit_group;" ::: "memory");
        asm volatile("cp.async.bulk.wait_group.read 0;" ::: "memory");
      }
      __syncwarp();
    };
    for (int t = id; t == id || (NCL != 66 && t < nsingle); t += ncl) {
      float acc[80];
      uint32_t prev = 0, bprev = 0;
      const bool tile = t < nsingle;
      const bool last = NCL == 66 || t + ncl >= nsingle;
      auto bstep = [&](int ks, int accf) {
        if (!(ks & 3)) TR(640 + ks / 2); if ((ks & 7) == 0) TG(144 + (ks >> 3));
        ring_wait();
        mbar_wait(sb + BAR_BFULL + 8 * bslot, bphase);
        if (!(ks & 3)) TR(641 + ks / 2);
        wg_fence();
        const uint32_t a = ring_addr() + wg * 512, bd = (((sb & 0x3FFFF) + OFF_Q + bslot * BB) >> 4) | ((4096u >> 4) << 16);
#pragma unroll
        for (int k = 0; k < 4; k++) wgmma_n160<1, 1>(acc, a + LBO64A + k * 128, HI64A, bd + k * 64, HI64, k == 0 ? accf : 1);
        wg_commit();
        if (ks > 0) {
          wg_wait<1>();
          release(prev);
          if (ks < 59 || !last) warp_arrive_cl(mapa(sb + BAR_BEMPTY + 8 * bprev, bprev & 1));
        }
        prev = r.slot; bprev = bslot;
        r.next();
        if (++bslot == 6) { bslot = 0; bphase ^= 1; }
      };
      const char* optr;
      uint32_t iv[30], n3[8], n4[8], n5[8], n6[8], n7[8];
      if (tile) {
        bstep(0, 0);
        bstep(1, 1);
        optr = out_ptr(u);
        if (t != id) optr = nullptr;
        load_inv(iv, (it + 1) & 1);
#pragma unroll 1
        for (int ks = 2; ks < 17; ks++) {
          bstep(ks, 1);
          switch (ks) {
            case 2: put(pb, iv, optr, IC<0>()); break;
            case 4: put(pb, iv, optr, IC<1>()); break;
            case 6: put(pb, iv, optr, IC<2>()); break;
            case 8: put(pb, iv, optr, IC<3>()); break;
            case 10: put(pb, iv, optr, IC<4>()); break;
            case 12: put(pb, iv, optr, IC<5>()); break;
            case 14: put(pb, iv, optr, IC<6>()); break;
            case 16: put(pb, iv, optr, IC<7>()); break;
            default: break;
          }
        }
        wg_wait<0>();
        reg_fence(acc);
#pragma unroll
        for (int i = 0; i < 8; i++) n3[i] = n4[i] = n5[i] = n6[i] = n7[i] = 0;
      } else {
        Ring r2 = r;
        auto first = [&](int ks) {
          if (ks == 0) { TR(640); TG(144); }
          if (gemm) { mbar_wait(sb + BAR_RFULL + 8 * r2.slot, r2.phase); mbar_wait(sb + BAR_BFULL + 16 * ks, 0); }
          wg_fence();
          const uint32_t a = (((sb & 0x3FFFF) + r2.slot * RING_BYTES) >> 4) + wg * 512;
          const uint32_t bd = (((sb & 0x3FFFF) + OFF_Q + 2 * ks * BB) >> 4) | ((4096u >> 4) << 16);
#pragma unroll
          for (int k = 0; k < 4; k++) wgmma_n160<1, 1>(acc, a + LBO64A + k * 128, HI64A, bd + k * 64, HI64, k + ks != 0);
          wg_commit();
          if (ks > 0) {
            wg_wait<1>();
            if (gemm) warp_arrive_cl(mapa(sb + BAR_BEMPTY + 16 * (ks - 1), 0));
          }
          r2.next();
        };
        first(0);
        optr = out_ptr(u);
        load_inv(iv, (it + 1) & 1);
        put(pb, iv, optr, IC<0>());
        first(1);
        put(pb, iv, optr, IC<1>());
        norm(n3, pb, iv, IC<3>()); norm(n4, pb, iv, IC<4>());
        first(2);
        put(pb, iv, optr, IC<2>());
        norm(n5, pb, iv, IC<5>()); norm(n6, pb, iv, IC<6>()); norm(n7, pb, iv, IC<7>());
        wg_wait<0>();
        reg_fence(acc);
      }
      if (unsafe(t == id)) {
        slow_path(P, unit_batch(u), unit_head(u, rank), wg, w, fresh_tid() & 31);
        optr = nullptr;
#pragma unroll
        for (int i = 0; i < 8; i++) n3[i] = n4[i] = n5[i] = n6[i] = n7[i] = 0;
      }
      if (tile && t == id) publish();
      if (!tile) {
        if (gemm) {
          float ac1[80];
          auto half = [&](float (&ac)[80], bool rel, int accf) {
            mbar_wait(sb + BAR_BFULL + 8 * bslot, bphase);
            wg_fence();
            const uint32_t a = ring_addr() + wg * 512, bd = (((sb & 0x3FFFF) + OFF_Q + bslot * BB) >> 4) | ((4096u >> 4) << 16);
#pragma unroll
            for (int k = 0; k < 4; k++) wgmma_n160<1, 1>(ac, a + LBO64A + k * 128, HI64A, bd + k * 64, HI64, k == 0 ? accf : 1);
            wg_commit();
            wg_wait<1>();
            if (rel) warp_arrive_cl(mapa(sb + BAR_BEMPTY + 8 * bprev, bprev & 1));
            bprev = bslot;
          };
          auto dstep = [&](int ks) {
            if (!(ks & 3)) TR(640 + ks / 2); if ((ks & 7) == 0) TG(144 + (ks >> 3));
            ring_wait();
            if (!(ks & 3)) TR(641 + ks / 2);
            half(acc, ks < 62, 1);
            release(prev);
            bslot++;
            half(ac1, ks < 61, 1);
            if (++bslot == 6) { bslot = 0; bphase ^= 1; }
            prev = r.slot; r.next();
          };
          bprev = 4; bslot = 1;
          half(ac1, true, 0);
          prev = r.slot; r.next(); bslot = 3;
          half(ac1, true, 1);
          release(prev); prev = r.slot; r.next(); bslot = 5;
          store(n3, optr, IC<3>());
          half(ac1, true, 1);
          release(prev); prev = r.slot; r.next(); bslot = 0; bphase = 1;
#pragma unroll 1
          for (int ks = 3; ks < 7; ks++) {
            dstep(ks);
            switch (ks) {
              case 3: store(n4, optr, IC<4>()); break;
              case 4: store(n5, optr, IC<5>()); break;
              case 5: store(n6, optr, IC<6>()); break;
              default: store(n7, optr, IC<7>()); break;
            }
          }
          publish();
#pragma unroll 1
          for (int ks = 7; ks < 64; ks++) {
            if (wg == 1 && ks == 62) turn_wait();
            dstep(ks);
          }
          if (wg == 0) turn_pass();
          wg_wait<0>();
          reg_fence(acc); reg_fence(ac1);
          TRL(158); TG(156);
          bar_sync(wg);
          out_tile(acc, 2 * id - 72);
          out_tile(ac1, 2 * id - 71);
        } else {
          store(n3, optr, IC<3>()); store(n4, optr, IC<4>()); store(n5, optr, IC<5>()); store(n6, optr, IC<6>()); store(n7, optr, IC<7>());
          publish();
        }
        break;
      }
#pragma unroll 1
      for (int ks = 17; ks < 64; ks++) {
        if (END_SKEW && wg == 1 && ks == 64 - END_SKEW) turn_wait();
        bstep(ks, 1);
      }
      if (END_SKEW && wg == 0) turn_pass();
      wg_wait<0>();
      reg_fence(acc);
      release(prev);
      if (!last) warp_arrive_cl(mapa(sb + BAR_BEMPTY + 8 * bprev, bprev & 1));
      TRL(158); TG(156);
      const int pos0 = row_block(t) * 256 + rank * 128 + wg * 64 + w * 16;
      if (last) {
        bar_sync(wg);
        out_tile(acc, t);
      } else {
        const int lane = fresh_tid() & 31;
        __nv_bfloat16* op0 = P.out + (size_t)o_row(pos0 + (lane >> 2)) * DM + (t & 3) * 160 + (lane & 3) * 2;
        __nv_bfloat16* op1 = P.out + (size_t)o_row(pos0 + (lane >> 2) + 8) * DM + (t & 3) * 160 + (lane & 3) * 2;
#pragma unroll
        for (int j = 0; j < 20; j++) {
          *reinterpret_cast<uint32_t*>(op0 + j * 8) = pack(acc[4 * j], acc[4 * j + 1]);
          *reinterpret_cast<uint32_t*>(op1 + j * 8) = pack(acc[4 * j + 2], acc[4 * j + 3]);
        }
      }
#pragma unroll
      for (int i = 0; i < 60; i++) pb[i] = 0;
    }
    TRL(159);
  }
}

typedef CUresult (*EncodeFn)(CUtensorMap*, CUtensorMapDataType, cuuint32_t, void*, const cuuint64_t*, const cuuint64_t*,
                             const cuuint32_t*, const cuuint32_t*, CUtensorMapInterleave, CUtensorMapSwizzle,
                             CUtensorMapL2promotion, CUtensorMapFloatOOBfill);

void make_map(EncodeFn enc, CUtensorMap* m, const void* p, int rank, const cuuint64_t* dims, const cuuint64_t* strides,
              const cuuint32_t* box, CUtensorMapSwizzle sw, CUtensorMapL2promotion promo) {
  cuuint32_t es[4] = {1, 1, 1, 1};
  enc(m, CU_TENSOR_MAP_DATA_TYPE_BFLOAT16, rank, const_cast<void*>(p), dims, strides, box, es, CU_TENSOR_MAP_INTERLEAVE_NONE, sw,
      promo, CU_TENSOR_MAP_FLOAT_OOB_FILL_NONE);
}

}

extern "C" void kernel_launch(void* const* d_in, const int* in_sizes, int n_in, void* d_out, int out_size) {
  static EncodeFn enc = nullptr;
  static int nclusters = 0;
  static void* o_ptr = nullptr;
  if (!enc) {
    cudaDriverEntryPointQueryResult qr;
    cudaGetDriverEntryPoint("cuTensorMapEncodeTiled", (void**)&enc, cudaEnableDefault, &qr);
    cudaFuncSetAttribute(fused_attn_kernel<66>, cudaFuncAttributeMaxDynamicSharedMemorySize, SMEM_BYTES);
    cudaFuncSetAttribute(fused_attn_kernel<0>, cudaFuncAttributeMaxDynamicSharedMemorySize, SMEM_BYTES);
    cudaGetSymbolAddress(&o_ptr, g_o);
    cudaLaunchConfig_t cfg = {};
    cfg.gridDim = 128; cfg.blockDim = 384; cfg.dynamicSmemBytes = SMEM_BYTES;
    cudaLaunchAttribute at; at.id = cudaLaunchAttributeClusterDimension;
    at.val.clusterDim.x = 2; at.val.clusterDim.y = 1; at.val.clusterDim.z = 1;
    cfg.attrs = &at; cfg.numAttrs = 1;
    int n = 0;
    cudaOccupancyMaxActiveClusters(&n, fused_attn_kernel<66>, &cfg);
    nclusters = n >= 66 ? MAXCL : (n >= 64 || n <= 0 ? 64 : n);
  }
  const __nv_bfloat16* x = (const __nv_bfloat16*)d_in[0];
  const __nv_bfloat16* k = (const __nv_bfloat16*)d_in[1];
  const __nv_bfloat16* v = (const __nv_bfloat16*)d_in[2];
  const __nv_bfloat16* wq = (const __nv_bfloat16*)d_in[3];
  const __nv_bfloat16* wo = (const __nv_bfloat16*)d_in[4];
  CUtensorMap tm_x, tm_wq, tm_k, tm_v, tm_o, tm_wo;
  const auto S128 = CU_TENSOR_MAP_SWIZZLE_128B;
  const auto P128 = CU_TENSOR_MAP_L2_PROMOTION_L2_128B, P256 = CU_TENSOR_MAP_L2_PROMOTION_L2_256B;
  { cuuint64_t d[2] = {DM, NB * SQ}, s[1] = {DM * 2}; cuuint32_t b[2] = {64, 120}; make_map(enc, &tm_x, x, 2, d, s, b, S128, X_PROMO); }
  { cuuint64_t d[3] = {64, DM, HD / 64}, s[2] = {HD * 2, 128}; cuuint32_t b[3] = {64, 64, 2}; make_map(enc, &tm_wq, wq, 3, d, s, b, S128, P256); }
  { cuuint64_t d[3] = {64, NB * NH * SK, 2}, s[2] = {DH * 2, 128}; cuuint32_t b[3] = {64, 64, 2};
    make_map(enc, &tm_k, k, 3, d, s, b, S128, P128); make_map(enc, &tm_v, v, 3, d, s, b, S128, P128); }
  { cuuint64_t d[4] = {256, 2, HD / 8, NROWS / 64}, s[3] = {512, NROWS * 16, 1024}; cuuint32_t b[4] = {256, 2, 8, 2};
    make_map(enc, &tm_o, o_ptr, 4, d, s, b, CU_TENSOR_MAP_SWIZZLE_NONE, P256); }
  { cuuint64_t d[3] = {32, HD, DM / 32}, s[2] = {DM * 2, 64}; cuuint32_t b[3] = {32, 64, 5};
    make_map(enc, &tm_wo, wo, 3, d, s, b, CU_TENSOR_MAP_SWIZZLE_64B, P128); }
  Params P{x, k, v, wq, (__nv_bfloat16*)d_out, (__nv_bfloat16*)o_ptr};
  if (nclusters == 66) fused_attn_kernel<66><<<132, 384, SMEM_BYTES>>>(tm_x, tm_wq, tm_k, tm_v, tm_o, tm_wo, P);
  else fused_attn_kernel<0><<<2 * nclusters, 384, SMEM_BYTES>>>(tm_x, tm_wq, tm_k, tm_v, tm_o, tm_wo, P);
}
```

```cpp
#include <cuda_runtime.h>
#include <cuda.h>
#include <cuda_bf16.h>
#include <stdint.h>

namespace {

constexpr int NB = 16, SQ = 240, DM = 640, NH = 32, SK = 1024, DH = 128, HD = NH * DH;
constexpr int NROWS = NB * SQ;
constexpr int NUNITS = 256;
#define DPRO 1
#define LATE_AT 4
#define ALT_FROM 4
#define END_SKEW 5
#define VREL 6
#define PF_HOLD 6
#define PF_N 4
#define PF_J0 3
#define PF_STEP 3
#define ROT 0
#define O_EF 1
#define B_ORDER 1
#define WO_PF 6
#define ROLE_AT 0
#define PAUSE_NS 11000
#define PAUSE_AT 2
#define EARLY 1
#define EARLY_X 2
#define EARLY_W 2
#define X_PROMO P128
#define PAUSE_J -1
#define PAUSE_SPREAD 0
#define WO_PF0 1
#define EPI_MIX 1
#define EREL_FROM 4
#define PRE9 0
#define MAXCL 66
#define SMID_TOP 88
constexpr int NOTILES = 60;
constexpr float QSCALE = 0.08838834764831845f * 1.4426950408889634f;
constexpr float L_MIN = 9.5367431640625e-07f;
constexpr float L_MAX = 1.152921504606846976e18f;

constexpr uint32_t RING_SLOTS = 6, RING_BYTES = 16384;
constexpr uint32_t XB = 15360;
constexpr uint32_t BB = 20480;
constexpr uint32_t OFF_Q = RING_SLOTS * RING_BYTES;
constexpr uint32_t OFF_P = OFF_Q + 4 * XB;
constexpr uint32_t OFF_INV = OFF_P + 4 * XB;
constexpr uint32_t OFF_L2 = OFF_INV + 1280;
constexpr uint32_t OFF_BAR = OFF_L2 + 4096;
constexpr uint32_t BAR_RFULL = OFF_BAR, BAR_REMPTY = BAR_RFULL + 48, BAR_XFULL = BAR_REMPTY + 48,
    BAR_XEMPTY = BAR_XFULL + 64, BAR_BFULL = BAR_XEMPTY + 32, BAR_BEMPTY = BAR_BFULL + 48, BAR_STAGE = BAR_BEMPTY + 48;
constexpr uint32_t BAR_ROLE = BAR_STAGE + 16, BAR_LSUM = BAR_ROLE + 24, BAR_INV = BAR_LSUM + 16;
constexpr uint32_t OFF_TR = BAR_INV + 16;
constexpr uint32_t SMEM_BYTES = OFF_TR + 1024;

constexpr uint32_t HI128 = (1u << 30) | (1024 >> 4);
constexpr uint32_t HI64 = (2u << 30) | (512 >> 4);
constexpr uint32_t HI64A = (2u << 30) | (1024 >> 4), LBO64A = (512u >> 4) << 16;

__device__ __nv_bfloat16 g_o[HD * NROWS];
__device__ unsigned g_cnt[67 * 8];
#define TS(i)
#define TRL(i)
#define TR(i)
#define TG(i)

struct Params {
  const __nv_bfloat16 *x, *k, *v, *wq;
  __nv_bfloat16 *out, *o;
};

__device__ __forceinline__ void wg_fence() { asm volatile("wgmma.fence.sync.aligned;" ::: "memory"); }
__device__ __forceinline__ void wg_commit() { asm volatile("wgmma.commit_group.sync.aligned;" ::: "memory"); }
template <int N> __device__ __forceinline__ void wg_wait() { asm volatile("wgmma.wait_group.sync.aligned %0;" ::"n"(N) : "memory"); }
template <int N> __device__ __forceinline__ void reg_fence(float (&r)[N]) {
#pragma unroll
  for (int i = 0; i < N; i++) asm volatile("" : "+f"(r[i])::"memory");
}
template <int TA, int TB>
__device__ __forceinline__ void wgmma_n120(float (&d)[60], uint32_t a_lo, uint32_t a_hi, uint32_t b_lo, uint32_t b_hi, int acc) {
  asm volatile(
      "{\n.reg .pred p;\n.reg .b64 da, db;\nsetp.ne.b32 p, %64, 0;\n"
      "mov.b64 da, {%60, %61};\nmov.b64 db, {%62, %63};\n"
      "wgmma.mma_async.sync.aligned.m64n120k16.f32.bf16.bf16 {"
      "%0, %1, %2, %3, %4, %5, %6, %7, %8, %9, %10, %11, %12, %13, %14, %15, %16, %17, %18, %19, %20, %21, %22, %23, "
      "%24, %25, %26, %27, %28, %29, %30, %31, %32, %33, %34, %35, %36, %37, %38, %39, %40, %41, %42, %43, %44, %45, "
      "%46, %47, %48, %49, %50, %51, %52, %53, %54, %55, %56, %57, %58, %59"
      "}, da, db, p, 1, 1, %65, %66;\n}\n"
      : "+f"(d[0]), "+f"(d[1]), "+f"(d[2]), "+f"(d[3]), "+f"(d[4]), "+f"(d[5]), "+f"(d[6]), "+f"(d[7]), "+f"(d[8]),
        "+f"(d[9]), "+f"(d[10]), "+f"(d[11]), "+f"(d[12]), "+f"(d[13]), "+f"(d[14]), "+f"(d[15]), "+f"(d[16]),
        "+f"(d[17]), "+f"(d[18]), "+f"(d[19]), "+f"(d[20]), "+f"(d[21]), "+f"(d[22]), "+f"(d[23]), "+f"(d[24]),
        "+f"(d[25]), "+f"(d[26]), "+f"(d[27]), "+f"(d[28]), "+f"(d[29]), "+f"(d[30]), "+f"(d[31]), "+f"(d[32]),
        "+f"(d[33]), "+f"(d[34]), "+f"(d[35]), "+f"(d[36]), "+f"(d[37]), "+f"(d[38]), "+f"(d[39]), "+f"(d[40]),
        "+f"(d[41]), "+f"(d[42]), "+f"(d[43]), "+f"(d[44]), "+f"(d[45]), "+f"(d[46]), "+f"(d[47]), "+f"(d[48]),
        "+f"(d[49]), "+f"(d[50]), "+f"(d[51]), "+f"(d[52]), "+f"(d[53]), "+f"(d[54]), "+f"(d[55]), "+f"(d[56]),
        "+f"(d[57]), "+f"(d[58]), "+f"(d[59])
      : "r"(a_lo), "r"(a_hi), "r"(b_lo), "r"(b_hi), "r"(acc), "n"(TA), "n"(TB));
}

template <int TA, int TB>
__device__ __forceinline__ void wgmma_n160(float (&d)[80], uint32_t a_lo, uint32_t a_hi, uint32_t b_lo, uint32_t b_hi, int acc) {
  asm volatile(
      "{\n.reg .pred p;\n.reg .b64 da, db;\nsetp.ne.b32 p, %84, 0;\n"
      "mov.b64 da, {%80, %81};\nmov.b64 db, {%82, %83};\n"
      "wgmma.mma_async.sync.aligned.m64n160k16.f32.bf16.bf16 {"
      "%0, %1, %2, %3, %4, %5, %6, %7, %8, %9, %10, %11, %12, %13, %14, %15, %16, %17, %18, %19, %20, %21, %22, %23, "
      "%24, %25, %26, %27, %28, %29, %30, %31, %32, %33, %34, %35, %36, %37, %38, %39, %40, %41, %42, %43, %44, %45, "
      "%46, %47, %48, %49, %50, %51, %52, %53, %54, %55, %56, %57, %58, %59, %60, %61, %62, %63, %64, %65, %66, %67, "
      "%68, %69, %70, %71, %72, %73, %74, %75, %76, %77, %78, %79"
      "}, da, db, p, 1, 1, %85, %86;\n}\n"
      : "+f"(d[0]), "+f"(d[1]), "+f"(d[2]), "+f"(d[3]), "+f"(d[4]), "+f"(d[5]), "+f"(d[6]), "+f"(d[7]), "+f"(d[8]),
        "+f"(d[9]), "+f"(d[10]), "+f"(d[11]), "+f"(d[12]), "+f"(d[13]), "+f"(d[14]), "+f"(d[15]), "+f"(d[16]),
        "+f"(d[17]), "+f"(d[18]), "+f"(d[19]), "+f"(d[20]), "+f"(d[21]), "+f"(d[22]), "+f"(d[23]), "+f"(d[24]),
        "+f"(d[25]), "+f"(d[26]), "+f"(d[27]), "+f"(d[28]), "+f"(d[29]), "+f"(d[30]), "+f"(d[31]), "+f"(d[32]),
        "+f"(d[33]), "+f"(d[34]), "+f"(d[35]), "+f"(d[36]), "+f"(d[37]), "+f"(d[38]), "+f"(d[39]), "+f"(d[40]),
        "+f"(d[41]), "+f"(d[42]), "+f"(d[43]), "+f"(d[44]), "+f"(d[45]), "+f"(d[46]), "+f"(d[47]), "+f"(d[48]),
        "+f"(d[49]), "+f"(d[50]), "+f"(d[51]), "+f"(d[52]), "+f"(d[53]), "+f"(d[54]), "+f"(d[55]), "+f"(d[56]),
        "+f"(d[57]), "+f"(d[58]), "+f"(d[59]), "+f"(d[60]), "+f"(d[61]), "+f"(d[62]), "+f"(d[63]), "+f"(d[64]),
        "+f"(d[65]), "+f"(d[66]), "+f"(d[67]), "+f"(d[68]), "+f"(d[69]), "+f"(d[70]), "+f"(d[71]), "+f"(d[72]),
        "+f"(d[73]), "+f"(d[74]), "+f"(d[75]), "+f"(d[76]), "+f"(d[77]), "+f"(d[78]), "+f"(d[79])
      : "r"(a_lo), "r"(a_hi), "r"(b_lo), "r"(b_hi), "r"(acc), "n"(TA), "n"(TB));
}
__device__ __forceinline__ void mbar_init(uint32_t bar, int cnt) { asm volatile("mbarrier.init.shared::cta.b64 [%0], %1;" ::"r"(bar), "r"(cnt)); }
__device__ __forceinline__ void mbar_expect(uint32_t bar, uint32_t bytes) {
  asm volatile("mbarrier.arrive.expect_tx.shared::cta.b64 _, [%0], %1;" ::"r"(bar), "r"(bytes) : "memory");
}
__device__ __forceinline__ uint32_t mapa(uint32_t addr, uint32_t cta) {
  uint32_t r; asm("mapa.shared::cluster.u32 %0, %1, %2;" : "=r"(r) : "r"(addr), "r"(cta)); return r;
}
__device__ __forceinline__ void mbar_expect_cl(uint32_t cbar, uint32_t bytes) {
  asm volatile("mbarrier.arrive.expect_tx.shared::cluster.b64 _, [%0], %1;" ::"r"(cbar), "r"(bytes) : "memory");
}
__device__ __forceinline__ void mbar_arrive(uint32_t bar) { asm volatile("mbarrier.arrive.shared::cta.b64 _, [%0];" ::"r"(bar) : "memory"); }
__device__ __forceinline__ void mbar_arrive_cl(uint32_t cbar) { asm volatile("mbarrier.arrive.shared::cluster.b64 _, [%0];" ::"r"(cbar) : "memory"); }
__device__ __forceinline__ void warp_arrive(uint32_t bar) {
  asm volatile("{\n.reg .pred p;\nelect.sync _|p, 0xffffffff;\n@p mbarrier.arrive.shared::cta.b64 _, [%0];\n}\n" ::"r"(bar) : "memory");
}
__device__ __forceinline__ void warp_arrive_cl(uint32_t cbar) {
  asm volatile("{\n.reg .pred p;\nelect.sync _|p, 0xffffffff;\n@p mbarrier.arrive.shared::cluster.b64 _, [%0];\n}\n" ::"r"(cbar) : "memory");
}
__device__ __forceinline__ void mbar_wait(uint32_t bar, uint32_t parity) {
  asm volatile(
      "{\n.reg .pred p;\n.reg .u32 n;\n"
      "mbarrier.try_wait.parity.shared::cta.b64 p, [%0], %1;\n@p bra WAIT_DONE;\n"
      "mov.u32 n, 0;\n"
      "WAIT_LOOP:\n"
      "mbarrier.try_wait.parity.shared::cta.b64 p, [%0], %1;\n@p bra WAIT_DONE;\n"
      "add.u32 n, n, 1;\nsetp.lt.u32 p, n, 0x4000000;\n@p bra WAIT_LOOP;\ntrap;\n"
      "WAIT_DONE:\n}\n" ::"r"(bar), "r"(parity) : "memory");
}
__device__ __forceinline__ void mbar_wait_cl(uint32_t bar, uint32_t parity) {
  asm volatile(
      "{\n.reg .pred p;\n.reg .u32 n;\nmov.u32 n, 0;\n"
      "WAIT_LOOP:\n"
      "mbarrier.try_wait.parity.acquire.cluster.shared::cta.b64 p, [%0], %1;\n@p bra WAIT_DONE;\n"
      "add.u32 n, n, 1;\nsetp.lt.u32 p, n, 0x4000000;\n@p bra WAIT_LOOP;\ntrap;\n"
      "WAIT_DONE:\n}\n" ::"r"(bar), "r"(parity) : "memory");
}
__device__ __forceinline__ void tma3d(uint32_t dst, const CUtensorMap* m, int c0, int c1, int c2, uint32_t bar) {
  asm volatile("cp.async.bulk.tensor.3d.shared::cluster.global.mbarrier::complete_tx::bytes [%0], [%1, {%3, %4, %5}], [%2];"
               ::"r"(dst), "l"(m), "r"(bar), "r"(c0), "r"(c1), "r"(c2) : "memory");
}
__device__ __forceinline__ void tma3d_hint(uint32_t dst, const CUtensorMap* m, int c0, int c1, int c2, uint32_t bar, uint64_t pol) {
  asm volatile("cp.async.bulk.tensor.3d.shared::cluster.global.mbarrier::complete_tx::bytes.L2::cache_hint [%0], [%1, {%3, %4, %5}], [%2], %6;"
               ::"r"(dst), "l"(m), "r"(bar), "r"(c0), "r"(c1), "r"(c2), "l"(pol) : "memory");
}
__device__ __forceinline__ void tma2d_mc(uint32_t dst, const CUtensorMap* m, int c0, int c1, uint32_t bar) {
  asm volatile("cp.async.bulk.tensor.2d.shared::cluster.global.mbarrier::complete_tx::bytes.multicast::cluster [%0], [%1, {%3, %4}], [%2], %5;"
               ::"r"(dst), "l"(m), "r"(bar), "r"(c0), "r"(c1), "h"((uint16_t)3) : "memory");
}
__device__ __forceinline__ void tma3d_mc(uint32_t dst, const CUtensorMap* m, int c0, int c1, int c2, uint32_t bar) {
  asm volatile("cp.async.bulk.tensor.3d.shared::cluster.global.mbarrier::complete_tx::bytes.multicast::cluster [%0], [%1, {%3, %4, %5}], [%2], %6;"
               ::"r"(dst), "l"(m), "r"(bar), "r"(c0), "r"(c1), "r"(c2), "h"((uint16_t)3) : "memory");
}
__device__ __forceinline__ void l2_prefetch(const void* p, uint32_t bytes) {
  asm volatile("cp.async.bulk.prefetch.L2.global [%0], %1;" ::"l"(p), "r"(bytes) : "memory");
}
__device__ __forceinline__ void fence_async_smem() { asm volatile("fence.proxy.async.shared::cta;" ::: "memory"); }
__device__ __forceinline__ void bar_sync(int wg) {
  if (wg == 0) asm volatile("bar.sync 1, 128;" ::: "memory");
  else asm volatile("bar.sync 2, 128;" ::: "memory");
}
__device__ __forceinline__ bool bar_red_or(int id, bool v) {
  uint32_t r;
  asm volatile("{\n.reg .pred p, q;\nsetp.ne.u32 p, %2, 0;\nbar.red.or.pred q, %1, 128, p;\nselp.u32 %0, 1, 0, q;\n}\n"
               : "=r"(r) : "r"(1 + id), "r"((uint32_t)v) : "memory");
  return r != 0;
}
__device__ __forceinline__ uint32_t hfma2(uint32_t a, uint32_t b, uint32_t c) { uint32_t r; asm("fma.rn.bf16x2 %0, %1, %2, %3;" : "=r"(r) : "r"(a), "r"(b), "r"(c)); return r; }
__device__ __forceinline__ float ex2(float x) { float y; asm("ex2.approx.ftz.f32 %0, %1;" : "=f"(y) : "f"(x)); return y; }
__device__ __forceinline__ uint32_t pack(float lo, float hi) { uint32_t r; asm("cvt.rn.bf16x2.f32 %0, %1, %2;" : "=r"(r) : "f"(hi), "f"(lo)); return r; }
__device__ __forceinline__ void stsm4t(uint32_t a, uint32_t r0, uint32_t r1, uint32_t r2, uint32_t r3) {
  asm volatile("stmatrix.sync.aligned.m8n8.x4.trans.shared.b16 [%0], {%1,%2,%3,%4};" ::"r"(a), "r"(r0), "r"(r1), "r"(r2), "r"(r3) : "memory");
}
__device__ __forceinline__ void stsm2t(uint32_t a, uint32_t r0, uint32_t r1) {
  asm volatile("stmatrix.sync.aligned.m8n8.x2.trans.shared.b16 [%0], {%1,%2};" ::"r"(a), "r"(r0), "r"(r1) : "memory");
}
__device__ __forceinline__ void mma16816(float (&d)[4], const uint32_t (&a)[4], uint32_t b0, uint32_t b1) {
  asm volatile("mma.sync.aligned.m16n8k16.row.col.f32.bf16.bf16.f32 {%0,%1,%2,%3}, {%4,%5,%6,%7}, {%8,%9}, {%0,%1,%2,%3};"
               : "+f"(d[0]), "+f"(d[1]), "+f"(d[2]), "+f"(d[3]) : "r"(a[0]), "r"(a[1]), "r"(a[2]), "r"(a[3]), "r"(b0), "r"(b1));
}

__device__ __forceinline__ uint32_t fresh_tid() { uint32_t t; asm volatile("mov.u32 %0, %tid.x;" : "=r"(t)); return t; }

template <int V> struct IC { static constexpr int value = V; };

struct Ring {
  uint32_t slot = 0, phase = 0;
  __device__ __forceinline__ void next() { if (++slot == RING_SLOTS) { slot = 0; phase ^= 1; } }
};

__device__ __forceinline__ void mma_tn(float (&o0)[60], float (&o1)[60], uint32_t a, uint32_t b, int acc) {
#pragma unroll
  for (int k = 0; k < 4; k++) {
    wgmma_n120<1, 0>(o0, a + k * 128, HI128, b + k * 2, HI128, k == 0 ? acc : 1);
    wgmma_n120<1, 0>(o1, a + 512 + k * 128, HI128, b + k * 2, HI128, k == 0 ? acc : 1);
  }
}
__device__ __forceinline__ void mma_tn_split(float (&o0)[60], float (&o1)[60], uint32_t a, uint32_t b) {
#pragma unroll
  for (int k = 0; k < 4; k++) wgmma_n120<1, 0>(o0, a + k * 128, HI128, b + k * 2, HI128, 1);
  wg_commit();
#pragma unroll
  for (int k = 0; k < 4; k++) wgmma_n120<1, 0>(o1, a + 512 + k * 128, HI128, b + k * 2, HI128, 1);
  wg_commit();
}
__device__ __forceinline__ void mma_qk(float (&s)[60], uint32_t a, uint32_t q) {
#pragma unroll
  for (int k = 0; k < 8; k++)
    wgmma_n120<0, 0>(s, a + (k >> 2) * 512 + (k & 3) * 2, HI128, q + (k >> 2) * (XB >> 4) + (k & 3) * 2, HI128, k != 0);
}
template <int J0, int J1, bool FIRST = false>
__device__ __forceinline__ void exp_store(const float (&s)[60], float (&l)[30], uint32_t dst) {
#pragma unroll
  for (int j = J0; j < J1; j += 2) {
    uint32_t p[4];
#pragma unroll
    for (int jj = 0; jj < 2; jj++) {
      if (j + jj < 15) {
        const int c = j + jj;
        float e0 = ex2(s[4 * c]), e1 = ex2(s[4 * c + 1]), e2 = ex2(s[4 * c + 2]), e3 = ex2(s[4 * c + 3]);
        if (FIRST) { l[2 * c] = e0 + e2; l[2 * c + 1] = e1 + e3; }
        else { l[2 * c] += e0; l[2 * c + 1] += e1; l[2 * c] += e2; l[2 * c + 1] += e3; }
        p[2 * jj] = pack(e0, e1); p[2 * jj + 1] = pack(e2, e3);
      }
    }
    if (j + 1 < 15) stsm4t(dst + j * 1024, p[0], p[1], p[2], p[3]);
    else stsm2t(dst + j * 1024, p[0], p[1]);
  }
}

__device__ __forceinline__ int o_pos(int b, int wg, int r) {
  const int j = r >> 3, q = (r >> 1) & 3, c = r & 1, o = b & 1, base = (b >> 1) * 480;
  if (j < 12) return base + (o * 9 + wg * 3 + (j >> 2)) * 32 + q * 8 + (j & 3) * 2 + c;
  if (j < 14) return base + (6 + 2 * o) * 32 + wg * 16 + q * 4 + (j - 12) * 2 + c;
  return base + 7 * 32 + (o * 2 + wg) * 8 + q * 2 + c;
}
__device__ __forceinline__ int o_row(int p) {
  const int pair = p / 480, a = (p - pair * 480) >> 5, in = p & 31, c = p & 1;
  int tile, row;
  if (a == 7) { tile = in >> 3; row = 112 + (in & 7); }
  else if (a == 6 || a == 8) { tile = a - 6 + (in >> 4); row = (12 + ((in >> 1) & 1)) * 8 + ((in >> 2) & 3) * 2 + c; }
  else { const int f = a > 8 ? a - 3 : a; tile = f / 3; row = ((f - tile * 3) * 4 + ((in >> 1) & 3)) * 8 + (in >> 3) * 2 + c; }
  return pair * 480 + tile * 120 + row;
}
__device__ __forceinline__ uint32_t o_idx(int k, int p) {
  return ((k >> 3) * (NROWS / 32) + (p >> 5)) * 256 + (k & 7) * 32 + ((((p >> 3) & 3) ^ ((k & 7) >> 1)) << 3) + (p & 7);
}

__device__ __forceinline__ void slow_path(const Params& P, int b, int h, int wg, int w, int lane) {
  const int g = lane >> 2, q = lane & 3, row0 = wg * 120;
  const uint16_t* wq = reinterpret_cast<const uint16_t*>(P.wq) + h * DH + g;
  const __nv_bfloat16* kp = P.k + (size_t)(b * NH + h) * SK * DH;
  const uint16_t* vp = reinterpret_cast<const uint16_t*>(P.v) + (size_t)(b * NH + h) * SK * DH + g;
#pragma unroll 1
  for (int t = w; t < 8; t += 4) {
    const int r0 = 16 * t + g, r1 = r0 + 8;
    const __nv_bfloat16* x0 = P.x + (size_t)(b * SQ + row0 + r0) * DM + 2 * q;
    const __nv_bfloat16* x1 = P.x + (size_t)(b * SQ + row0 + min(r1, 119)) * DM + 2 * q;
    float o[16][4];
#pragma unroll
    for (int n = 0; n < 16; n++) o[n][0] = o[n][1] = o[n][2] = o[n][3] = 0.f;
#pragma unroll 1
    for (int k0 = 0; k0 < DM; k0 += 16) {
      uint32_t a[4] = {*(const uint32_t*)(x0 + k0), *(const uint32_t*)(x1 + k0), *(const uint32_t*)(x0 + k0 + 8), *(const uint32_t*)(x1 + k0 + 8)};
      const uint16_t* wr = wq + (size_t)(k0 + 2 * q) * HD;
#pragma unroll
      for (int n = 0; n < 16; n++) {
        if ((n & 3) == 0) __syncwarp();
        mma16816(o[n], a, wr[8 * n] | ((uint32_t)wr[8 * n + HD] << 16), wr[8 * n + 8 * HD] | ((uint32_t)wr[8 * n + 9 * HD] << 16));
      }
    }
    uint32_t qa[8][4];
#pragma unroll
    for (int k = 0; k < 8; k++) {
      qa[k][0] = pack(o[2 * k][0] * QSCALE, o[2 * k][1] * QSCALE);
      qa[k][1] = pack(o[2 * k][2] * QSCALE, o[2 * k][3] * QSCALE);
      qa[k][2] = pack(o[2 * k + 1][0] * QSCALE, o[2 * k + 1][1] * QSCALE);
      qa[k][3] = pack(o[2 * k + 1][2] * QSCALE, o[2 * k + 1][3] * QSCALE);
    }
#pragma unroll
    for (int n = 0; n < 16; n++) o[n][0] = o[n][1] = o[n][2] = o[n][3] = 0.f;
    float m0 = -INFINITY, m1 = -INFINITY, l0 = 0.f, l1 = 0.f;
#pragma unroll 1
    for (int key0 = 0; key0 < SK; key0 += 16) {
      float s[2][4];
#pragma unroll
      for (int nt = 0; nt < 2; nt++) {
        s[nt][0] = s[nt][1] = s[nt][2] = s[nt][3] = 0.f;
        const __nv_bfloat16* kr = kp + (size_t)(key0 + 8 * nt + g) * DH + 2 * q;
#pragma unroll
        for (int k = 0; k < 8; k++) mma16816(s[nt], qa[k], *(const uint32_t*)(kr + 16 * k), *(const uint32_t*)(kr + 16 * k + 8));
      }
      float n0 = fmaxf(fmaxf(s[0][0], s[0][1]), fmaxf(s[1][0], s[1][1])), n1 = fmaxf(fmaxf(s[0][2], s[0][3]), fmaxf(s[1][2], s[1][3]));
      n0 = fmaxf(n0, __shfl_xor_sync(~0u, n0, 1)); n1 = fmaxf(n1, __shfl_xor_sync(~0u, n1, 1));
      n0 = fmaxf(n0, __shfl_xor_sync(~0u, n0, 2)); n1 = fmaxf(n1, __shfl_xor_sync(~0u, n1, 2));
      n0 = fmaxf(n0, m0); n1 = fmaxf(n1, m1);
      const float z0 = n0 == -INFINITY ? 0.f : n0, z1 = n1 == -INFINITY ? 0.f : n1;
      const float c0 = ex2(m0 - z0), c1 = ex2(m1 - z1);
      m0 = n0; m1 = n1;
#pragma unroll
      for (int nt = 0; nt < 2; nt++) {
        s[nt][0] = ex2(s[nt][0] - z0); s[nt][1] = ex2(s[nt][1] - z0);
        s[nt][2] = ex2(s[nt][2] - z1); s[nt][3] = ex2(s[nt][3] - z1);
      }
      l0 = l0 * c0 + s[0][0] + s[0][1] + s[1][0] + s[1][1];
      l1 = l1 * c1 + s[0][2] + s[0][3] + s[1][2] + s[1][3];
      uint32_t pa[4] = {pack(s[0][0], s[0][1]), pack(s[0][2], s[0][3]), pack(s[1][0], s[1][1]), pack(s[1][2], s[1][3])};
      const uint16_t* vr = vp + (size_t)(key0 + 2 * q) * DH;
#pragma unroll
      for (int n = 0; n < 16; n++) {
        if ((n & 3) == 0) __syncwarp();
        o[n][0] *= c0; o[n][1] *= c0; o[n][2] *= c1; o[n][3] *= c1;
        mma16816(o[n], pa, vr[8 * n] | ((uint32_t)vr[8 * n + DH] << 16), vr[8 * n + 8 * DH] | ((uint32_t)vr[8 * n + 9 * DH] << 16));
      }
    }
    l0 += __shfl_xor_sync(~0u, l0, 1); l1 += __shfl_xor_sync(~0u, l1, 1);
    l0 += __shfl_xor_sync(~0u, l0, 2); l1 += __shfl_xor_sync(~0u, l1, 2);
    const float i0 = 1.f / l0, i1 = 1.f / l1;
    __nv_bfloat16* oc0 = P.o + o_idx(h * DH + 2 * q, o_pos(b, wg, r0));
    __nv_bfloat16* oc1 = P.o + o_idx(h * DH + 2 * q, o_pos(b, wg, min(r1, 119)));
#pragma unroll
    for (int n = 0; n < 16; n++) {
      oc0[8 * n * NROWS] = __float2bfloat16(o[n][0] * i0);
      oc0[8 * n * NROWS + 32] = __float2bfloat16(o[n][1] * i0);
      if (r1 < 120) {
        oc1[8 * n * NROWS] = __float2bfloat16(o[n][2] * i1);
        oc1[8 * n * NROWS + 32] = __float2bfloat16(o[n][3] * i1);
      }
    }
  }
}

__device__ __forceinline__ int bk(int ks) { return B_ORDER && ks < 48 ? 32 - (ks & 48) + (ks & 15) : ks; }
__device__ __forceinline__ uint32_t x_slot(uint32_t wg, uint32_t j) { return j < 2 ? (2 * wg + j) * XB : (2 * j + wg) * XB; }
__device__ __forceinline__ int row_block(int t) { return t >= 44 ? (t >> 2) - 11 : (t >> 2) + 4; }
__device__ __forceinline__ int unit_batch(int u) { return (u & 63) >> 2; }
__device__ __forceinline__ int unit_head(int u, int rank) { return (u >> 6) * 8 + (u & 3) * 2 + rank; }

template <int NCL>
__global__ void __cluster_dims__(2, 1, 1) __launch_bounds__(384, 1)
fused_attn_kernel(const __grid_constant__ CUtensorMap tm_x, const __grid_constant__ CUtensorMap tm_wq,
                  const __grid_constant__ CUtensorMap tm_k, const __grid_constant__ CUtensorMap tm_v,
                  const __grid_constant__ CUtensorMap tm_o, const __grid_constant__ CUtensorMap tm_wo,
                  const __grid_constant__ Params P) {
  extern __shared__ uint8_t smem_raw[];
  const uint32_t sb = ((uint32_t)__cvta_generic_to_shared(smem_raw) + 1023) & ~1023u;
  if (threadIdx.x == 0) TS(152);
  const int warp = __shfl_sync(~0u, threadIdx.x >> 5, 0);
  const int lane = threadIdx.x & 31;
  const int rank = blockIdx.x & 1, cl = blockIdx.x >> 1, ncl = NCL ? NCL : gridDim.x >> 1;

  const int nsingle = NCL == 66 ? 44 : NOTILES;
  auto role = [&]() {
    mbar_wait(sb + BAR_ROLE + 16, 0);
    int id;
    asm volatile("ld.shared.u32 %0, [%1];" : "=r"(id) : "r"(sb + BAR_ROLE + 8) : "memory");
    return id;
  };

  if (EARLY && threadIdx.x == 128) asm volatile("prefetch.tensormap [%0];" ::"l"(&tm_x) : "memory");
  if (threadIdx.x == 0) {
    if (EARLY) asm volatile("prefetch.tensormap [%0];" ::"l"(&tm_wq) : "memory");
    for (int i = 0; i < 6; i++) {
      mbar_init(sb + BAR_RFULL + 8 * i, 1); mbar_init(sb + BAR_REMPTY + 8 * i, 8);
      mbar_init(sb + BAR_BFULL + 8 * i, 1); mbar_init(sb + BAR_BEMPTY + 8 * i, 16);
    }
    for (int i = 0; i < 8; i++) mbar_init(sb + BAR_XFULL + 8 * i, 1);
    for (int i = 0; i < 4; i++) mbar_init(sb + BAR_XEMPTY + 8 * i, 8);
    for (int i = 0; i < 2; i++) { mbar_init(sb + BAR_STAGE + 8 * i, 4); mbar_init(sb + BAR_LSUM + 8 * i, 4); mbar_init(sb + BAR_INV + 8 * i, 1); }
    mbar_init(sb + BAR_ROLE, 1); mbar_init(sb + BAR_ROLE + 16, 1);
    asm volatile("fence.mbarrier_init.release.cluster;" ::: "memory");
  }
  __syncwarp();
  asm volatile("barrier.cluster.arrive.relaxed.aligned;" ::: "memory");
  auto first_w = [&](int s) {
    mbar_expect(sb + BAR_RFULL + 8 * s, RING_BYTES);
    tma3d(sb + s * RING_BYTES, &tm_wq, 0, s * 64, 2 * unit_head(cl, rank), sb + BAR_RFULL + 8 * s);
  };
  if (EARLY && threadIdx.x == 0) first_w(0);
  __syncwarp();
  asm volatile("barrier.cluster.wait.aligned;" ::: "memory");
  if (EARLY && threadIdx.x == 128) {
#pragma unroll 1
    for (int s = 0; s < EARLY_X; s++) {
      const uint32_t fb = sb + BAR_XFULL + 32 * rank + 8 * s;
      mbar_expect(fb, XB);
      mbar_expect_cl(mapa(fb, rank ^ 1), XB);
      tma2d_mc(sb + OFF_Q + x_slot(rank, s), &tm_x, s * 64, unit_batch(cl) * SQ + rank * 120, fb);
      if (s + 1 < EARLY_W) first_w(s + 1);
    }
  }
  __syncwarp();
  if (threadIdx.x == 0) TS(153);

  if (warp >= 8) {
    asm volatile("setmaxnreg.dec.sync.aligned.u32 24;");
    if (warp == 8) {
      uint64_t pol;
      asm volatile("createpolicy.fractional.L2::evict_first.b64 %0, 1.0;" : "=l"(pol));
      Ring r;
      if (EARLY) r.slot = EARLY_W;
      auto load = [&](const CUtensorMap* m, int c1, int c2, bool ef) {
        mbar_wait(sb + BAR_REMPTY + 8 * r.slot, r.phase ^ 1);
        if (lane == 0) {
          mbar_expect(sb + BAR_RFULL + 8 * r.slot, RING_BYTES);
          if (ef) tma3d_hint(sb + r.slot * RING_BYTES, m, 0, c1, c2, sb + BAR_RFULL + 8 * r.slot, pol);
          else tma3d(sb + r.slot * RING_BYTES, m, 0, c1, c2, sb + BAR_RFULL + 8 * r.slot);
        }
        r.next();
      };
      const int rot = ROT * (blockIdx.x * 5 + (blockIdx.x >> 4));
      auto pause = [&](int u0) {
        if (PAUSE_NS && NCL == 66 && u0 == PAUSE_AT * 66) {
          const int id = role();
          if (id >= 44 && id < 58) {
            unsigned t0, t1;
            asm volatile("mov.u32 %0, %globaltimer_lo;" : "=r"(t0));
            do { __nanosleep(200); asm volatile("mov.u32 %0, %globaltimer_lo;" : "=r"(t1)); } while (t1 - t0 < PAUSE_NS + (id - 44) * PAUSE_SPREAD);
          }
        }
      };
      for (int u0 = 0;; u0 += ncl) {
        const int u = __shfl_sync(~0u, (u0 >= 3 * ncl ? role() : cl) + u0, 0);
        if (u >= NUNITS) break;
        if (PAUSE_J < 0) pause(u0);
        const int h = unit_head(u, rank);
        const int krow = (unit_batch(u) * NH + h) * SK;
#pragma unroll 1
        for (int s = EARLY && u0 == 0 ? EARLY_W : 0; s < 10; s++) {
          if (u0 == 0 && s == 0 && lane == 0) TS(154);
          load(&tm_wq, s * 64, 2 * h, false);
          if (u0 == 0 && s == 0 && lane == 0) TS(155);
          const int sp = u0 == 0 ? s - PF_HOLD : s;
          if (sp >= 0 && sp < PF_N && lane == 0) l2_prefetch(P.v + (size_t)(krow + ((PF_J0 + sp * PF_STEP + rot) & 15) * 64) * DH, 16384);
        }
#pragma unroll 1
        for (int j = 0; j <= 16; j++) {
          if (j == PAUSE_J) pause(u0);
          if (j < 16) load(&tm_k, krow + ((j + rot) & 15) * 64, 0, true);
          if (j == 1 + DPRO) load(&tm_v, krow + (rot & 15) * 64, 0, true);
          if (j > 1) load(&tm_v, krow + ((j - 1 + rot) & 15) * 64, 0, true);
        }
      }
      const int id = __shfl_sync(~0u, role(), 0);
      const bool dbl = NCL == 66 && id >= 58;
      for (int t = dbl ? 2 * id - 72 : id; t < (dbl ? NOTILES : nsingle); t += ncl) {
        const int row0 = row_block(t) * 256 + rank * 128;
        const int b0 = (row0 & ~31) / SQ, b1 = (row0 + 127) / SQ;
#pragma unroll 1
        for (int ks = 0; ks < 64; ks++) {
          if (dbl ? (ks & 15) == 0 : ks == 0 || ks == 48) {
            const unsigned* c = &g_cnt[((lane & 1 ? b1 : b0) * 4 + (ks || dbl ? ks >> 4 : min(lane >> 1, 2))) * 8];
            unsigned v, n = 0;
            do {
              asm volatile("ld.acquire.gpu.global.u32 %0, [%1];" : "=r"(v) : "l"(c) : "memory");
              if (++n > (1u << 26)) __trap();
            } while (v < 16);
            __syncwarp();
            asm volatile("fence.proxy.async.global;" ::: "memory");
          }
          mbar_wait(sb + BAR_REMPTY + 8 * r.slot, r.phase ^ 1);
          if (lane == 0) {
            mbar_expect(sb + BAR_RFULL + 8 * r.slot, RING_BYTES);
            asm volatile("cp.async.bulk.tensor.4d.shared::cluster.global.mbarrier::complete_tx::bytes.L2::cache_hint [%0], [%1, {%3, %3, %4, %5}], [%2], %6;"
                         ::"r"(sb + r.slot * RING_BYTES), "l"(&tm_o), "r"(sb + BAR_RFULL + 8 * r.slot), "r"(0), "r"((dbl ? ks : bk(ks)) * 8), "r"(row0 >> 6), "l"(pol) : "memory");
          }
          r.next();
        }
      }
      if (lane == 0 && atomicAdd(&g_cnt[64 * 8], 1) == gridDim.x - 1) {
        for (int i = 0; i < 67; i++) g_cnt[i * 8] = 0;
      }
    } else if (warp == 9) {
      if (lane == 0) {
        uint32_t it = 0;
        for (;; it++) {
          const int u = (it >= 3 ? role() : cl) + it * ncl;
          if (u >= NUNITS) break;
          const int row = unit_batch(u) * SQ + rank * 120;
#pragma unroll 1
          for (int s = EARLY && it == 0 ? EARLY_X : 0; s < 10; s++) {
            const uint32_t j = s & 3, par = ((s >> 2) + (j < 2 ? it : 0)) & 1;
            mbar_wait(sb + BAR_XEMPTY + 8 * j, par ^ 1);
            const uint32_t fb = sb + BAR_XFULL + 32 * rank + 8 * j;
            mbar_expect(fb, XB);
            mbar_expect_cl(mapa(fb, rank ^ 1), XB);
            tma2d_mc(sb + OFF_Q + x_slot(rank, j), &tm_x, s * 64, row, fb);
          }
        }
        const int id = role();
        const bool dbl = NCL == 66 && id >= 58;
        uint32_t slot = rank, phase = 0;
        if (WO_PF0 && dbl)
          asm volatile("cp.async.bulk.prefetch.tensor.3d.L2.global [%0, {%1, %2, %3}];" ::"l"(&tm_wo), "r"(0), "r"((2 + ((id >> 1) & 3)) * 64), "r"(((2 * id - 72 + rank) & 3) * 5) : "memory");
        for (int t = dbl ? 2 * id - 72 + rank : id; t < (dbl ? NOTILES : nsingle); t += ncl) {
#pragma unroll 1
          for (int ks = dbl ? 0 : rank; ks < 64; ks += dbl ? 1 : 2) {
            mbar_wait(sb + BAR_BEMPTY + 8 * slot, phase);
            const uint32_t fb = sb + BAR_BFULL + 8 * slot;
            mbar_expect(fb, BB);
            mbar_expect_cl(mapa(fb, rank ^ 1), BB);
            tma3d_mc(sb + OFF_Q + slot * BB, &tm_wo, 0, (dbl ? ks : bk(ks)) * 64, (t & 3) * 5, fb);
            if (WO_PF && dbl && ks + WO_PF < 64 && (ks & 3) == ((id >> 1) & 3))
              asm volatile("cp.async.bulk.prefetch.tensor.3d.L2.global [%0, {%1, %2, %3}];" ::"l"(&tm_wo), "r"(0), "r"((ks + WO_PF) * 64), "r"((t & 3) * 5) : "memory");
            slot += 2;
            if (slot >= 6) { slot -= 6; phase ^= 1; }
          }
        }
      }
    } else {
      const int wg = warp - 10;
      {
        mbar_wait(sb + BAR_RFULL, 0);
        const __nv_bfloat16* xs = P.x + (size_t)(unit_batch(cl) * SQ + ((cl & 3) * 2 + rank) * 30 + min(lane, 29)) * DM + 256 + wg * 64;
#pragma unroll
        for (int i = 0; i < 3; i++) asm volatile("prefetch.global.L2 [%0];" ::"l"(xs + i * 128));
        if (lane < 16) asm volatile("prefetch.global.L2 [%0];" ::"l"(P.wq + (size_t)(384 + unit_batch(cl) * 16 + lane) * HD + unit_head(cl, rank) * DH + wg * 64));
      }
      auto take_role = [&]() {
          if (wg == 0 && rank == 0 && lane == 0) {
            int id = cl;
            if (NCL == 66) {
              uint32_t smid;
              asm("mov.u32 %0, %smid;" : "=r"(smid));
              id = smid >= SMID_TOP ? 65 - atomicAdd(&g_cnt[65 * 8], 1) : atomicAdd(&g_cnt[66 * 8], 1);
            }
    #pragma unroll
            for (int c = 0; c < 2; c++) {
              const uint32_t a = mapa(sb + BAR_ROLE, c);
              asm volatile("st.shared::cluster.u32 [%0 + 8], %1;\nmbarrier.arrive.release.cluster.shared::cluster.b64 _, [%0];" ::"r"(a), "r"(id) : "memory");
            }
          }
          if (wg == 0 && lane == 0) {
            mbar_wait_cl(sb + BAR_ROLE, 0);
            mbar_arrive(sb + BAR_ROLE + 16);
          }
      };
      if (ROLE_AT < 0) { take_role(); __syncwarp(); }
      for (uint32_t it = 0;; it++) {
        const int u = __shfl_sync(~0u, (it >= 3 ? role() : cl) + it * ncl, 0);
        if (u >= NUNITS) break;
        mbar_wait(sb + BAR_LSUM + 8 * wg, it & 1);
        float l4[4], v[4];
        const uint32_t a = sb + OFF_L2 + wg * 2048 + lane * 16;
        asm volatile("ld.shared.v4.f32 {%0, %1, %2, %3}, [%4];" : "=f"(l4[0]), "=f"(l4[1]), "=f"(l4[2]), "=f"(l4[3]) : "r"(a) : "memory");
#pragma unroll
        for (int g = 1; g < 4; g++) {
          asm volatile("ld.shared.v4.f32 {%0, %1, %2, %3}, [%4];" : "=f"(v[0]), "=f"(v[1]), "=f"(v[2]), "=f"(v[3]) : "r"(a + g * 512) : "memory");
#pragma unroll
          for (int c = 0; c < 4; c++) l4[c] += v[c];
        }
#pragma unroll
        for (int c = 0; c < 4; c++) {
          float inv;
          asm("rcp.approx.ftz.f32 %0, %1;" : "=f"(inv) : "f"(l4[c]));
          l4[c] = l4[c] >= L_MIN && l4[c] <= L_MAX ? inv : __uint_as_float(0x7FFFFFFFu);
        }
        const uint32_t h0 = pack(l4[0], l4[1]), h1 = pack(l4[2], l4[3]);
        const uint32_t e0 = pack(l4[0] - __uint_as_float(h0 << 16), l4[1] - __uint_as_float(h0 & 0xFFFF0000u));
        const uint32_t e1 = pack(l4[2] - __uint_as_float(h1 << 16), l4[3] - __uint_as_float(h1 & 0xFFFF0000u));
        asm volatile("st.shared.v4.u32 [%0], {%1, %2, %3, %4};" ::"r"(sb + OFF_INV + wg * 640 + (lane & 3) * 144 + (lane >> 2) * 16), "r"(h0), "r"(e0), "r"(h1), "r"(e1) : "memory");
        __syncwarp();
        if (lane == 0) {
          mbar_arrive(sb + BAR_INV + 8 * wg);
          if ((int)it == ROLE_AT) {
            take_role();
          }
          mbar_wait(sb + BAR_STAGE + 8 * wg, it & 1);
          __threadfence();
          asm volatile("red.relaxed.gpu.global.add.u32 [%0], 1;" ::"l"(&g_cnt[(unit_batch(u) * 4 + (u >> 6)) * 8]) : "memory");
        }
        __syncwarp();
      }
    }
  } else {
    asm volatile("setmaxnreg.inc.sync.aligned.u32 240;");
    const int wg = warp >> 2, w = warp & 3;
    const uint32_t qreg = sb + OFF_Q + wg * 2 * XB, preg = sb + OFF_P + (2 + wg) * XB;
    const uint32_t st_off = ((lane >> 4) * 8 + (lane & 7)) * 128 + (((2 * w + ((lane >> 3) & 1)) ^ (lane & 7)) << 4);
    const uint32_t xempty = mapa(sb + BAR_XEMPTY, wg);
    Ring r;
    uint32_t it = 0;
    const uint32_t qd = (qreg & 0x3FFFF) >> 4, pd = (preg & 0x3FFFF) >> 4;
    auto ring_addr = [&]() { return ((sb & 0x3FFFF) + r.slot * RING_BYTES) >> 4; };
    auto ring_wait = [&]() { mbar_wait(sb + BAR_RFULL + 8 * r.slot, r.phase); };
    auto release = [&](uint32_t slot) { warp_arrive(sb + BAR_REMPTY + 8 * slot); };
    auto turn_wait = [&]() {
      if (wg == 0) asm volatile("bar.sync 3, 256;" ::: "memory");
      else asm volatile("bar.sync 4, 256;" ::: "memory");
    };
    auto turn_pass = [&]() {
      if (wg == 0) asm volatile("bar.arrive 4, 256;" ::: "memory");
      else asm volatile("bar.arrive 3, 256;" ::: "memory");
    };

    uint32_t chk = 0;
    auto load_inv = [&](uint32_t (&iv)[30], uint32_t parity) {
      const int lane = fresh_tid() & 31;
      mbar_wait(sb + BAR_INV + 8 * wg, parity);
      chk = 0;
#pragma unroll
      for (int j = 0; j < 7; j++)
        asm volatile("ld.shared.v4.u32 {%0, %1, %2, %3}, [%4];" : "=r"(iv[4 * j]), "=r"(iv[4 * j + 1]), "=r"(iv[4 * j + 2]), "=r"(iv[4 * j + 3])
                     : "r"(sb + OFF_INV + wg * 640 + (lane & 3) * 144 + j * 16) : "memory");
      asm volatile("ld.shared.v2.u32 {%0, %1}, [%2];" : "=r"(iv[28]), "=r"(iv[29]) : "r"(sb + OFF_INV + wg * 640 + (lane & 3) * 144 + 112) : "memory");
    };
    auto norm = [&](uint32_t (&n)[8], const uint32_t (&po)[60], const uint32_t (&iv)[30], auto part) {
      constexpr int k = decltype(part)::value >> 1, j0 = (decltype(part)::value & 1) * 8;
#pragma unroll
      for (int j = 0; j < 8; j++)
        n[j] = j0 + j < 15 ? hfma2(po[15 * k + (j0 + j) % 15], iv[2 * ((j0 + j) % 15)], hfma2(po[15 * k + (j0 + j) % 15], iv[2 * ((j0 + j) % 15) + 1], 0x80008000u)) : 0x3F803F80u;
#pragma unroll
      for (int j = 0; j < 8; j += 2) chk = hfma2(n[j], n[j + 1], chk);
    };
    int od1, od2;
    auto store = [&](const uint32_t (&n)[8], const char* optr, auto part) {
      constexpr int k = decltype(part)::value >> 1, off = (8 * (k & 1) + 64 * (k >> 1)) * NROWS * 2;
      if ((decltype(part)::value & 1) == 0)
        asm volatile(
            "{\n.reg .pred p;\nsetp.ne.u64 p, %8, 0;\n"
            "@p st.global.v4.u32 [%8 + %9], {%0, %1, %2, %3};\n@p st.global.v4.u32 [%8 + %9 + 512], {%4, %5, %6, %7};\n}\n"
            ::"r"(n[0]), "r"(n[1]), "r"(n[2]), "r"(n[3]), "r"(n[4]), "r"(n[5]), "r"(n[6]), "r"(n[7]), "l"(optr), "n"(off) : "memory");
      else
        asm volatile(
            "{\n.reg .pred p;\n.reg .b64 b, c;\nsetp.ne.u64 p, %7, 0;\nmad.wide.s32 b, %9, 1, %7;\nmad.wide.s32 c, %10, 1, %7;\n"
            "@p st.global.v4.u32 [%7 + %8 + 1024], {%0, %1, %2, %3};\n@p st.global.v2.u32 [b + %8], {%4, %5};\n@p st.global.u32 [c + %8], %6;\n}\n"
            ::"r"(n[0]), "r"(n[1]), "r"(n[2]), "r"(n[3]), "r"(n[4]), "r"(n[5]), "r"(n[6]), "l"(optr), "n"(off), "r"(od1), "r"(od2) : "memory");
    };
    auto put = [&](const uint32_t (&po)[60], const uint32_t (&iv)[30], const char* optr, auto part) {
      uint32_t n[8];
      norm(n, po, iv, part);
      store(n, optr, part);
    };
    auto out_ptr = [&](int u) {
      const int lane = fresh_tid() & 31;
      const int k = unit_head(u, rank) * DH + 16 * w + (lane >> 2), b = unit_batch(u), q = lane & 3;
      const uint32_t i0 = o_idx(k, o_pos(b, wg, 2 * q));
      od1 = 2 * (int)(o_idx(k, o_pos(b, wg, 96 + 2 * q)) - i0);
      od2 = 2 * (int)(o_idx(k, o_pos(b, wg, 112 + 2 * q)) - i0);
      return reinterpret_cast<const char*>(P.o + i0);
    };
    auto unsafe = [&](bool valid) {
      const bool b = valid && ((chk & 0x7F80u) == 0x7F80u || (chk & 0x7F800000u) == 0x7F800000u);
      return __any_sync(~0u, bar_red_or(wg, b));
    };
    auto publish = [&]() { __syncwarp(); warp_arrive(sb + BAR_STAGE + 8 * wg); };

    uint32_t po[60];
#pragma unroll
    for (int i = 0; i < 60; i++) po[i] = 0;
    int id = 0;
    bool more;
    do {
      float o0[60], o1[60];
      uint32_t prev = 0;
      auto qstep = [&](int s, int acc) {
        const uint32_t j = s & 3, par = ((s >> 2) + (j < 2 ? it : 0)) & 1;
        TR(it * 160 + 3 * s);
        ring_wait();
        TR(it * 160 + 3 * s + 1);
        mbar_wait(sb + BAR_XFULL + 32 * wg + 8 * j, par);
        TR(it * 160 + 3 * s + 2);
        if (s >= ALT_FROM) turn_wait();
        wg_fence();
        mma_tn(o0, o1, ring_addr(), ((sb & 0x3FFFF) + OFF_Q + x_slot(wg, j)) >> 4, acc);
        wg_commit();
        if (s >= ALT_FROM || (s == ALT_FROM - 1 && wg == 1)) turn_pass();
        if (s > 0 && s <= EREL_FROM) {
          wg_wait<1>();
          release(prev);
          if (s <= 6) warp_arrive_cl(xempty + 8 * ((s - 1) & 3));
        }
        prev = r.slot;
        r.next();
      };
      auto qdone = [&](int s) {
        if (s >= EREL_FROM) {
          wg_wait<0>();
          release(prev);
          if (s <= 5) warp_arrive_cl(xempty + 8 * (s & 3));
        }
      };
      qstep(0, 0);
      qstep(1, 1);
      const int up = (it > 3 ? id : cl) + ((int)it - 1) * ncl;
      const char* optr = out_ptr(up);
      if (it == 0) optr = nullptr;
      uint32_t n7[8];
      {
        uint32_t iv[30];
        load_inv(iv, (it + 1) & 1); put(po, iv, optr, IC<0>());
        qstep(2, 1); put(po, iv, optr, IC<1>()); qdone(2);
        qstep(3, 1); put(po, iv, optr, IC<2>()); qdone(3);
        qstep(4, 1); put(po, iv, optr, IC<3>()); qdone(4);
        qstep(5, 1); put(po, iv, optr, IC<4>()); qdone(5);
        qstep(6, 1); put(po, iv, optr, IC<5>()); qdone(6);
        qstep(7, 1); put(po, iv, optr, IC<6>());
        norm(n7, po, iv, IC<7>());
        qdone(7);
        if (LATE_AT == 3 || (LATE_AT == 5 && wg == 1)) store(n7, optr, IC<7>());
      }
      TR(it * 160 + 24);
      const uint32_t a8 = ring_addr(), slot8 = r.slot;
      ring_wait();
      r.next();
      TR(it * 160 + 25);
      mbar_wait(sb + BAR_XFULL + 32 * wg, it & 1);
      TR(it * 160 + 26);
      auto wait9 = [&]() {
        TR(it * 160 + 27);
        ring_wait();
        TR(it * 160 + 28);
        mbar_wait(sb + BAR_XFULL + 32 * wg + 8, it & 1);
        TR(it * 160 + 29);
      };
      if (PRE9) wait9();
      turn_wait();
      wg_fence();
      mma_tn(o0, o1, a8, qd, 1);
      wg_commit();
      if (!PRE9) { wait9(); wg_fence(); }
      mma_tn_split(o0, o1, ring_addr(), qd + (XB >> 4));
      turn_pass();
      wg_wait<2>();
      if (EREL_FROM > 7) release(prev);
      release(slot8);
      if (LATE_AT == 4 || (LATE_AT == 5 && wg == 0)) store(n7, optr, IC<7>());
      auto put_q = [&](const float (&o)[60], uint32_t dst) {
        bar_sync(wg);
#pragma unroll
        for (int j = 0; j < 14; j += 2)
          stsm4t(dst + j * 1024, pack(o[4 * j] * QSCALE, o[4 * j + 1] * QSCALE), pack(o[4 * j + 2] * QSCALE, o[4 * j + 3] * QSCALE),
                 pack(o[4 * j + 4] * QSCALE, o[4 * j + 5] * QSCALE), pack(o[4 * j + 6] * QSCALE, o[4 * j + 7] * QSCALE));
        stsm2t(dst + 14 * 1024, pack(o[56] * QSCALE, o[57] * QSCALE), pack(o[58] * QSCALE, o[59] * QSCALE));
      };
      wg_wait<1>();
      reg_fence(o0);
      put_q(o0, qreg + st_off);
      wg_wait<0>();
      reg_fence(o1);
      release(r.slot);
      r.next();
      TR(it * 160 + 30);
      put_q(o1, qreg + XB + st_off);
      fence_async_smem();
      if (unsafe(it > 0)) {
        slow_path(P, unit_batch(up), unit_head(up, rank), wg, w, fresh_tid() & 31);
        optr = nullptr;
        if (!DPRO) {
#pragma unroll
          for (int i = 0; i < 60; i++) o0[i] = o1[i] = 0.f;
        }
      }
      TR(it * 160 + 32); TG(it * 160 + 142);

      float sc[60], l[30];
      uint32_t slot0 = r.slot;
      ring_wait();
      TR(it * 160 + 33);
      turn_wait();
      wg_fence();
      mma_qk(sc, ring_addr(), qd);
      wg_commit();
      r.next();
      uint32_t slot1 = r.slot;
      ring_wait();
      wg_fence();
      mma_qk(o1, ring_addr(), qd);
      wg_commit();
      r.next();
      turn_pass();
      if (LATE_AT == 0) store(n7, optr, IC<7>());
      wg_wait<1>();
      reg_fence(sc);
      TR(it * 160 + 35);
      release(slot0);
      exp_store<0, 15, true>(sc, l, preg + st_off);
      TR(it * 160 + 38); TG(it * 160 + 43);
      slot0 = r.slot;
      ring_wait();
      wg_fence();
      mma_qk(sc, ring_addr(), qd);
      wg_commit();
      r.next();
      wg_wait<1>();
      reg_fence(o1);
      TR(it * 160 + 41);
      release(slot1);
      exp_store<0, 15>(o1, l, preg - 2 * XB + st_off);
      fence_async_smem();
      bar_sync(wg);
      TR(it * 160 + 44);
      slot1 = r.slot;
      ring_wait();
      turn_wait();
      wg_fence();
      mma_tn(o0, o1, ring_addr(), pd, 0);
      wg_commit();
      r.next();
      ring_wait();
      wg_fence();
      mma_tn(o0, o1, ring_addr(), pd - (2 * XB >> 4), 1);
      wg_commit();
      turn_pass();
      if (LATE_AT == 1) store(n7, optr, IC<7>());
      if (it > 0) publish();
      if (it >= 2) id = __shfl_sync(~0u, role(), 0);
      wg_wait<1>();
      reg_fence(sc);
      release(slot0);
      release(slot1);
      bar_sync(wg);
      TR(it * 160 + 47);
      exp_store<0, VREL>(sc, l, preg + st_off);
      wg_wait<0>();
      reg_fence(o0); reg_fence(o1);
      release(r.slot);
      r.next();
      exp_store<VREL, 15>(sc, l, preg + st_off);
      fence_async_smem();
      bar_sync(wg);
      more = id + ((int)it + 1) * ncl < NUNITS;
      const bool gemm = id < nsingle || (NCL == 66 && id >= 58);
#pragma unroll 1
      for (int s = DPRO ? 3 : 1; s < 16; s++) {
        const uint32_t kslot = r.slot;
        TR(it * 160 + 32 + 6 * s); TG(it * 160 + 37 + 6 * s);
        if (s == 8) TRL(it * 160 + 139);
        ring_wait();
        TR(it * 160 + 33 + 6 * s);
        turn_wait();
        wg_fence();
        mma_qk(sc, ring_addr(), qd);
        wg_commit();
        r.next();
        TR(it * 160 + 36 + 6 * s);
        ring_wait();
        TR(it * 160 + 34 + 6 * s);
        wg_fence();
        mma_tn(o0, o1, ring_addr(), pd - ((s - 1) & 1) * (2 * XB >> 4), DPRO || s != 1);
        wg_commit();
        if (wg == 0 || s < 15) turn_pass();
        wg_wait<1>();
        reg_fence(sc);
        TR(it * 160 + 35 + 6 * s);
        release(kslot);
        if (s == 15) {
          if (more) { warp_arrive_cl(xempty); warp_arrive_cl(xempty + 8); }
          else if (gemm) for (int i = 0; i < 3; i++) warp_arrive_cl(mapa(sb + BAR_BEMPTY + 8 * i, i & 1));
        }
        exp_store<0, VREL>(sc, l, preg - (s & 1) * 2 * XB + st_off);
        wg_wait<0>();
        reg_fence(o0); reg_fence(o1);
        release(r.slot);
        r.next();
        exp_store<VREL, 15>(sc, l, preg - (s & 1) * 2 * XB + st_off);
        fence_async_smem();
      }
      const uint32_t tid = fresh_tid();
      bar_sync(wg);
      TR(it * 160 + 128);
      ring_wait();
      wg_fence();
      mma_tn_split(o0, o1, ring_addr(), pd - (2 * XB >> 4));
      {
        float a[16], b[8], c[4];
        const bool b4 = tid & 16, b3 = tid & 8, b2 = tid & 4;
#pragma unroll
        for (int i = 0; i < 16; i++) {
          const float hi = i < 14 ? l[(16 + i) % 30] : 1.f;
          a[i] = (b4 ? hi : l[i]) + __shfl_xor_sync(~0u, b4 ? l[i] : hi, 16);
        }
#pragma unroll
        for (int i = 0; i < 8; i++) b[i] = (b3 ? a[8 + i] : a[i]) + __shfl_xor_sync(~0u, b3 ? a[i] : a[8 + i], 8);
#pragma unroll
        for (int i = 0; i < 4; i++) c[i] = (b2 ? b[4 + i] : b[i]) + __shfl_xor_sync(~0u, b2 ? b[i] : b[4 + i], 4);
        asm volatile("st.shared.v4.f32 [%0], {%1, %2, %3, %4};" ::"r"(sb + OFF_L2 + tid * 16), "f"(c[0]), "f"(c[1]),
                     "f"(c[2]), "f"(c[3]) : "memory");
        __syncwarp();
        warp_arrive(sb + BAR_LSUM + 8 * wg);
      }
      TR(it * 160 + 132);
      TR(it * 160 + 133);
      wg_wait<1>();
      reg_fence(o0);
      TR(it * 160 + 134);
#pragma unroll
      for (int j = 0; j < 15; j++) { po[j] = pack(o0[4 * j], o0[4 * j + 1]); po[15 + j] = pack(o0[4 * j + 2], o0[4 * j + 3]); }
      wg_wait<0>();
      reg_fence(o1);
      release(r.slot);
      r.next();
      if (more) { warp_arrive_cl(xempty + 16); warp_arrive_cl(xempty + 24); }
      else if (gemm) for (int i = 3; i < 6; i++) warp_arrive_cl(mapa(sb + BAR_BEMPTY + 8 * i, i & 1));
      TR(it * 160 + 130);
#pragma unroll
      for (int j = 0; j < 15; j++) { po[30 + j] = pack(o1[4 * j], o1[4 * j + 1]); po[45 + j] = pack(o1[4 * j + 2], o1[4 * j + 3]); }
      TR(it * 160 + 131); TG(it * 160 + 143);
      it++;
    } while (more);
    const bool gemm = id < nsingle || (NCL == 66 && id >= 58);
    const int u = (it > 3 ? id : cl) + ((int)it - 1) * ncl;
    uint32_t pb[60];
#pragma unroll
    for (int i = 0; i < 60; i++) pb[i] = NCL != 66 ? po[i] ^ (gridDim.y - 1) : po[i];

    uint32_t bslot = 0, bphase = 0;
    auto out_row = [&](int lane) {
      const int row = lane & 15;
      return sb + wg * 8192 + (row < 12 ? w * RING_BYTES + row * 656 : (4 + (w >> 1)) * RING_BYTES + ((w & 1) * 4 + row - 12) * 656);
    };
    auto out_stage = [&](const float (&acc)[80], uint32_t col_off) {
      const int lane = fresh_tid() & 31;
      const uint32_t sa = out_row(lane) + col_off + (lane >> 4) * 16;
#pragma unroll
      for (int j = 0; j < 20; j += 2)
        asm volatile("stmatrix.sync.aligned.m8n8.x4.shared.b16 [%0], {%1,%2,%3,%4};" ::"r"(sa + j * 16), "r"(pack(acc[4 * j], acc[4 * j + 1])),
                     "r"(pack(acc[4 * j + 2], acc[4 * j + 3])), "r"(pack(acc[4 * j + 4], acc[4 * j + 5])), "r"(pack(acc[4 * j + 6], acc[4 * j + 7])) : "memory");
    };
    auto out_store = [&](int t, uint32_t bytes) {
      const int lane = fresh_tid() & 31;
      if (EPI_MIX && wg == 1) {
        __syncwarp();
#pragma unroll 1
        for (int h = 0; h < 2; h++) {
          const int row = h * 8 + (lane >> 2);
          const uint32_t src = out_row(row) + (lane & 3) * 16;
          char* dst = reinterpret_cast<char*>(P.out + (size_t)o_row(row_block(t) * 256 + rank * 128 + 64 + w * 16 + row) * DM + (t & 3) * 160) + (lane & 3) * 16;
#pragma unroll 1
          for (uint32_t c = 0; c < bytes; c += 320) {
            uint4 v[5];
#pragma unroll
            for (int i = 0; i < 5; i++)
              asm volatile("ld.shared.v4.u32 {%0, %1, %2, %3}, [%4];" : "=r"(v[i].x), "=r"(v[i].y), "=r"(v[i].z), "=r"(v[i].w) : "r"(src + c + i * 64) : "memory");
#pragma unroll
            for (int i = 0; i < 5; i++) *reinterpret_cast<uint4*>(dst + c + i * 64) = v[i];
          }
        }
        return;
      }
      fence_async_smem();
      __syncwarp();
      if (lane < 16) {
        __nv_bfloat16* dst = P.out + (size_t)o_row(row_block(t) * 256 + rank * 128 + wg * 64 + w * 16 + lane) * DM + (t & 3) * 160;
        asm volatile("cp.async.bulk.global.shared::cta.bulk_group [%0], [%1], %2;" ::"l"(dst), "r"(out_row(lane)), "r"(bytes) : "memory");
        asm volatile("cp.async.bulk.commit_group;" ::: "memory");
        asm volatile("cp.async.bulk.wait_group.read 0;" ::: "memory");
      }
    };
    for (int t = id; t == id || (NCL != 66 && t < nsingle); t += ncl) {
      float acc[80];
      uint32_t prev = 0, bprev = 0;
      const bool tile = t < nsingle;
      const bool last = NCL == 66 || t + ncl >= nsingle;
      auto bstep = [&](int ks, int accf) {
        if (!(ks & 3)) TR(640 + ks / 2); if ((ks & 7) == 0) TG(144 + (ks >> 3));
        ring_wait();
        mbar_wait(sb + BAR_BFULL + 8 * bslot, bphase);
        if (!(ks & 3)) TR(641 + ks / 2);
        wg_fence();
        const uint32_t a = ring_addr() + wg * 512, bd = (((sb & 0x3FFFF) + OFF_Q + bslot * BB) >> 4) | ((4096u >> 4) << 16);
#pragma unroll
        for (int k = 0; k < 4; k++) wgmma_n160<1, 1>(acc, a + LBO64A + k * 128, HI64A, bd + k * 64, HI64, k == 0 ? accf : 1);
        wg_commit();
        if (ks > 0) {
          wg_wait<1>();
          release(prev);
          if (ks < 59 || !last) warp_arrive_cl(mapa(sb + BAR_BEMPTY + 8 * bprev, bprev & 1));
        }
        prev = r.slot; bprev = bslot;
        r.next();
        if (++bslot == 6) { bslot = 0; bphase ^= 1; }
      };
      const char* optr;
      uint32_t iv[30], n3[8], n4[8], n5[8], n6[8], n7[8];
      if (tile) {
        bstep(0, 0);
        bstep(1, 1);
        optr = out_ptr(u);
        if (t != id) optr = nullptr;
        load_inv(iv, (it + 1) & 1);
#pragma unroll 1
        for (int ks = 2; ks < 17; ks++) {
          bstep(ks, 1);
          switch (ks) {
            case 2: put(pb, iv, optr, IC<0>()); break;
            case 4: put(pb, iv, optr, IC<1>()); break;
            case 6: put(pb, iv, optr, IC<2>()); break;
            case 8: put(pb, iv, optr, IC<3>()); break;
            case 10: put(pb, iv, optr, IC<4>()); break;
            case 12: put(pb, iv, optr, IC<5>()); break;
            case 14: put(pb, iv, optr, IC<6>()); break;
            case 16: put(pb, iv, optr, IC<7>()); break;
            default: break;
          }
        }
        wg_wait<0>();
        reg_fence(acc);
#pragma unroll
        for (int i = 0; i < 8; i++) n3[i] = n4[i] = n5[i] = n6[i] = n7[i] = 0;
      } else {
        Ring r2 = r;
        auto first = [&](int ks) {
          if (ks == 0) { TR(640); TG(144); }
          if (gemm) { mbar_wait(sb + BAR_RFULL + 8 * r2.slot, r2.phase); mbar_wait(sb + BAR_BFULL + 16 * ks, 0); }
          wg_fence();
          const uint32_t a = (((sb & 0x3FFFF) + r2.slot * RING_BYTES) >> 4) + wg * 512;
          const uint32_t bd = (((sb & 0x3FFFF) + OFF_Q + 2 * ks * BB) >> 4) | ((4096u >> 4) << 16);
#pragma unroll
          for (int k = 0; k < 4; k++) wgmma_n160<1, 1>(acc, a + LBO64A + k * 128, HI64A, bd + k * 64, HI64, k + ks != 0);
          wg_commit();
          if (ks > 0) {
            wg_wait<1>();
            if (gemm) warp_arrive_cl(mapa(sb + BAR_BEMPTY + 16 * (ks - 1), 0));
          }
          r2.next();
        };
        first(0);
        optr = out_ptr(u);
        load_inv(iv, (it + 1) & 1);
        put(pb, iv, optr, IC<0>());
        first(1);
        put(pb, iv, optr, IC<1>());
        norm(n3, pb, iv, IC<3>()); norm(n4, pb, iv, IC<4>());
        first(2);
        put(pb, iv, optr, IC<2>());
        norm(n5, pb, iv, IC<5>()); norm(n6, pb, iv, IC<6>()); norm(n7, pb, iv, IC<7>());
        wg_wait<0>();
        reg_fence(acc);
      }
      if (unsafe(t == id)) {
        slow_path(P, unit_batch(u), unit_head(u, rank), wg, w, fresh_tid() & 31);
        optr = nullptr;
#pragma unroll
        for (int i = 0; i < 8; i++) n3[i] = n4[i] = n5[i] = n6[i] = n7[i] = 0;
      }
      if (tile && t == id) publish();
      if (!tile) {
        if (gemm) {
          float ac1[80];
          auto half = [&](float (&ac)[80], bool rel, int accf) {
            mbar_wait(sb + BAR_BFULL + 8 * bslot, bphase);
            wg_fence();
            const uint32_t a = ring_addr() + wg * 512, bd = (((sb & 0x3FFFF) + OFF_Q + bslot * BB) >> 4) | ((4096u >> 4) << 16);
#pragma unroll
            for (int k = 0; k < 4; k++) wgmma_n160<1, 1>(ac, a + LBO64A + k * 128, HI64A, bd + k * 64, HI64, k == 0 ? accf : 1);
            wg_commit();
            wg_wait<1>();
            if (rel) warp_arrive_cl(mapa(sb + BAR_BEMPTY + 8 * bprev, bprev & 1));
            bprev = bslot;
          };
          auto dstep = [&](int ks) {
            if (!(ks & 3)) TR(640 + ks / 2); if ((ks & 7) == 0) TG(144 + (ks >> 3));
            ring_wait();
            if (!(ks & 3)) TR(641 + ks / 2);
            half(acc, ks < 62, 1);
            release(prev);
            bslot++;
            half(ac1, ks < 61, 1);
            if (++bslot == 6) { bslot = 0; bphase ^= 1; }
            prev = r.slot; r.next();
          };
          bprev = 4; bslot = 1;
          half(ac1, true, 0);
          prev = r.slot; r.next(); bslot = 3;
          half(ac1, true, 1);
          release(prev); prev = r.slot; r.next(); bslot = 5;
          store(n3, optr, IC<3>());
          half(ac1, true, 1);
          release(prev); prev = r.slot; r.next(); bslot = 0; bphase = 1;
#pragma unroll 1
          for (int ks = 3; ks < 7; ks++) {
            dstep(ks);
            switch (ks) {
              case 3: store(n4, optr, IC<4>()); break;
              case 4: store(n5, optr, IC<5>()); break;
              case 5: store(n6, optr, IC<6>()); break;
              default: store(n7, optr, IC<7>()); break;
            }
          }
          publish();
#pragma unroll 1
          for (int ks = 7; ks < 64; ks++) {
            if (wg == 1 && ks == 62) turn_wait();
            dstep(ks);
          }
          if (wg == 0) turn_pass();
          wg_wait<0>();
          reg_fence(acc); reg_fence(ac1);
          TRL(158); TG(156);
          bar_sync(wg);
          out_stage(acc, 0);
          out_stage(ac1, 320);
          out_store(2 * id - 72, 640);
        } else {
          store(n3, optr, IC<3>()); store(n4, optr, IC<4>()); store(n5, optr, IC<5>()); store(n6, optr, IC<6>()); store(n7, optr, IC<7>());
          publish();
        }
        break;
      }
#pragma unroll 1
      for (int ks = 17; ks < 64; ks++) {
        if (END_SKEW && wg == 1 && ks == 64 - END_SKEW) turn_wait();
        bstep(ks, 1);
      }
      if (END_SKEW && wg == 0) turn_pass();
      wg_wait<0>();
      reg_fence(acc);
      release(prev);
      if (!last) warp_arrive_cl(mapa(sb + BAR_BEMPTY + 8 * bprev, bprev & 1));
      TRL(158); TG(156);
      const int pos0 = row_block(t) * 256 + rank * 128 + wg * 64 + w * 16;
      if (last) {
        bar_sync(wg);
        out_stage(acc, 0);
        out_store(t, 320);
      } else {
        const int lane = fresh_tid() & 31;
        __nv_bfloat16* op0 = P.out + (size_t)o_row(pos0 + (lane >> 2)) * DM + (t & 3) * 160 + (lane & 3) * 2;
        __nv_bfloat16* op1 = P.out + (size_t)o_row(pos0 + (lane >> 2) + 8) * DM + (t & 3) * 160 + (lane & 3) * 2;
#pragma unroll
        for (int j = 0; j < 20; j++) {
          *reinterpret_cast<uint32_t*>(op0 + j * 8) = pack(acc[4 * j], acc[4 * j + 1]);
          *reinterpret_cast<uint32_t*>(op1 + j * 8) = pack(acc[4 * j + 2], acc[4 * j + 3]);
        }
      }
#pragma unroll
      for (int i = 0; i < 60; i++) pb[i] = 0;
    }
    TRL(159);
  }
}

typedef CUresult (*EncodeFn)(CUtensorMap*, CUtensorMapDataType, cuuint32_t, void*, const cuuint64_t*, const cuuint64_t*,
                             const cuuint32_t*, const cuuint32_t*, CUtensorMapInterleave, CUtensorMapSwizzle,
                             CUtensorMapL2promotion, CUtensorMapFloatOOBfill);

void make_map(EncodeFn enc, CUtensorMap* m, const void* p, int rank, const cuuint64_t* dims, const cuuint64_t* strides,
              const cuuint32_t* box, CUtensorMapSwizzle sw, CUtensorMapL2promotion promo) {
  cuuint32_t es[4] = {1, 1, 1, 1};
  enc(m, CU_TENSOR_MAP_DATA_TYPE_BFLOAT16, rank, const_cast<void*>(p), dims, strides, box, es, CU_TENSOR_MAP_INTERLEAVE_NONE, sw,
      promo, CU_TENSOR_MAP_FLOAT_OOB_FILL_NONE);
}

}

extern "C" void kernel_launch(void* const* d_in, const int* in_sizes, int n_in, void* d_out, int out_size) {
  static EncodeFn enc = nullptr;
  static int nclusters = 0;
  static void* o_ptr = nullptr;
  if (!enc) {
    cudaDriverEntryPointQueryResult qr;
    cudaGetDriverEntryPoint("cuTensorMapEncodeTiled", (void**)&enc, cudaEnableDefault, &qr);
    cudaFuncSetAttribute(fused_attn_kernel<66>, cudaFuncAttributeMaxDynamicSharedMemorySize, SMEM_BYTES);
    cudaFuncSetAttribute(fused_attn_kernel<0>, cudaFuncAttributeMaxDynamicSharedMemorySize, SMEM_BYTES);
    cudaGetSymbolAddress(&o_ptr, g_o);
    cudaLaunchConfig_t cfg = {};
    cfg.gridDim = 128; cfg.blockDim = 384; cfg.dynamicSmemBytes = SMEM_BYTES;
    cudaLaunchAttribute at; at.id = cudaLaunchAttributeClusterDimension;
    at.val.clusterDim.x = 2; at.val.clusterDim.y = 1; at.val.clusterDim.z = 1;
    cfg.attrs = &at; cfg.numAttrs = 1;
    int n = 0;
    cudaOccupancyMaxActiveClusters(&n, fused_attn_kernel<66>, &cfg);
    nclusters = n >= 66 ? MAXCL : (n >= 64 || n <= 0 ? 64 : n);
  }
  const __nv_bfloat16* x = (const __nv_bfloat16*)d_in[0];
  const __nv_bfloat16* k = (const __nv_bfloat16*)d_in[1];
  const __nv_bfloat16* v = (const __nv_bfloat16*)d_in[2];
  const __nv_bfloat16* wq = (const __nv_bfloat16*)d_in[3];
  const __nv_bfloat16* wo = (const __nv_bfloat16*)d_in[4];
  CUtensorMap tm_x, tm_wq, tm_k, tm_v, tm_o, tm_wo;
  const auto S128 = CU_TENSOR_MAP_SWIZZLE_128B;
  const auto P128 = CU_TENSOR_MAP_L2_PROMOTION_L2_128B, P256 = CU_TENSOR_MAP_L2_PROMOTION_L2_256B;
  { cuuint64_t d[2] = {DM, NB * SQ}, s[1] = {DM * 2}; cuuint32_t b[2] = {64, 120}; make_map(enc, &tm_x, x, 2, d, s, b, S128, X_PROMO); }
  { cuuint64_t d[3] = {64, DM, HD / 64}, s[2] = {HD * 2, 128}; cuuint32_t b[3] = {64, 64, 2}; make_map(enc, &tm_wq, wq, 3, d, s, b, S128, P256); }
  { cuuint64_t d[3] = {64, NB * NH * SK, 2}, s[2] = {DH * 2, 128}; cuuint32_t b[3] = {64, 64, 2};
    make_map(enc, &tm_k, k, 3, d, s, b, S128, P128); make_map(enc, &tm_v, v, 3, d, s, b, S128, P128); }
  { cuuint64_t d[4] = {256, 2, HD / 8, NROWS / 64}, s[3] = {512, NROWS * 16, 1024}; cuuint32_t b[4] = {256, 2, 8, 2};
    make_map(enc, &tm_o, o_ptr, 4, d, s, b, CU_TENSOR_MAP_SWIZZLE_NONE, P256); }
  { cuuint64_t d[3] = {32, HD, DM / 32}, s[2] = {DM * 2, 64}; cuuint32_t b[3] = {32, 64, 5};
    make_map(enc, &tm_wo, wo, 3, d, s, b, CU_TENSOR_MAP_SWIZZLE_64B, P128); }
  Params P{x, k, v, wq, (__nv_bfloat16*)d_out, (__nv_bfloat16*)o_ptr};
  if (nclusters == 66) fused_attn_kernel<66><<<132, 384, SMEM_BYTES>>>(tm_x, tm_wq, tm_k, tm_v, tm_o, tm_wo, P);
  else fused_attn_kernel<0><<<2 * nclusters, 384, SMEM_BYTES>>>(tm_x, tm_wq, tm_k, tm_v, tm_o, tm_wo, P);
}
```

```cpp
#include <cuda_runtime.h>
#include <cuda.h>
#include <cuda_bf16.h>
#include <stdint.h>

namespace {

constexpr int NB = 16, SQ = 240, DM = 640, NH = 32, SK = 1024, DH = 128, HD = NH * DH;
constexpr int NROWS = NB * SQ;
constexpr int NUNITS = 256;
#define DPRO 1
#define LATE_AT 4
#define ALT_FROM 4
#define END_SKEW 5
#define VREL 6
#define PF_HOLD 6
#define PF_N 4
#define PF_J0 3
#define PF_STEP 3
#define ROT 0
#define O_EF 1
#define B_ORDER 1
#define WO_PF 6
#define ROLE_AT 0
#define PAUSE_NS 11000
#define PAUSE_AT 2
#define EARLY 1
#define EARLY_X 2
#define EARLY_W 2
#define X_PROMO P128
#define PAUSE_J -1
#define PAUSE_SPREAD 0
#define WO_PF0 1
#define EPI_MIX 1
#define K2_AT 0
#define EREL_FROM 4
#define PRE9 0
#define MAXCL 66
#define SMID_TOP 88
constexpr int NOTILES = 60;
constexpr float QSCALE = 0.08838834764831845f * 1.4426950408889634f;
constexpr float L_MIN = 9.5367431640625e-07f;
constexpr float L_MAX = 1.152921504606846976e18f;

constexpr uint32_t RING_SLOTS = 6, RING_BYTES = 16384;
constexpr uint32_t XB = 15360;
constexpr uint32_t BB = 20480;
constexpr uint32_t OFF_Q = RING_SLOTS * RING_BYTES;
constexpr uint32_t OFF_P = OFF_Q + 4 * XB;
constexpr uint32_t OFF_INV = OFF_P + 4 * XB;
constexpr uint32_t OFF_L2 = OFF_INV + 1280;
constexpr uint32_t OFF_BAR = OFF_L2 + 4096;
constexpr uint32_t BAR_RFULL = OFF_BAR, BAR_REMPTY = BAR_RFULL + 48, BAR_XFULL = BAR_REMPTY + 48,
    BAR_XEMPTY = BAR_XFULL + 64, BAR_BFULL = BAR_XEMPTY + 32, BAR_BEMPTY = BAR_BFULL + 48, BAR_STAGE = BAR_BEMPTY + 48;
constexpr uint32_t BAR_ROLE = BAR_STAGE + 16, BAR_LSUM = BAR_ROLE + 24, BAR_INV = BAR_LSUM + 16;
constexpr uint32_t OFF_TR = BAR_INV + 16;
constexpr uint32_t SMEM_BYTES = OFF_TR + 1024;

constexpr uint32_t HI128 = (1u << 30) | (1024 >> 4);
constexpr uint32_t HI64 = (2u << 30) | (512 >> 4);
constexpr uint32_t HI64A = (2u << 30) | (1024 >> 4), LBO64A = (512u >> 4) << 16;

__device__ __nv_bfloat16 g_o[HD * NROWS];
__device__ unsigned g_cnt[67 * 8];
#define TS(i)
#define TRL(i)
#define TR(i)
#define TG(i)

struct Params {
  const __nv_bfloat16 *x, *k, *v, *wq;
  __nv_bfloat16 *out, *o;
};

__device__ __forceinline__ void wg_fence() { asm volatile("wgmma.fence.sync.aligned;" ::: "memory"); }
__device__ __forceinline__ void wg_commit() { asm volatile("wgmma.commit_group.sync.aligned;" ::: "memory"); }
template <int N> __device__ __forceinline__ void wg_wait() { asm volatile("wgmma.wait_group.sync.aligned %0;" ::"n"(N) : "memory"); }
template <int N> __device__ __forceinline__ void reg_fence(float (&r)[N]) {
#pragma unroll
  for (int i = 0; i < N; i++) asm volatile("" : "+f"(r[i])::"memory");
}
template <int TA, int TB>
__device__ __forceinline__ void wgmma_n120(float (&d)[60], uint32_t a_lo, uint32_t a_hi, uint32_t b_lo, uint32_t b_hi, int acc) {
  asm volatile(
      "{\n.reg .pred p;\n.reg .b64 da, db;\nsetp.ne.b32 p, %64, 0;\n"
      "mov.b64 da, {%60, %61};\nmov.b64 db, {%62, %63};\n"
      "wgmma.mma_async.sync.aligned.m64n120k16.f32.bf16.bf16 {"
      "%0, %1, %2, %3, %4, %5, %6, %7, %8, %9, %10, %11, %12, %13, %14, %15, %16, %17, %18, %19, %20, %21, %22, %23, "
      "%24, %25, %26, %27, %28, %29, %30, %31, %32, %33, %34, %35, %36, %37, %38, %39, %40, %41, %42, %43, %44, %45, "
      "%46, %47, %48, %49, %50, %51, %52, %53, %54, %55, %56, %57, %58, %59"
      "}, da, db, p, 1, 1, %65, %66;\n}\n"
      : "+f"(d[0]), "+f"(d[1]), "+f"(d[2]), "+f"(d[3]), "+f"(d[4]), "+f"(d[5]), "+f"(d[6]), "+f"(d[7]), "+f"(d[8]),
        "+f"(d[9]), "+f"(d[10]), "+f"(d[11]), "+f"(d[12]), "+f"(d[13]), "+f"(d[14]), "+f"(d[15]), "+f"(d[16]),
        "+f"(d[17]), "+f"(d[18]), "+f"(d[19]), "+f"(d[20]), "+f"(d[21]), "+f"(d[22]), "+f"(d[23]), "+f"(d[24]),
        "+f"(d[25]), "+f"(d[26]), "+f"(d[27]), "+f"(d[28]), "+f"(d[29]), "+f"(d[30]), "+f"(d[31]), "+f"(d[32]),
        "+f"(d[33]), "+f"(d[34]), "+f"(d[35]), "+f"(d[36]), "+f"(d[37]), "+f"(d[38]), "+f"(d[39]), "+f"(d[40]),
        "+f"(d[41]), "+f"(d[42]), "+f"(d[43]), "+f"(d[44]), "+f"(d[45]), "+f"(d[46]), "+f"(d[47]), "+f"(d[48]),
        "+f"(d[49]), "+f"(d[50]), "+f"(d[51]), "+f"(d[52]), "+f"(d[53]), "+f"(d[54]), "+f"(d[55]), "+f"(d[56]),
        "+f"(d[57]), "+f"(d[58]), "+f"(d[59])
      : "r"(a_lo), "r"(a_hi), "r"(b_lo), "r"(b_hi), "r"(acc), "n"(TA), "n"(TB));
}

template <int TA, int TB>
__device__ __forceinline__ void wgmma_n160(float (&d)[80], uint32_t a_lo, uint32_t a_hi, uint32_t b_lo, uint32_t b_hi, int acc) {
  asm volatile(
      "{\n.reg .pred p;\n.reg .b64 da, db;\nsetp.ne.b32 p, %84, 0;\n"
      "mov.b64 da, {%80, %81};\nmov.b64 db, {%82, %83};\n"
      "wgmma.mma_async.sync.aligned.m64n160k16.f32.bf16.bf16 {"
      "%0, %1, %2, %3, %4, %5, %6, %7, %8, %9, %10, %11, %12, %13, %14, %15, %16, %17, %18, %19, %20, %21, %22, %23, "
      "%24, %25, %26, %27, %28, %29, %30, %31, %32, %33, %34, %35, %36, %37, %38, %39, %40, %41, %42, %43, %44, %45, "
      "%46, %47, %48, %49, %50, %51, %52, %53, %54, %55, %56, %57, %58, %59, %60, %61, %62, %63, %64, %65, %66, %67, "
      "%68, %69, %70, %71, %72, %73, %74, %75, %76, %77, %78, %79"
      "}, da, db, p, 1, 1, %85, %86;\n}\n"
      : "+f"(d[0]), "+f"(d[1]), "+f"(d[2]), "+f"(d[3]), "+f"(d[4]), "+f"(d[5]), "+f"(d[6]), "+f"(d[7]), "+f"(d[8]),
        "+f"(d[9]), "+f"(d[10]), "+f"(d[11]), "+f"(d[12]), "+f"(d[13]), "+f"(d[14]), "+f"(d[15]), "+f"(d[16]),
        "+f"(d[17]), "+f"(d[18]), "+f"(d[19]), "+f"(d[20]), "+f"(d[21]), "+f"(d[22]), "+f"(d[23]), "+f"(d[24]),
        "+f"(d[25]), "+f"(d[26]), "+f"(d[27]), "+f"(d[28]), "+f"(d[29]), "+f"(d[30]), "+f"(d[31]), "+f"(d[32]),
        "+f"(d[33]), "+f"(d[34]), "+f"(d[35]), "+f"(d[36]), "+f"(d[37]), "+f"(d[38]), "+f"(d[39]), "+f"(d[40]),
        "+f"(d[41]), "+f"(d[42]), "+f"(d[43]), "+f"(d[44]), "+f"(d[45]), "+f"(d[46]), "+f"(d[47]), "+f"(d[48]),
        "+f"(d[49]), "+f"(d[50]), "+f"(d[51]), "+f"(d[52]), "+f"(d[53]), "+f"(d[54]), "+f"(d[55]), "+f"(d[56]),
        "+f"(d[57]), "+f"(d[58]), "+f"(d[59]), "+f"(d[60]), "+f"(d[61]), "+f"(d[62]), "+f"(d[63]), "+f"(d[64]),
        "+f"(d[65]), "+f"(d[66]), "+f"(d[67]), "+f"(d[68]), "+f"(d[69]), "+f"(d[70]), "+f"(d[71]), "+f"(d[72]),
        "+f"(d[73]), "+f"(d[74]), "+f"(d[75]), "+f"(d[76]), "+f"(d[77]), "+f"(d[78]), "+f"(d[79])
      : "r"(a_lo), "r"(a_hi), "r"(b_lo), "r"(b_hi), "r"(acc), "n"(TA), "n"(TB));
}
__device__ __forceinline__ void mbar_init(uint32_t bar, int cnt) { asm volatile("mbarrier.init.shared::cta.b64 [%0], %1;" ::"r"(bar), "r"(cnt)); }
__device__ __forceinline__ void mbar_expect(uint32_t bar, uint32_t bytes) {
  asm volatile("mbarrier.arrive.expect_tx.shared::cta.b64 _, [%0], %1;" ::"r"(bar), "r"(bytes) : "memory");
}
__device__ __forceinline__ uint32_t mapa(uint32_t addr, uint32_t cta) {
  uint32_t r; asm("mapa.shared::cluster.u32 %0, %1, %2;" : "=r"(r) : "r"(addr), "r"(cta)); return r;
}
__device__ __forceinline__ void mbar_expect_cl(uint32_t cbar, uint32_t bytes) {
  asm volatile("mbarrier.arrive.expect_tx.shared::cluster.b64 _, [%0], %1;" ::"r"(cbar), "r"(bytes) : "memory");
}
__device__ __forceinline__ void mbar_arrive(uint32_t bar) { asm volatile("mbarrier.arrive.shared::cta.b64 _, [%0];" ::"r"(bar) : "memory"); }
__device__ __forceinline__ void mbar_arrive_cl(uint32_t cbar) { asm volatile("mbarrier.arrive.shared::cluster.b64 _, [%0];" ::"r"(cbar) : "memory"); }
__device__ __forceinline__ void warp_arrive(uint32_t bar) {
  asm volatile("{\n.reg .pred p;\nelect.sync _|p, 0xffffffff;\n@p mbarrier.arrive.shared::cta.b64 _, [%0];\n}\n" ::"r"(bar) : "memory");
}
__device__ __forceinline__ void warp_arrive_cl(uint32_t cbar) {
  asm volatile("{\n.reg .pred p;\nelect.sync _|p, 0xffffffff;\n@p mbarrier.arrive.shared::cluster.b64 _, [%0];\n}\n" ::"r"(cbar) : "memory");
}
__device__ __forceinline__ void mbar_wait(uint32_t bar, uint32_t parity) {
  asm volatile(
      "{\n.reg .pred p;\n.reg .u32 n;\n"
      "mbarrier.try_wait.parity.shared::cta.b64 p, [%0], %1;\n@p bra WAIT_DONE;\n"
      "mov.u32 n, 0;\n"
      "WAIT_LOOP:\n"
      "mbarrier.try_wait.parity.shared::cta.b64 p, [%0], %1;\n@p bra WAIT_DONE;\n"
      "add.u32 n, n, 1;\nsetp.lt.u32 p, n, 0x4000000;\n@p bra WAIT_LOOP;\ntrap;\n"
      "WAIT_DONE:\n}\n" ::"r"(bar), "r"(parity) : "memory");
}
__device__ __forceinline__ void mbar_wait_cl(uint32_t bar, uint32_t parity) {
  asm volatile(
      "{\n.reg .pred p;\n.reg .u32 n;\nmov.u32 n, 0;\n"
      "WAIT_LOOP:\n"
      "mbarrier.try_wait.parity.acquire.cluster.shared::cta.b64 p, [%0], %1;\n@p bra WAIT_DONE;\n"
      "add.u32 n, n, 1;\nsetp.lt.u32 p, n, 0x4000000;\n@p bra WAIT_LOOP;\ntrap;\n"
      "WAIT_DONE:\n}\n" ::"r"(bar), "r"(parity) : "memory");
}
__device__ __forceinline__ void tma3d(uint32_t dst, const CUtensorMap* m, int c0, int c1, int c2, uint32_t bar) {
  asm volatile("cp.async.bulk.tensor.3d.shared::cluster.global.mbarrier::complete_tx::bytes [%0], [%1, {%3, %4, %5}], [%2];"
               ::"r"(dst), "l"(m), "r"(bar), "r"(c0), "r"(c1), "r"(c2) : "memory");
}
__device__ __forceinline__ void tma3d_hint(uint32_t dst, const CUtensorMap* m, int c0, int c1, int c2, uint32_t bar, uint64_t pol) {
  asm volatile("cp.async.bulk.tensor.3d.shared::cluster.global.mbarrier::complete_tx::bytes.L2::cache_hint [%0], [%1, {%3, %4, %5}], [%2], %6;"
               ::"r"(dst), "l"(m), "r"(bar), "r"(c0), "r"(c1), "r"(c2), "l"(pol) : "memory");
}
__device__ __forceinline__ void tma2d_mc(uint32_t dst, const CUtensorMap* m, int c0, int c1, uint32_t bar) {
  asm volatile("cp.async.bulk.tensor.2d.shared::cluster.global.mbarrier::complete_tx::bytes.multicast::cluster [%0], [%1, {%3, %4}], [%2], %5;"
               ::"r"(dst), "l"(m), "r"(bar), "r"(c0), "r"(c1), "h"((uint16_t)3) : "memory");
}
__device__ __forceinline__ void tma3d_mc(uint32_t dst, const CUtensorMap* m, int c0, int c1, int c2, uint32_t bar) {
  asm volatile("cp.async.bulk.tensor.3d.shared::cluster.global.mbarrier::complete_tx::bytes.multicast::cluster [%0], [%1, {%3, %4, %5}], [%2], %6;"
               ::"r"(dst), "l"(m), "r"(bar), "r"(c0), "r"(c1), "r"(c2), "h"((uint16_t)3) : "memory");
}
__device__ __forceinline__ void l2_prefetch(const void* p, uint32_t bytes) {
  asm volatile("cp.async.bulk.prefetch.L2.global [%0], %1;" ::"l"(p), "r"(bytes) : "memory");
}
__device__ __forceinline__ void fence_async_smem() { asm volatile("fence.proxy.async.shared::cta;" ::: "memory"); }
__device__ __forceinline__ void bar_sync(int wg) {
  if (wg == 0) asm volatile("bar.sync 1, 128;" ::: "memory");
  else asm volatile("bar.sync 2, 128;" ::: "memory");
}
__device__ __forceinline__ bool bar_red_or(int id, bool v) {
  uint32_t r;
  asm volatile("{\n.reg .pred p, q;\nsetp.ne.u32 p, %2, 0;\nbar.red.or.pred q, %1, 128, p;\nselp.u32 %0, 1, 0, q;\n}\n"
               : "=r"(r) : "r"(1 + id), "r"((uint32_t)v) : "memory");
  return r != 0;
}
__device__ __forceinline__ uint32_t hfma2(uint32_t a, uint32_t b, uint32_t c) { uint32_t r; asm("fma.rn.bf16x2 %0, %1, %2, %3;" : "=r"(r) : "r"(a), "r"(b), "r"(c)); return r; }
__device__ __forceinline__ float ex2(float x) { float y; asm("ex2.approx.ftz.f32 %0, %1;" : "=f"(y) : "f"(x)); return y; }
__device__ __forceinline__ uint32_t pack(float lo, float hi) { uint32_t r; asm("cvt.rn.bf16x2.f32 %0, %1, %2;" : "=r"(r) : "f"(hi), "f"(lo)); return r; }
__device__ __forceinline__ void stsm4t(uint32_t a, uint32_t r0, uint32_t r1, uint32_t r2, uint32_t r3) {
  asm volatile("stmatrix.sync.aligned.m8n8.x4.trans.shared.b16 [%0], {%1,%2,%3,%4};" ::"r"(a), "r"(r0), "r"(r1), "r"(r2), "r"(r3) : "memory");
}
__device__ __forceinline__ void stsm2t(uint32_t a, uint32_t r0, uint32_t r1) {
  asm volatile("stmatrix.sync.aligned.m8n8.x2.trans.shared.b16 [%0], {%1,%2};" ::"r"(a), "r"(r0), "r"(r1) : "memory");
}
__device__ __forceinline__ void mma16816(float (&d)[4], const uint32_t (&a)[4], uint32_t b0, uint32_t b1) {
  asm volatile("mma.sync.aligned.m16n8k16.row.col.f32.bf16.bf16.f32 {%0,%1,%2,%3}, {%4,%5,%6,%7}, {%8,%9}, {%0,%1,%2,%3};"
               : "+f"(d[0]), "+f"(d[1]), "+f"(d[2]), "+f"(d[3]) : "r"(a[0]), "r"(a[1]), "r"(a[2]), "r"(a[3]), "r"(b0), "r"(b1));
}

__device__ __forceinline__ uint32_t fresh_tid() { uint32_t t; asm volatile("mov.u32 %0, %tid.x;" : "=r"(t)); return t; }

template <int V> struct IC { static constexpr int value = V; };

struct Ring {
  uint32_t slot = 0, phase = 0;
  __device__ __forceinline__ void next() { if (++slot == RING_SLOTS) { slot = 0; phase ^= 1; } }
};

__device__ __forceinline__ void mma_tn(float (&o0)[60], float (&o1)[60], uint32_t a, uint32_t b, int acc) {
#pragma unroll
  for (int k = 0; k < 4; k++) {
    wgmma_n120<1, 0>(o0, a + k * 128, HI128, b + k * 2, HI128, k == 0 ? acc : 1);
    wgmma_n120<1, 0>(o1, a + 512 + k * 128, HI128, b + k * 2, HI128, k == 0 ? acc : 1);
  }
}
__device__ __forceinline__ void mma_tn_split(float (&o0)[60], float (&o1)[60], uint32_t a, uint32_t b) {
#pragma unroll
  for (int k = 0; k < 4; k++) wgmma_n120<1, 0>(o0, a + k * 128, HI128, b + k * 2, HI128, 1);
  wg_commit();
#pragma unroll
  for (int k = 0; k < 4; k++) wgmma_n120<1, 0>(o1, a + 512 + k * 128, HI128, b + k * 2, HI128, 1);
  wg_commit();
}
__device__ __forceinline__ void mma_qk(float (&s)[60], uint32_t a, uint32_t q) {
#pragma unroll
  for (int k = 0; k < 8; k++)
    wgmma_n120<0, 0>(s, a + (k >> 2) * 512 + (k & 3) * 2, HI128, q + (k >> 2) * (XB >> 4) + (k & 3) * 2, HI128, k != 0);
}
template <int J0, int J1, bool FIRST = false>
__device__ __forceinline__ void exp_store(const float (&s)[60], float (&l)[30], uint32_t dst) {
#pragma unroll
  for (int j = J0; j < J1; j += 2) {
    uint32_t p[4];
#pragma unroll
    for (int jj = 0; jj < 2; jj++) {
      if (j + jj < 15) {
        const int c = j + jj;
        float e0 = ex2(s[4 * c]), e1 = ex2(s[4 * c + 1]), e2 = ex2(s[4 * c + 2]), e3 = ex2(s[4 * c + 3]);
        if (FIRST) { l[2 * c] = e0 + e2; l[2 * c + 1] = e1 + e3; }
        else { l[2 * c] += e0; l[2 * c + 1] += e1; l[2 * c] += e2; l[2 * c + 1] += e3; }
        p[2 * jj] = pack(e0, e1); p[2 * jj + 1] = pack(e2, e3);
      }
    }
    if (j + 1 < 15) stsm4t(dst + j * 1024, p[0], p[1], p[2], p[3]);
    else stsm2t(dst + j * 1024, p[0], p[1]);
  }
}

__device__ __forceinline__ int o_pos(int b, int wg, int r) {
  const int j = r >> 3, q = (r >> 1) & 3, c = r & 1, o = b & 1, base = (b >> 1) * 480;
  if (j < 12) return base + (o * 9 + wg * 3 + (j >> 2)) * 32 + q * 8 + (j & 3) * 2 + c;
  if (j < 14) return base + (6 + 2 * o) * 32 + wg * 16 + q * 4 + (j - 12) * 2 + c;
  return base + 7 * 32 + (o * 2 + wg) * 8 + q * 2 + c;
}
__device__ __forceinline__ int o_row(int p) {
  const int pair = p / 480, a = (p - pair * 480) >> 5, in = p & 31, c = p & 1;
  int tile, row;
  if (a == 7) { tile = in >> 3; row = 112 + (in & 7); }
  else if (a == 6 || a == 8) { tile = a - 6 + (in >> 4); row = (12 + ((in >> 1) & 1)) * 8 + ((in >> 2) & 3) * 2 + c; }
  else { const int f = a > 8 ? a - 3 : a; tile = f / 3; row = ((f - tile * 3) * 4 + ((in >> 1) & 3)) * 8 + (in >> 3) * 2 + c; }
  return pair * 480 + tile * 120 + row;
}
__device__ __forceinline__ uint32_t o_idx(int k, int p) {
  return ((k >> 3) * (NROWS / 32) + (p >> 5)) * 256 + (k & 7) * 32 + ((((p >> 3) & 3) ^ ((k & 7) >> 1)) << 3) + (p & 7);
}

__device__ __forceinline__ void slow_path(const Params& P, int b, int h, int wg, int w, int lane) {
  const int g = lane >> 2, q = lane & 3, row0 = wg * 120;
  const uint16_t* wq = reinterpret_cast<const uint16_t*>(P.wq) + h * DH + g;
  const __nv_bfloat16* kp = P.k + (size_t)(b * NH + h) * SK * DH;
  const uint16_t* vp = reinterpret_cast<const uint16_t*>(P.v) + (size_t)(b * NH + h) * SK * DH + g;
#pragma unroll 1
  for (int t = w; t < 8; t += 4) {
    const int r0 = 16 * t + g, r1 = r0 + 8;
    const __nv_bfloat16* x0 = P.x + (size_t)(b * SQ + row0 + r0) * DM + 2 * q;
    const __nv_bfloat16* x1 = P.x + (size_t)(b * SQ + row0 + min(r1, 119)) * DM + 2 * q;
    float o[16][4];
#pragma unroll
    for (int n = 0; n < 16; n++) o[n][0] = o[n][1] = o[n][2] = o[n][3] = 0.f;
#pragma unroll 1
    for (int k0 = 0; k0 < DM; k0 += 16) {
      uint32_t a[4] = {*(const uint32_t*)(x0 + k0), *(const uint32_t*)(x1 + k0), *(const uint32_t*)(x0 + k0 + 8), *(const uint32_t*)(x1 + k0 + 8)};
      const uint16_t* wr = wq + (size_t)(k0 + 2 * q) * HD;
#pragma unroll
      for (int n = 0; n < 16; n++) {
        if ((n & 3) == 0) __syncwarp();
        mma16816(o[n], a, wr[8 * n] | ((uint32_t)wr[8 * n + HD] << 16), wr[8 * n + 8 * HD] | ((uint32_t)wr[8 * n + 9 * HD] << 16));
      }
    }
    uint32_t qa[8][4];
#pragma unroll
    for (int k = 0; k < 8; k++) {
      qa[k][0] = pack(o[2 * k][0] * QSCALE, o[2 * k][1] * QSCALE);
      qa[k][1] = pack(o[2 * k][2] * QSCALE, o[2 * k][3] * QSCALE);
      qa[k][2] = pack(o[2 * k + 1][0] * QSCALE, o[2 * k + 1][1] * QSCALE);
      qa[k][3] = pack(o[2 * k + 1][2] * QSCALE, o[2 * k + 1][3] * QSCALE);
    }
#pragma unroll
    for (int n = 0; n < 16; n++) o[n][0] = o[n][1] = o[n][2] = o[n][3] = 0.f;
    float m0 = -INFINITY, m1 = -INFINITY, l0 = 0.f, l1 = 0.f;
#pragma unroll 1
    for (int key0 = 0; key0 < SK; key0 += 16) {
      float s[2][4];
#pragma unroll
      for (int nt = 0; nt < 2; nt++) {
        s[nt][0] = s[nt][1] = s[nt][2] = s[nt][3] = 0.f;
        const __nv_bfloat16* kr = kp + (size_t)(key0 + 8 * nt + g) * DH + 2 * q;
#pragma unroll
        for (int k = 0; k < 8; k++) mma16816(s[nt], qa[k], *(const uint32_t*)(kr + 16 * k), *(const uint32_t*)(kr + 16 * k + 8));
      }
      float n0 = fmaxf(fmaxf(s[0][0], s[0][1]), fmaxf(s[1][0], s[1][1])), n1 = fmaxf(fmaxf(s[0][2], s[0][3]), fmaxf(s[1][2], s[1][3]));
      n0 = fmaxf(n0, __shfl_xor_sync(~0u, n0, 1)); n1 = fmaxf(n1, __shfl_xor_sync(~0u, n1, 1));
      n0 = fmaxf(n0, __shfl_xor_sync(~0u, n0, 2)); n1 = fmaxf(n1, __shfl_xor_sync(~0u, n1, 2));
      n0 = fmaxf(n0, m0); n1 = fmaxf(n1, m1);
      const float z0 = n0 == -INFINITY ? 0.f : n0, z1 = n1 == -INFINITY ? 0.f : n1;
      const float c0 = ex2(m0 - z0), c1 = ex2(m1 - z1);
      m0 = n0; m1 = n1;
#pragma unroll
      for (int nt = 0; nt < 2; nt++) {
        s[nt][0] = ex2(s[nt][0] - z0); s[nt][1] = ex2(s[nt][1] - z0);
        s[nt][2] = ex2(s[nt][2] - z1); s[nt][3] = ex2(s[nt][3] - z1);
      }
      l0 = l0 * c0 + s[0][0] + s[0][1] + s[1][0] + s[1][1];
      l1 = l1 * c1 + s[0][2] + s[0][3] + s[1][2] + s[1][3];
      uint32_t pa[4] = {pack(s[0][0], s[0][1]), pack(s[0][2], s[0][3]), pack(s[1][0], s[1][1]), pack(s[1][2], s[1][3])};
      const uint16_t* vr = vp + (size_t)(key0 + 2 * q) * DH;
#pragma unroll
      for (int n = 0; n < 16; n++) {
        if ((n & 3) == 0) __syncwarp();
        o[n][0] *= c0; o[n][1] *= c0; o[n][2] *= c1; o[n][3] *= c1;
        mma16816(o[n], pa, vr[8 * n] | ((uint32_t)vr[8 * n + DH] << 16), vr[8 * n + 8 * DH] | ((uint32_t)vr[8 * n + 9 * DH] << 16));
      }
    }
    l0 += __shfl_xor_sync(~0u, l0, 1); l1 += __shfl_xor_sync(~0u, l1, 1);
    l0 += __shfl_xor_sync(~0u, l0, 2); l1 += __shfl_xor_sync(~0u, l1, 2);
    const float i0 = 1.f / l0, i1 = 1.f / l1;
    __nv_bfloat16* oc0 = P.o + o_idx(h * DH + 2 * q, o_pos(b, wg, r0));
    __nv_bfloat16* oc1 = P.o + o_idx(h * DH + 2 * q, o_pos(b, wg, min(r1, 119)));
#pragma unroll
    for (int n = 0; n < 16; n++) {
      oc0[8 * n * NROWS] = __float2bfloat16(o[n][0] * i0);
      oc0[8 * n * NROWS + 32] = __float2bfloat16(o[n][1] * i0);
      if (r1 < 120) {
        oc1[8 * n * NROWS] = __float2bfloat16(o[n][2] * i1);
        oc1[8 * n * NROWS + 32] = __float2bfloat16(o[n][3] * i1);
      }
    }
  }
}

__device__ __forceinline__ int bk(int ks) { return B_ORDER && ks < 48 ? 32 - (ks & 48) + (ks & 15) : ks; }
__device__ __forceinline__ uint32_t x_slot(uint32_t wg, uint32_t j) { return j < 2 ? (2 * wg + j) * XB : (2 * j + wg) * XB; }
__device__ __forceinline__ int row_block(int t) { return t >= 44 ? (t >> 2) - 11 : (t >> 2) + 4; }
__device__ __forceinline__ int unit_batch(int u) { return (u & 63) >> 2; }
__device__ __forceinline__ int unit_head(int u, int rank) { return (u >> 6) * 8 + (u & 3) * 2 + rank; }

template <int NCL>
__global__ void __cluster_dims__(2, 1, 1) __launch_bounds__(384, 1)
fused_attn_kernel(const __grid_constant__ CUtensorMap tm_x, const __grid_constant__ CUtensorMap tm_wq,
                  const __grid_constant__ CUtensorMap tm_k, const __grid_constant__ CUtensorMap tm_v,
                  const __grid_constant__ CUtensorMap tm_o, const __grid_constant__ CUtensorMap tm_wo,
                  const __grid_constant__ Params P) {
  extern __shared__ uint8_t smem_raw[];
  const uint32_t sb = ((uint32_t)__cvta_generic_to_shared(smem_raw) + 1023) & ~1023u;
  if (threadIdx.x == 0) TS(152);
  const int warp = __shfl_sync(~0u, threadIdx.x >> 5, 0);
  const int lane = threadIdx.x & 31;
  const int rank = blockIdx.x & 1, cl = blockIdx.x >> 1, ncl = NCL ? NCL : gridDim.x >> 1;

  const int nsingle = NCL == 66 ? 44 : NOTILES;
  auto role = [&]() {
    mbar_wait(sb + BAR_ROLE + 16, 0);
    int id;
    asm volatile("ld.shared.u32 %0, [%1];" : "=r"(id) : "r"(sb + BAR_ROLE + 8) : "memory");
    return id;
  };

  if (EARLY && threadIdx.x == 128) asm volatile("prefetch.tensormap [%0];" ::"l"(&tm_x) : "memory");
  if (threadIdx.x == 0) {
    if (EARLY) asm volatile("prefetch.tensormap [%0];" ::"l"(&tm_wq) : "memory");
    for (int i = 0; i < 6; i++) {
      mbar_init(sb + BAR_RFULL + 8 * i, 1); mbar_init(sb + BAR_REMPTY + 8 * i, 8);
      mbar_init(sb + BAR_BFULL + 8 * i, 1); mbar_init(sb + BAR_BEMPTY + 8 * i, 16);
    }
    for (int i = 0; i < 8; i++) mbar_init(sb + BAR_XFULL + 8 * i, 1);
    for (int i = 0; i < 4; i++) mbar_init(sb + BAR_XEMPTY + 8 * i, 8);
    for (int i = 0; i < 2; i++) { mbar_init(sb + BAR_STAGE + 8 * i, 4); mbar_init(sb + BAR_LSUM + 8 * i, 4); mbar_init(sb + BAR_INV + 8 * i, 1); }
    mbar_init(sb + BAR_ROLE, 1); mbar_init(sb + BAR_ROLE + 16, 1);
    asm volatile("fence.mbarrier_init.release.cluster;" ::: "memory");
  }
  __syncwarp();
  asm volatile("barrier.cluster.arrive.relaxed.aligned;" ::: "memory");
  auto first_w = [&](int s) {
    mbar_expect(sb + BAR_RFULL + 8 * s, RING_BYTES);
    tma3d(sb + s * RING_BYTES, &tm_wq, 0, s * 64, 2 * unit_head(cl, rank), sb + BAR_RFULL + 8 * s);
  };
  if (EARLY && threadIdx.x == 0) first_w(0);
  __syncwarp();
  asm volatile("barrier.cluster.wait.aligned;" ::: "memory");
  if (EARLY && threadIdx.x == 128) {
#pragma unroll 1
    for (int s = 0; s < EARLY_X; s++) {
      const uint32_t fb = sb + BAR_XFULL + 32 * rank + 8 * s;
      mbar_expect(fb, XB);
      mbar_expect_cl(mapa(fb, rank ^ 1), XB);
      tma2d_mc(sb + OFF_Q + x_slot(rank, s), &tm_x, s * 64, unit_batch(cl) * SQ + rank * 120, fb);
      if (s + 1 < EARLY_W) first_w(s + 1);
    }
  }
  __syncwarp();
  if (threadIdx.x == 0) TS(153);

  if (warp >= 8) {
    asm volatile("setmaxnreg.dec.sync.aligned.u32 24;");
    if (warp == 8) {
      uint64_t pol;
      asm volatile("createpolicy.fractional.L2::evict_first.b64 %0, 1.0;" : "=l"(pol));
      Ring r;
      if (EARLY) r.slot = EARLY_W;
      auto load = [&](const CUtensorMap* m, int c1, int c2, bool ef) {
        mbar_wait(sb + BAR_REMPTY + 8 * r.slot, r.phase ^ 1);
        if (lane == 0) {
          mbar_expect(sb + BAR_RFULL + 8 * r.slot, RING_BYTES);
          if (ef) tma3d_hint(sb + r.slot * RING_BYTES, m, 0, c1, c2, sb + BAR_RFULL + 8 * r.slot, pol);
          else tma3d(sb + r.slot * RING_BYTES, m, 0, c1, c2, sb + BAR_RFULL + 8 * r.slot);
        }
        r.next();
      };
      const int rot = ROT * (blockIdx.x * 5 + (blockIdx.x >> 4));
      auto pause = [&](int u0) {
        if (PAUSE_NS && NCL == 66 && u0 == PAUSE_AT * 66) {
          const int id = role();
          if (id >= 44 && id < 58) {
            unsigned t0, t1;
            asm volatile("mov.u32 %0, %globaltimer_lo;" : "=r"(t0));
            do { __nanosleep(200); asm volatile("mov.u32 %0, %globaltimer_lo;" : "=r"(t1)); } while (t1 - t0 < PAUSE_NS + (id - 44) * PAUSE_SPREAD);
          }
        }
      };
      for (int u0 = 0;; u0 += ncl) {
        const int u = __shfl_sync(~0u, (u0 >= 3 * ncl ? role() : cl) + u0, 0);
        if (u >= NUNITS) break;
        if (PAUSE_J < 0) pause(u0);
        const int h = unit_head(u, rank);
        const int krow = (unit_batch(u) * NH + h) * SK;
#pragma unroll 1
        for (int s = EARLY && u0 == 0 ? EARLY_W : 0; s < 10; s++) {
          if (u0 == 0 && s == 0 && lane == 0) TS(154);
          load(&tm_wq, s * 64, 2 * h, false);
          if (u0 == 0 && s == 0 && lane == 0) TS(155);
          const int sp = u0 == 0 ? s - PF_HOLD : s;
          if (sp >= 0 && sp < PF_N && lane == 0) l2_prefetch(P.v + (size_t)(krow + ((PF_J0 + sp * PF_STEP + rot) & 15) * 64) * DH, 16384);
        }
#pragma unroll 1
        for (int j = 0; j <= 16; j++) {
          if (j == PAUSE_J) pause(u0);
          if (j < 16) load(&tm_k, krow + ((j + rot) & 15) * 64, 0, true);
          if (j == 1 + DPRO) load(&tm_v, krow + (rot & 15) * 64, 0, true);
          if (j > 1) load(&tm_v, krow + ((j - 1 + rot) & 15) * 64, 0, true);
        }
      }
      const int id = __shfl_sync(~0u, role(), 0);
      const bool dbl = NCL == 66 && id >= 58;
      for (int t = dbl ? 2 * id - 72 : id; t < (dbl ? NOTILES : nsingle); t += ncl) {
        const int row0 = row_block(t) * 256 + rank * 128;
        const int b0 = (row0 & ~31) / SQ, b1 = (row0 + 127) / SQ;
#pragma unroll 1
        for (int ks = 0; ks < 64; ks++) {
          if (dbl ? (ks & 15) == 0 : ks == 0 || ks == 48) {
            const unsigned* c = &g_cnt[((lane & 1 ? b1 : b0) * 4 + (ks || dbl ? ks >> 4 : min(lane >> 1, 2))) * 8];
            unsigned v, n = 0;
            do {
              asm volatile("ld.acquire.gpu.global.u32 %0, [%1];" : "=r"(v) : "l"(c) : "memory");
              if (++n > (1u << 26)) __trap();
            } while (v < 16);
            __syncwarp();
            asm volatile("fence.proxy.async.global;" ::: "memory");
          }
          mbar_wait(sb + BAR_REMPTY + 8 * r.slot, r.phase ^ 1);
          if (lane == 0) {
            mbar_expect(sb + BAR_RFULL + 8 * r.slot, RING_BYTES);
            asm volatile("cp.async.bulk.tensor.4d.shared::cluster.global.mbarrier::complete_tx::bytes.L2::cache_hint [%0], [%1, {%3, %3, %4, %5}], [%2], %6;"
                         ::"r"(sb + r.slot * RING_BYTES), "l"(&tm_o), "r"(sb + BAR_RFULL + 8 * r.slot), "r"(0), "r"((dbl ? ks : bk(ks)) * 8), "r"(row0 >> 6), "l"(pol) : "memory");
          }
          r.next();
        }
      }
      if (lane == 0 && atomicAdd(&g_cnt[64 * 8], 1) == gridDim.x - 1) {
        for (int i = 0; i < 67; i++) g_cnt[i * 8] = 0;
      }
    } else if (warp == 9) {
      if (lane == 0) {
        uint32_t it = 0;
        for (;; it++) {
          const int u = (it >= 3 ? role() : cl) + it * ncl;
          if (u >= NUNITS) break;
          const int row = unit_batch(u) * SQ + rank * 120;
#pragma unroll 1
          for (int s = EARLY && it == 0 ? EARLY_X : 0; s < 10; s++) {
            const uint32_t j = s & 3, par = ((s >> 2) + (j < 2 ? it : 0)) & 1;
            mbar_wait(sb + BAR_XEMPTY + 8 * j, par ^ 1);
            const uint32_t fb = sb + BAR_XFULL + 32 * rank + 8 * j;
            mbar_expect(fb, XB);
            mbar_expect_cl(mapa(fb, rank ^ 1), XB);
            tma2d_mc(sb + OFF_Q + x_slot(rank, j), &tm_x, s * 64, row, fb);
          }
        }
        const int id = role();
        const bool dbl = NCL == 66 && id >= 58;
        uint32_t slot = rank, phase = 0;
        if (WO_PF0 && dbl)
          asm volatile("cp.async.bulk.prefetch.tensor.3d.L2.global [%0, {%1, %2, %3}];" ::"l"(&tm_wo), "r"(0), "r"((2 + ((id >> 1) & 3)) * 64), "r"(((2 * id - 72 + rank) & 3) * 5) : "memory");
        for (int t = dbl ? 2 * id - 72 + rank : id; t < (dbl ? NOTILES : nsingle); t += ncl) {
#pragma unroll 1
          for (int ks = dbl ? 0 : rank; ks < 64; ks += dbl ? 1 : 2) {
            mbar_wait(sb + BAR_BEMPTY + 8 * slot, phase);
            const uint32_t fb = sb + BAR_BFULL + 8 * slot;
            mbar_expect(fb, BB);
            mbar_expect_cl(mapa(fb, rank ^ 1), BB);
            tma3d_mc(sb + OFF_Q + slot * BB, &tm_wo, 0, (dbl ? ks : bk(ks)) * 64, (t & 3) * 5, fb);
            if (WO_PF && dbl && ks + WO_PF < 64 && (ks & 3) == ((id >> 1) & 3))
              asm volatile("cp.async.bulk.prefetch.tensor.3d.L2.global [%0, {%1, %2, %3}];" ::"l"(&tm_wo), "r"(0), "r"((ks + WO_PF) * 64), "r"((t & 3) * 5) : "memory");
            slot += 2;
            if (slot >= 6) { slot -= 6; phase ^= 1; }
          }
        }
      }
    } else {
      const int wg = warp - 10;
      {
        mbar_wait(sb + BAR_RFULL, 0);
        const __nv_bfloat16* xs = P.x + (size_t)(unit_batch(cl) * SQ + ((cl & 3) * 2 + rank) * 30 + min(lane, 29)) * DM + 256 + wg * 64;
#pragma unroll
        for (int i = 0; i < 3; i++) asm volatile("prefetch.global.L2 [%0];" ::"l"(xs + i * 128));
        if (lane < 16) asm volatile("prefetch.global.L2 [%0];" ::"l"(P.wq + (size_t)(384 + unit_batch(cl) * 16 + lane) * HD + unit_head(cl, rank) * DH + wg * 64));
      }
      auto take_role = [&]() {
          if (wg == 0 && rank == 0 && lane == 0) {
            int id = cl;
            if (NCL == 66) {
              uint32_t smid;
              asm("mov.u32 %0, %smid;" : "=r"(smid));
              id = smid >= SMID_TOP ? 65 - atomicAdd(&g_cnt[65 * 8], 1) : atomicAdd(&g_cnt[66 * 8], 1);
            }
    #pragma unroll
            for (int c = 0; c < 2; c++) {
              const uint32_t a = mapa(sb + BAR_ROLE, c);
              asm volatile("st.shared::cluster.u32 [%0 + 8], %1;\nmbarrier.arrive.release.cluster.shared::cluster.b64 _, [%0];" ::"r"(a), "r"(id) : "memory");
            }
          }
          if (wg == 0 && lane == 0) {
            mbar_wait_cl(sb + BAR_ROLE, 0);
            mbar_arrive(sb + BAR_ROLE + 16);
          }
      };
      if (ROLE_AT < 0) { take_role(); __syncwarp(); }
      for (uint32_t it = 0;; it++) {
        const int u = __shfl_sync(~0u, (it >= 3 ? role() : cl) + it * ncl, 0);
        if (u >= NUNITS) break;
        mbar_wait(sb + BAR_LSUM + 8 * wg, it & 1);
        float l4[4], v[4];
        const uint32_t a = sb + OFF_L2 + wg * 2048 + lane * 16;
        asm volatile("ld.shared.v4.f32 {%0, %1, %2, %3}, [%4];" : "=f"(l4[0]), "=f"(l4[1]), "=f"(l4[2]), "=f"(l4[3]) : "r"(a) : "memory");
#pragma unroll
        for (int g = 1; g < 4; g++) {
          asm volatile("ld.shared.v4.f32 {%0, %1, %2, %3}, [%4];" : "=f"(v[0]), "=f"(v[1]), "=f"(v[2]), "=f"(v[3]) : "r"(a + g * 512) : "memory");
#pragma unroll
          for (int c = 0; c < 4; c++) l4[c] += v[c];
        }
#pragma unroll
        for (int c = 0; c < 4; c++) {
          float inv;
          asm("rcp.approx.ftz.f32 %0, %1;" : "=f"(inv) : "f"(l4[c]));
          l4[c] = l4[c] >= L_MIN && l4[c] <= L_MAX ? inv : __uint_as_float(0x7FFFFFFFu);
        }
        const uint32_t h0 = pack(l4[0], l4[1]), h1 = pack(l4[2], l4[3]);
        const uint32_t e0 = pack(l4[0] - __uint_as_float(h0 << 16), l4[1] - __uint_as_float(h0 & 0xFFFF0000u));
        const uint32_t e1 = pack(l4[2] - __uint_as_float(h1 << 16), l4[3] - __uint_as_float(h1 & 0xFFFF0000u));
        asm volatile("st.shared.v4.u32 [%0], {%1, %2, %3, %4};" ::"r"(sb + OFF_INV + wg * 640 + (lane & 3) * 144 + (lane >> 2) * 16), "r"(h0), "r"(e0), "r"(h1), "r"(e1) : "memory");
        __syncwarp();
        if (lane == 0) {
          mbar_arrive(sb + BAR_INV + 8 * wg);
          if ((int)it == ROLE_AT) {
            take_role();
          }
          mbar_wait(sb + BAR_STAGE + 8 * wg, it & 1);
          __threadfence();
          asm volatile("red.relaxed.gpu.global.add.u32 [%0], 1;" ::"l"(&g_cnt[(unit_batch(u) * 4 + (u >> 6)) * 8]) : "memory");
        }
        __syncwarp();
      }
    }
  } else {
    asm volatile("setmaxnreg.inc.sync.aligned.u32 240;");
    const int wg = warp >> 2, w = warp & 3;
    const uint32_t qreg = sb + OFF_Q + wg * 2 * XB, preg = sb + OFF_P + (2 + wg) * XB;
    const uint32_t st_off = ((lane >> 4) * 8 + (lane & 7)) * 128 + (((2 * w + ((lane >> 3) & 1)) ^ (lane & 7)) << 4);
    const uint32_t xempty = mapa(sb + BAR_XEMPTY, wg);
    Ring r;
    uint32_t it = 0;
    const uint32_t qd = (qreg & 0x3FFFF) >> 4, pd = (preg & 0x3FFFF) >> 4;
    auto ring_addr = [&]() { return ((sb & 0x3FFFF) + r.slot * RING_BYTES) >> 4; };
    auto ring_wait = [&]() { mbar_wait(sb + BAR_RFULL + 8 * r.slot, r.phase); };
    auto release = [&](uint32_t slot) { warp_arrive(sb + BAR_REMPTY + 8 * slot); };
    auto turn_wait = [&]() {
      if (wg == 0) asm volatile("bar.sync 3, 256;" ::: "memory");
      else asm volatile("bar.sync 4, 256;" ::: "memory");
    };
    auto turn_pass = [&]() {
      if (wg == 0) asm volatile("bar.arrive 4, 256;" ::: "memory");
      else asm volatile("bar.arrive 3, 256;" ::: "memory");
    };

    uint32_t chk = 0;
    auto load_inv = [&](uint32_t (&iv)[30], uint32_t parity) {
      const int lane = fresh_tid() & 31;
      mbar_wait(sb + BAR_INV + 8 * wg, parity);
      chk = 0;
#pragma unroll
      for (int j = 0; j < 7; j++)
        asm volatile("ld.shared.v4.u32 {%0, %1, %2, %3}, [%4];" : "=r"(iv[4 * j]), "=r"(iv[4 * j + 1]), "=r"(iv[4 * j + 2]), "=r"(iv[4 * j + 3])
                     : "r"(sb + OFF_INV + wg * 640 + (lane & 3) * 144 + j * 16) : "memory");
      asm volatile("ld.shared.v2.u32 {%0, %1}, [%2];" : "=r"(iv[28]), "=r"(iv[29]) : "r"(sb + OFF_INV + wg * 640 + (lane & 3) * 144 + 112) : "memory");
    };
    auto norm = [&](uint32_t (&n)[8], const uint32_t (&po)[60], const uint32_t (&iv)[30], auto part) {
      constexpr int k = decltype(part)::value >> 1, j0 = (decltype(part)::value & 1) * 8;
#pragma unroll
      for (int j = 0; j < 8; j++)
        n[j] = j0 + j < 15 ? hfma2(po[15 * k + (j0 + j) % 15], iv[2 * ((j0 + j) % 15)], hfma2(po[15 * k + (j0 + j) % 15], iv[2 * ((j0 + j) % 15) + 1], 0x80008000u)) : 0x3F803F80u;
#pragma unroll
      for (int j = 0; j < 8; j += 2) chk = hfma2(n[j], n[j + 1], chk);
    };
    int od1, od2;
    auto store = [&](const uint32_t (&n)[8], const char* optr, auto part) {
      constexpr int k = decltype(part)::value >> 1, off = (8 * (k & 1) + 64 * (k >> 1)) * NROWS * 2;
      if ((decltype(part)::value & 1) == 0)
        asm volatile(
            "{\n.reg .pred p;\nsetp.ne.u64 p, %8, 0;\n"
            "@p st.global.v4.u32 [%8 + %9], {%0, %1, %2, %3};\n@p st.global.v4.u32 [%8 + %9 + 512], {%4, %5, %6, %7};\n}\n"
            ::"r"(n[0]), "r"(n[1]), "r"(n[2]), "r"(n[3]), "r"(n[4]), "r"(n[5]), "r"(n[6]), "r"(n[7]), "l"(optr), "n"(off) : "memory");
      else
        asm volatile(
            "{\n.reg .pred p;\n.reg .b64 b, c;\nsetp.ne.u64 p, %7, 0;\nmad.wide.s32 b, %9, 1, %7;\nmad.wide.s32 c, %10, 1, %7;\n"
            "@p st.global.v4.u32 [%7 + %8 + 1024], {%0, %1, %2, %3};\n@p st.global.v2.u32 [b + %8], {%4, %5};\n@p st.global.u32 [c + %8], %6;\n}\n"
            ::"r"(n[0]), "r"(n[1]), "r"(n[2]), "r"(n[3]), "r"(n[4]), "r"(n[5]), "r"(n[6]), "l"(optr), "n"(off), "r"(od1), "r"(od2) : "memory");
    };
    auto put = [&](const uint32_t (&po)[60], const uint32_t (&iv)[30], const char* optr, auto part) {
      uint32_t n[8];
      norm(n, po, iv, part);
      store(n, optr, part);
    };
    auto out_ptr = [&](int u) {
      const int lane = fresh_tid() & 31;
      const int k = unit_head(u, rank) * DH + 16 * w + (lane >> 2), b = unit_batch(u), q = lane & 3;
      const uint32_t i0 = o_idx(k, o_pos(b, wg, 2 * q));
      od1 = 2 * (int)(o_idx(k, o_pos(b, wg, 96 + 2 * q)) - i0);
      od2 = 2 * (int)(o_idx(k, o_pos(b, wg, 112 + 2 * q)) - i0);
      return reinterpret_cast<const char*>(P.o + i0);
    };
    auto unsafe = [&](bool valid) {
      const bool b = valid && ((chk & 0x7F80u) == 0x7F80u || (chk & 0x7F800000u) == 0x7F800000u);
      return __any_sync(~0u, bar_red_or(wg, b));
    };
    auto publish = [&]() { __syncwarp(); warp_arrive(sb + BAR_STAGE + 8 * wg); };

    uint32_t po[60];
#pragma unroll
    for (int i = 0; i < 60; i++) po[i] = 0;
    int id = 0;
    bool more;
    do {
      float o0[60], o1[60];
      uint32_t prev = 0;
      auto qstep = [&](int s, int acc) {
        const uint32_t j = s & 3, par = ((s >> 2) + (j < 2 ? it : 0)) & 1;
        TR(it * 160 + 3 * s);
        ring_wait();
        TR(it * 160 + 3 * s + 1);
        mbar_wait(sb + BAR_XFULL + 32 * wg + 8 * j, par);
        TR(it * 160 + 3 * s + 2);
        if (s >= ALT_FROM) turn_wait();
        wg_fence();
        mma_tn(o0, o1, ring_addr(), ((sb & 0x3FFFF) + OFF_Q + x_slot(wg, j)) >> 4, acc);
        wg_commit();
        if (s >= ALT_FROM || (s == ALT_FROM - 1 && wg == 1)) turn_pass();
        if (s > 0 && s <= EREL_FROM) {
          wg_wait<1>();
          release(prev);
          if (s <= 6) warp_arrive_cl(xempty + 8 * ((s - 1) & 3));
        }
        prev = r.slot;
        r.next();
      };
      auto qdone = [&](int s) {
        if (s >= EREL_FROM) {
          wg_wait<0>();
          release(prev);
          if (s <= 5) warp_arrive_cl(xempty + 8 * (s & 3));
        }
      };
      qstep(0, 0);
      qstep(1, 1);
      const int up = (it > 3 ? id : cl) + ((int)it - 1) * ncl;
      const char* optr = out_ptr(up);
      if (it == 0) optr = nullptr;
      uint32_t n7[8];
      {
        uint32_t iv[30];
        load_inv(iv, (it + 1) & 1); put(po, iv, optr, IC<0>());
        qstep(2, 1); put(po, iv, optr, IC<1>()); qdone(2);
        qstep(3, 1); put(po, iv, optr, IC<2>()); qdone(3);
        qstep(4, 1); put(po, iv, optr, IC<3>()); qdone(4);
        qstep(5, 1); put(po, iv, optr, IC<4>()); qdone(5);
        qstep(6, 1); put(po, iv, optr, IC<5>()); qdone(6);
        qstep(7, 1); put(po, iv, optr, IC<6>());
        norm(n7, po, iv, IC<7>());
        qdone(7);
        if (LATE_AT == 3 || (LATE_AT == 5 && wg == 1)) store(n7, optr, IC<7>());
      }
      TR(it * 160 + 24);
      const uint32_t a8 = ring_addr(), slot8 = r.slot;
      ring_wait();
      r.next();
      TR(it * 160 + 25);
      mbar_wait(sb + BAR_XFULL + 32 * wg, it & 1);
      TR(it * 160 + 26);
      auto wait9 = [&]() {
        TR(it * 160 + 27);
        ring_wait();
        TR(it * 160 + 28);
        mbar_wait(sb + BAR_XFULL + 32 * wg + 8, it & 1);
        TR(it * 160 + 29);
      };
      if (PRE9 == 1 || (PRE9 == 2 && wg == 1)) wait9();
      if (PRE9 == 3) ring_wait();
      turn_wait();
      wg_fence();
      mma_tn(o0, o1, a8, qd, 1);
      wg_commit();
      if (PRE9 == 0 || (PRE9 == 2 && wg == 0)) wait9();
      if (PRE9 == 3) mbar_wait(sb + BAR_XFULL + 32 * wg + 8, it & 1);
      if (PRE9 != 1) wg_fence();
      mma_tn_split(o0, o1, ring_addr(), qd + (XB >> 4));
      turn_pass();
      wg_wait<2>();
      if (EREL_FROM > 7) release(prev);
      release(slot8);
      if (LATE_AT == 4 || (LATE_AT == 5 && wg == 0)) store(n7, optr, IC<7>());
      auto put_q = [&](const float (&o)[60], uint32_t dst) {
        bar_sync(wg);
#pragma unroll
        for (int j = 0; j < 14; j += 2)
          stsm4t(dst + j * 1024, pack(o[4 * j] * QSCALE, o[4 * j + 1] * QSCALE), pack(o[4 * j + 2] * QSCALE, o[4 * j + 3] * QSCALE),
                 pack(o[4 * j + 4] * QSCALE, o[4 * j + 5] * QSCALE), pack(o[4 * j + 6] * QSCALE, o[4 * j + 7] * QSCALE));
        stsm2t(dst + 14 * 1024, pack(o[56] * QSCALE, o[57] * QSCALE), pack(o[58] * QSCALE, o[59] * QSCALE));
      };
      wg_wait<1>();
      reg_fence(o0);
      put_q(o0, qreg + st_off);
      wg_wait<0>();
      reg_fence(o1);
      release(r.slot);
      r.next();
      TR(it * 160 + 30);
      put_q(o1, qreg + XB + st_off);
      fence_async_smem();
      if (unsafe(it > 0)) {
        slow_path(P, unit_batch(up), unit_head(up, rank), wg, w, fresh_tid() & 31);
        optr = nullptr;
        if (!DPRO) {
#pragma unroll
          for (int i = 0; i < 60; i++) o0[i] = o1[i] = 0.f;
        }
      }
      TR(it * 160 + 32); TG(it * 160 + 142);

      float sc[60], l[30];
      uint32_t slot0 = r.slot;
      ring_wait();
      TR(it * 160 + 33);
      turn_wait();
      wg_fence();
      mma_qk(sc, ring_addr(), qd);
      wg_commit();
      r.next();
      uint32_t slot1 = r.slot;
      ring_wait();
      wg_fence();
      mma_qk(o1, ring_addr(), qd);
      wg_commit();
      r.next();
      turn_pass();
      if (LATE_AT == 0) store(n7, optr, IC<7>());
      wg_wait<1>();
      reg_fence(sc);
      TR(it * 160 + 35);
      release(slot0);
      exp_store<0, 15, true>(sc, l, preg + st_off);
      TR(it * 160 + 38); TG(it * 160 + 43);
      slot0 = r.slot;
      if (K2_AT > 0) {
        wg_wait<0>();
        reg_fence(o1);
        release(slot1);
        exp_store<0, K2_AT>(o1, l, preg - 2 * XB + st_off);
      }
      ring_wait();
      wg_fence();
      mma_qk(sc, ring_addr(), qd);
      wg_commit();
      r.next();
      if (K2_AT == 0) {
        wg_wait<1>();
        reg_fence(o1);
        release(slot1);
      }
      TR(it * 160 + 41);
      exp_store<K2_AT, 15>(o1, l, preg - 2 * XB + st_off);
      fence_async_smem();
      TR(it * 160 + 44);
      slot1 = r.slot;
      ring_wait();
      turn_wait();
      wg_fence();
      mma_tn(o0, o1, ring_addr(), pd, 0);
      wg_commit();
      r.next();
      ring_wait();
      wg_fence();
      mma_tn(o0, o1, ring_addr(), pd - (2 * XB >> 4), 1);
      wg_commit();
      turn_pass();
      if (LATE_AT == 1) store(n7, optr, IC<7>());
      if (it > 0) publish();
      if (it >= 2) id = __shfl_sync(~0u, role(), 0);
      wg_wait<1>();
      reg_fence(sc);
      release(slot0);
      release(slot1);
      bar_sync(wg);
      TR(it * 160 + 47);
      exp_store<0, VREL>(sc, l, preg + st_off);
      wg_wait<0>();
      reg_fence(o0); reg_fence(o1);
      release(r.slot);
      r.next();
      exp_store<VREL, 15>(sc, l, preg + st_off);
      fence_async_smem();
      more = id + ((int)it + 1) * ncl < NUNITS;
      const bool gemm = id < nsingle || (NCL == 66 && id >= 58);
#pragma unroll 1
      for (int s = DPRO ? 3 : 1; s < 16; s++) {
        const uint32_t kslot = r.slot;
        TR(it * 160 + 32 + 6 * s); TG(it * 160 + 37 + 6 * s);
        if (s == 8) TRL(it * 160 + 139);
        ring_wait();
        TR(it * 160 + 33 + 6 * s);
        turn_wait();
        wg_fence();
        mma_qk(sc, ring_addr(), qd);
        wg_commit();
        r.next();
        TR(it * 160 + 36 + 6 * s);
        ring_wait();
        TR(it * 160 + 34 + 6 * s);
        wg_fence();
        mma_tn(o0, o1, ring_addr(), pd - ((s - 1) & 1) * (2 * XB >> 4), DPRO || s != 1);
        wg_commit();
        if (wg == 0 || s < 15) turn_pass();
        wg_wait<1>();
        reg_fence(sc);
        TR(it * 160 + 35 + 6 * s);
        release(kslot);
        if (s == 15) {
          if (more) { warp_arrive_cl(xempty); warp_arrive_cl(xempty + 8); }
          else if (gemm) for (int i = 0; i < 3; i++) warp_arrive_cl(mapa(sb + BAR_BEMPTY + 8 * i, i & 1));
        }
        exp_store<0, VREL>(sc, l, preg - (s & 1) * 2 * XB + st_off);
        wg_wait<0>();
        reg_fence(o0); reg_fence(o1);
        release(r.slot);
        r.next();
        exp_store<VREL, 15>(sc, l, preg - (s & 1) * 2 * XB + st_off);
        fence_async_smem();
      }
      const uint32_t tid = fresh_tid();
      bar_sync(wg);
      TR(it * 160 + 128);
      ring_wait();
      wg_fence();
      mma_tn_split(o0, o1, ring_addr(), pd - (2 * XB >> 4));
      {
        float a[16], b[8], c[4];
        const bool b4 = tid & 16, b3 = tid & 8, b2 = tid & 4;
#pragma unroll
        for (int i = 0; i < 16; i++) {
          const float hi = i < 14 ? l[(16 + i) % 30] : 1.f;
          a[i] = (b4 ? hi : l[i]) + __shfl_xor_sync(~0u, b4 ? l[i] : hi, 16);
        }
#pragma unroll
        for (int i = 0; i < 8; i++) b[i] = (b3 ? a[8 + i] : a[i]) + __shfl_xor_sync(~0u, b3 ? a[i] : a[8 + i], 8);
#pragma unroll
        for (int i = 0; i < 4; i++) c[i] = (b2 ? b[4 + i] : b[i]) + __shfl_xor_sync(~0u, b2 ? b[i] : b[4 + i], 4);
        asm volatile("st.shared.v4.f32 [%0], {%1, %2, %3, %4};" ::"r"(sb + OFF_L2 + tid * 16), "f"(c[0]), "f"(c[1]),
                     "f"(c[2]), "f"(c[3]) : "memory");
        __syncwarp();
        warp_arrive(sb + BAR_LSUM + 8 * wg);
      }
      TR(it * 160 + 132);
      TR(it * 160 + 133);
      wg_wait<1>();
      reg_fence(o0);
      TR(it * 160 + 134);
#pragma unroll
      for (int j = 0; j < 15; j++) { po[j] = pack(o0[4 * j], o0[4 * j + 1]); po[15 + j] = pack(o0[4 * j + 2], o0[4 * j + 3]); }
      wg_wait<0>();
      reg_fence(o1);
      release(r.slot);
      r.next();
      if (more) { warp_arrive_cl(xempty + 16); warp_arrive_cl(xempty + 24); }
      else if (gemm) for (int i = 3; i < 6; i++) warp_arrive_cl(mapa(sb + BAR_BEMPTY + 8 * i, i & 1));
      TR(it * 160 + 130);
#pragma unroll
      for (int j = 0; j < 15; j++) { po[30 + j] = pack(o1[4 * j], o1[4 * j + 1]); po[45 + j] = pack(o1[4 * j + 2], o1[4 * j + 3]); }
      TR(it * 160 + 131); TG(it * 160 + 143);
      it++;
    } while (more);
    const bool gemm = id < nsingle || (NCL == 66 && id >= 58);
    const int u = (it > 3 ? id : cl) + ((int)it - 1) * ncl;
    uint32_t pb[60];
#pragma unroll
    for (int i = 0; i < 60; i++) pb[i] = NCL != 66 ? po[i] ^ (gridDim.y - 1) : po[i];

    uint32_t bslot = 0, bphase = 0;
    auto out_row = [&](int lane) {
      const int row = lane & 15;
      return sb + wg * 8192 + (row < 12 ? w * RING_BYTES + row * 656 : (4 + (w >> 1)) * RING_BYTES + ((w & 1) * 4 + row - 12) * 656);
    };
    auto out_stage = [&](const float (&acc)[80], uint32_t col_off) {
      const int lane = fresh_tid() & 31;
      const uint32_t sa = out_row(lane) + col_off + (lane >> 4) * 16;
#pragma unroll
      for (int j = 0; j < 20; j += 2)
        asm volatile("stmatrix.sync.aligned.m8n8.x4.shared.b16 [%0], {%1,%2,%3,%4};" ::"r"(sa + j * 16), "r"(pack(acc[4 * j], acc[4 * j + 1])),
                     "r"(pack(acc[4 * j + 2], acc[4 * j + 3])), "r"(pack(acc[4 * j + 4], acc[4 * j + 5])), "r"(pack(acc[4 * j + 6], acc[4 * j + 7])) : "memory");
    };
    auto out_store = [&](int t, uint32_t bytes) {
      const int lane = fresh_tid() & 31;
      if (EPI_MIX && wg == 1) {
        __syncwarp();
#pragma unroll 1
        for (int h = 0; h < 2; h++) {
          const int row = h * 8 + (lane >> 2);
          const uint32_t src = out_row(row) + (lane & 3) * 16;
          char* dst = reinterpret_cast<char*>(P.out + (size_t)o_row(row_block(t) * 256 + rank * 128 + 64 + w * 16 + row) * DM + (t & 3) * 160) + (lane & 3) * 16;
#pragma unroll 1
          for (uint32_t c = 0; c < bytes; c += 320) {
            uint4 v[5];
#pragma unroll
            for (int i = 0; i < 5; i++)
              asm volatile("ld.shared.v4.u32 {%0, %1, %2, %3}, [%4];" : "=r"(v[i].x), "=r"(v[i].y), "=r"(v[i].z), "=r"(v[i].w) : "r"(src + c + i * 64) : "memory");
#pragma unroll
            for (int i = 0; i < 5; i++) *reinterpret_cast<uint4*>(dst + c + i * 64) = v[i];
          }
        }
        return;
      }
      fence_async_smem();
      __syncwarp();
      if (lane < 16) {
        __nv_bfloat16* dst = P.out + (size_t)o_row(row_block(t) * 256 + rank * 128 + wg * 64 + w * 16 + lane) * DM + (t & 3) * 160;
        asm volatile("cp.async.bulk.global.shared::cta.bulk_group [%0], [%1], %2;" ::"l"(dst), "r"(out_row(lane)), "r"(bytes) : "memory");
        asm volatile("cp.async.bulk.commit_group;" ::: "memory");
        asm volatile("cp.async.bulk.wait_group.read 0;" ::: "memory");
      }
    };
    for (int t = id; t == id || (NCL != 66 && t < nsingle); t += ncl) {
      float acc[80];
      uint32_t prev = 0, bprev = 0;
      const bool tile = t < nsingle;
      const bool last = NCL == 66 || t + ncl >= nsingle;
      auto bstep = [&](int ks, int accf) {
        if (!(ks & 3)) TR(640 + ks / 2); if ((ks & 7) == 0) TG(144 + (ks >> 3));
        ring_wait();
        mbar_wait(sb + BAR_BFULL + 8 * bslot, bphase);
        if (!(ks & 3)) TR(641 + ks / 2);
        wg_fence();
        const uint32_t a = ring_addr() + wg * 512, bd = (((sb & 0x3FFFF) + OFF_Q + bslot * BB) >> 4) | ((4096u >> 4) << 16);
#pragma unroll
        for (int k = 0; k < 4; k++) wgmma_n160<1, 1>(acc, a + LBO64A + k * 128, HI64A, bd + k * 64, HI64, k == 0 ? accf : 1);
        wg_commit();
        if (ks > 0) {
          wg_wait<1>();
          release(prev);
          if (ks < 59 || !last) warp_arrive_cl(mapa(sb + BAR_BEMPTY + 8 * bprev, bprev & 1));
        }
        prev = r.slot; bprev = bslot;
        r.next();
        if (++bslot == 6) { bslot = 0; bphase ^= 1; }
      };
      const char* optr;
      uint32_t iv[30], n3[8], n4[8], n5[8], n6[8], n7[8];
      if (tile) {
        bstep(0, 0);
        bstep(1, 1);
        optr = out_ptr(u);
        if (t != id) optr = nullptr;
        load_inv(iv, (it + 1) & 1);
#pragma unroll 1
        for (int ks = 2; ks < 17; ks++) {
          bstep(ks, 1);
          switch (ks) {
            case 2: put(pb, iv, optr, IC<0>()); break;
            case 4: put(pb, iv, optr, IC<1>()); break;
            case 6: put(pb, iv, optr, IC<2>()); break;
            case 8: put(pb, iv, optr, IC<3>()); break;
            case 10: put(pb, iv, optr, IC<4>()); break;
            case 12: put(pb, iv, optr, IC<5>()); break;
            case 14: put(pb, iv, optr, IC<6>()); break;
            case 16: put(pb, iv, optr, IC<7>()); break;
            default: break;
          }
        }
        wg_wait<0>();
        reg_fence(acc);
#pragma unroll
        for (int i = 0; i < 8; i++) n3[i] = n4[i] = n5[i] = n6[i] = n7[i] = 0;
      } else {
        Ring r2 = r;
        auto first = [&](int ks) {
          if (ks == 0) { TR(640); TG(144); }
          if (gemm) { mbar_wait(sb + BAR_RFULL + 8 * r2.slot, r2.phase); mbar_wait(sb + BAR_BFULL + 16 * ks, 0); }
          wg_fence();
          const uint32_t a = (((sb & 0x3FFFF) + r2.slot * RING_BYTES) >> 4) + wg * 512;
          const uint32_t bd = (((sb & 0x3FFFF) + OFF_Q + 2 * ks * BB) >> 4) | ((4096u >> 4) << 16);
#pragma unroll
          for (int k = 0; k < 4; k++) wgmma_n160<1, 1>(acc, a + LBO64A + k * 128, HI64A, bd + k * 64, HI64, k + ks != 0);
          wg_commit();
          if (ks > 0) {
            wg_wait<1>();
            if (gemm) warp_arrive_cl(mapa(sb + BAR_BEMPTY + 16 * (ks - 1), 0));
          }
          r2.next();
        };
        first(0);
        optr = out_ptr(u);
        load_inv(iv, (it + 1) & 1);
        put(pb, iv, optr, IC<0>());
        first(1);
        put(pb, iv, optr, IC<1>());
        norm(n3, pb, iv, IC<3>()); norm(n4, pb, iv, IC<4>());
        first(2);
        put(pb, iv, optr, IC<2>());
        norm(n5, pb, iv, IC<5>()); norm(n6, pb, iv, IC<6>()); norm(n7, pb, iv, IC<7>());
        wg_wait<0>();
        reg_fence(acc);
      }
      if (unsafe(t == id)) {
        slow_path(P, unit_batch(u), unit_head(u, rank), wg, w, fresh_tid() & 31);
        optr = nullptr;
#pragma unroll
        for (int i = 0; i < 8; i++) n3[i] = n4[i] = n5[i] = n6[i] = n7[i] = 0;
      }
      if (tile && t == id) publish();
      if (!tile) {
        if (gemm) {
          float ac1[80];
          auto half = [&](float (&ac)[80], bool rel, int accf) {
            mbar_wait(sb + BAR_BFULL + 8 * bslot, bphase);
            wg_fence();
            const uint32_t a = ring_addr() + wg * 512, bd = (((sb & 0x3FFFF) + OFF_Q + bslot * BB) >> 4) | ((4096u >> 4) << 16);
#pragma unroll
            for (int k = 0; k < 4; k++) wgmma_n160<1, 1>(ac, a + LBO64A + k * 128, HI64A, bd + k * 64, HI64, k == 0 ? accf : 1);
            wg_commit();
            wg_wait<1>();
            if (rel) warp_arrive_cl(mapa(sb + BAR_BEMPTY + 8 * bprev, bprev & 1));
            bprev = bslot;
          };
          auto dstep = [&](int ks) {
            if (!(ks & 3)) TR(640 + ks / 2); if ((ks & 7) == 0) TG(144 + (ks >> 3));
            ring_wait();
            if (!(ks & 3)) TR(641 + ks / 2);
            half(acc, ks < 62, 1);
            release(prev);
            bslot++;
            half(ac1, ks < 61, 1);
            if (++bslot == 6) { bslot = 0; bphase ^= 1; }
            prev = r.slot; r.next();
          };
          bprev = 4; bslot = 1;
          half(ac1, true, 0);
          prev = r.slot; r.next(); bslot = 3;
          half(ac1, true, 1);
          release(prev); prev = r.slot; r.next(); bslot = 5;
          store(n3, optr, IC<3>());
          half(ac1, true, 1);
          release(prev); prev = r.slot; r.next(); bslot = 0; bphase = 1;
#pragma unroll 1
          for (int ks = 3; ks < 7; ks++) {
            dstep(ks);
            switch (ks) {
              case 3: store(n4, optr, IC<4>()); break;
              case 4: store(n5, optr, IC<5>()); break;
              case 5: store(n6, optr, IC<6>()); break;
              default: store(n7, optr, IC<7>()); break;
            }
          }
          publish();
#pragma unroll 1
          for (int ks = 7; ks < 64; ks++) {
            if (wg == 1 && ks == 62) turn_wait();
            dstep(ks);
          }
          if (wg == 0) turn_pass();
          wg_wait<0>();
          reg_fence(acc); reg_fence(ac1);
          TRL(158); TG(156);
          bar_sync(wg);
          out_stage(acc, 0);
          out_stage(ac1, 320);
          out_store(2 * id - 72, 640);
        } else {
          store(n3, optr, IC<3>()); store(n4, optr, IC<4>()); store(n5, optr, IC<5>()); store(n6, optr, IC<6>()); store(n7, optr, IC<7>());
          publish();
        }
        break;
      }
#pragma unroll 1
      for (int ks = 17; ks < 64; ks++) {
        if (END_SKEW && wg == 1 && ks == 64 - END_SKEW) turn_wait();
        bstep(ks, 1);
      }
      if (END_SKEW && wg == 0) turn_pass();
      wg_wait<0>();
      reg_fence(acc);
      release(prev);
      if (!last) warp_arrive_cl(mapa(sb + BAR_BEMPTY + 8 * bprev, bprev & 1));
      TRL(158); TG(156);
      const int pos0 = row_block(t) * 256 + rank * 128 + wg * 64 + w * 16;
      if (last) {
        bar_sync(wg);
        out_stage(acc, 0);
        out_store(t, 320);
      } else {
        const int lane = fresh_tid() & 31;
        __nv_bfloat16* op0 = P.out + (size_t)o_row(pos0 + (lane >> 2)) * DM + (t & 3) * 160 + (lane & 3) * 2;
        __nv_bfloat16* op1 = P.out + (size_t)o_row(pos0 + (lane >> 2) + 8) * DM + (t & 3) * 160 + (lane & 3) * 2;
#pragma unroll
        for (int j = 0; j < 20; j++) {
          *reinterpret_cast<uint32_t*>(op0 + j * 8) = pack(acc[4 * j], acc[4 * j + 1]);
          *reinterpret_cast<uint32_t*>(op1 + j * 8) = pack(acc[4 * j + 2], acc[4 * j + 3]);
        }
      }
#pragma unroll
      for (int i = 0; i < 60; i++) pb[i] = 0;
    }
    TRL(159);
  }
}

typedef CUresult (*EncodeFn)(CUtensorMap*, CUtensorMapDataType, cuuint32_t, void*, const cuuint64_t*, const cuuint64_t*,
                             const cuuint32_t*, const cuuint32_t*, CUtensorMapInterleave, CUtensorMapSwizzle,
                             CUtensorMapL2promotion, CUtensorMapFloatOOBfill);

void make_map(EncodeFn enc, CUtensorMap* m, const void* p, int rank, const cuuint64_t* dims, const cuuint64_t* strides,
              const cuuint32_t* box, CUtensorMapSwizzle sw, CUtensorMapL2promotion promo) {
  cuuint32_t es[4] = {1, 1, 1, 1};
  enc(m, CU_TENSOR_MAP_DATA_TYPE_BFLOAT16, rank, const_cast<void*>(p), dims, strides, box, es, CU_TENSOR_MAP_INTERLEAVE_NONE, sw,
      promo, CU_TENSOR_MAP_FLOAT_OOB_FILL_NONE);
}

}

extern "C" void kernel_launch(void* const* d_in, const int* in_sizes, int n_in, void* d_out, int out_size) {
  static EncodeFn enc = nullptr;
  static int nclusters = 0;
  static void* o_ptr = nullptr;
  if (!enc) {
    cudaDriverEntryPointQueryResult qr;
    cudaGetDriverEntryPoint("cuTensorMapEncodeTiled", (void**)&enc, cudaEnableDefault, &qr);
    cudaFuncSetAttribute(fused_attn_kernel<66>, cudaFuncAttributeMaxDynamicSharedMemorySize, SMEM_BYTES);
    cudaFuncSetAttribute(fused_attn_kernel<0>, cudaFuncAttributeMaxDynamicSharedMemorySize, SMEM_BYTES);
    cudaGetSymbolAddress(&o_ptr, g_o);
    cudaLaunchConfig_t cfg = {};
    cfg.gridDim = 128; cfg.blockDim = 384; cfg.dynamicSmemBytes = SMEM_BYTES;
    cudaLaunchAttribute at; at.id = cudaLaunchAttributeClusterDimension;
    at.val.clusterDim.x = 2; at.val.clusterDim.y = 1; at.val.clusterDim.z = 1;
    cfg.attrs = &at; cfg.numAttrs = 1;
    int n = 0;
    cudaOccupancyMaxActiveClusters(&n, fused_attn_kernel<66>, &cfg);
    nclusters = n >= 66 ? MAXCL : (n >= 64 || n <= 0 ? 64 : n);
  }
  const __nv_bfloat16* x = (const __nv_bfloat16*)d_in[0];
  const __nv_bfloat16* k = (const __nv_bfloat16*)d_in[1];
  const __nv_bfloat16* v = (const __nv_bfloat16*)d_in[2];
  const __nv_bfloat16* wq = (const __nv_bfloat16*)d_in[3];
  const __nv_bfloat16* wo = (const __nv_bfloat16*)d_in[4];
  CUtensorMap tm_x, tm_wq, tm_k, tm_v, tm_o, tm_wo;
  const auto S128 = CU_TENSOR_MAP_SWIZZLE_128B;
  const auto P128 = CU_TENSOR_MAP_L2_PROMOTION_L2_128B, P256 = CU_TENSOR_MAP_L2_PROMOTION_L2_256B;
  { cuuint64_t d[2] = {DM, NB * SQ}, s[1] = {DM * 2}; cuuint32_t b[2] = {64, 120}; make_map(enc, &tm_x, x, 2, d, s, b, S128, X_PROMO); }
  { cuuint64_t d[3] = {64, DM, HD / 64}, s[2] = {HD * 2, 128}; cuuint32_t b[3] = {64, 64, 2}; make_map(enc, &tm_wq, wq, 3, d, s, b, S128, P256); }
  { cuuint64_t d[3] = {64, NB * NH * SK, 2}, s[2] = {DH * 2, 128}; cuuint32_t b[3] = {64, 64, 2};
    make_map(enc, &tm_k, k, 3, d, s, b, S128, P128); make_map(enc, &tm_v, v, 3, d, s, b, S128, P128); }
  { cuuint64_t d[4] = {256, 2, HD / 8, NROWS / 64}, s[3] = {512, NROWS * 16, 1024}; cuuint32_t b[4] = {256, 2, 8, 2};
    make_map(enc, &tm_o, o_ptr, 4, d, s, b, CU_TENSOR_MAP_SWIZZLE_NONE, P256); }
  { cuuint64_t d[3] = {32, HD, DM / 32}, s[2] = {DM * 2, 64}; cuuint32_t b[3] = {32, 64, 5};
    make_map(enc, &tm_wo, wo, 3, d, s, b, CU_TENSOR_MAP_SWIZZLE_64B, P128); }
  Params P{x, k, v, wq, (__nv_bfloat16*)d_out, (__nv_bfloat16*)o_ptr};
  if (nclusters == 66) fused_attn_kernel<66><<<132, 384, SMEM_BYTES>>>(tm_x, tm_wq, tm_k, tm_v, tm_o, tm_wo, P);
  else fused_attn_kernel<0><<<2 * nclusters, 384, SMEM_BYTES>>>(tm_x, tm_wq, tm_k, tm_v, tm_o, tm_wo, P);
}
```

```cpp
#include <cuda_runtime.h>
#include <cuda.h>
#include <cuda_bf16.h>
#include <stdint.h>

namespace {

constexpr int NB = 16, SQ = 240, DM = 640, NH = 32, SK = 1024, DH = 128, HD = NH * DH;
constexpr int NROWS = NB * SQ;
constexpr int NUNITS = 256;
#define DPRO 1
#define LATE_AT 4
#define ALT_FROM 4
#define END_SKEW 5
#define VREL 6
#define PF_HOLD 6
#define PF_N 4
#define PF_J0 3
#define PF_STEP 3
#define ROT 0
#define O_EF 1
#define B_ORDER 1
#define WO_PF 6
#define ROLE_AT 0
#define PAUSE_NS 11000
#define PAUSE_AT 2
#define EARLY 1
#define EARLY_X 2
#define EARLY_W 2
#define X_PROMO P128
#define PAUSE_J -1
#define PAUSE_SPREAD 0
#define WO_PF0 1
#define EPI_MIX 1
#define K2_AT 0
#define SLP 15
#define EREL_FROM 4
#define PRE9 0
#define MAXCL 66
#define SMID_TOP 88
constexpr int NOTILES = 60;
constexpr float QSCALE = 0.08838834764831845f * 1.4426950408889634f;
constexpr float L_MIN = 9.5367431640625e-07f;
constexpr float L_MAX = 1.152921504606846976e18f;

constexpr uint32_t RING_SLOTS = 6, RING_BYTES = 16384;
constexpr uint32_t XB = 15360;
constexpr uint32_t BB = 20480;
constexpr uint32_t OFF_Q = RING_SLOTS * RING_BYTES;
constexpr uint32_t OFF_P = OFF_Q + 4 * XB;
constexpr uint32_t OFF_INV = OFF_P + 4 * XB;
constexpr uint32_t OFF_L2 = OFF_INV + 1280;
constexpr uint32_t OFF_BAR = OFF_L2 + 4096;
constexpr uint32_t BAR_RFULL = OFF_BAR, BAR_REMPTY = BAR_RFULL + 48, BAR_XFULL = BAR_REMPTY + 48,
    BAR_XEMPTY = BAR_XFULL + 64, BAR_BFULL = BAR_XEMPTY + 32, BAR_BEMPTY = BAR_BFULL + 48, BAR_STAGE = BAR_BEMPTY + 48;
constexpr uint32_t BAR_ROLE = BAR_STAGE + 16, BAR_LSUM = BAR_ROLE + 24, BAR_INV = BAR_LSUM + 16;
constexpr uint32_t OFF_TR = BAR_INV + 16;
constexpr uint32_t SMEM_BYTES = OFF_TR + 1024;

constexpr uint32_t HI128 = (1u << 30) | (1024 >> 4);
constexpr uint32_t HI64 = (2u << 30) | (512 >> 4);
constexpr uint32_t HI64A = (2u << 30) | (1024 >> 4), LBO64A = (512u >> 4) << 16;

__device__ __nv_bfloat16 g_o[HD * NROWS];
__device__ unsigned g_cnt[67 * 8];
#define TS(i)
#define TRL(i)
#define TR(i)
#define TG(i)

struct Params {
  const __nv_bfloat16 *x, *k, *v, *wq;
  __nv_bfloat16 *out, *o;
};

__device__ __forceinline__ void wg_fence() { asm volatile("wgmma.fence.sync.aligned;" ::: "memory"); }
__device__ __forceinline__ void wg_commit() { asm volatile("wgmma.commit_group.sync.aligned;" ::: "memory"); }
template <int N> __device__ __forceinline__ void wg_wait() { asm volatile("wgmma.wait_group.sync.aligned %0;" ::"n"(N) : "memory"); }
template <int N> __device__ __forceinline__ void reg_fence(float (&r)[N]) {
#pragma unroll
  for (int i = 0; i < N; i++) asm volatile("" : "+f"(r[i])::"memory");
}
template <int TA, int TB>
__device__ __forceinline__ void wgmma_n120(float (&d)[60], uint32_t a_lo, uint32_t a_hi, uint32_t b_lo, uint32_t b_hi, int acc) {
  asm volatile(
      "{\n.reg .pred p;\n.reg .b64 da, db;\nsetp.ne.b32 p, %64, 0;\n"
      "mov.b64 da, {%60, %61};\nmov.b64 db, {%62, %63};\n"
      "wgmma.mma_async.sync.aligned.m64n120k16.f32.bf16.bf16 {"
      "%0, %1, %2, %3, %4, %5, %6, %7, %8, %9, %10, %11, %12, %13, %14, %15, %16, %17, %18, %19, %20, %21, %22, %23, "
      "%24, %25, %26, %27, %28, %29, %30, %31, %32, %33, %34, %35, %36, %37, %38, %39, %40, %41, %42, %43, %44, %45, "
      "%46, %47, %48, %49, %50, %51, %52, %53, %54, %55, %56, %57, %58, %59"
      "}, da, db, p, 1, 1, %65, %66;\n}\n"
      : "+f"(d[0]), "+f"(d[1]), "+f"(d[2]), "+f"(d[3]), "+f"(d[4]), "+f"(d[5]), "+f"(d[6]), "+f"(d[7]), "+f"(d[8]),
        "+f"(d[9]), "+f"(d[10]), "+f"(d[11]), "+f"(d[12]), "+f"(d[13]), "+f"(d[14]), "+f"(d[15]), "+f"(d[16]),
        "+f"(d[17]), "+f"(d[18]), "+f"(d[19]), "+f"(d[20]), "+f"(d[21]), "+f"(d[22]), "+f"(d[23]), "+f"(d[24]),
        "+f"(d[25]), "+f"(d[26]), "+f"(d[27]), "+f"(d[28]), "+f"(d[29]), "+f"(d[30]), "+f"(d[31]), "+f"(d[32]),
        "+f"(d[33]), "+f"(d[34]), "+f"(d[35]), "+f"(d[36]), "+f"(d[37]), "+f"(d[38]), "+f"(d[39]), "+f"(d[40]),
        "+f"(d[41]), "+f"(d[42]), "+f"(d[43]), "+f"(d[44]), "+f"(d[45]), "+f"(d[46]), "+f"(d[47]), "+f"(d[48]),
        "+f"(d[49]), "+f"(d[50]), "+f"(d[51]), "+f"(d[52]), "+f"(d[53]), "+f"(d[54]), "+f"(d[55]), "+f"(d[56]),
        "+f"(d[57]), "+f"(d[58]), "+f"(d[59])
      : "r"(a_lo), "r"(a_hi), "r"(b_lo), "r"(b_hi), "r"(acc), "n"(TA), "n"(TB));
}

template <int TA, int TB>
__device__ __forceinline__ void wgmma_n160(float (&d)[80], uint32_t a_lo, uint32_t a_hi, uint32_t b_lo, uint32_t b_hi, int acc) {
  asm volatile(
      "{\n.reg .pred p;\n.reg .b64 da, db;\nsetp.ne.b32 p, %84, 0;\n"
      "mov.b64 da, {%80, %81};\nmov.b64 db, {%82, %83};\n"
      "wgmma.mma_async.sync.aligned.m64n160k16.f32.bf16.bf16 {"
      "%0, %1, %2, %3, %4, %5, %6, %7, %8, %9, %10, %11, %12, %13, %14, %15, %16, %17, %18, %19, %20, %21, %22, %23, "
      "%24, %25, %26, %27, %28, %29, %30, %31, %32, %33, %34, %35, %36, %37, %38, %39, %40, %41, %42, %43, %44, %45, "
      "%46, %47, %48, %49, %50, %51, %52, %53, %54, %55, %56, %57, %58, %59, %60, %61, %62, %63, %64, %65, %66, %67, "
      "%68, %69, %70, %71, %72, %73, %74, %75, %76, %77, %78, %79"
      "}, da, db, p, 1, 1, %85, %86;\n}\n"
      : "+f"(d[0]), "+f"(d[1]), "+f"(d[2]), "+f"(d[3]), "+f"(d[4]), "+f"(d[5]), "+f"(d[6]), "+f"(d[7]), "+f"(d[8]),
        "+f"(d[9]), "+f"(d[10]), "+f"(d[11]), "+f"(d[12]), "+f"(d[13]), "+f"(d[14]), "+f"(d[15]), "+f"(d[16]),
        "+f"(d[17]), "+f"(d[18]), "+f"(d[19]), "+f"(d[20]), "+f"(d[21]), "+f"(d[22]), "+f"(d[23]), "+f"(d[24]),
        "+f"(d[25]), "+f"(d[26]), "+f"(d[27]), "+f"(d[28]), "+f"(d[29]), "+f"(d[30]), "+f"(d[31]), "+f"(d[32]),
        "+f"(d[33]), "+f"(d[34]), "+f"(d[35]), "+f"(d[36]), "+f"(d[37]), "+f"(d[38]), "+f"(d[39]), "+f"(d[40]),
        "+f"(d[41]), "+f"(d[42]), "+f"(d[43]), "+f"(d[44]), "+f"(d[45]), "+f"(d[46]), "+f"(d[47]), "+f"(d[48]),
        "+f"(d[49]), "+f"(d[50]), "+f"(d[51]), "+f"(d[52]), "+f"(d[53]), "+f"(d[54]), "+f"(d[55]), "+f"(d[56]),
        "+f"(d[57]), "+f"(d[58]), "+f"(d[59]), "+f"(d[60]), "+f"(d[61]), "+f"(d[62]), "+f"(d[63]), "+f"(d[64]),
        "+f"(d[65]), "+f"(d[66]), "+f"(d[67]), "+f"(d[68]), "+f"(d[69]), "+f"(d[70]), "+f"(d[71]), "+f"(d[72]),
        "+f"(d[73]), "+f"(d[74]), "+f"(d[75]), "+f"(d[76]), "+f"(d[77]), "+f"(d[78]), "+f"(d[79])
      : "r"(a_lo), "r"(a_hi), "r"(b_lo), "r"(b_hi), "r"(acc), "n"(TA), "n"(TB));
}
__device__ __forceinline__ void mbar_init(uint32_t bar, int cnt) { asm volatile("mbarrier.init.shared::cta.b64 [%0], %1;" ::"r"(bar), "r"(cnt)); }
__device__ __forceinline__ void mbar_expect(uint32_t bar, uint32_t bytes) {
  asm volatile("mbarrier.arrive.expect_tx.shared::cta.b64 _, [%0], %1;" ::"r"(bar), "r"(bytes) : "memory");
}
__device__ __forceinline__ uint32_t mapa(uint32_t addr, uint32_t cta) {
  uint32_t r; asm("mapa.shared::cluster.u32 %0, %1, %2;" : "=r"(r) : "r"(addr), "r"(cta)); return r;
}
__device__ __forceinline__ void mbar_expect_cl(uint32_t cbar, uint32_t bytes) {
  asm volatile("mbarrier.arrive.expect_tx.shared::cluster.b64 _, [%0], %1;" ::"r"(cbar), "r"(bytes) : "memory");
}
__device__ __forceinline__ void mbar_arrive(uint32_t bar) { asm volatile("mbarrier.arrive.shared::cta.b64 _, [%0];" ::"r"(bar) : "memory"); }
__device__ __forceinline__ void mbar_arrive_cl(uint32_t cbar) { asm volatile("mbarrier.arrive.shared::cluster.b64 _, [%0];" ::"r"(cbar) : "memory"); }
__device__ __forceinline__ void warp_arrive(uint32_t bar) {
  asm volatile("{\n.reg .pred p;\nelect.sync _|p, 0xffffffff;\n@p mbarrier.arrive.shared::cta.b64 _, [%0];\n}\n" ::"r"(bar) : "memory");
}
__device__ __forceinline__ void warp_arrive_cl(uint32_t cbar) {
  asm volatile("{\n.reg .pred p;\nelect.sync _|p, 0xffffffff;\n@p mbarrier.arrive.shared::cluster.b64 _, [%0];\n}\n" ::"r"(cbar) : "memory");
}
__device__ __forceinline__ void mbar_wait(uint32_t bar, uint32_t parity) {
  asm volatile(
      "{\n.reg .pred p;\n.reg .u32 n;\n"
      "mbarrier.try_wait.parity.shared::cta.b64 p, [%0], %1;\n@p bra WAIT_DONE;\n"
      "mov.u32 n, 0;\n"
      "WAIT_LOOP:\n"
      "mbarrier.try_wait.parity.shared::cta.b64 p, [%0], %1;\n@p bra WAIT_DONE;\n"
      "add.u32 n, n, 1;\nsetp.lt.u32 p, n, 0x4000000;\n@p bra WAIT_LOOP;\ntrap;\n"
      "WAIT_DONE:\n}\n" ::"r"(bar), "r"(parity) : "memory");
}
__device__ __forceinline__ void mbar_sleep(uint32_t bar, uint32_t parity) {
  asm volatile(
      "{\n.reg .pred p;\n.reg .u32 n;\nmov.u32 n, 0;\n"
      "WAIT_LOOP:\n"
      "mbarrier.try_wait.parity.shared::cta.b64 p, [%0], %1, 4000;\n@p bra WAIT_DONE;\n"
      "add.u32 n, n, 1;\nsetp.lt.u32 p, n, 0x400000;\n@p bra WAIT_LOOP;\ntrap;\n"
      "WAIT_DONE:\n}\n" ::"r"(bar), "r"(parity) : "memory");
}
__device__ __forceinline__ void mbar_wait_cl(uint32_t bar, uint32_t parity) {
  asm volatile(
      "{\n.reg .pred p;\n.reg .u32 n;\nmov.u32 n, 0;\n"
      "WAIT_LOOP:\n"
      "mbarrier.try_wait.parity.acquire.cluster.shared::cta.b64 p, [%0], %1;\n@p bra WAIT_DONE;\n"
      "add.u32 n, n, 1;\nsetp.lt.u32 p, n, 0x4000000;\n@p bra WAIT_LOOP;\ntrap;\n"
      "WAIT_DONE:\n}\n" ::"r"(bar), "r"(parity) : "memory");
}
__device__ __forceinline__ void tma3d(uint32_t dst, const CUtensorMap* m, int c0, int c1, int c2, uint32_t bar) {
  asm volatile("cp.async.bulk.tensor.3d.shared::cluster.global.mbarrier::complete_tx::bytes [%0], [%1, {%3, %4, %5}], [%2];"
               ::"r"(dst), "l"(m), "r"(bar), "r"(c0), "r"(c1), "r"(c2) : "memory");
}
__device__ __forceinline__ void tma3d_hint(uint32_t dst, const CUtensorMap* m, int c0, int c1, int c2, uint32_t bar, uint64_t pol) {
  asm volatile("cp.async.bulk.tensor.3d.shared::cluster.global.mbarrier::complete_tx::bytes.L2::cache_hint [%0], [%1, {%3, %4, %5}], [%2], %6;"
               ::"r"(dst), "l"(m), "r"(bar), "r"(c0), "r"(c1), "r"(c2), "l"(pol) : "memory");
}
__device__ __forceinline__ void tma2d_mc(uint32_t dst, const CUtensorMap* m, int c0, int c1, uint32_t bar) {
  asm volatile("cp.async.bulk.tensor.2d.shared::cluster.global.mbarrier::complete_tx::bytes.multicast::cluster [%0], [%1, {%3, %4}], [%2], %5;"
               ::"r"(dst), "l"(m), "r"(bar), "r"(c0), "r"(c1), "h"((uint16_t)3) : "memory");
}
__device__ __forceinline__ void tma3d_mc(uint32_t dst, const CUtensorMap* m, int c0, int c1, int c2, uint32_t bar) {
  asm volatile("cp.async.bulk.tensor.3d.shared::cluster.global.mbarrier::complete_tx::bytes.multicast::cluster [%0], [%1, {%3, %4, %5}], [%2], %6;"
               ::"r"(dst), "l"(m), "r"(bar), "r"(c0), "r"(c1), "r"(c2), "h"((uint16_t)3) : "memory");
}
__device__ __forceinline__ void l2_prefetch(const void* p, uint32_t bytes) {
  asm volatile("cp.async.bulk.prefetch.L2.global [%0], %1;" ::"l"(p), "r"(bytes) : "memory");
}
__device__ __forceinline__ void fence_async_smem() { asm volatile("fence.proxy.async.shared::cta;" ::: "memory"); }
__device__ __forceinline__ void bar_sync(int wg) {
  if (wg == 0) asm volatile("bar.sync 1, 128;" ::: "memory");
  else asm volatile("bar.sync 2, 128;" ::: "memory");
}
__device__ __forceinline__ bool bar_red_or(int id, bool v) {
  uint32_t r;
  asm volatile("{\n.reg .pred p, q;\nsetp.ne.u32 p, %2, 0;\nbar.red.or.pred q, %1, 128, p;\nselp.u32 %0, 1, 0, q;\n}\n"
               : "=r"(r) : "r"(1 + id), "r"((uint32_t)v) : "memory");
  return r != 0;
}
__device__ __forceinline__ uint32_t hfma2(uint32_t a, uint32_t b, uint32_t c) { uint32_t r; asm("fma.rn.bf16x2 %0, %1, %2, %3;" : "=r"(r) : "r"(a), "r"(b), "r"(c)); return r; }
__device__ __forceinline__ float ex2(float x) { float y; asm("ex2.approx.ftz.f32 %0, %1;" : "=f"(y) : "f"(x)); return y; }
__device__ __forceinline__ uint32_t pack(float lo, float hi) { uint32_t r; asm("cvt.rn.bf16x2.f32 %0, %1, %2;" : "=r"(r) : "f"(hi), "f"(lo)); return r; }
__device__ __forceinline__ void stsm4t(uint32_t a, uint32_t r0, uint32_t r1, uint32_t r2, uint32_t r3) {
  asm volatile("stmatrix.sync.aligned.m8n8.x4.trans.shared.b16 [%0], {%1,%2,%3,%4};" ::"r"(a), "r"(r0), "r"(r1), "r"(r2), "r"(r3) : "memory");
}
__device__ __forceinline__ void stsm2t(uint32_t a, uint32_t r0, uint32_t r1) {
  asm volatile("stmatrix.sync.aligned.m8n8.x2.trans.shared.b16 [%0], {%1,%2};" ::"r"(a), "r"(r0), "r"(r1) : "memory");
}
__device__ __forceinline__ void mma16816(float (&d)[4], const uint32_t (&a)[4], uint32_t b0, uint32_t b1) {
  asm volatile("mma.sync.aligned.m16n8k16.row.col.f32.bf16.bf16.f32 {%0,%1,%2,%3}, {%4,%5,%6,%7}, {%8,%9}, {%0,%1,%2,%3};"
               : "+f"(d[0]), "+f"(d[1]), "+f"(d[2]), "+f"(d[3]) : "r"(a[0]), "r"(a[1]), "r"(a[2]), "r"(a[3]), "r"(b0), "r"(b1));
}

__device__ __forceinline__ uint32_t fresh_tid() { uint32_t t; asm volatile("mov.u32 %0, %tid.x;" : "=r"(t)); return t; }

template <int V> struct IC { static constexpr int value = V; };

struct Ring {
  uint32_t slot = 0, phase = 0;
  __device__ __forceinline__ void next() { if (++slot == RING_SLOTS) { slot = 0; phase ^= 1; } }
};

__device__ __forceinline__ void mma_tn(float (&o0)[60], float (&o1)[60], uint32_t a, uint32_t b, int acc) {
#pragma unroll
  for (int k = 0; k < 4; k++) {
    wgmma_n120<1, 0>(o0, a + k * 128, HI128, b + k * 2, HI128, k == 0 ? acc : 1);
    wgmma_n120<1, 0>(o1, a + 512 + k * 128, HI128, b + k * 2, HI128, k == 0 ? acc : 1);
  }
}
__device__ __forceinline__ void mma_tn_split(float (&o0)[60], float (&o1)[60], uint32_t a, uint32_t b) {
#pragma unroll
  for (int k = 0; k < 4; k++) wgmma_n120<1, 0>(o0, a + k * 128, HI128, b + k * 2, HI128, 1);
  wg_commit();
#pragma unroll
  for (int k = 0; k < 4; k++) wgmma_n120<1, 0>(o1, a + 512 + k * 128, HI128, b + k * 2, HI128, 1);
  wg_commit();
}
__device__ __forceinline__ void mma_qk(float (&s)[60], uint32_t a, uint32_t q) {
#pragma unroll
  for (int k = 0; k < 8; k++)
    wgmma_n120<0, 0>(s, a + (k >> 2) * 512 + (k & 3) * 2, HI128, q + (k >> 2) * (XB >> 4) + (k & 3) * 2, HI128, k != 0);
}
template <int J0, int J1, bool FIRST = false>
__device__ __forceinline__ void exp_store(const float (&s)[60], float (&l)[30], uint32_t dst) {
#pragma unroll
  for (int j = J0; j < J1; j += 2) {
    uint32_t p[4];
#pragma unroll
    for (int jj = 0; jj < 2; jj++) {
      if (j + jj < 15) {
        const int c = j + jj;
        float e0 = ex2(s[4 * c]), e1 = ex2(s[4 * c + 1]), e2 = ex2(s[4 * c + 2]), e3 = ex2(s[4 * c + 3]);
        if (FIRST) { l[2 * c] = e0 + e2; l[2 * c + 1] = e1 + e3; }
        else { l[2 * c] += e0; l[2 * c + 1] += e1; l[2 * c] += e2; l[2 * c + 1] += e3; }
        p[2 * jj] = pack(e0, e1); p[2 * jj + 1] = pack(e2, e3);
      }
    }
    if (j + 1 < 15) stsm4t(dst + j * 1024, p[0], p[1], p[2], p[3]);
    else stsm2t(dst + j * 1024, p[0], p[1]);
  }
}

__device__ __forceinline__ int o_pos(int b, int wg, int r) {
  const int j = r >> 3, q = (r >> 1) & 3, c = r & 1, o = b & 1, base = (b >> 1) * 480;
  if (j < 12) return base + (o * 9 + wg * 3 + (j >> 2)) * 32 + q * 8 + (j & 3) * 2 + c;
  if (j < 14) return base + (6 + 2 * o) * 32 + wg * 16 + q * 4 + (j - 12) * 2 + c;
  return base + 7 * 32 + (o * 2 + wg) * 8 + q * 2 + c;
}
__device__ __forceinline__ int o_row(int p) {
  const int pair = p / 480, a = (p - pair * 480) >> 5, in = p & 31, c = p & 1;
  int tile, row;
  if (a == 7) { tile = in >> 3; row = 112 + (in & 7); }
  else if (a == 6 || a == 8) { tile = a - 6 + (in >> 4); row = (12 + ((in >> 1) & 1)) * 8 + ((in >> 2) & 3) * 2 + c; }
  else { const int f = a > 8 ? a - 3 : a; tile = f / 3; row = ((f - tile * 3) * 4 + ((in >> 1) & 3)) * 8 + (in >> 3) * 2 + c; }
  return pair * 480 + tile * 120 + row;
}
__device__ __forceinline__ uint32_t o_idx(int k, int p) {
  return ((k >> 3) * (NROWS / 32) + (p >> 5)) * 256 + (k & 7) * 32 + ((((p >> 3) & 3) ^ ((k & 7) >> 1)) << 3) + (p & 7);
}

__device__ __forceinline__ void slow_path(const Params& P, int b, int h, int wg, int w, int lane) {
  const int g = lane >> 2, q = lane & 3, row0 = wg * 120;
  const uint16_t* wq = reinterpret_cast<const uint16_t*>(P.wq) + h * DH + g;
  const __nv_bfloat16* kp = P.k + (size_t)(b * NH + h) * SK * DH;
  const uint16_t* vp = reinterpret_cast<const uint16_t*>(P.v) + (size_t)(b * NH + h) * SK * DH + g;
#pragma unroll 1
  for (int t = w; t < 8; t += 4) {
    const int r0 = 16 * t + g, r1 = r0 + 8;
    const __nv_bfloat16* x0 = P.x + (size_t)(b * SQ + row0 + r0) * DM + 2 * q;
    const __nv_bfloat16* x1 = P.x + (size_t)(b * SQ + row0 + min(r1, 119)) * DM + 2 * q;
    float o[16][4];
#pragma unroll
    for (int n = 0; n < 16; n++) o[n][0] = o[n][1] = o[n][2] = o[n][3] = 0.f;
#pragma unroll 1
    for (int k0 = 0; k0 < DM; k0 += 16) {
      uint32_t a[4] = {*(const uint32_t*)(x0 + k0), *(const uint32_t*)(x1 + k0), *(const uint32_t*)(x0 + k0 + 8), *(const uint32_t*)(x1 + k0 + 8)};
      const uint16_t* wr = wq + (size_t)(k0 + 2 * q) * HD;
#pragma unroll
      for (int n = 0; n < 16; n++) {
        if ((n & 3) == 0) __syncwarp();
        mma16816(o[n], a, wr[8 * n] | ((uint32_t)wr[8 * n + HD] << 16), wr[8 * n + 8 * HD] | ((uint32_t)wr[8 * n + 9 * HD] << 16));
      }
    }
    uint32_t qa[8][4];
#pragma unroll
    for (int k = 0; k < 8; k++) {
      qa[k][0] = pack(o[2 * k][0] * QSCALE, o[2 * k][1] * QSCALE);
      qa[k][1] = pack(o[2 * k][2] * QSCALE, o[2 * k][3] * QSCALE);
      qa[k][2] = pack(o[2 * k + 1][0] * QSCALE, o[2 * k + 1][1] * QSCALE);
      qa[k][3] = pack(o[2 * k + 1][2] * QSCALE, o[2 * k + 1][3] * QSCALE);
    }
#pragma unroll
    for (int n = 0; n < 16; n++) o[n][0] = o[n][1] = o[n][2] = o[n][3] = 0.f;
    float m0 = -INFINITY, m1 = -INFINITY, l0 = 0.f, l1 = 0.f;
#pragma unroll 1
    for (int key0 = 0; key0 < SK; key0 += 16) {
      float s[2][4];
#pragma unroll
      for (int nt = 0; nt < 2; nt++) {
        s[nt][0] = s[nt][1] = s[nt][2] = s[nt][3] = 0.f;
        const __nv_bfloat16* kr = kp + (size_t)(key0 + 8 * nt + g) * DH + 2 * q;
#pragma unroll
        for (int k = 0; k < 8; k++) mma16816(s[nt], qa[k], *(const uint32_t*)(kr + 16 * k), *(const uint32_t*)(kr + 16 * k + 8));
      }
      float n0 = fmaxf(fmaxf(s[0][0], s[0][1]), fmaxf(s[1][0], s[1][1])), n1 = fmaxf(fmaxf(s[0][2], s[0][3]), fmaxf(s[1][2], s[1][3]));
      n0 = fmaxf(n0, __shfl_xor_sync(~0u, n0, 1)); n1 = fmaxf(n1, __shfl_xor_sync(~0u, n1, 1));
      n0 = fmaxf(n0, __shfl_xor_sync(~0u, n0, 2)); n1 = fmaxf(n1, __shfl_xor_sync(~0u, n1, 2));
      n0 = fmaxf(n0, m0); n1 = fmaxf(n1, m1);
      const float z0 = n0 == -INFINITY ? 0.f : n0, z1 = n1 == -INFINITY ? 0.f : n1;
      const float c0 = ex2(m0 - z0), c1 = ex2(m1 - z1);
      m0 = n0; m1 = n1;
#pragma unroll
      for (int nt = 0; nt < 2; nt++) {
        s[nt][0] = ex2(s[nt][0] - z0); s[nt][1] = ex2(s[nt][1] - z0);
        s[nt][2] = ex2(s[nt][2] - z1); s[nt][3] = ex2(s[nt][3] - z1);
      }
      l0 = l0 * c0 + s[0][0] + s[0][1] + s[1][0] + s[1][1];
      l1 = l1 * c1 + s[0][2] + s[0][3] + s[1][2] + s[1][3];
      uint32_t pa[4] = {pack(s[0][0], s[0][1]), pack(s[0][2], s[0][3]), pack(s[1][0], s[1][1]), pack(s[1][2], s[1][3])};
      const uint16_t* vr = vp + (size_t)(key0 + 2 * q) * DH;
#pragma unroll
      for (int n = 0; n < 16; n++) {
        if ((n & 3) == 0) __syncwarp();
        o[n][0] *= c0; o[n][1] *= c0; o[n][2] *= c1; o[n][3] *= c1;
        mma16816(o[n], pa, vr[8 * n] | ((uint32_t)vr[8 * n + DH] << 16), vr[8 * n + 8 * DH] | ((uint32_t)vr[8 * n + 9 * DH] << 16));
      }
    }
    l0 += __shfl_xor_sync(~0u, l0, 1); l1 += __shfl_xor_sync(~0u, l1, 1);
    l0 += __shfl_xor_sync(~0u, l0, 2); l1 += __shfl_xor_sync(~0u, l1, 2);
    const float i0 = 1.f / l0, i1 = 1.f / l1;
    __nv_bfloat16* oc0 = P.o + o_idx(h * DH + 2 * q, o_pos(b, wg, r0));
    __nv_bfloat16* oc1 = P.o + o_idx(h * DH + 2 * q, o_pos(b, wg, min(r1, 119)));
#pragma unroll
    for (int n = 0; n < 16; n++) {
      oc0[8 * n * NROWS] = __float2bfloat16(o[n][0] * i0);
      oc0[8 * n * NROWS + 32] = __float2bfloat16(o[n][1] * i0);
      if (r1 < 120) {
        oc1[8 * n * NROWS] = __float2bfloat16(o[n][2] * i1);
        oc1[8 * n * NROWS + 32] = __float2bfloat16(o[n][3] * i1);
      }
    }
  }
}

__device__ __forceinline__ int bk(int ks) { return B_ORDER && ks < 48 ? 32 - (ks & 48) + (ks & 15) : ks; }
__device__ __forceinline__ uint32_t x_slot(uint32_t wg, uint32_t j) { return j < 2 ? (2 * wg + j) * XB : (2 * j + wg) * XB; }
__device__ __forceinline__ int row_block(int t) { return t >= 44 ? (t >> 2) - 11 : (t >> 2) + 4; }
__device__ __forceinline__ int unit_batch(int u) { return (u & 63) >> 2; }
__device__ __forceinline__ int unit_head(int u, int rank) { return (u >> 6) * 8 + (u & 3) * 2 + rank; }

template <int NCL>
__global__ void __cluster_dims__(2, 1, 1) __launch_bounds__(384, 1)
fused_attn_kernel(const __grid_constant__ CUtensorMap tm_x, const __grid_constant__ CUtensorMap tm_wq,
                  const __grid_constant__ CUtensorMap tm_k, const __grid_constant__ CUtensorMap tm_v,
                  const __grid_constant__ CUtensorMap tm_o, const __grid_constant__ CUtensorMap tm_wo,
                  const __grid_constant__ Params P) {
  extern __shared__ uint8_t smem_raw[];
  const uint32_t sb = ((uint32_t)__cvta_generic_to_shared(smem_raw) + 1023) & ~1023u;
  if (threadIdx.x == 0) TS(152);
  const int warp = __shfl_sync(~0u, threadIdx.x >> 5, 0);
  const int lane = threadIdx.x & 31;
  const int rank = blockIdx.x & 1, cl = blockIdx.x >> 1, ncl = NCL ? NCL : gridDim.x >> 1;

  const int nsingle = NCL == 66 ? 44 : NOTILES;
  auto role = [&]() {
    mbar_wait(sb + BAR_ROLE + 16, 0);
    int id;
    asm volatile("ld.shared.u32 %0, [%1];" : "=r"(id) : "r"(sb + BAR_ROLE + 8) : "memory");
    return id;
  };

  if (EARLY && threadIdx.x == 128) asm volatile("prefetch.tensormap [%0];" ::"l"(&tm_x) : "memory");
  if (threadIdx.x == 0) {
    if (EARLY) asm volatile("prefetch.tensormap [%0];" ::"l"(&tm_wq) : "memory");
    for (int i = 0; i < 6; i++) {
      mbar_init(sb + BAR_RFULL + 8 * i, 1); mbar_init(sb + BAR_REMPTY + 8 * i, 8);
      mbar_init(sb + BAR_BFULL + 8 * i, 1); mbar_init(sb + BAR_BEMPTY + 8 * i, 16);
    }
    for (int i = 0; i < 8; i++) mbar_init(sb + BAR_XFULL + 8 * i, 1);
    for (int i = 0; i < 4; i++) mbar_init(sb + BAR_XEMPTY + 8 * i, 8);
    for (int i = 0; i < 2; i++) { mbar_init(sb + BAR_STAGE + 8 * i, 4); mbar_init(sb + BAR_LSUM + 8 * i, 4); mbar_init(sb + BAR_INV + 8 * i, 1); }
    mbar_init(sb + BAR_ROLE, 1); mbar_init(sb + BAR_ROLE + 16, 1);
    asm volatile("fence.mbarrier_init.release.cluster;" ::: "memory");
  }
  __syncwarp();
  asm volatile("barrier.cluster.arrive.relaxed.aligned;" ::: "memory");
  auto first_w = [&](int s) {
    mbar_expect(sb + BAR_RFULL + 8 * s, RING_BYTES);
    tma3d(sb + s * RING_BYTES, &tm_wq, 0, s * 64, 2 * unit_head(cl, rank), sb + BAR_RFULL + 8 * s);
  };
  if (EARLY && threadIdx.x == 0) first_w(0);
  __syncwarp();
  asm volatile("barrier.cluster.wait.aligned;" ::: "memory");
  if (EARLY && threadIdx.x == 128) {
#pragma unroll 1
    for (int s = 0; s < EARLY_X; s++) {
      const uint32_t fb = sb + BAR_XFULL + 32 * rank + 8 * s;
      mbar_expect(fb, XB);
      mbar_expect_cl(mapa(fb, rank ^ 1), XB);
      tma2d_mc(sb + OFF_Q + x_slot(rank, s), &tm_x, s * 64, unit_batch(cl) * SQ + rank * 120, fb);
      if (s + 1 < EARLY_W) first_w(s + 1);
    }
  }
  __syncwarp();
  if (threadIdx.x == 0) TS(153);

  if (warp >= 8) {
    asm volatile("setmaxnreg.dec.sync.aligned.u32 24;");
    if (warp == 8) {
      uint64_t pol;
      asm volatile("createpolicy.fractional.L2::evict_first.b64 %0, 1.0;" : "=l"(pol));
      Ring r;
      if (EARLY) r.slot = EARLY_W;
      auto load = [&](const CUtensorMap* m, int c1, int c2, bool ef) {
        if (SLP & 8) mbar_sleep(sb + BAR_REMPTY + 8 * r.slot, r.phase ^ 1); else mbar_wait(sb + BAR_REMPTY + 8 * r.slot, r.phase ^ 1);
        if (lane == 0) {
          mbar_expect(sb + BAR_RFULL + 8 * r.slot, RING_BYTES);
          if (ef) tma3d_hint(sb + r.slot * RING_BYTES, m, 0, c1, c2, sb + BAR_RFULL + 8 * r.slot, pol);
          else tma3d(sb + r.slot * RING_BYTES, m, 0, c1, c2, sb + BAR_RFULL + 8 * r.slot);
        }
        r.next();
      };
      const int rot = ROT * (blockIdx.x * 5 + (blockIdx.x >> 4));
      auto pause = [&](int u0) {
        if (PAUSE_NS && NCL == 66 && u0 == PAUSE_AT * 66) {
          const int id = role();
          if (id >= 44 && id < 58) {
            unsigned t0, t1;
            asm volatile("mov.u32 %0, %globaltimer_lo;" : "=r"(t0));
            do { __nanosleep(200); asm volatile("mov.u32 %0, %globaltimer_lo;" : "=r"(t1)); } while (t1 - t0 < PAUSE_NS + (id - 44) * PAUSE_SPREAD);
          }
        }
      };
      for (int u0 = 0;; u0 += ncl) {
        const int u = __shfl_sync(~0u, (u0 >= 3 * ncl ? role() : cl) + u0, 0);
        if (u >= NUNITS) break;
        if (PAUSE_J < 0) pause(u0);
        const int h = unit_head(u, rank);
        const int krow = (unit_batch(u) * NH + h) * SK;
#pragma unroll 1
        for (int s = EARLY && u0 == 0 ? EARLY_W : 0; s < 10; s++) {
          if (u0 == 0 && s == 0 && lane == 0) TS(154);
          load(&tm_wq, s * 64, 2 * h, false);
          if (u0 == 0 && s == 0 && lane == 0) TS(155);
          const int sp = u0 == 0 ? s - PF_HOLD : s;
          if (sp >= 0 && sp < PF_N && lane == 0) l2_prefetch(P.v + (size_t)(krow + ((PF_J0 + sp * PF_STEP + rot) & 15) * 64) * DH, 16384);
        }
#pragma unroll 1
        for (int j = 0; j <= 16; j++) {
          if (j == PAUSE_J) pause(u0);
          if (j < 16) load(&tm_k, krow + ((j + rot) & 15) * 64, 0, true);
          if (j == 1 + DPRO) load(&tm_v, krow + (rot & 15) * 64, 0, true);
          if (j > 1) load(&tm_v, krow + ((j - 1 + rot) & 15) * 64, 0, true);
        }
      }
      const int id = __shfl_sync(~0u, role(), 0);
      const bool dbl = NCL == 66 && id >= 58;
      for (int t = dbl ? 2 * id - 72 : id; t < (dbl ? NOTILES : nsingle); t += ncl) {
        const int row0 = row_block(t) * 256 + rank * 128;
        const int b0 = (row0 & ~31) / SQ, b1 = (row0 + 127) / SQ;
#pragma unroll 1
        for (int ks = 0; ks < 64; ks++) {
          if (dbl ? (ks & 15) == 0 : ks == 0 || ks == 48) {
            const unsigned* c = &g_cnt[((lane & 1 ? b1 : b0) * 4 + (ks || dbl ? ks >> 4 : min(lane >> 1, 2))) * 8];
            unsigned v, n = 0;
            do {
              asm volatile("ld.acquire.gpu.global.u32 %0, [%1];" : "=r"(v) : "l"(c) : "memory");
              if (++n > (1u << 26)) __trap();
            } while (v < 16);
            __syncwarp();
            asm volatile("fence.proxy.async.global;" ::: "memory");
          }
          mbar_wait(sb + BAR_REMPTY + 8 * r.slot, r.phase ^ 1);
          if (lane == 0) {
            mbar_expect(sb + BAR_RFULL + 8 * r.slot, RING_BYTES);
            asm volatile("cp.async.bulk.tensor.4d.shared::cluster.global.mbarrier::complete_tx::bytes.L2::cache_hint [%0], [%1, {%3, %3, %4, %5}], [%2], %6;"
                         ::"r"(sb + r.slot * RING_BYTES), "l"(&tm_o), "r"(sb + BAR_RFULL + 8 * r.slot), "r"(0), "r"((dbl ? ks : bk(ks)) * 8), "r"(row0 >> 6), "l"(pol) : "memory");
          }
          r.next();
        }
      }
      if (lane == 0 && atomicAdd(&g_cnt[64 * 8], 1) == gridDim.x - 1) {
        for (int i = 0; i < 67; i++) g_cnt[i * 8] = 0;
      }
    } else if (warp == 9) {
      if (lane == 0) {
        uint32_t it = 0;
        for (;; it++) {
          const int u = (it >= 3 ? role() : cl) + it * ncl;
          if (u >= NUNITS) break;
          const int row = unit_batch(u) * SQ + rank * 120;
#pragma unroll 1
          for (int s = EARLY && it == 0 ? EARLY_X : 0; s < 10; s++) {
            const uint32_t j = s & 3, par = ((s >> 2) + (j < 2 ? it : 0)) & 1;
            if ((SLP & 4) && s == 0) mbar_sleep(sb + BAR_XEMPTY, par ^ 1);
            mbar_wait(sb + BAR_XEMPTY + 8 * j, par ^ 1);
            const uint32_t fb = sb + BAR_XFULL + 32 * rank + 8 * j;
            mbar_expect(fb, XB);
            mbar_expect_cl(mapa(fb, rank ^ 1), XB);
            tma2d_mc(sb + OFF_Q + x_slot(rank, j), &tm_x, s * 64, row, fb);
          }
        }
        const int id = role();
        const bool dbl = NCL == 66 && id >= 58;
        uint32_t slot = rank, phase = 0;
        if (WO_PF0 && dbl)
          asm volatile("cp.async.bulk.prefetch.tensor.3d.L2.global [%0, {%1, %2, %3}];" ::"l"(&tm_wo), "r"(0), "r"((2 + ((id >> 1) & 3)) * 64), "r"(((2 * id - 72 + rank) & 3) * 5) : "memory");
        if ((SLP & 4) && (dbl || id < nsingle)) mbar_sleep(sb + BAR_BEMPTY + 8 * rank, 0);
        for (int t = dbl ? 2 * id - 72 + rank : id; t < (dbl ? NOTILES : nsingle); t += ncl) {
#pragma unroll 1
          for (int ks = dbl ? 0 : rank; ks < 64; ks += dbl ? 1 : 2) {
            mbar_wait(sb + BAR_BEMPTY + 8 * slot, phase);
            const uint32_t fb = sb + BAR_BFULL + 8 * slot;
            mbar_expect(fb, BB);
            mbar_expect_cl(mapa(fb, rank ^ 1), BB);
            tma3d_mc(sb + OFF_Q + slot * BB, &tm_wo, 0, (dbl ? ks : bk(ks)) * 64, (t & 3) * 5, fb);
            if (WO_PF && dbl && ks + WO_PF < 64 && (ks & 3) == ((id >> 1) & 3))
              asm volatile("cp.async.bulk.prefetch.tensor.3d.L2.global [%0, {%1, %2, %3}];" ::"l"(&tm_wo), "r"(0), "r"((ks + WO_PF) * 64), "r"((t & 3) * 5) : "memory");
            slot += 2;
            if (slot >= 6) { slot -= 6; phase ^= 1; }
          }
        }
      }
    } else {
      const int wg = warp - 10;
      {
        mbar_wait(sb + BAR_RFULL, 0);
        const __nv_bfloat16* xs = P.x + (size_t)(unit_batch(cl) * SQ + ((cl & 3) * 2 + rank) * 30 + min(lane, 29)) * DM + 256 + wg * 64;
#pragma unroll
        for (int i = 0; i < 3; i++) asm volatile("prefetch.global.L2 [%0];" ::"l"(xs + i * 128));
        if (lane < 16) asm volatile("prefetch.global.L2 [%0];" ::"l"(P.wq + (size_t)(384 + unit_batch(cl) * 16 + lane) * HD + unit_head(cl, rank) * DH + wg * 64));
      }
      auto take_role = [&]() {
          if (wg == 0 && rank == 0 && lane == 0) {
            int id = cl;
            if (NCL == 66) {
              uint32_t smid;
              asm("mov.u32 %0, %smid;" : "=r"(smid));
              id = smid >= SMID_TOP ? 65 - atomicAdd(&g_cnt[65 * 8], 1) : atomicAdd(&g_cnt[66 * 8], 1);
            }
    #pragma unroll
            for (int c = 0; c < 2; c++) {
              const uint32_t a = mapa(sb + BAR_ROLE, c);
              asm volatile("st.shared::cluster.u32 [%0 + 8], %1;\nmbarrier.arrive.release.cluster.shared::cluster.b64 _, [%0];" ::"r"(a), "r"(id) : "memory");
            }
          }
          if (wg == 0 && lane == 0) {
            mbar_wait_cl(sb + BAR_ROLE, 0);
            mbar_arrive(sb + BAR_ROLE + 16);
          }
      };
      if (ROLE_AT < 0) { take_role(); __syncwarp(); }
      for (uint32_t it = 0;; it++) {
        const int u = __shfl_sync(~0u, (it >= 3 ? role() : cl) + it * ncl, 0);
        if (u >= NUNITS) break;
        if (SLP & 1) mbar_sleep(sb + BAR_LSUM + 8 * wg, it & 1); else mbar_wait(sb + BAR_LSUM + 8 * wg, it & 1);
        float l4[4], v[4];
        const uint32_t a = sb + OFF_L2 + wg * 2048 + lane * 16;
        asm volatile("ld.shared.v4.f32 {%0, %1, %2, %3}, [%4];" : "=f"(l4[0]), "=f"(l4[1]), "=f"(l4[2]), "=f"(l4[3]) : "r"(a) : "memory");
#pragma unroll
        for (int g = 1; g < 4; g++) {
          asm volatile("ld.shared.v4.f32 {%0, %1, %2, %3}, [%4];" : "=f"(v[0]), "=f"(v[1]), "=f"(v[2]), "=f"(v[3]) : "r"(a + g * 512) : "memory");
#pragma unroll
          for (int c = 0; c < 4; c++) l4[c] += v[c];
        }
#pragma unroll
        for (int c = 0; c < 4; c++) {
          float inv;
          asm("rcp.approx.ftz.f32 %0, %1;" : "=f"(inv) : "f"(l4[c]));
          l4[c] = l4[c] >= L_MIN && l4[c] <= L_MAX ? inv : __uint_as_float(0x7FFFFFFFu);
        }
        const uint32_t h0 = pack(l4[0], l4[1]), h1 = pack(l4[2], l4[3]);
        const uint32_t e0 = pack(l4[0] - __uint_as_float(h0 << 16), l4[1] - __uint_as_float(h0 & 0xFFFF0000u));
        const uint32_t e1 = pack(l4[2] - __uint_as_float(h1 << 16), l4[3] - __uint_as_float(h1 & 0xFFFF0000u));
        asm volatile("st.shared.v4.u32 [%0], {%1, %2, %3, %4};" ::"r"(sb + OFF_INV + wg * 640 + (lane & 3) * 144 + (lane >> 2) * 16), "r"(h0), "r"(e0), "r"(h1), "r"(e1) : "memory");
        __syncwarp();
        if (lane == 0) {
          mbar_arrive(sb + BAR_INV + 8 * wg);
          if ((int)it == ROLE_AT) {
            take_role();
          }
          if (SLP & 2) mbar_sleep(sb + BAR_STAGE + 8 * wg, it & 1); else mbar_wait(sb + BAR_STAGE + 8 * wg, it & 1);
          __threadfence();
          asm volatile("red.relaxed.gpu.global.add.u32 [%0], 1;" ::"l"(&g_cnt[(unit_batch(u) * 4 + (u >> 6)) * 8]) : "memory");
        }
        __syncwarp();
      }
    }
  } else {
    asm volatile("setmaxnreg.inc.sync.aligned.u32 240;");
    const int wg = warp >> 2, w = warp & 3;
    const uint32_t qreg = sb + OFF_Q + wg * 2 * XB, preg = sb + OFF_P + (2 + wg) * XB;
    const uint32_t st_off = ((lane >> 4) * 8 + (lane & 7)) * 128 + (((2 * w + ((lane >> 3) & 1)) ^ (lane & 7)) << 4);
    const uint32_t xempty = mapa(sb + BAR_XEMPTY, wg);
    Ring r;
    uint32_t it = 0;
    const uint32_t qd = (qreg & 0x3FFFF) >> 4, pd = (preg & 0x3FFFF) >> 4;
    auto ring_addr = [&]() { return ((sb & 0x3FFFF) + r.slot * RING_BYTES) >> 4; };
    auto ring_wait = [&]() { mbar_wait(sb + BAR_RFULL + 8 * r.slot, r.phase); };
    auto release = [&](uint32_t slot) { warp_arrive(sb + BAR_REMPTY + 8 * slot); };
    auto turn_wait = [&]() {
      if (wg == 0) asm volatile("bar.sync 3, 256;" ::: "memory");
      else asm volatile("bar.sync 4, 256;" ::: "memory");
    };
    auto turn_pass = [&]() {
      if (wg == 0) asm volatile("bar.arrive 4, 256;" ::: "memory");
      else asm volatile("bar.arrive 3, 256;" ::: "memory");
    };

    uint32_t chk = 0;
    auto load_inv = [&](uint32_t (&iv)[30], uint32_t parity) {
      const int lane = fresh_tid() & 31;
      mbar_wait(sb + BAR_INV + 8 * wg, parity);
      chk = 0;
#pragma unroll
      for (int j = 0; j < 7; j++)
        asm volatile("ld.shared.v4.u32 {%0, %1, %2, %3}, [%4];" : "=r"(iv[4 * j]), "=r"(iv[4 * j + 1]), "=r"(iv[4 * j + 2]), "=r"(iv[4 * j + 3])
                     : "r"(sb + OFF_INV + wg * 640 + (lane & 3) * 144 + j * 16) : "memory");
      asm volatile("ld.shared.v2.u32 {%0, %1}, [%2];" : "=r"(iv[28]), "=r"(iv[29]) : "r"(sb + OFF_INV + wg * 640 + (lane & 3) * 144 + 112) : "memory");
    };
    auto norm = [&](uint32_t (&n)[8], const uint32_t (&po)[60], const uint32_t (&iv)[30], auto part) {
      constexpr int k = decltype(part)::value >> 1, j0 = (decltype(part)::value & 1) * 8;
#pragma unroll
      for (int j = 0; j < 8; j++)
        n[j] = j0 + j < 15 ? hfma2(po[15 * k + (j0 + j) % 15], iv[2 * ((j0 + j) % 15)], hfma2(po[15 * k + (j0 + j) % 15], iv[2 * ((j0 + j) % 15) + 1], 0x80008000u)) : 0x3F803F80u;
#pragma unroll
      for (int j = 0; j < 8; j += 2) chk = hfma2(n[j], n[j + 1], chk);
    };
    int od1, od2;
    auto store = [&](const uint32_t (&n)[8], const char* optr, auto part) {
      constexpr int k = decltype(part)::value >> 1, off = (8 * (k & 1) + 64 * (k >> 1)) * NROWS * 2;
      if ((decltype(part)::value & 1) == 0)
        asm volatile(
            "{\n.reg .pred p;\nsetp.ne.u64 p, %8, 0;\n"
            "@p st.global.v4.u32 [%8 + %9], {%0, %1, %2, %3};\n@p st.global.v4.u32 [%8 + %9 + 512], {%4, %5, %6, %7};\n}\n"
            ::"r"(n[0]), "r"(n[1]), "r"(n[2]), "r"(n[3]), "r"(n[4]), "r"(n[5]), "r"(n[6]), "r"(n[7]), "l"(optr), "n"(off) : "memory");
      else
        asm volatile(
            "{\n.reg .pred p;\n.reg .b64 b, c;\nsetp.ne.u64 p, %7, 0;\nmad.wide.s32 b, %9, 1, %7;\nmad.wide.s32 c, %10, 1, %7;\n"
            "@p st.global.v4.u32 [%7 + %8 + 1024], {%0, %1, %2, %3};\n@p st.global.v2.u32 [b + %8], {%4, %5};\n@p st.global.u32 [c + %8], %6;\n}\n"
            ::"r"(n[0]), "r"(n[1]), "r"(n[2]), "r"(n[3]), "r"(n[4]), "r"(n[5]), "r"(n[6]), "l"(optr), "n"(off), "r"(od1), "r"(od2) : "memory");
    };
    auto put = [&](const uint32_t (&po)[60], const uint32_t (&iv)[30], const char* optr, auto part) {
      uint32_t n[8];
      norm(n, po, iv, part);
      store(n, optr, part);
    };
    auto out_ptr = [&](int u) {
      const int lane = fresh_tid() & 31;
      const int k = unit_head(u, rank) * DH + 16 * w + (lane >> 2), b = unit_batch(u), q = lane & 3;
      const uint32_t i0 = o_idx(k, o_pos(b, wg, 2 * q));
      od1 = 2 * (int)(o_idx(k, o_pos(b, wg, 96 + 2 * q)) - i0);
      od2 = 2 * (int)(o_idx(k, o_pos(b, wg, 112 + 2 * q)) - i0);
      return reinterpret_cast<const char*>(P.o + i0);
    };
    auto unsafe = [&](bool valid) {
      const bool b = valid && ((chk & 0x7F80u) == 0x7F80u || (chk & 0x7F800000u) == 0x7F800000u);
      return __any_sync(~0u, bar_red_or(wg, b));
    };
    auto publish = [&]() { __syncwarp(); warp_arrive(sb + BAR_STAGE + 8 * wg); };

    uint32_t po[60];
#pragma unroll
    for (int i = 0; i < 60; i++) po[i] = 0;
    int id = 0;
    bool more;
    do {
      float o0[60], o1[60];
      uint32_t prev = 0;
      auto qstep = [&](int s, int acc) {
        const uint32_t j = s & 3, par = ((s >> 2) + (j < 2 ? it : 0)) & 1;
        TR(it * 160 + 3 * s);
        ring_wait();
        TR(it * 160 + 3 * s + 1);
        mbar_wait(sb + BAR_XFULL + 32 * wg + 8 * j, par);
        TR(it * 160 + 3 * s + 2);
        if (s >= ALT_FROM) turn_wait();
        wg_fence();
        mma_tn(o0, o1, ring_addr(), ((sb & 0x3FFFF) + OFF_Q + x_slot(wg, j)) >> 4, acc);
        wg_commit();
        if (s >= ALT_FROM || (s == ALT_FROM - 1 && wg == 1)) turn_pass();
        if (s > 0 && s <= EREL_FROM) {
          wg_wait<1>();
          release(prev);
          if (s <= 6) warp_arrive_cl(xempty + 8 * ((s - 1) & 3));
        }
        prev = r.slot;
        r.next();
      };
      auto qdone = [&](int s) {
        if (s >= EREL_FROM) {
          wg_wait<0>();
          release(prev);
          if (s <= 5) warp_arrive_cl(xempty + 8 * (s & 3));
        }
      };
      qstep(0, 0);
      qstep(1, 1);
      const int up = (it > 3 ? id : cl) + ((int)it - 1) * ncl;
      const char* optr = out_ptr(up);
      if (it == 0) optr = nullptr;
      uint32_t n7[8];
      {
        uint32_t iv[30];
        load_inv(iv, (it + 1) & 1); put(po, iv, optr, IC<0>());
        qstep(2, 1); put(po, iv, optr, IC<1>()); qdone(2);
        qstep(3, 1); put(po, iv, optr, IC<2>()); qdone(3);
        qstep(4, 1); put(po, iv, optr, IC<3>()); qdone(4);
        qstep(5, 1); put(po, iv, optr, IC<4>()); qdone(5);
        qstep(6, 1); put(po, iv, optr, IC<5>()); qdone(6);
        qstep(7, 1); put(po, iv, optr, IC<6>());
        norm(n7, po, iv, IC<7>());
        qdone(7);
        if (LATE_AT == 3 || (LATE_AT == 5 && wg == 1)) store(n7, optr, IC<7>());
      }
      TR(it * 160 + 24);
      const uint32_t a8 = ring_addr(), slot8 = r.slot;
      ring_wait();
      r.next();
      TR(it * 160 + 25);
      mbar_wait(sb + BAR_XFULL + 32 * wg, it & 1);
      TR(it * 160 + 26);
      auto wait9 = [&]() {
        TR(it * 160 + 27);
        ring_wait();
        TR(it * 160 + 28);
        mbar_wait(sb + BAR_XFULL + 32 * wg + 8, it & 1);
        TR(it * 160 + 29);
      };
      if (PRE9 == 1 || (PRE9 == 2 && wg == 1)) wait9();
      if (PRE9 == 3) ring_wait();
      turn_wait();
      wg_fence();
      mma_tn(o0, o1, a8, qd, 1);
      wg_commit();
      if (PRE9 == 0 || (PRE9 == 2 && wg == 0)) wait9();
      if (PRE9 == 3) mbar_wait(sb + BAR_XFULL + 32 * wg + 8, it & 1);
      if (PRE9 != 1) wg_fence();
      mma_tn_split(o0, o1, ring_addr(), qd + (XB >> 4));
      turn_pass();
      wg_wait<2>();
      if (EREL_FROM > 7) release(prev);
      release(slot8);
      if (LATE_AT == 4 || (LATE_AT == 5 && wg == 0)) store(n7, optr, IC<7>());
      auto put_q = [&](const float (&o)[60], uint32_t dst) {
        bar_sync(wg);
#pragma unroll
        for (int j = 0; j < 14; j += 2)
          stsm4t(dst + j * 1024, pack(o[4 * j] * QSCALE, o[4 * j + 1] * QSCALE), pack(o[4 * j + 2] * QSCALE, o[4 * j + 3] * QSCALE),
                 pack(o[4 * j + 4] * QSCALE, o[4 * j + 5] * QSCALE), pack(o[4 * j + 6] * QSCALE, o[4 * j + 7] * QSCALE));
        stsm2t(dst + 14 * 1024, pack(o[56] * QSCALE, o[57] * QSCALE), pack(o[58] * QSCALE, o[59] * QSCALE));
      };
      wg_wait<1>();
      reg_fence(o0);
      put_q(o0, qreg + st_off);
      wg_wait<0>();
      reg_fence(o1);
      release(r.slot);
      r.next();
      TR(it * 160 + 30);
      put_q(o1, qreg + XB + st_off);
      fence_async_smem();
      if (unsafe(it > 0)) {
        slow_path(P, unit_batch(up), unit_head(up, rank), wg, w, fresh_tid() & 31);
        optr = nullptr;
        if (!DPRO) {
#pragma unroll
          for (int i = 0; i < 60; i++) o0[i] = o1[i] = 0.f;
        }
      }
      TR(it * 160 + 32); TG(it * 160 + 142);

      float sc[60], l[30];
      uint32_t slot0 = r.slot;
      ring_wait();
      TR(it * 160 + 33);
      turn_wait();
      wg_fence();
      mma_qk(sc, ring_addr(), qd);
      wg_commit();
      r.next();
      uint32_t slot1 = r.slot;
      ring_wait();
      wg_fence();
      mma_qk(o1, ring_addr(), qd);
      wg_commit();
      r.next();
      turn_pass();
      if (LATE_AT == 0) store(n7, optr, IC<7>());
      wg_wait<1>();
      reg_fence(sc);
      TR(it * 160 + 35);
      release(slot0);
      exp_store<0, 15, true>(sc, l, preg + st_off);
      TR(it * 160 + 38); TG(it * 160 + 43);
      slot0 = r.slot;
      if (K2_AT > 0) {
        wg_wait<0>();
        reg_fence(o1);
        release(slot1);
        exp_store<0, K2_AT>(o1, l, preg - 2 * XB + st_off);
      }
      ring_wait();
      wg_fence();
      mma_qk(sc, ring_addr(), qd);
      wg_commit();
      r.next();
      if (K2_AT == 0) {
        wg_wait<1>();
        reg_fence(o1);
        release(slot1);
      }
      TR(it * 160 + 41);
      exp_store<K2_AT, 15>(o1, l, preg - 2 * XB + st_off);
      fence_async_smem();
      TR(it * 160 + 44);
      slot1 = r.slot;
      ring_wait();
      turn_wait();
      wg_fence();
      mma_tn(o0, o1, ring_addr(), pd, 0);
      wg_commit();
      r.next();
      ring_wait();
      wg_fence();
      mma_tn(o0, o1, ring_addr(), pd - (2 * XB >> 4), 1);
      wg_commit();
      turn_pass();
      if (LATE_AT == 1) store(n7, optr, IC<7>());
      if (it > 0) publish();
      if (it >= 2) id = __shfl_sync(~0u, role(), 0);
      wg_wait<1>();
      reg_fence(sc);
      release(slot0);
      release(slot1);
      bar_sync(wg);
      TR(it * 160 + 47);
      exp_store<0, VREL>(sc, l, preg + st_off);
      wg_wait<0>();
      reg_fence(o0); reg_fence(o1);
      release(r.slot);
      r.next();
      exp_store<VREL, 15>(sc, l, preg + st_off);
      fence_async_smem();
      more = id + ((int)it + 1) * ncl < NUNITS;
      const bool gemm = id < nsingle || (NCL == 66 && id >= 58);
#pragma unroll 1
      for (int s = DPRO ? 3 : 1; s < 16; s++) {
        const uint32_t kslot = r.slot;
        TR(it * 160 + 32 + 6 * s); TG(it * 160 + 37 + 6 * s);
        if (s == 8) TRL(it * 160 + 139);
        ring_wait();
        TR(it * 160 + 33 + 6 * s);
        turn_wait();
        wg_fence();
        mma_qk(sc, ring_addr(), qd);
        wg_commit();
        r.next();
        TR(it * 160 + 36 + 6 * s);
        ring_wait();
        TR(it * 160 + 34 + 6 * s);
        wg_fence();
        mma_tn(o0, o1, ring_addr(), pd - ((s - 1) & 1) * (2 * XB >> 4), DPRO || s != 1);
        wg_commit();
        if (wg == 0 || s < 15) turn_pass();
        wg_wait<1>();
        reg_fence(sc);
        TR(it * 160 + 35 + 6 * s);
        release(kslot);
        if (s == 15) {
          if (more) { warp_arrive_cl(xempty); warp_arrive_cl(xempty + 8); }
          else if (gemm) for (int i = 0; i < 3; i++) warp_arrive_cl(mapa(sb + BAR_BEMPTY + 8 * i, i & 1));
        }
        exp_store<0, VREL>(sc, l, preg - (s & 1) * 2 * XB + st_off);
        wg_wait<0>();
        reg_fence(o0); reg_fence(o1);
        release(r.slot);
        r.next();
        exp_store<VREL, 15>(sc, l, preg - (s & 1) * 2 * XB + st_off);
        fence_async_smem();
      }
      const uint32_t tid = fresh_tid();
      bar_sync(wg);
      TR(it * 160 + 128);
      ring_wait();
      wg_fence();
      mma_tn_split(o0, o1, ring_addr(), pd - (2 * XB >> 4));
      {
        float a[16], b[8], c[4];
        const bool b4 = tid & 16, b3 = tid & 8, b2 = tid & 4;
#pragma unroll
        for (int i = 0; i < 16; i++) {
          const float hi = i < 14 ? l[(16 + i) % 30] : 1.f;
          a[i] = (b4 ? hi : l[i]) + __shfl_xor_sync(~0u, b4 ? l[i] : hi, 16);
        }
#pragma unroll
        for (int i = 0; i < 8; i++) b[i] = (b3 ? a[8 + i] : a[i]) + __shfl_xor_sync(~0u, b3 ? a[i] : a[8 + i], 8);
#pragma unroll
        for (int i = 0; i < 4; i++) c[i] = (b2 ? b[4 + i] : b[i]) + __shfl_xor_sync(~0u, b2 ? b[i] : b[4 + i], 4);
        asm volatile("st.shared.v4.f32 [%0], {%1, %2, %3, %4};" ::"r"(sb + OFF_L2 + tid * 16), "f"(c[0]), "f"(c[1]),
                     "f"(c[2]), "f"(c[3]) : "memory");
        __syncwarp();
        warp_arrive(sb + BAR_LSUM + 8 * wg);
      }
      TR(it * 160 + 132);
      TR(it * 160 + 133);
      wg_wait<1>();
      reg_fence(o0);
      TR(it * 160 + 134);
#pragma unroll
      for (int j = 0; j < 15; j++) { po[j] = pack(o0[4 * j], o0[4 * j + 1]); po[15 + j] = pack(o0[4 * j + 2], o0[4 * j + 3]); }
      wg_wait<0>();
      reg_fence(o1);
      release(r.slot);
      r.next();
      if (more) { warp_arrive_cl(xempty + 16); warp_arrive_cl(xempty + 24); }
      else if (gemm) for (int i = 3; i < 6; i++) warp_arrive_cl(mapa(sb + BAR_BEMPTY + 8 * i, i & 1));
      TR(it * 160 + 130);
#pragma unroll
      for (int j = 0; j < 15; j++) { po[30 + j] = pack(o1[4 * j], o1[4 * j + 1]); po[45 + j] = pack(o1[4 * j + 2], o1[4 * j + 3]); }
      TR(it * 160 + 131); TG(it * 160 + 143);
      it++;
    } while (more);
    const bool gemm = id < nsingle || (NCL == 66 && id >= 58);
    const int u = (it > 3 ? id : cl) + ((int)it - 1) * ncl;
    uint32_t pb[60];
#pragma unroll
    for (int i = 0; i < 60; i++) pb[i] = NCL != 66 ? po[i] ^ (gridDim.y - 1) : po[i];

    uint32_t bslot = 0, bphase = 0;
    auto out_row = [&](int lane) {
      const int row = lane & 15;
      return sb + wg * 8192 + (row < 12 ? w * RING_BYTES + row * 656 : (4 + (w >> 1)) * RING_BYTES + ((w & 1) * 4 + row - 12) * 656);
    };
    auto out_stage = [&](const float (&acc)[80], uint32_t col_off) {
      const int lane = fresh_tid() & 31;
      const uint32_t sa = out_row(lane) + col_off + (lane >> 4) * 16;
#pragma unroll
      for (int j = 0; j < 20; j += 2)
        asm volatile("stmatrix.sync.aligned.m8n8.x4.shared.b16 [%0], {%1,%2,%3,%4};" ::"r"(sa + j * 16), "r"(pack(acc[4 * j], acc[4 * j + 1])),
                     "r"(pack(acc[4 * j + 2], acc[4 * j + 3])), "r"(pack(acc[4 * j + 4], acc[4 * j + 5])), "r"(pack(acc[4 * j + 6], acc[4 * j + 7])) : "memory");
    };
    auto out_store = [&](int t, uint32_t bytes) {
      const int lane = fresh_tid() & 31;
      if (EPI_MIX && wg == 1) {
        __syncwarp();
#pragma unroll 1
        for (int h = 0; h < 2; h++) {
          const int row = h * 8 + (lane >> 2);
          const uint32_t src = out_row(row) + (lane & 3) * 16;
          char* dst = reinterpret_cast<char*>(P.out + (size_t)o_row(row_block(t) * 256 + rank * 128 + 64 + w * 16 + row) * DM + (t & 3) * 160) + (lane & 3) * 16;
#pragma unroll 1
          for (uint32_t c = 0; c < bytes; c += 320) {
            uint4 v[5];
#pragma unroll
            for (int i = 0; i < 5; i++)
              asm volatile("ld.shared.v4.u32 {%0, %1, %2, %3}, [%4];" : "=r"(v[i].x), "=r"(v[i].y), "=r"(v[i].z), "=r"(v[i].w) : "r"(src + c + i * 64) : "memory");
#pragma unroll
            for (int i = 0; i < 5; i++) *reinterpret_cast<uint4*>(dst + c + i * 64) = v[i];
          }
        }
        return;
      }
      fence_async_smem();
      __syncwarp();
      if (lane < 16) {
        __nv_bfloat16* dst = P.out + (size_t)o_row(row_block(t) * 256 + rank * 128 + wg * 64 + w * 16 + lane) * DM + (t & 3) * 160;
        asm volatile("cp.async.bulk.global.shared::cta.bulk_group [%0], [%1], %2;" ::"l"(dst), "r"(out_row(lane)), "r"(bytes) : "memory");
        asm volatile("cp.async.bulk.commit_group;" ::: "memory");
        asm volatile("cp.async.bulk.wait_group.read 0;" ::: "memory");
      }
    };
    for (int t = id; t == id || (NCL != 66 && t < nsingle); t += ncl) {
      float acc[80];
      uint32_t prev = 0, bprev = 0;
      const bool tile = t < nsingle;
      const bool last = NCL == 66 || t + ncl >= nsingle;
      auto bstep = [&](int ks, int accf) {
        if (!(ks & 3)) TR(640 + ks / 2); if ((ks & 7) == 0) TG(144 + (ks >> 3));
        ring_wait();
        mbar_wait(sb + BAR_BFULL + 8 * bslot, bphase);
        if (!(ks & 3)) TR(641 + ks / 2);
        wg_fence();
        const uint32_t a = ring_addr() + wg * 512, bd = (((sb & 0x3FFFF) + OFF_Q + bslot * BB) >> 4) | ((4096u >> 4) << 16);
#pragma unroll
        for (int k = 0; k < 4; k++) wgmma_n160<1, 1>(acc, a + LBO64A + k * 128, HI64A, bd + k * 64, HI64, k == 0 ? accf : 1);
        wg_commit();
        if (ks > 0) {
          wg_wait<1>();
          release(prev);
          if (ks < 59 || !last) warp_arrive_cl(mapa(sb + BAR_BEMPTY + 8 * bprev, bprev & 1));
        }
        prev = r.slot; bprev = bslot;
        r.next();
        if (++bslot == 6) { bslot = 0; bphase ^= 1; }
      };
      const char* optr;
      uint32_t iv[30], n3[8], n4[8], n5[8], n6[8], n7[8];
      if (tile) {
        bstep(0, 0);
        bstep(1, 1);
        optr = out_ptr(u);
        if (t != id) optr = nullptr;
        load_inv(iv, (it + 1) & 1);
#pragma unroll 1
        for (int ks = 2; ks < 17; ks++) {
          bstep(ks, 1);
          switch (ks) {
            case 2: put(pb, iv, optr, IC<0>()); break;
            case 4: put(pb, iv, optr, IC<1>()); break;
            case 6: put(pb, iv, optr, IC<2>()); break;
            case 8: put(pb, iv, optr, IC<3>()); break;
            case 10: put(pb, iv, optr, IC<4>()); break;
            case 12: put(pb, iv, optr, IC<5>()); break;
            case 14: put(pb, iv, optr, IC<6>()); break;
            case 16: put(pb, iv, optr, IC<7>()); break;
            default: break;
          }
        }
        wg_wait<0>();
        reg_fence(acc);
#pragma unroll
        for (int i = 0; i < 8; i++) n3[i] = n4[i] = n5[i] = n6[i] = n7[i] = 0;
      } else {
        Ring r2 = r;
        auto first = [&](int ks) {
          if (ks == 0) { TR(640); TG(144); }
          if (gemm) { mbar_wait(sb + BAR_RFULL + 8 * r2.slot, r2.phase); mbar_wait(sb + BAR_BFULL + 16 * ks, 0); }
          wg_fence();
          const uint32_t a = (((sb & 0x3FFFF) + r2.slot * RING_BYTES) >> 4) + wg * 512;
          const uint32_t bd = (((sb & 0x3FFFF) + OFF_Q + 2 * ks * BB) >> 4) | ((4096u >> 4) << 16);
#pragma unroll
          for (int k = 0; k < 4; k++) wgmma_n160<1, 1>(acc, a + LBO64A + k * 128, HI64A, bd + k * 64, HI64, k + ks != 0);
          wg_commit();
          if (ks > 0) {
            wg_wait<1>();
            if (gemm) warp_arrive_cl(mapa(sb + BAR_BEMPTY + 16 * (ks - 1), 0));
          }
          r2.next();
        };
        first(0);
        optr = out_ptr(u);
        load_inv(iv, (it + 1) & 1);
        put(pb, iv, optr, IC<0>());
        first(1);
        put(pb, iv, optr, IC<1>());
        norm(n3, pb, iv, IC<3>()); norm(n4, pb, iv, IC<4>());
        first(2);
        put(pb, iv, optr, IC<2>());
        norm(n5, pb, iv, IC<5>()); norm(n6, pb, iv, IC<6>()); norm(n7, pb, iv, IC<7>());
        wg_wait<0>();
        reg_fence(acc);
      }
      if (unsafe(t == id)) {
        slow_path(P, unit_batch(u), unit_head(u, rank), wg, w, fresh_tid() & 31);
        optr = nullptr;
#pragma unroll
        for (int i = 0; i < 8; i++) n3[i] = n4[i] = n5[i] = n6[i] = n7[i] = 0;
      }
      if (tile && t == id) publish();
      if (!tile) {
        if (gemm) {
          float ac1[80];
          auto half = [&](float (&ac)[80], bool rel, int accf) {
            mbar_wait(sb + BAR_BFULL + 8 * bslot, bphase);
            wg_fence();
            const uint32_t a = ring_addr() + wg * 512, bd = (((sb & 0x3FFFF) + OFF_Q + bslot * BB) >> 4) | ((4096u >> 4) << 16);
#pragma unroll
            for (int k = 0; k < 4; k++) wgmma_n160<1, 1>(ac, a + LBO64A + k * 128, HI64A, bd + k * 64, HI64, k == 0 ? accf : 1);
            wg_commit();
            wg_wait<1>();
            if (rel) warp_arrive_cl(mapa(sb + BAR_BEMPTY + 8 * bprev, bprev & 1));
            bprev = bslot;
          };
          auto dstep = [&](int ks) {
            if (!(ks & 3)) TR(640 + ks / 2); if ((ks & 7) == 0) TG(144 + (ks >> 3));
            ring_wait();
            if (!(ks & 3)) TR(641 + ks / 2);
            half(acc, ks < 62, 1);
            release(prev);
            bslot++;
            half(ac1, ks < 61, 1);
            if (++bslot == 6) { bslot = 0; bphase ^= 1; }
            prev = r.slot; r.next();
          };
          bprev = 4; bslot = 1;
          half(ac1, true, 0);
          prev = r.slot; r.next(); bslot = 3;
          half(ac1, true, 1);
          release(prev); prev = r.slot; r.next(); bslot = 5;
          store(n3, optr, IC<3>());
          half(ac1, true, 1);
          release(prev); prev = r.slot; r.next(); bslot = 0; bphase = 1;
#pragma unroll 1
          for (int ks = 3; ks < 7; ks++) {
            dstep(ks);
            switch (ks) {
              case 3: store(n4, optr, IC<4>()); break;
              case 4: store(n5, optr, IC<5>()); break;
              case 5: store(n6, optr, IC<6>()); break;
              default: store(n7, optr, IC<7>()); break;
            }
          }
          publish();
#pragma unroll 1
          for (int ks = 7; ks < 64; ks++) {
            if (wg == 1 && ks == 62) turn_wait();
            dstep(ks);
          }
          if (wg == 0) turn_pass();
          wg_wait<0>();
          reg_fence(acc); reg_fence(ac1);
          TRL(158); TG(156);
          bar_sync(wg);
          out_stage(acc, 0);
          out_stage(ac1, 320);
          out_store(2 * id - 72, 640);
        } else {
          store(n3, optr, IC<3>()); store(n4, optr, IC<4>()); store(n5, optr, IC<5>()); store(n6, optr, IC<6>()); store(n7, optr, IC<7>());
          publish();
        }
        break;
      }
#pragma unroll 1
      for (int ks = 17; ks < 64; ks++) {
        if (END_SKEW && wg == 1 && ks == 64 - END_SKEW) turn_wait();
        bstep(ks, 1);
      }
      if (END_SKEW && wg == 0) turn_pass();
      wg_wait<0>();
      reg_fence(acc);
      release(prev);
      if (!last) warp_arrive_cl(mapa(sb + BAR_BEMPTY + 8 * bprev, bprev & 1));
      TRL(158); TG(156);
      const int pos0 = row_block(t) * 256 + rank * 128 + wg * 64 + w * 16;
      if (last) {
        bar_sync(wg);
        out_stage(acc, 0);
        out_store(t, 320);
      } else {
        const int lane = fresh_tid() & 31;
        __nv_bfloat16* op0 = P.out + (size_t)o_row(pos0 + (lane >> 2)) * DM + (t & 3) * 160 + (lane & 3) * 2;
        __nv_bfloat16* op1 = P.out + (size_t)o_row(pos0 + (lane >> 2) + 8) * DM + (t & 3) * 160 + (lane & 3) * 2;
#pragma unroll
        for (int j = 0; j < 20; j++) {
          *reinterpret_cast<uint32_t*>(op0 + j * 8) = pack(acc[4 * j], acc[4 * j + 1]);
          *reinterpret_cast<uint32_t*>(op1 + j * 8) = pack(acc[4 * j + 2], acc[4 * j + 3]);
        }
      }
#pragma unroll
      for (int i = 0; i < 60; i++) pb[i] = 0;
    }
    TRL(159);
  }
}

typedef CUresult (*EncodeFn)(CUtensorMap*, CUtensorMapDataType, cuuint32_t, void*, const cuuint64_t*, const cuuint64_t*,
                             const cuuint32_t*, const cuuint32_t*, CUtensorMapInterleave, CUtensorMapSwizzle,
                             CUtensorMapL2promotion, CUtensorMapFloatOOBfill);

void make_map(EncodeFn enc, CUtensorMap* m, const void* p, int rank, const cuuint64_t* dims, const cuuint64_t* strides,
              const cuuint32_t* box, CUtensorMapSwizzle sw, CUtensorMapL2promotion promo) {
  cuuint32_t es[4] = {1, 1, 1, 1};
  enc(m, CU_TENSOR_MAP_DATA_TYPE_BFLOAT16, rank, const_cast<void*>(p), dims, strides, box, es, CU_TENSOR_MAP_INTERLEAVE_NONE, sw,
      promo, CU_TENSOR_MAP_FLOAT_OOB_FILL_NONE);
}

}

extern "C" void kernel_launch(void* const* d_in, const int* in_sizes, int n_in, void* d_out, int out_size) {
  static EncodeFn enc = nullptr;
  static int nclusters = 0;
  static void* o_ptr = nullptr;
  if (!enc) {
    cudaDriverEntryPointQueryResult qr;
    cudaGetDriverEntryPoint("cuTensorMapEncodeTiled", (void**)&enc, cudaEnableDefault, &qr);
    cudaFuncSetAttribute(fused_attn_kernel<66>, cudaFuncAttributeMaxDynamicSharedMemorySize, SMEM_BYTES);
    cudaFuncSetAttribute(fused_attn_kernel<0>, cudaFuncAttributeMaxDynamicSharedMemorySize, SMEM_BYTES);
    cudaGetSymbolAddress(&o_ptr, g_o);
    cudaLaunchConfig_t cfg = {};
    cfg.gridDim = 128; cfg.blockDim = 384; cfg.dynamicSmemBytes = SMEM_BYTES;
    cudaLaunchAttribute at; at.id = cudaLaunchAttributeClusterDimension;
    at.val.clusterDim.x = 2; at.val.clusterDim.y = 1; at.val.clusterDim.z = 1;
    cfg.attrs = &at; cfg.numAttrs = 1;
    int n = 0;
    cudaOccupancyMaxActiveClusters(&n, fused_attn_kernel<66>, &cfg);
    nclusters = n >= 66 ? MAXCL : (n >= 64 || n <= 0 ? 64 : n);
  }
  const __nv_bfloat16* x = (const __nv_bfloat16*)d_in[0];
  const __nv_bfloat16* k = (const __nv_bfloat16*)d_in[1];
  const __nv_bfloat16* v = (const __nv_bfloat16*)d_in[2];
  const __nv_bfloat16* wq = (const __nv_bfloat16*)d_in[3];
  const __nv_bfloat16* wo = (const __nv_bfloat16*)d_in[4];
  CUtensorMap tm_x, tm_wq, tm_k, tm_v, tm_o, tm_wo;
  const auto S128 = CU_TENSOR_MAP_SWIZZLE_128B;
  const auto P128 = CU_TENSOR_MAP_L2_PROMOTION_L2_128B, P256 = CU_TENSOR_MAP_L2_PROMOTION_L2_256B;
  { cuuint64_t d[2] = {DM, NB * SQ}, s[1] = {DM * 2}; cuuint32_t b[2] = {64, 120}; make_map(enc, &tm_x, x, 2, d, s, b, S128, X_PROMO); }
  { cuuint64_t d[3] = {64, DM, HD / 64}, s[2] = {HD * 2, 128}; cuuint32_t b[3] = {64, 64, 2}; make_map(enc, &tm_wq, wq, 3, d, s, b, S128, P256); }
  { cuuint64_t d[3] = {64, NB * NH * SK, 2}, s[2] = {DH * 2, 128}; cuuint32_t b[3] = {64, 64, 2};
    make_map(enc, &tm_k, k, 3, d, s, b, S128, P128); make_map(enc, &tm_v, v, 3, d, s, b, S128, P128); }
  { cuuint64_t d[4] = {256, 2, HD / 8, NROWS / 64}, s[3] = {512, NROWS * 16, 1024}; cuuint32_t b[4] = {256, 2, 8, 2};
    make_map(enc, &tm_o, o_ptr, 4, d, s, b, CU_TENSOR_MAP_SWIZZLE_NONE, P256); }
  { cuuint64_t d[3] = {32, HD, DM / 32}, s[2] = {DM * 2, 64}; cuuint32_t b[3] = {32, 64, 5};
    make_map(enc, &tm_wo, wo, 3, d, s, b, CU_TENSOR_MAP_SWIZZLE_64B, P128); }
  Params P{x, k, v, wq, (__nv_bfloat16*)d_out, (__nv_bfloat16*)o_ptr};
  if (nclusters == 66) fused_attn_kernel<66><<<132, 384, SMEM_BYTES>>>(tm_x, tm_wq, tm_k, tm_v, tm_o, tm_wo, P);
  else fused_attn_kernel<0><<<2 * nclusters, 384, SMEM_BYTES>>>(tm_x, tm_wq, tm_k, tm_v, tm_o, tm_wo, P);
}
```

```cpp
#include <cuda_runtime.h>
#include <cuda.h>
#include <cuda_bf16.h>
#include <stdint.h>

namespace {

constexpr int NB = 16, SQ = 240, DM = 640, NH = 32, SK = 1024, DH = 128, HD = NH * DH;
constexpr int NROWS = NB * SQ;
constexpr int NUNITS = 256;
#define DPRO 1
#define LATE_AT 4
#define ALT_FROM 4
#define END_SKEW 5
#define VREL 6
#define PF_HOLD 6
#define PF_N 4
#define PF_J0 3
#define PF_STEP 3
#define ROT 0
#define O_EF 1
#define B_ORDER 1
#define WO_PF 6
#define ROLE_AT 0
#define PAUSE_NS 11000
#define PAUSE_AT 2
#define EARLY 1
#define EARLY_X 2
#define EARLY_W 2
#define X_PROMO P128
#define PAUSE_J -1
#define PAUSE_SPREAD 0
#define WO_PF0 1
#define EPI_MIX 1
#define K2_AT 0
#define SLP 15
#define EREL_FROM 4
#define PRE9 0
#define MAXCL 66
#define SMID_TOP 88
constexpr int NOTILES = 60;
constexpr float QSCALE = 0.08838834764831845f * 1.4426950408889634f;
constexpr float L_MIN = 9.5367431640625e-07f;
constexpr float L_MAX = 1.152921504606846976e18f;

constexpr uint32_t RING_SLOTS = 6, RING_BYTES = 16384;
constexpr uint32_t XB = 15360;
constexpr uint32_t BB = 20480;
constexpr uint32_t OFF_Q = RING_SLOTS * RING_BYTES;
constexpr uint32_t OFF_P = OFF_Q + 4 * XB;
constexpr uint32_t OFF_INV = OFF_P + 4 * XB;
constexpr uint32_t OFF_L2 = OFF_INV + 1280;
constexpr uint32_t OFF_BAR = OFF_L2 + 4096;
constexpr uint32_t BAR_RFULL = OFF_BAR, BAR_REMPTY = BAR_RFULL + 48, BAR_XFULL = BAR_REMPTY + 48,
    BAR_XEMPTY = BAR_XFULL + 64, BAR_BFULL = BAR_XEMPTY + 32, BAR_BEMPTY = BAR_BFULL + 48, BAR_STAGE = BAR_BEMPTY + 48;
constexpr uint32_t BAR_ROLE = BAR_STAGE + 16, BAR_LSUM = BAR_ROLE + 24, BAR_INV = BAR_LSUM + 16;
constexpr uint32_t OFF_TR = BAR_INV + 16;
constexpr uint32_t SMEM_BYTES = OFF_TR + 1024;

constexpr uint32_t HI128 = (1u << 30) | (1024 >> 4);
constexpr uint32_t HI64 = (2u << 30) | (512 >> 4);
constexpr uint32_t HI64A = (2u << 30) | (1024 >> 4), LBO64A = (512u >> 4) << 16;

__device__ __nv_bfloat16 g_o[HD * NROWS];
__device__ unsigned g_cnt[67 * 8];
#define TS(i)
#define TI(i)
#define TRL(i)
#define TR(i)
#define TG(i)

struct Params {
  const __nv_bfloat16 *x, *k, *v, *wq;
  __nv_bfloat16 *out, *o;
};

__device__ __forceinline__ void wg_fence() { asm volatile("wgmma.fence.sync.aligned;" ::: "memory"); }
__device__ __forceinline__ void wg_commit() { asm volatile("wgmma.commit_group.sync.aligned;" ::: "memory"); }
template <int N> __device__ __forceinline__ void wg_wait() { asm volatile("wgmma.wait_group.sync.aligned %0;" ::"n"(N) : "memory"); }
template <int N> __device__ __forceinline__ void reg_fence(float (&r)[N]) {
#pragma unroll
  for (int i = 0; i < N; i++) asm volatile("" : "+f"(r[i])::"memory");
}
template <int TA, int TB>
__device__ __forceinline__ void wgmma_n120(float (&d)[60], uint32_t a_lo, uint32_t a_hi, uint32_t b_lo, uint32_t b_hi, int acc) {
  asm volatile(
      "{\n.reg .pred p;\n.reg .b64 da, db;\nsetp.ne.b32 p, %64, 0;\n"
      "mov.b64 da, {%60, %61};\nmov.b64 db, {%62, %63};\n"
      "wgmma.mma_async.sync.aligned.m64n120k16.f32.bf16.bf16 {"
      "%0, %1, %2, %3, %4, %5, %6, %7, %8, %9, %10, %11, %12, %13, %14, %15, %16, %17, %18, %19, %20, %21, %22, %23, "
      "%24, %25, %26, %27, %28, %29, %30, %31, %32, %33, %34, %35, %36, %37, %38, %39, %40, %41, %42, %43, %44, %45, "
      "%46, %47, %48, %49, %50, %51, %52, %53, %54, %55, %56, %57, %58, %59"
      "}, da, db, p, 1, 1, %65, %66;\n}\n"
      : "+f"(d[0]), "+f"(d[1]), "+f"(d[2]), "+f"(d[3]), "+f"(d[4]), "+f"(d[5]), "+f"(d[6]), "+f"(d[7]), "+f"(d[8]),
        "+f"(d[9]), "+f"(d[10]), "+f"(d[11]), "+f"(d[12]), "+f"(d[13]), "+f"(d[14]), "+f"(d[15]), "+f"(d[16]),
        "+f"(d[17]), "+f"(d[18]), "+f"(d[19]), "+f"(d[20]), "+f"(d[21]), "+f"(d[22]), "+f"(d[23]), "+f"(d[24]),
        "+f"(d[25]), "+f"(d[26]), "+f"(d[27]), "+f"(d[28]), "+f"(d[29]), "+f"(d[30]), "+f"(d[31]), "+f"(d[32]),
        "+f"(d[33]), "+f"(d[34]), "+f"(d[35]), "+f"(d[36]), "+f"(d[37]), "+f"(d[38]), "+f"(d[39]), "+f"(d[40]),
        "+f"(d[41]), "+f"(d[42]), "+f"(d[43]), "+f"(d[44]), "+f"(d[45]), "+f"(d[46]), "+f"(d[47]), "+f"(d[48]),
        "+f"(d[49]), "+f"(d[50]), "+f"(d[51]), "+f"(d[52]), "+f"(d[53]), "+f"(d[54]), "+f"(d[55]), "+f"(d[56]),
        "+f"(d[57]), "+f"(d[58]), "+f"(d[59])
      : "r"(a_lo), "r"(a_hi), "r"(b_lo), "r"(b_hi), "r"(acc), "n"(TA), "n"(TB));
}

template <int TA, int TB>
__device__ __forceinline__ void wgmma_n160(float (&d)[80], uint32_t a_lo, uint32_t a_hi, uint32_t b_lo, uint32_t b_hi, int acc) {
  asm volatile(
      "{\n.reg .pred p;\n.reg .b64 da, db;\nsetp.ne.b32 p, %84, 0;\n"
      "mov.b64 da, {%80, %81};\nmov.b64 db, {%82, %83};\n"
      "wgmma.mma_async.sync.aligned.m64n160k16.f32.bf16.bf16 {"
      "%0, %1, %2, %3, %4, %5, %6, %7, %8, %9, %10, %11, %12, %13, %14, %15, %16, %17, %18, %19, %20, %21, %22, %23, "
      "%24, %25, %26, %27, %28, %29, %30, %31, %32, %33, %34, %35, %36, %37, %38, %39, %40, %41, %42, %43, %44, %45, "
      "%46, %47, %48, %49, %50, %51, %52, %53, %54, %55, %56, %57, %58, %59, %60, %61, %62, %63, %64, %65, %66, %67, "
      "%68, %69, %70, %71, %72, %73, %74, %75, %76, %77, %78, %79"
      "}, da, db, p, 1, 1, %85, %86;\n}\n"
      : "+f"(d[0]), "+f"(d[1]), "+f"(d[2]), "+f"(d[3]), "+f"(d[4]), "+f"(d[5]), "+f"(d[6]), "+f"(d[7]), "+f"(d[8]),
        "+f"(d[9]), "+f"(d[10]), "+f"(d[11]), "+f"(d[12]), "+f"(d[13]), "+f"(d[14]), "+f"(d[15]), "+f"(d[16]),
        "+f"(d[17]), "+f"(d[18]), "+f"(d[19]), "+f"(d[20]), "+f"(d[21]), "+f"(d[22]), "+f"(d[23]), "+f"(d[24]),
        "+f"(d[25]), "+f"(d[26]), "+f"(d[27]), "+f"(d[28]), "+f"(d[29]), "+f"(d[30]), "+f"(d[31]), "+f"(d[32]),
        "+f"(d[33]), "+f"(d[34]), "+f"(d[35]), "+f"(d[36]), "+f"(d[37]), "+f"(d[38]), "+f"(d[39]), "+f"(d[40]),
        "+f"(d[41]), "+f"(d[42]), "+f"(d[43]), "+f"(d[44]), "+f"(d[45]), "+f"(d[46]), "+f"(d[47]), "+f"(d[48]),
        "+f"(d[49]), "+f"(d[50]), "+f"(d[51]), "+f"(d[52]), "+f"(d[53]), "+f"(d[54]), "+f"(d[55]), "+f"(d[56]),
        "+f"(d[57]), "+f"(d[58]), "+f"(d[59]), "+f"(d[60]), "+f"(d[61]), "+f"(d[62]), "+f"(d[63]), "+f"(d[64]),
        "+f"(d[65]), "+f"(d[66]), "+f"(d[67]), "+f"(d[68]), "+f"(d[69]), "+f"(d[70]), "+f"(d[71]), "+f"(d[72]),
        "+f"(d[73]), "+f"(d[74]), "+f"(d[75]), "+f"(d[76]), "+f"(d[77]), "+f"(d[78]), "+f"(d[79])
      : "r"(a_lo), "r"(a_hi), "r"(b_lo), "r"(b_hi), "r"(acc), "n"(TA), "n"(TB));
}
__device__ __forceinline__ void mbar_init(uint32_t bar, int cnt) { asm volatile("mbarrier.init.shared::cta.b64 [%0], %1;" ::"r"(bar), "r"(cnt)); }
__device__ __forceinline__ void mbar_expect(uint32_t bar, uint32_t bytes) {
  asm volatile("mbarrier.arrive.expect_tx.shared::cta.b64 _, [%0], %1;" ::"r"(bar), "r"(bytes) : "memory");
}
__device__ __forceinline__ uint32_t mapa(uint32_t addr, uint32_t cta) {
  uint32_t r; asm("mapa.shared::cluster.u32 %0, %1, %2;" : "=r"(r) : "r"(addr), "r"(cta)); return r;
}
__device__ __forceinline__ void mbar_expect_cl(uint32_t cbar, uint32_t bytes) {
  asm volatile("mbarrier.arrive.expect_tx.shared::cluster.b64 _, [%0], %1;" ::"r"(cbar), "r"(bytes) : "memory");
}
__device__ __forceinline__ void mbar_arrive(uint32_t bar) { asm volatile("mbarrier.arrive.shared::cta.b64 _, [%0];" ::"r"(bar) : "memory"); }
__device__ __forceinline__ void mbar_arrive_cl(uint32_t cbar) { asm volatile("mbarrier.arrive.shared::cluster.b64 _, [%0];" ::"r"(cbar) : "memory"); }
__device__ __forceinline__ void warp_arrive(uint32_t bar) {
  asm volatile("{\n.reg .pred p;\nelect.sync _|p, 0xffffffff;\n@p mbarrier.arrive.shared::cta.b64 _, [%0];\n}\n" ::"r"(bar) : "memory");
}
__device__ __forceinline__ void warp_arrive_cl(uint32_t cbar) {
  asm volatile("{\n.reg .pred p;\nelect.sync _|p, 0xffffffff;\n@p mbarrier.arrive.shared::cluster.b64 _, [%0];\n}\n" ::"r"(cbar) : "memory");
}
__device__ __forceinline__ void mbar_wait(uint32_t bar, uint32_t parity) {
  asm volatile(
      "{\n.reg .pred p;\n.reg .u32 n;\n"
      "mbarrier.try_wait.parity.shared::cta.b64 p, [%0], %1;\n@p bra WAIT_DONE;\n"
      "mov.u32 n, 0;\n"
      "WAIT_LOOP:\n"
      "mbarrier.try_wait.parity.shared::cta.b64 p, [%0], %1;\n@p bra WAIT_DONE;\n"
      "add.u32 n, n, 1;\nsetp.lt.u32 p, n, 0x4000000;\n@p bra WAIT_LOOP;\ntrap;\n"
      "WAIT_DONE:\n}\n" ::"r"(bar), "r"(parity) : "memory");
}
__device__ __forceinline__ void mbar_sleep(uint32_t bar, uint32_t parity) {
  asm volatile(
      "{\n.reg .pred p;\n.reg .u32 n;\nmov.u32 n, 0;\n"
      "WAIT_LOOP:\n"
      "mbarrier.try_wait.parity.shared::cta.b64 p, [%0], %1, 4000;\n@p bra WAIT_DONE;\n"
      "add.u32 n, n, 1;\nsetp.lt.u32 p, n, 0x400000;\n@p bra WAIT_LOOP;\ntrap;\n"
      "WAIT_DONE:\n}\n" ::"r"(bar), "r"(parity) : "memory");
}
__device__ __forceinline__ void mbar_wait_cl(uint32_t bar, uint32_t parity) {
  asm volatile(
      "{\n.reg .pred p;\n.reg .u32 n;\nmov.u32 n, 0;\n"
      "WAIT_LOOP:\n"
      "mbarrier.try_wait.parity.acquire.cluster.shared::cta.b64 p, [%0], %1;\n@p bra WAIT_DONE;\n"
      "add.u32 n, n, 1;\nsetp.lt.u32 p, n, 0x4000000;\n@p bra WAIT_LOOP;\ntrap;\n"
      "WAIT_DONE:\n}\n" ::"r"(bar), "r"(parity) : "memory");
}
__device__ __forceinline__ void tma3d(uint32_t dst, const CUtensorMap* m, int c0, int c1, int c2, uint32_t bar) {
  asm volatile("cp.async.bulk.tensor.3d.shared::cluster.global.mbarrier::complete_tx::bytes [%0], [%1, {%3, %4, %5}], [%2];"
               ::"r"(dst), "l"(m), "r"(bar), "r"(c0), "r"(c1), "r"(c2) : "memory");
}
__device__ __forceinline__ void tma3d_hint(uint32_t dst, const CUtensorMap* m, int c0, int c1, int c2, uint32_t bar, uint64_t pol) {
  asm volatile("cp.async.bulk.tensor.3d.shared::cluster.global.mbarrier::complete_tx::bytes.L2::cache_hint [%0], [%1, {%3, %4, %5}], [%2], %6;"
               ::"r"(dst), "l"(m), "r"(bar), "r"(c0), "r"(c1), "r"(c2), "l"(pol) : "memory");
}
__device__ __forceinline__ void tma2d_mc(uint32_t dst, const CUtensorMap* m, int c0, int c1, uint32_t bar) {
  asm volatile("cp.async.bulk.tensor.2d.shared::cluster.global.mbarrier::complete_tx::bytes.multicast::cluster [%0], [%1, {%3, %4}], [%2], %5;"
               ::"r"(dst), "l"(m), "r"(bar), "r"(c0), "r"(c1), "h"((uint16_t)3) : "memory");
}
__device__ __forceinline__ void tma3d_mc(uint32_t dst, const CUtensorMap* m, int c0, int c1, int c2, uint32_t bar) {
  asm volatile("cp.async.bulk.tensor.3d.shared::cluster.global.mbarrier::complete_tx::bytes.multicast::cluster [%0], [%1, {%3, %4, %5}], [%2], %6;"
               ::"r"(dst), "l"(m), "r"(bar), "r"(c0), "r"(c1), "r"(c2), "h"((uint16_t)3) : "memory");
}
__device__ __forceinline__ void l2_prefetch(const void* p, uint32_t bytes) {
  asm volatile("cp.async.bulk.prefetch.L2.global [%0], %1;" ::"l"(p), "r"(bytes) : "memory");
}
__device__ __forceinline__ void fence_async_smem() { asm volatile("fence.proxy.async.shared::cta;" ::: "memory"); }
__device__ __forceinline__ void bar_sync(int wg) {
  if (wg == 0) asm volatile("bar.sync 1, 128;" ::: "memory");
  else asm volatile("bar.sync 2, 128;" ::: "memory");
}
__device__ __forceinline__ bool bar_red_or(int id, bool v) {
  uint32_t r;
  asm volatile("{\n.reg .pred p, q;\nsetp.ne.u32 p, %2, 0;\nbar.red.or.pred q, %1, 128, p;\nselp.u32 %0, 1, 0, q;\n}\n"
               : "=r"(r) : "r"(1 + id), "r"((uint32_t)v) : "memory");
  return r != 0;
}
__device__ __forceinline__ uint32_t hfma2(uint32_t a, uint32_t b, uint32_t c) { uint32_t r; asm("fma.rn.bf16x2 %0, %1, %2, %3;" : "=r"(r) : "r"(a), "r"(b), "r"(c)); return r; }
__device__ __forceinline__ float ex2(float x) { float y; asm("ex2.approx.ftz.f32 %0, %1;" : "=f"(y) : "f"(x)); return y; }
__device__ __forceinline__ uint32_t pack(float lo, float hi) { uint32_t r; asm("cvt.rn.bf16x2.f32 %0, %1, %2;" : "=r"(r) : "f"(hi), "f"(lo)); return r; }
__device__ __forceinline__ void stsm4t(uint32_t a, uint32_t r0, uint32_t r1, uint32_t r2, uint32_t r3) {
  asm volatile("stmatrix.sync.aligned.m8n8.x4.trans.shared.b16 [%0], {%1,%2,%3,%4};" ::"r"(a), "r"(r0), "r"(r1), "r"(r2), "r"(r3) : "memory");
}
__device__ __forceinline__ void stsm2t(uint32_t a, uint32_t r0, uint32_t r1) {
  asm volatile("stmatrix.sync.aligned.m8n8.x2.trans.shared.b16 [%0], {%1,%2};" ::"r"(a), "r"(r0), "r"(r1) : "memory");
}
__device__ __forceinline__ void mma16816(float (&d)[4], const uint32_t (&a)[4], uint32_t b0, uint32_t b1) {
  asm volatile("mma.sync.aligned.m16n8k16.row.col.f32.bf16.bf16.f32 {%0,%1,%2,%3}, {%4,%5,%6,%7}, {%8,%9}, {%0,%1,%2,%3};"
               : "+f"(d[0]), "+f"(d[1]), "+f"(d[2]), "+f"(d[3]) : "r"(a[0]), "r"(a[1]), "r"(a[2]), "r"(a[3]), "r"(b0), "r"(b1));
}

__device__ __forceinline__ uint32_t fresh_tid() { uint32_t t; asm volatile("mov.u32 %0, %tid.x;" : "=r"(t)); return t; }

template <int V> struct IC { static constexpr int value = V; };

struct Ring {
  uint32_t slot = 0, phase = 0;
  __device__ __forceinline__ void next() { if (++slot == RING_SLOTS) { slot = 0; phase ^= 1; } }
};

__device__ __forceinline__ void mma_tn(float (&o0)[60], float (&o1)[60], uint32_t a, uint32_t b, int acc) {
#pragma unroll
  for (int k = 0; k < 4; k++) {
    wgmma_n120<1, 0>(o0, a + k * 128, HI128, b + k * 2, HI128, k == 0 ? acc : 1);
    wgmma_n120<1, 0>(o1, a + 512 + k * 128, HI128, b + k * 2, HI128, k == 0 ? acc : 1);
  }
}
__device__ __forceinline__ void mma_tn_split(float (&o0)[60], float (&o1)[60], uint32_t a, uint32_t b) {
#pragma unroll
  for (int k = 0; k < 4; k++) wgmma_n120<1, 0>(o0, a + k * 128, HI128, b + k * 2, HI128, 1);
  wg_commit();
#pragma unroll
  for (int k = 0; k < 4; k++) wgmma_n120<1, 0>(o1, a + 512 + k * 128, HI128, b + k * 2, HI128, 1);
  wg_commit();
}
__device__ __forceinline__ void mma_qk(float (&s)[60], uint32_t a, uint32_t q) {
#pragma unroll
  for (int k = 0; k < 8; k++)
    wgmma_n120<0, 0>(s, a + (k >> 2) * 512 + (k & 3) * 2, HI128, q + (k >> 2) * (XB >> 4) + (k & 3) * 2, HI128, k != 0);
}
template <int J0, int J1, bool FIRST = false>
__device__ __forceinline__ void exp_store(const float (&s)[60], float (&l)[30], uint32_t dst) {
#pragma unroll
  for (int j = J0; j < J1; j += 2) {
    uint32_t p[4];
#pragma unroll
    for (int jj = 0; jj < 2; jj++) {
      if (j + jj < 15) {
        const int c = j + jj;
        float e0 = ex2(s[4 * c]), e1 = ex2(s[4 * c + 1]), e2 = ex2(s[4 * c + 2]), e3 = ex2(s[4 * c + 3]);
        if (FIRST) { l[2 * c] = e0 + e2; l[2 * c + 1] = e1 + e3; }
        else { l[2 * c] += e0; l[2 * c + 1] += e1; l[2 * c] += e2; l[2 * c + 1] += e3; }
        p[2 * jj] = pack(e0, e1); p[2 * jj + 1] = pack(e2, e3);
      }
    }
    if (j + 1 < 15) stsm4t(dst + j * 1024, p[0], p[1], p[2], p[3]);
    else stsm2t(dst + j * 1024, p[0], p[1]);
  }
}

__device__ __forceinline__ int o_pos(int b, int wg, int r) {
  const int j = r >> 3, q = (r >> 1) & 3, c = r & 1, o = b & 1, base = (b >> 1) * 480;
  if (j < 12) return base + (o * 9 + wg * 3 + (j >> 2)) * 32 + q * 8 + (j & 3) * 2 + c;
  if (j < 14) return base + (6 + 2 * o) * 32 + wg * 16 + q * 4 + (j - 12) * 2 + c;
  return base + 7 * 32 + (o * 2 + wg) * 8 + q * 2 + c;
}
__device__ __forceinline__ int o_row(int p) {
  const int pair = p / 480, a = (p - pair * 480) >> 5, in = p & 31, c = p & 1;
  int tile, row;
  if (a == 7) { tile = in >> 3; row = 112 + (in & 7); }
  else if (a == 6 || a == 8) { tile = a - 6 + (in >> 4); row = (12 + ((in >> 1) & 1)) * 8 + ((in >> 2) & 3) * 2 + c; }
  else { const int f = a > 8 ? a - 3 : a; tile = f / 3; row = ((f - tile * 3) * 4 + ((in >> 1) & 3)) * 8 + (in >> 3) * 2 + c; }
  return pair * 480 + tile * 120 + row;
}
__device__ __forceinline__ uint32_t o_idx(int k, int p) {
  return ((k >> 3) * (NROWS / 32) + (p >> 5)) * 256 + (k & 7) * 32 + ((((p >> 3) & 3) ^ ((k & 7) >> 1)) << 3) + (p & 7);
}

__device__ __forceinline__ void slow_path(const Params& P, int b, int h, int wg, int w, int lane) {
  const int g = lane >> 2, q = lane & 3, row0 = wg * 120;
  const uint16_t* wq = reinterpret_cast<const uint16_t*>(P.wq) + h * DH + g;
  const __nv_bfloat16* kp = P.k + (size_t)(b * NH + h) * SK * DH;
  const uint16_t* vp = reinterpret_cast<const uint16_t*>(P.v) + (size_t)(b * NH + h) * SK * DH + g;
#pragma unroll 1
  for (int t = w; t < 8; t += 4) {
    const int r0 = 16 * t + g, r1 = r0 + 8;
    const __nv_bfloat16* x0 = P.x + (size_t)(b * SQ + row0 + r0) * DM + 2 * q;
    const __nv_bfloat16* x1 = P.x + (size_t)(b * SQ + row0 + min(r1, 119)) * DM + 2 * q;
    float o[16][4];
#pragma unroll
    for (int n = 0; n < 16; n++) o[n][0] = o[n][1] = o[n][2] = o[n][3] = 0.f;
#pragma unroll 1
    for (int k0 = 0; k0 < DM; k0 += 16) {
      uint32_t a[4] = {*(const uint32_t*)(x0 + k0), *(const uint32_t*)(x1 + k0), *(const uint32_t*)(x0 + k0 + 8), *(const uint32_t*)(x1 + k0 + 8)};
      const uint16_t* wr = wq + (size_t)(k0 + 2 * q) * HD;
#pragma unroll
      for (int n = 0; n < 16; n++) {
        if ((n & 3) == 0) __syncwarp();
        mma16816(o[n], a, wr[8 * n] | ((uint32_t)wr[8 * n + HD] << 16), wr[8 * n + 8 * HD] | ((uint32_t)wr[8 * n + 9 * HD] << 16));
      }
    }
    uint32_t qa[8][4];
#pragma unroll
    for (int k = 0; k < 8; k++) {
      qa[k][0] = pack(o[2 * k][0] * QSCALE, o[2 * k][1] * QSCALE);
      qa[k][1] = pack(o[2 * k][2] * QSCALE, o[2 * k][3] * QSCALE);
      qa[k][2] = pack(o[2 * k + 1][0] * QSCALE, o[2 * k + 1][1] * QSCALE);
      qa[k][3] = pack(o[2 * k + 1][2] * QSCALE, o[2 * k + 1][3] * QSCALE);
    }
#pragma unroll
    for (int n = 0; n < 16; n++) o[n][0] = o[n][1] = o[n][2] = o[n][3] = 0.f;
    float m0 = -INFINITY, m1 = -INFINITY, l0 = 0.f, l1 = 0.f;
#pragma unroll 1
    for (int key0 = 0; key0 < SK; key0 += 16) {
      float s[2][4];
#pragma unroll
      for (int nt = 0; nt < 2; nt++) {
        s[nt][0] = s[nt][1] = s[nt][2] = s[nt][3] = 0.f;
        const __nv_bfloat16* kr = kp + (size_t)(key0 + 8 * nt + g) * DH + 2 * q;
#pragma unroll
        for (int k = 0; k < 8; k++) mma16816(s[nt], qa[k], *(const uint32_t*)(kr + 16 * k), *(const uint32_t*)(kr + 16 * k + 8));
      }
      float n0 = fmaxf(fmaxf(s[0][0], s[0][1]), fmaxf(s[1][0], s[1][1])), n1 = fmaxf(fmaxf(s[0][2], s[0][3]), fmaxf(s[1][2], s[1][3]));
      n0 = fmaxf(n0, __shfl_xor_sync(~0u, n0, 1)); n1 = fmaxf(n1, __shfl_xor_sync(~0u, n1, 1));
      n0 = fmaxf(n0, __shfl_xor_sync(~0u, n0, 2)); n1 = fmaxf(n1, __shfl_xor_sync(~0u, n1, 2));
      n0 = fmaxf(n0, m0); n1 = fmaxf(n1, m1);
      const float z0 = n0 == -INFINITY ? 0.f : n0, z1 = n1 == -INFINITY ? 0.f : n1;
      const float c0 = ex2(m0 - z0), c1 = ex2(m1 - z1);
      m0 = n0; m1 = n1;
#pragma unroll
      for (int nt = 0; nt < 2; nt++) {
        s[nt][0] = ex2(s[nt][0] - z0); s[nt][1] = ex2(s[nt][1] - z0);
        s[nt][2] = ex2(s[nt][2] - z1); s[nt][3] = ex2(s[nt][3] - z1);
      }
      l0 = l0 * c0 + s[0][0] + s[0][1] + s[1][0] + s[1][1];
      l1 = l1 * c1 + s[0][2] + s[0][3] + s[1][2] + s[1][3];
      uint32_t pa[4] = {pack(s[0][0], s[0][1]), pack(s[0][2], s[0][3]), pack(s[1][0], s[1][1]), pack(s[1][2], s[1][3])};
      const uint16_t* vr = vp + (size_t)(key0 + 2 * q) * DH;
#pragma unroll
      for (int n = 0; n < 16; n++) {
        if ((n & 3) == 0) __syncwarp();
        o[n][0] *= c0; o[n][1] *= c0; o[n][2] *= c1; o[n][3] *= c1;
        mma16816(o[n], pa, vr[8 * n] | ((uint32_t)vr[8 * n + DH] << 16), vr[8 * n + 8 * DH] | ((uint32_t)vr[8 * n + 9 * DH] << 16));
      }
    }
    l0 += __shfl_xor_sync(~0u, l0, 1); l1 += __shfl_xor_sync(~0u, l1, 1);
    l0 += __shfl_xor_sync(~0u, l0, 2); l1 += __shfl_xor_sync(~0u, l1, 2);
    const float i0 = 1.f / l0, i1 = 1.f / l1;
    __nv_bfloat16* oc0 = P.o + o_idx(h * DH + 2 * q, o_pos(b, wg, r0));
    __nv_bfloat16* oc1 = P.o + o_idx(h * DH + 2 * q, o_pos(b, wg, min(r1, 119)));
#pragma unroll
    for (int n = 0; n < 16; n++) {
      oc0[8 * n * NROWS] = __float2bfloat16(o[n][0] * i0);
      oc0[8 * n * NROWS + 32] = __float2bfloat16(o[n][1] * i0);
      if (r1 < 120) {
        oc1[8 * n * NROWS] = __float2bfloat16(o[n][2] * i1);
        oc1[8 * n * NROWS + 32] = __float2bfloat16(o[n][3] * i1);
      }
    }
  }
}

__device__ __forceinline__ int bk(int ks) { return B_ORDER && ks < 48 ? 32 - (ks & 48) + (ks & 15) : ks; }
__device__ __forceinline__ uint32_t x_slot(uint32_t wg, uint32_t j) { return j < 2 ? (2 * wg + j) * XB : (2 * j + wg) * XB; }
__device__ __forceinline__ int row_block(int t) { return t >= 44 ? (t >> 2) - 11 : (t >> 2) + 4; }
__device__ __forceinline__ int unit_batch(int u) { return (u & 63) >> 2; }
__device__ __forceinline__ int unit_head(int u, int rank) { return (u >> 6) * 8 + (u & 3) * 2 + rank; }

template <int NCL>
__global__ void __cluster_dims__(2, 1, 1) __launch_bounds__(384, 1)
fused_attn_kernel(const __grid_constant__ CUtensorMap tm_x, const __grid_constant__ CUtensorMap tm_wq,
                  const __grid_constant__ CUtensorMap tm_k, const __grid_constant__ CUtensorMap tm_v,
                  const __grid_constant__ CUtensorMap tm_o, const __grid_constant__ CUtensorMap tm_wo,
                  const __grid_constant__ Params P) {
  extern __shared__ uint8_t smem_raw[];
  const uint32_t sb = ((uint32_t)__cvta_generic_to_shared(smem_raw) + 1023) & ~1023u;
  if (threadIdx.x == 0) TS(152);
  const int warp = __shfl_sync(~0u, threadIdx.x >> 5, 0);
  const int lane = threadIdx.x & 31;
  const int rank = blockIdx.x & 1, cl = blockIdx.x >> 1, ncl = NCL ? NCL : gridDim.x >> 1;

  const int nsingle = NCL == 66 ? 44 : NOTILES;
  auto role = [&]() {
    mbar_wait(sb + BAR_ROLE + 16, 0);
    int id;
    asm volatile("ld.shared.u32 %0, [%1];" : "=r"(id) : "r"(sb + BAR_ROLE + 8) : "memory");
    return id;
  };

  if (EARLY && threadIdx.x == 128) asm volatile("prefetch.tensormap [%0];" ::"l"(&tm_x) : "memory");
  if (threadIdx.x == 0) {
    if (EARLY) asm volatile("prefetch.tensormap [%0];" ::"l"(&tm_wq) : "memory");
    for (int i = 0; i < 6; i++) {
      mbar_init(sb + BAR_RFULL + 8 * i, 1); mbar_init(sb + BAR_REMPTY + 8 * i, 8);
      mbar_init(sb + BAR_BFULL + 8 * i, 1); mbar_init(sb + BAR_BEMPTY + 8 * i, 16);
    }
    for (int i = 0; i < 8; i++) mbar_init(sb + BAR_XFULL + 8 * i, 1);
    for (int i = 0; i < 4; i++) mbar_init(sb + BAR_XEMPTY + 8 * i, 8);
    for (int i = 0; i < 2; i++) { mbar_init(sb + BAR_STAGE + 8 * i, 4); mbar_init(sb + BAR_LSUM + 8 * i, 4); mbar_init(sb + BAR_INV + 8 * i, 1); }
    mbar_init(sb + BAR_ROLE, 1); mbar_init(sb + BAR_ROLE + 16, 1);
    asm volatile("fence.mbarrier_init.release.cluster;" ::: "memory");
  }
  __syncwarp();
  asm volatile("barrier.cluster.arrive.relaxed.aligned;" ::: "memory");
  auto first_w = [&](int s) {
    mbar_expect(sb + BAR_RFULL + 8 * s, RING_BYTES);
    tma3d(sb + s * RING_BYTES, &tm_wq, 0, s * 64, 2 * unit_head(cl, rank), sb + BAR_RFULL + 8 * s);
  };
  if (EARLY && threadIdx.x == 0) first_w(0);
  __syncwarp();
  asm volatile("barrier.cluster.wait.aligned;" ::: "memory");
  if (EARLY && threadIdx.x == 128) {
#pragma unroll 1
    for (int s = 0; s < EARLY_X; s++) {
      const uint32_t fb = sb + BAR_XFULL + 32 * rank + 8 * s;
      mbar_expect(fb, XB);
      mbar_expect_cl(mapa(fb, rank ^ 1), XB);
      tma2d_mc(sb + OFF_Q + x_slot(rank, s), &tm_x, s * 64, unit_batch(cl) * SQ + rank * 120, fb);
      if (s + 1 < EARLY_W) first_w(s + 1);
    }
  }
  __syncwarp();
  if (threadIdx.x == 0) TS(153);

  if (warp >= 8) {
    asm volatile("setmaxnreg.dec.sync.aligned.u32 24;");
    if (warp == 8) {
      uint64_t pol;
      asm volatile("createpolicy.fractional.L2::evict_first.b64 %0, 1.0;" : "=l"(pol));
      Ring r;
      if (EARLY) r.slot = EARLY_W;
      auto load = [&](const CUtensorMap* m, int c1, int c2, bool ef) {
        if (SLP & 8) mbar_sleep(sb + BAR_REMPTY + 8 * r.slot, r.phase ^ 1); else mbar_wait(sb + BAR_REMPTY + 8 * r.slot, r.phase ^ 1);
        if (lane == 0) {
          mbar_expect(sb + BAR_RFULL + 8 * r.slot, RING_BYTES);
          if (ef) tma3d_hint(sb + r.slot * RING_BYTES, m, 0, c1, c2, sb + BAR_RFULL + 8 * r.slot, pol);
          else tma3d(sb + r.slot * RING_BYTES, m, 0, c1, c2, sb + BAR_RFULL + 8 * r.slot);
        }
        r.next();
      };
      const int rot = ROT * (blockIdx.x * 5 + (blockIdx.x >> 4));
      auto pause = [&](int u0) {
        if (PAUSE_NS && NCL == 66 && u0 == PAUSE_AT * 66) {
          const int id = role();
          if (id >= 44 && id < 58) {
            unsigned t0, t1;
            asm volatile("mov.u32 %0, %globaltimer_lo;" : "=r"(t0));
            do { __nanosleep(200); asm volatile("mov.u32 %0, %globaltimer_lo;" : "=r"(t1)); } while (t1 - t0 < PAUSE_NS + (id - 44) * PAUSE_SPREAD);
          }
        }
      };
      for (int u0 = 0;; u0 += ncl) {
        const int u = __shfl_sync(~0u, (u0 >= 3 * ncl ? role() : cl) + u0, 0);
        if (u >= NUNITS) break;
        if (PAUSE_J < 0) pause(u0);
        const int h = unit_head(u, rank);
        const int krow = (unit_batch(u) * NH + h) * SK;
#pragma unroll 1
        for (int s = EARLY && u0 == 0 ? EARLY_W : 0; s < 10; s++) {
          if (u0 == 0 && s == 0 && lane == 0) TS(154);
          load(&tm_wq, s * 64, 2 * h, false);
          if (u0 == 0 && s == 0 && lane == 0) TS(155);
          const int sp = u0 == 0 ? s - PF_HOLD : s;
          if (sp >= 0 && sp < PF_N && lane == 0) l2_prefetch(P.v + (size_t)(krow + ((PF_J0 + sp * PF_STEP + rot) & 15) * 64) * DH, 16384);
        }
#pragma unroll 1
        for (int j = 0; j <= 16; j++) {
          if (j == PAUSE_J) pause(u0);
          if (j < 16) load(&tm_k, krow + ((j + rot) & 15) * 64, 0, true);
          if (j == 1 + DPRO) load(&tm_v, krow + (rot & 15) * 64, 0, true);
          if (j > 1) load(&tm_v, krow + ((j - 1 + rot) & 15) * 64, 0, true);
        }
      }
      const int id = __shfl_sync(~0u, role(), 0);
      const bool dbl = NCL == 66 && id >= 58;
      for (int t = dbl ? 2 * id - 72 : id; t < (dbl ? NOTILES : nsingle); t += ncl) {
        const int row0 = row_block(t) * 256 + rank * 128;
        const int b0 = (row0 & ~31) / SQ, b1 = (row0 + 127) / SQ;
#pragma unroll 1
        for (int ks = 0; ks < 64; ks++) {
          if (dbl ? (ks & 15) == 0 : ks == 0 || ks == 48) {
            const unsigned* c = &g_cnt[((lane & 1 ? b1 : b0) * 4 + (ks || dbl ? ks >> 4 : min(lane >> 1, 2))) * 8];
            unsigned v, n = 0;
            do {
              asm volatile("ld.acquire.gpu.global.u32 %0, [%1];" : "=r"(v) : "l"(c) : "memory");
              if (++n > (1u << 26)) __trap();
            } while (v < 16);
            __syncwarp();
            asm volatile("fence.proxy.async.global;" ::: "memory");
          }
          mbar_wait(sb + BAR_REMPTY + 8 * r.slot, r.phase ^ 1);
          if (lane == 0) {
            mbar_expect(sb + BAR_RFULL + 8 * r.slot, RING_BYTES);
            asm volatile("cp.async.bulk.tensor.4d.shared::cluster.global.mbarrier::complete_tx::bytes.L2::cache_hint [%0], [%1, {%3, %3, %4, %5}], [%2], %6;"
                         ::"r"(sb + r.slot * RING_BYTES), "l"(&tm_o), "r"(sb + BAR_RFULL + 8 * r.slot), "r"(0), "r"((dbl ? ks : bk(ks)) * 8), "r"(row0 >> 6), "l"(pol) : "memory");
          }
          r.next();
        }
      }
      if (lane == 0 && atomicAdd(&g_cnt[64 * 8], 1) == gridDim.x - 1) {
        for (int i = 0; i < 67; i++) g_cnt[i * 8] = 0;
      }
    } else if (warp == 9) {
      if (lane == 0) {
        uint32_t it = 0;
        for (;; it++) {
          const int u = (it >= 3 ? role() : cl) + it * ncl;
          if (u >= NUNITS) break;
          const int row = unit_batch(u) * SQ + rank * 120;
#pragma unroll 1
          for (int s = EARLY && it == 0 ? EARLY_X : 0; s < 10; s++) {
            const uint32_t j = s & 3, par = ((s >> 2) + (j < 2 ? it : 0)) & 1;
            if ((SLP & 4) && s == 0) mbar_sleep(sb + BAR_XEMPTY, par ^ 1);
            mbar_wait(sb + BAR_XEMPTY + 8 * j, par ^ 1);
            const uint32_t fb = sb + BAR_XFULL + 32 * rank + 8 * j;
            mbar_expect(fb, XB);
            mbar_expect_cl(mapa(fb, rank ^ 1), XB);
            tma2d_mc(sb + OFF_Q + x_slot(rank, j), &tm_x, s * 64, row, fb);
          }
        }
        const int id = role();
        const bool dbl = NCL == 66 && id >= 58;
        uint32_t slot = rank, phase = 0;
        if (WO_PF0 && dbl)
          asm volatile("cp.async.bulk.prefetch.tensor.3d.L2.global [%0, {%1, %2, %3}];" ::"l"(&tm_wo), "r"(0), "r"((2 + ((id >> 1) & 3)) * 64), "r"(((2 * id - 72 + rank) & 3) * 5) : "memory");
        if ((SLP & 4) && (dbl || id < nsingle)) mbar_sleep(sb + BAR_BEMPTY + 8 * rank, 0);
        for (int t = dbl ? 2 * id - 72 + rank : id; t < (dbl ? NOTILES : nsingle); t += ncl) {
#pragma unroll 1
          for (int ks = dbl ? 0 : rank; ks < 64; ks += dbl ? 1 : 2) {
            mbar_wait(sb + BAR_BEMPTY + 8 * slot, phase);
            const uint32_t fb = sb + BAR_BFULL + 8 * slot;
            mbar_expect(fb, BB);
            mbar_expect_cl(mapa(fb, rank ^ 1), BB);
            tma3d_mc(sb + OFF_Q + slot * BB, &tm_wo, 0, (dbl ? ks : bk(ks)) * 64, (t & 3) * 5, fb);
            if (WO_PF && dbl && ks + WO_PF < 64 && (ks & 3) == ((id >> 1) & 3))
              asm volatile("cp.async.bulk.prefetch.tensor.3d.L2.global [%0, {%1, %2, %3}];" ::"l"(&tm_wo), "r"(0), "r"((ks + WO_PF) * 64), "r"((t & 3) * 5) : "memory");
            slot += 2;
            if (slot >= 6) { slot -= 6; phase ^= 1; }
          }
        }
      }
    } else {
      const int wg = warp - 10;
      {
        mbar_wait(sb + BAR_RFULL, 0);
        const __nv_bfloat16* xs = P.x + (size_t)(unit_batch(cl) * SQ + ((cl & 3) * 2 + rank) * 30 + min(lane, 29)) * DM + 256 + wg * 64;
#pragma unroll
        for (int i = 0; i < 3; i++) asm volatile("prefetch.global.L2 [%0];" ::"l"(xs + i * 128));
        if (lane < 16) asm volatile("prefetch.global.L2 [%0];" ::"l"(P.wq + (size_t)(384 + unit_batch(cl) * 16 + lane) * HD + unit_head(cl, rank) * DH + wg * 64));
      }
      auto take_role = [&]() {
          if (wg == 0 && rank == 0 && lane == 0) {
            int id = cl;
            if (NCL == 66) {
              uint32_t smid;
              asm("mov.u32 %0, %smid;" : "=r"(smid));
              id = smid >= SMID_TOP ? 65 - atomicAdd(&g_cnt[65 * 8], 1) : atomicAdd(&g_cnt[66 * 8], 1);
            }
    #pragma unroll
            for (int c = 0; c < 2; c++) {
              const uint32_t a = mapa(sb + BAR_ROLE, c);
              asm volatile("st.shared::cluster.u32 [%0 + 8], %1;\nmbarrier.arrive.release.cluster.shared::cluster.b64 _, [%0];" ::"r"(a), "r"(id) : "memory");
            }
          }
          if (wg == 0 && lane == 0) {
            mbar_wait_cl(sb + BAR_ROLE, 0);
            mbar_arrive(sb + BAR_ROLE + 16);
          }
      };
      if (ROLE_AT < 0) { take_role(); __syncwarp(); }
      for (uint32_t it = 0;; it++) {
        const int u = __shfl_sync(~0u, (it >= 3 ? role() : cl) + it * ncl, 0);
        if (u >= NUNITS) break;
        if (SLP & 1) mbar_sleep(sb + BAR_LSUM + 8 * wg, it & 1); else mbar_wait(sb + BAR_LSUM + 8 * wg, it & 1);
        float l4[4], v[4];
        const uint32_t a = sb + OFF_L2 + wg * 2048 + lane * 16;
        asm volatile("ld.shared.v4.f32 {%0, %1, %2, %3}, [%4];" : "=f"(l4[0]), "=f"(l4[1]), "=f"(l4[2]), "=f"(l4[3]) : "r"(a) : "memory");
#pragma unroll
        for (int g = 1; g < 4; g++) {
          asm volatile("ld.shared.v4.f32 {%0, %1, %2, %3}, [%4];" : "=f"(v[0]), "=f"(v[1]), "=f"(v[2]), "=f"(v[3]) : "r"(a + g * 512) : "memory");
#pragma unroll
          for (int c = 0; c < 4; c++) l4[c] += v[c];
        }
#pragma unroll
        for (int c = 0; c < 4; c++) {
          float inv;
          asm("rcp.approx.ftz.f32 %0, %1;" : "=f"(inv) : "f"(l4[c]));
          l4[c] = l4[c] >= L_MIN && l4[c] <= L_MAX ? inv : __uint_as_float(0x7FFFFFFFu);
        }
        const uint32_t h0 = pack(l4[0], l4[1]), h1 = pack(l4[2], l4[3]);
        const uint32_t e0 = pack(l4[0] - __uint_as_float(h0 << 16), l4[1] - __uint_as_float(h0 & 0xFFFF0000u));
        const uint32_t e1 = pack(l4[2] - __uint_as_float(h1 << 16), l4[3] - __uint_as_float(h1 & 0xFFFF0000u));
        asm volatile("st.shared.v4.u32 [%0], {%1, %2, %3, %4};" ::"r"(sb + OFF_INV + wg * 640 + (lane & 3) * 144 + (lane >> 2) * 16), "r"(h0), "r"(e0), "r"(h1), "r"(e1) : "memory");
        __syncwarp();
        if (lane == 0) {
          mbar_arrive(sb + BAR_INV + 8 * wg);
          if ((int)it == ROLE_AT) {
            take_role();
          }
          if (SLP & 2) mbar_sleep(sb + BAR_STAGE + 8 * wg, it & 1); else mbar_wait(sb + BAR_STAGE + 8 * wg, it & 1);
          __threadfence();
          asm volatile("red.relaxed.gpu.global.add.u32 [%0], 1;" ::"l"(&g_cnt[(unit_batch(u) * 4 + (u >> 6)) * 8]) : "memory");
        }
        __syncwarp();
      }
    }
  } else {
    asm volatile("setmaxnreg.inc.sync.aligned.u32 240;");
    const int wg = warp >> 2, w = warp & 3;
    const uint32_t qreg = sb + OFF_Q + wg * 2 * XB, preg = sb + OFF_P + (2 + wg) * XB;
    const uint32_t st_off = ((lane >> 4) * 8 + (lane & 7)) * 128 + (((2 * w + ((lane >> 3) & 1)) ^ (lane & 7)) << 4);
    const uint32_t xempty = mapa(sb + BAR_XEMPTY, wg);
    Ring r;
    uint32_t it = 0;
    const uint32_t qd = (qreg & 0x3FFFF) >> 4, pd = (preg & 0x3FFFF) >> 4;
    auto ring_addr = [&]() { return ((sb & 0x3FFFF) + r.slot * RING_BYTES) >> 4; };
    auto ring_wait = [&]() { mbar_wait(sb + BAR_RFULL + 8 * r.slot, r.phase); };
    auto release = [&](uint32_t slot) { warp_arrive(sb + BAR_REMPTY + 8 * slot); };
    auto turn_wait = [&]() {
      if (wg == 0) asm volatile("bar.sync 3, 256;" ::: "memory");
      else asm volatile("bar.sync 4, 256;" ::: "memory");
    };
    auto turn_pass = [&]() {
      if (wg == 0) asm volatile("bar.arrive 4, 256;" ::: "memory");
      else asm volatile("bar.arrive 3, 256;" ::: "memory");
    };

    uint32_t chk = 0;
    auto load_inv = [&](uint32_t (&iv)[30], uint32_t parity) {
      const int lane = fresh_tid() & 31;
      mbar_wait(sb + BAR_INV + 8 * wg, parity);
      chk = 0;
#pragma unroll
      for (int j = 0; j < 7; j++)
        asm volatile("ld.shared.v4.u32 {%0, %1, %2, %3}, [%4];" : "=r"(iv[4 * j]), "=r"(iv[4 * j + 1]), "=r"(iv[4 * j + 2]), "=r"(iv[4 * j + 3])
                     : "r"(sb + OFF_INV + wg * 640 + (lane & 3) * 144 + j * 16) : "memory");
      asm volatile("ld.shared.v2.u32 {%0, %1}, [%2];" : "=r"(iv[28]), "=r"(iv[29]) : "r"(sb + OFF_INV + wg * 640 + (lane & 3) * 144 + 112) : "memory");
    };
    auto norm = [&](uint32_t (&n)[8], const uint32_t (&po)[60], const uint32_t (&iv)[30], auto part) {
      constexpr int k = decltype(part)::value >> 1, j0 = (decltype(part)::value & 1) * 8;
#pragma unroll
      for (int j = 0; j < 8; j++)
        n[j] = j0 + j < 15 ? hfma2(po[15 * k + (j0 + j) % 15], iv[2 * ((j0 + j) % 15)], hfma2(po[15 * k + (j0 + j) % 15], iv[2 * ((j0 + j) % 15) + 1], 0x80008000u)) : 0x3F803F80u;
#pragma unroll
      for (int j = 0; j < 8; j += 2) chk = hfma2(n[j], n[j + 1], chk);
    };
    int od1, od2;
    auto store = [&](const uint32_t (&n)[8], const char* optr, auto part) {
      constexpr int k = decltype(part)::value >> 1, off = (8 * (k & 1) + 64 * (k >> 1)) * NROWS * 2;
      if ((decltype(part)::value & 1) == 0)
        asm volatile(
            "{\n.reg .pred p;\nsetp.ne.u64 p, %8, 0;\n"
            "@p st.global.v4.u32 [%8 + %9], {%0, %1, %2, %3};\n@p st.global.v4.u32 [%8 + %9 + 512], {%4, %5, %6, %7};\n}\n"
            ::"r"(n[0]), "r"(n[1]), "r"(n[2]), "r"(n[3]), "r"(n[4]), "r"(n[5]), "r"(n[6]), "r"(n[7]), "l"(optr), "n"(off) : "memory");
      else
        asm volatile(
            "{\n.reg .pred p;\n.reg .b64 b, c;\nsetp.ne.u64 p, %7, 0;\nmad.wide.s32 b, %9, 1, %7;\nmad.wide.s32 c, %10, 1, %7;\n"
            "@p st.global.v4.u32 [%7 + %8 + 1024], {%0, %1, %2, %3};\n@p st.global.v2.u32 [b + %8], {%4, %5};\n@p st.global.u32 [c + %8], %6;\n}\n"
            ::"r"(n[0]), "r"(n[1]), "r"(n[2]), "r"(n[3]), "r"(n[4]), "r"(n[5]), "r"(n[6]), "l"(optr), "n"(off), "r"(od1), "r"(od2) : "memory");
    };
    auto put = [&](const uint32_t (&po)[60], const uint32_t (&iv)[30], const char* optr, auto part) {
      uint32_t n[8];
      norm(n, po, iv, part);
      store(n, optr, part);
    };
    auto out_ptr = [&](int u) {
      const int lane = fresh_tid() & 31;
      const int k = unit_head(u, rank) * DH + 16 * w + (lane >> 2), b = unit_batch(u), q = lane & 3;
      const uint32_t i0 = o_idx(k, o_pos(b, wg, 2 * q));
      od1 = 2 * (int)(o_idx(k, o_pos(b, wg, 96 + 2 * q)) - i0);
      od2 = 2 * (int)(o_idx(k, o_pos(b, wg, 112 + 2 * q)) - i0);
      return reinterpret_cast<const char*>(P.o + i0);
    };
    auto unsafe = [&](bool valid) {
      const bool b = valid && ((chk & 0x7F80u) == 0x7F80u || (chk & 0x7F800000u) == 0x7F800000u);
      return __any_sync(~0u, bar_red_or(wg, b));
    };
    auto publish = [&]() { __syncwarp(); warp_arrive(sb + BAR_STAGE + 8 * wg); };

    uint32_t po[60];
#pragma unroll
    for (int i = 0; i < 60; i++) po[i] = 0;
    int id = 0;
    bool more;
    do {
      float o0[60], o1[60];
      uint32_t prev = 0;
      auto qstep = [&](int s, int acc) {
        const uint32_t j = s & 3, par = ((s >> 2) + (j < 2 ? it : 0)) & 1;
        TR(it * 160 + 3 * s);
        ring_wait();
        TR(it * 160 + 3 * s + 1);
        mbar_wait(sb + BAR_XFULL + 32 * wg + 8 * j, par);
        TR(it * 160 + 3 * s + 2);
        if (s >= ALT_FROM) turn_wait();
        TI(s);
        wg_fence();
        mma_tn(o0, o1, ring_addr(), ((sb & 0x3FFFF) + OFF_Q + x_slot(wg, j)) >> 4, acc);
        wg_commit();
        if (s >= ALT_FROM || (s == ALT_FROM - 1 && wg == 1)) turn_pass();
        if (s > 0 && s <= EREL_FROM) {
          wg_wait<1>();
          release(prev);
          if (s <= 6) warp_arrive_cl(xempty + 8 * ((s - 1) & 3));
        }
        prev = r.slot;
        r.next();
      };
      auto qdone = [&](int s) {
        if (s >= EREL_FROM) {
          wg_wait<0>();
          release(prev);
          if (s <= 5) warp_arrive_cl(xempty + 8 * (s & 3));
        }
      };
      qstep(0, 0);
      qstep(1, 1);
      const int up = (it > 3 ? id : cl) + ((int)it - 1) * ncl;
      const char* optr = out_ptr(up);
      if (it == 0) optr = nullptr;
      uint32_t n7[8];
      {
        uint32_t iv[30];
        load_inv(iv, (it + 1) & 1); put(po, iv, optr, IC<0>());
        qstep(2, 1); put(po, iv, optr, IC<1>()); qdone(2);
        qstep(3, 1); put(po, iv, optr, IC<2>()); qdone(3);
        qstep(4, 1); put(po, iv, optr, IC<3>()); qdone(4);
        qstep(5, 1); put(po, iv, optr, IC<4>()); qdone(5);
        qstep(6, 1); put(po, iv, optr, IC<5>()); qdone(6);
        qstep(7, 1); put(po, iv, optr, IC<6>());
        norm(n7, po, iv, IC<7>());
        qdone(7);
        if (LATE_AT == 3 || (LATE_AT == 5 && wg == 1)) store(n7, optr, IC<7>());
      }
      TR(it * 160 + 24);
      const uint32_t a8 = ring_addr(), slot8 = r.slot;
      ring_wait();
      r.next();
      TR(it * 160 + 25);
      mbar_wait(sb + BAR_XFULL + 32 * wg, it & 1);
      TR(it * 160 + 26);
      auto wait9 = [&]() {
        TR(it * 160 + 27);
        ring_wait();
        TR(it * 160 + 28);
        mbar_wait(sb + BAR_XFULL + 32 * wg + 8, it & 1);
        TR(it * 160 + 29);
      };
      if (PRE9 == 1 || (PRE9 == 2 && wg == 1)) wait9();
      if (PRE9 == 3) ring_wait();
      turn_wait();
      TI(8);
      wg_fence();
      mma_tn(o0, o1, a8, qd, 1);
      wg_commit();
      if (PRE9 == 0 || (PRE9 == 2 && wg == 0)) wait9();
      if (PRE9 == 3) mbar_wait(sb + BAR_XFULL + 32 * wg + 8, it & 1);
      TI(9);
      if (PRE9 != 1) wg_fence();
      mma_tn_split(o0, o1, ring_addr(), qd + (XB >> 4));
      turn_pass();
      wg_wait<2>();
      if (EREL_FROM > 7) release(prev);
      release(slot8);
      if (LATE_AT == 4 || (LATE_AT == 5 && wg == 0)) store(n7, optr, IC<7>());
      auto put_q = [&](const float (&o)[60], uint32_t dst) {
        bar_sync(wg);
#pragma unroll
        for (int j = 0; j < 14; j += 2)
          stsm4t(dst + j * 1024, pack(o[4 * j] * QSCALE, o[4 * j + 1] * QSCALE), pack(o[4 * j + 2] * QSCALE, o[4 * j + 3] * QSCALE),
                 pack(o[4 * j + 4] * QSCALE, o[4 * j + 5] * QSCALE), pack(o[4 * j + 6] * QSCALE, o[4 * j + 7] * QSCALE));
        stsm2t(dst + 14 * 1024, pack(o[56] * QSCALE, o[57] * QSCALE), pack(o[58] * QSCALE, o[59] * QSCALE));
      };
      wg_wait<1>();
      reg_fence(o0);
      put_q(o0, qreg + st_off);
      wg_wait<0>();
      reg_fence(o1);
      release(r.slot);
      r.next();
      TR(it * 160 + 30);
      put_q(o1, qreg + XB + st_off);
      fence_async_smem();
      if (unsafe(it > 0)) {
        slow_path(P, unit_batch(up), unit_head(up, rank), wg, w, fresh_tid() & 31);
        optr = nullptr;
        if (!DPRO) {
#pragma unroll
          for (int i = 0; i < 60; i++) o0[i] = o1[i] = 0.f;
        }
      }
      TR(it * 160 + 32); TG(it * 160 + 142);

      float sc[60], l[30];
      uint32_t slot0 = r.slot;
      ring_wait();
      TR(it * 160 + 33);
      turn_wait();
      TI(10);
      wg_fence();
      mma_qk(sc, ring_addr(), qd);
      wg_commit();
      r.next();
      uint32_t slot1 = r.slot;
      ring_wait();
      TI(11);
      wg_fence();
      mma_qk(o1, ring_addr(), qd);
      wg_commit();
      r.next();
      turn_pass();
      if (LATE_AT == 0) store(n7, optr, IC<7>());
      wg_wait<1>();
      reg_fence(sc);
      TR(it * 160 + 35);
      release(slot0);
      exp_store<0, 15, true>(sc, l, preg + st_off);
      TR(it * 160 + 38); TG(it * 160 + 43);
      slot0 = r.slot;
      if (K2_AT > 0) {
        wg_wait<0>();
        reg_fence(o1);
        release(slot1);
        exp_store<0, K2_AT>(o1, l, preg - 2 * XB + st_off);
      }
      ring_wait();
      TI(12);
      wg_fence();
      mma_qk(sc, ring_addr(), qd);
      wg_commit();
      r.next();
      if (K2_AT == 0) {
        wg_wait<1>();
        reg_fence(o1);
        release(slot1);
      }
      TR(it * 160 + 41);
      exp_store<K2_AT, 15>(o1, l, preg - 2 * XB + st_off);
      fence_async_smem();
      TR(it * 160 + 44);
      slot1 = r.slot;
      ring_wait();
      turn_wait();
      TI(13);
      wg_fence();
      mma_tn(o0, o1, ring_addr(), pd, 0);
      wg_commit();
      r.next();
      ring_wait();
      wg_fence();
      mma_tn(o0, o1, ring_addr(), pd - (2 * XB >> 4), 1);
      wg_commit();
      turn_pass();
      if (LATE_AT == 1) store(n7, optr, IC<7>());
      if (it > 0) publish();
      if (it >= 2) id = __shfl_sync(~0u, role(), 0);
      wg_wait<1>();
      reg_fence(sc);
      release(slot0);
      release(slot1);
      bar_sync(wg);
      TR(it * 160 + 47);
      exp_store<0, VREL>(sc, l, preg + st_off);
      wg_wait<0>();
      reg_fence(o0); reg_fence(o1);
      release(r.slot);
      r.next();
      exp_store<VREL, 15>(sc, l, preg + st_off);
      fence_async_smem();
      more = id + ((int)it + 1) * ncl < NUNITS;
      const bool gemm = id < nsingle || (NCL == 66 && id >= 58);
#pragma unroll 1
      for (int s = DPRO ? 3 : 1; s < 16; s++) {
        const uint32_t kslot = r.slot;
        TR(it * 160 + 32 + 6 * s); TG(it * 160 + 37 + 6 * s);
        if (s == 8) TRL(it * 160 + 139);
        ring_wait();
        TR(it * 160 + 33 + 6 * s);
        turn_wait();
        TI(11 + s);
        wg_fence();
        mma_qk(sc, ring_addr(), qd);
        wg_commit();
        r.next();
        TR(it * 160 + 36 + 6 * s);
        ring_wait();
        TR(it * 160 + 34 + 6 * s);
        wg_fence();
        mma_tn(o0, o1, ring_addr(), pd - ((s - 1) & 1) * (2 * XB >> 4), DPRO || s != 1);
        wg_commit();
        if (wg == 0 || s < 15) turn_pass();
        wg_wait<1>();
        reg_fence(sc);
        TR(it * 160 + 35 + 6 * s);
        release(kslot);
        if (s == 15) {
          if (more) { warp_arrive_cl(xempty); warp_arrive_cl(xempty + 8); }
          else if (gemm) for (int i = 0; i < 3; i++) warp_arrive_cl(mapa(sb + BAR_BEMPTY + 8 * i, i & 1));
        }
        exp_store<0, VREL>(sc, l, preg - (s & 1) * 2 * XB + st_off);
        wg_wait<0>();
        reg_fence(o0); reg_fence(o1);
        release(r.slot);
        r.next();
        exp_store<VREL, 15>(sc, l, preg - (s & 1) * 2 * XB + st_off);
        fence_async_smem();
      }
      const uint32_t tid = fresh_tid();
      bar_sync(wg);
      TR(it * 160 + 128);
      ring_wait();
      TI(27);
      wg_fence();
      mma_tn_split(o0, o1, ring_addr(), pd - (2 * XB >> 4));
      {
        float a[16], b[8], c[4];
        const bool b4 = tid & 16, b3 = tid & 8, b2 = tid & 4;
#pragma unroll
        for (int i = 0; i < 16; i++) {
          const float hi = i < 14 ? l[(16 + i) % 30] : 1.f;
          a[i] = (b4 ? hi : l[i]) + __shfl_xor_sync(~0u, b4 ? l[i] : hi, 16);
        }
#pragma unroll
        for (int i = 0; i < 8; i++) b[i] = (b3 ? a[8 + i] : a[i]) + __shfl_xor_sync(~0u, b3 ? a[i] : a[8 + i], 8);
#pragma unroll
        for (int i = 0; i < 4; i++) c[i] = (b2 ? b[4 + i] : b[i]) + __shfl_xor_sync(~0u, b2 ? b[i] : b[4 + i], 4);
        asm volatile("st.shared.v4.f32 [%0], {%1, %2, %3, %4};" ::"r"(sb + OFF_L2 + tid * 16), "f"(c[0]), "f"(c[1]),
                     "f"(c[2]), "f"(c[3]) : "memory");
        __syncwarp();
        warp_arrive(sb + BAR_LSUM + 8 * wg);
      }
      TR(it * 160 + 132);
      TR(it * 160 + 133);
      wg_wait<1>();
      reg_fence(o0);
      TR(it * 160 + 134);
#pragma unroll
      for (int j = 0; j < 15; j++) { po[j] = pack(o0[4 * j], o0[4 * j + 1]); po[15 + j] = pack(o0[4 * j + 2], o0[4 * j + 3]); }
      wg_wait<0>();
      reg_fence(o1);
      release(r.slot);
      r.next();
      if (more) { warp_arrive_cl(xempty + 16); warp_arrive_cl(xempty + 24); }
      else if (gemm) for (int i = 3; i < 6; i++) warp_arrive_cl(mapa(sb + BAR_BEMPTY + 8 * i, i & 1));
      TR(it * 160 + 130);
#pragma unroll
      for (int j = 0; j < 15; j++) { po[30 + j] = pack(o1[4 * j], o1[4 * j + 1]); po[45 + j] = pack(o1[4 * j + 2], o1[4 * j + 3]); }
      TR(it * 160 + 131); TG(it * 160 + 143);
      it++;
    } while (more);
    const bool gemm = id < nsingle || (NCL == 66 && id >= 58);
    const int u = (it > 3 ? id : cl) + ((int)it - 1) * ncl;
    uint32_t pb[60];
#pragma unroll
    for (int i = 0; i < 60; i++) pb[i] = NCL != 66 ? po[i] ^ (gridDim.y - 1) : po[i];

    uint32_t bslot = 0, bphase = 0;
    auto out_row = [&](int lane) {
      const int row = lane & 15;
      return sb + wg * 8192 + (row < 12 ? w * RING_BYTES + row * 656 : (4 + (w >> 1)) * RING_BYTES + ((w & 1) * 4 + row - 12) * 656);
    };
    auto out_stage = [&](const float (&acc)[80], uint32_t col_off) {
      const int lane = fresh_tid() & 31;
      const uint32_t sa = out_row(lane) + col_off + (lane >> 4) * 16;
#pragma unroll
      for (int j = 0; j < 20; j += 2)
        asm volatile("stmatrix.sync.aligned.m8n8.x4.shared.b16 [%0], {%1,%2,%3,%4};" ::"r"(sa + j * 16), "r"(pack(acc[4 * j], acc[4 * j + 1])),
                     "r"(pack(acc[4 * j + 2], acc[4 * j + 3])), "r"(pack(acc[4 * j + 4], acc[4 * j + 5])), "r"(pack(acc[4 * j + 6], acc[4 * j + 7])) : "memory");
    };
    auto out_store = [&](int t, uint32_t bytes) {
      const int lane = fresh_tid() & 31;
      if (EPI_MIX && wg == 1) {
        __syncwarp();
#pragma unroll 1
        for (int h = 0; h < 2; h++) {
          const int row = h * 8 + (lane >> 2);
          const uint32_t src = out_row(row) + (lane & 3) * 16;
          char* dst = reinterpret_cast<char*>(P.out + (size_t)o_row(row_block(t) * 256 + rank * 128 + 64 + w * 16 + row) * DM + (t & 3) * 160) + (lane & 3) * 16;
#pragma unroll 1
          for (uint32_t c = 0; c < bytes; c += 320) {
            uint4 v[5];
#pragma unroll
            for (int i = 0; i < 5; i++)
              asm volatile("ld.shared.v4.u32 {%0, %1, %2, %3}, [%4];" : "=r"(v[i].x), "=r"(v[i].y), "=r"(v[i].z), "=r"(v[i].w) : "r"(src + c + i * 64) : "memory");
#pragma unroll
            for (int i = 0; i < 5; i++) *reinterpret_cast<uint4*>(dst + c + i * 64) = v[i];
          }
        }
        return;
      }
      fence_async_smem();
      __syncwarp();
      if (lane < 16) {
        __nv_bfloat16* dst = P.out + (size_t)o_row(row_block(t) * 256 + rank * 128 + wg * 64 + w * 16 + lane) * DM + (t & 3) * 160;
        asm volatile("cp.async.bulk.global.shared::cta.bulk_group [%0], [%1], %2;" ::"l"(dst), "r"(out_row(lane)), "r"(bytes) : "memory");
        asm volatile("cp.async.bulk.commit_group;" ::: "memory");
        asm volatile("cp.async.bulk.wait_group.read 0;" ::: "memory");
      }
    };
    for (int t = id; t == id || (NCL != 66 && t < nsingle); t += ncl) {
      float acc[80];
      uint32_t prev = 0, bprev = 0;
      const bool tile = t < nsingle;
      const bool last = NCL == 66 || t + ncl >= nsingle;
      auto bstep = [&](int ks, int accf) {
        if (!(ks & 3)) TR(640 + ks / 2); if ((ks & 7) == 0) TG(144 + (ks >> 3));
        ring_wait();
        mbar_wait(sb + BAR_BFULL + 8 * bslot, bphase);
        if (!(ks & 3)) TR(641 + ks / 2);
        wg_fence();
        const uint32_t a = ring_addr() + wg * 512, bd = (((sb & 0x3FFFF) + OFF_Q + bslot * BB) >> 4) | ((4096u >> 4) << 16);
#pragma unroll
        for (int k = 0; k < 4; k++) wgmma_n160<1, 1>(acc, a + LBO64A + k * 128, HI64A, bd + k * 64, HI64, k == 0 ? accf : 1);
        wg_commit();
        if (ks > 0) {
          wg_wait<1>();
          release(prev);
          if (ks < 59 || !last) warp_arrive_cl(mapa(sb + BAR_BEMPTY + 8 * bprev, bprev & 1));
        }
        prev = r.slot; bprev = bslot;
        r.next();
        if (++bslot == 6) { bslot = 0; bphase ^= 1; }
      };
      const char* optr;
      uint32_t iv[30], n3[8], n4[8], n5[8], n6[8], n7[8];
      if (tile) {
        bstep(0, 0);
        bstep(1, 1);
        optr = out_ptr(u);
        if (t != id) optr = nullptr;
        load_inv(iv, (it + 1) & 1);
#pragma unroll 1
        for (int ks = 2; ks < 17; ks++) {
          bstep(ks, 1);
          switch (ks) {
            case 2: put(pb, iv, optr, IC<0>()); break;
            case 4: put(pb, iv, optr, IC<1>()); break;
            case 6: put(pb, iv, optr, IC<2>()); break;
            case 8: put(pb, iv, optr, IC<3>()); break;
            case 10: put(pb, iv, optr, IC<4>()); break;
            case 12: put(pb, iv, optr, IC<5>()); break;
            case 14: put(pb, iv, optr, IC<6>()); break;
            case 16: put(pb, iv, optr, IC<7>()); break;
            default: break;
          }
        }
        wg_wait<0>();
        reg_fence(acc);
#pragma unroll
        for (int i = 0; i < 8; i++) n3[i] = n4[i] = n5[i] = n6[i] = n7[i] = 0;
      } else {
        Ring r2 = r;
        auto first = [&](int ks) {
          if (ks == 0) { TR(640); TG(144); }
          if (gemm) { mbar_wait(sb + BAR_RFULL + 8 * r2.slot, r2.phase); mbar_wait(sb + BAR_BFULL + 16 * ks, 0); }
          wg_fence();
          const uint32_t a = (((sb & 0x3FFFF) + r2.slot * RING_BYTES) >> 4) + wg * 512;
          const uint32_t bd = (((sb & 0x3FFFF) + OFF_Q + 2 * ks * BB) >> 4) | ((4096u >> 4) << 16);
#pragma unroll
          for (int k = 0; k < 4; k++) wgmma_n160<1, 1>(acc, a + LBO64A + k * 128, HI64A, bd + k * 64, HI64, k + ks != 0);
          wg_commit();
          if (ks > 0) {
            wg_wait<1>();
            if (gemm) warp_arrive_cl(mapa(sb + BAR_BEMPTY + 16 * (ks - 1), 0));
          }
          r2.next();
        };
        first(0);
        optr = out_ptr(u);
        load_inv(iv, (it + 1) & 1);
        put(pb, iv, optr, IC<0>());
        first(1);
        put(pb, iv, optr, IC<1>());
        norm(n3, pb, iv, IC<3>()); norm(n4, pb, iv, IC<4>());
        first(2);
        put(pb, iv, optr, IC<2>());
        norm(n5, pb, iv, IC<5>()); norm(n6, pb, iv, IC<6>()); norm(n7, pb, iv, IC<7>());
        wg_wait<0>();
        reg_fence(acc);
      }
      if (unsafe(t == id)) {
        slow_path(P, unit_batch(u), unit_head(u, rank), wg, w, fresh_tid() & 31);
        optr = nullptr;
#pragma unroll
        for (int i = 0; i < 8; i++) n3[i] = n4[i] = n5[i] = n6[i] = n7[i] = 0;
      }
      if (tile && t == id) publish();
      if (!tile) {
        if (gemm) {
          float ac1[80];
          auto half = [&](float (&ac)[80], bool rel, int accf) {
            mbar_wait(sb + BAR_BFULL + 8 * bslot, bphase);
            wg_fence();
            const uint32_t a = ring_addr() + wg * 512, bd = (((sb & 0x3FFFF) + OFF_Q + bslot * BB) >> 4) | ((4096u >> 4) << 16);
#pragma unroll
            for (int k = 0; k < 4; k++) wgmma_n160<1, 1>(ac, a + LBO64A + k * 128, HI64A, bd + k * 64, HI64, k == 0 ? accf : 1);
            wg_commit();
            wg_wait<1>();
            if (rel) warp_arrive_cl(mapa(sb + BAR_BEMPTY + 8 * bprev, bprev & 1));
            bprev = bslot;
          };
          auto dstep = [&](int ks) {
            if (!(ks & 3)) TR(640 + ks / 2); if ((ks & 7) == 0) TG(144 + (ks >> 3));
            ring_wait();
            if (!(ks & 3)) TR(641 + ks / 2);
            half(acc, ks < 62, 1);
            release(prev);
            bslot++;
            half(ac1, ks < 61, 1);
            if (++bslot == 6) { bslot = 0; bphase ^= 1; }
            prev = r.slot; r.next();
          };
          bprev = 4; bslot = 1;
          half(ac1, true, 0);
          prev = r.slot; r.next(); bslot = 3;
          half(ac1, true, 1);
          release(prev); prev = r.slot; r.next(); bslot = 5;
          store(n3, optr, IC<3>());
          half(ac1, true, 1);
          release(prev); prev = r.slot; r.next(); bslot = 0; bphase = 1;
#pragma unroll 1
          for (int ks = 3; ks < 7; ks++) {
            dstep(ks);
            switch (ks) {
              case 3: store(n4, optr, IC<4>()); break;
              case 4: store(n5, optr, IC<5>()); break;
              case 5: store(n6, optr, IC<6>()); break;
              default: store(n7, optr, IC<7>()); break;
            }
          }
          publish();
#pragma unroll 1
          for (int ks = 7; ks < 64; ks++) {
            if (wg == 1 && ks == 62) turn_wait();
            dstep(ks);
          }
          if (wg == 0) turn_pass();
          wg_wait<0>();
          reg_fence(acc); reg_fence(ac1);
          TRL(158); TG(156);
          bar_sync(wg);
          out_stage(acc, 0);
          out_stage(ac1, 320);
          out_store(2 * id - 72, 640);
        } else {
          store(n3, optr, IC<3>()); store(n4, optr, IC<4>()); store(n5, optr, IC<5>()); store(n6, optr, IC<6>()); store(n7, optr, IC<7>());
          publish();
        }
        break;
      }
#pragma unroll 1
      for (int ks = 17; ks < 64; ks++) {
        if (END_SKEW && wg == 1 && ks == 64 - END_SKEW) turn_wait();
        bstep(ks, 1);
      }
      if (END_SKEW && wg == 0) turn_pass();
      wg_wait<0>();
      reg_fence(acc);
      release(prev);
      if (!last) warp_arrive_cl(mapa(sb + BAR_BEMPTY + 8 * bprev, bprev & 1));
      TRL(158); TG(156);
      const int pos0 = row_block(t) * 256 + rank * 128 + wg * 64 + w * 16;
      if (last) {
        bar_sync(wg);
        out_stage(acc, 0);
        out_store(t, 320);
      } else {
        const int lane = fresh_tid() & 31;
        __nv_bfloat16* op0 = P.out + (size_t)o_row(pos0 + (lane >> 2)) * DM + (t & 3) * 160 + (lane & 3) * 2;
        __nv_bfloat16* op1 = P.out + (size_t)o_row(pos0 + (lane >> 2) + 8) * DM + (t & 3) * 160 + (lane & 3) * 2;
#pragma unroll
        for (int j = 0; j < 20; j++) {
          *reinterpret_cast<uint32_t*>(op0 + j * 8) = pack(acc[4 * j], acc[4 * j + 1]);
          *reinterpret_cast<uint32_t*>(op1 + j * 8) = pack(acc[4 * j + 2], acc[4 * j + 3]);
        }
      }
#pragma unroll
      for (int i = 0; i < 60; i++) pb[i] = 0;
    }
    TRL(159);
  }
}

typedef CUresult (*EncodeFn)(CUtensorMap*, CUtensorMapDataType, cuuint32_t, void*, const cuuint64_t*, const cuuint64_t*,
                             const cuuint32_t*, const cuuint32_t*, CUtensorMapInterleave, CUtensorMapSwizzle,
                             CUtensorMapL2promotion, CUtensorMapFloatOOBfill);

void make_map(EncodeFn enc, CUtensorMap* m, const void* p, int rank, const cuuint64_t* dims, const cuuint64_t* strides,
              const cuuint32_t* box, CUtensorMapSwizzle sw, CUtensorMapL2promotion promo) {
  cuuint32_t es[4] = {1, 1, 1, 1};
  enc(m, CU_TENSOR_MAP_DATA_TYPE_BFLOAT16, rank, const_cast<void*>(p), dims, strides, box, es, CU_TENSOR_MAP_INTERLEAVE_NONE, sw,
      promo, CU_TENSOR_MAP_FLOAT_OOB_FILL_NONE);
}

}

extern "C" void kernel_launch(void* const* d_in, const int* in_sizes, int n_in, void* d_out, int out_size) {
  static EncodeFn enc = nullptr;
  static int nclusters = 0;
  static void* o_ptr = nullptr;
  if (!enc) {
    cudaDriverEntryPointQueryResult qr;
    cudaGetDriverEntryPoint("cuTensorMapEncodeTiled", (void**)&enc, cudaEnableDefault, &qr);
    cudaFuncSetAttribute(fused_attn_kernel<66>, cudaFuncAttributeMaxDynamicSharedMemorySize, SMEM_BYTES);
    cudaFuncSetAttribute(fused_attn_kernel<0>, cudaFuncAttributeMaxDynamicSharedMemorySize, SMEM_BYTES);
    cudaGetSymbolAddress(&o_ptr, g_o);
    cudaLaunchConfig_t cfg = {};
    cfg.gridDim = 128; cfg.blockDim = 384; cfg.dynamicSmemBytes = SMEM_BYTES;
    cudaLaunchAttribute at; at.id = cudaLaunchAttributeClusterDimension;
    at.val.clusterDim.x = 2; at.val.clusterDim.y = 1; at.val.clusterDim.z = 1;
    cfg.attrs = &at; cfg.numAttrs = 1;
    int n = 0;
    cudaOccupancyMaxActiveClusters(&n, fused_attn_kernel<66>, &cfg);
    nclusters = n >= 66 ? MAXCL : (n >= 64 || n <= 0 ? 64 : n);
  }
  const __nv_bfloat16* x = (const __nv_bfloat16*)d_in[0];
  const __nv_bfloat16* k = (const __nv_bfloat16*)d_in[1];
  const __nv_bfloat16* v = (const __nv_bfloat16*)d_in[2];
  const __nv_bfloat16* wq = (const __nv_bfloat16*)d_in[3];
  const __nv_bfloat16* wo = (const __nv_bfloat16*)d_in[4];
  CUtensorMap tm_x, tm_wq, tm_k, tm_v, tm_o, tm_wo;
  const auto S128 = CU_TENSOR_MAP_SWIZZLE_128B;
  const auto P128 = CU_TENSOR_MAP_L2_PROMOTION_L2_128B, P256 = CU_TENSOR_MAP_L2_PROMOTION_L2_256B;
  { cuuint64_t d[2] = {DM, NB * SQ}, s[1] = {DM * 2}; cuuint32_t b[2] = {64, 120}; make_map(enc, &tm_x, x, 2, d, s, b, S128, X_PROMO); }
  { cuuint64_t d[3] = {64, DM, HD / 64}, s[2] = {HD * 2, 128}; cuuint32_t b[3] = {64, 64, 2}; make_map(enc, &tm_wq, wq, 3, d, s, b, S128, P256); }
  { cuuint64_t d[3] = {64, NB * NH * SK, 2}, s[2] = {DH * 2, 128}; cuuint32_t b[3] = {64, 64, 2};
    make_map(enc, &tm_k, k, 3, d, s, b, S128, P128); make_map(enc, &tm_v, v, 3, d, s, b, S128, P128); }
  { cuuint64_t d[4] = {256, 2, HD / 8, NROWS / 64}, s[3] = {512, NROWS * 16, 1024}; cuuint32_t b[4] = {256, 2, 8, 2};
    make_map(enc, &tm_o, o_ptr, 4, d, s, b, CU_TENSOR_MAP_SWIZZLE_NONE, P256); }
  { cuuint64_t d[3] = {32, HD, DM / 32}, s[2] = {DM * 2, 64}; cuuint32_t b[3] = {32, 64, 5};
    make_map(enc, &tm_wo, wo, 3, d, s, b, CU_TENSOR_MAP_SWIZZLE_64B, P128); }
  Params P{x, k, v, wq, (__nv_bfloat16*)d_out, (__nv_bfloat16*)o_ptr};
  if (nclusters == 66) fused_attn_kernel<66><<<132, 384, SMEM_BYTES>>>(tm_x, tm_wq, tm_k, tm_v, tm_o, tm_wo, P);
  else fused_attn_kernel<0><<<2 * nclusters, 384, SMEM_BYTES>>>(tm_x, tm_wq, tm_k, tm_v, tm_o, tm_wo, P);
}
```

```cpp
#include <cuda_runtime.h>
#include <cuda.h>
#include <cuda_bf16.h>
#include <stdint.h>

namespace {

constexpr int NB = 16, SQ = 240, DM = 640, NH = 32, SK = 1024, DH = 128, HD = NH * DH;
constexpr int NROWS = NB * SQ;
constexpr int NUNITS = 256;
#define DPRO 1
#define LATE_AT 0
#define ALT_FROM 4
#define END_SKEW 5
#define VREL 6
#define PF_HOLD 6
#define PF_N 4
#define PF_J0 3
#define PF_STEP 3
#define ROT 0
#define O_EF 1
#define B_ORDER 1
#define WO_PF 6
#define ROLE_AT 0
#define PAUSE_NS 11000
#define PAUSE_AT 2
#define EARLY 1
#define EARLY_X 2
#define EARLY_W 2
#define X_PROMO P128
#define PAUSE_J -1
#define PAUSE_SPREAD 0
#define WO_PF0 1
#define EPI_MIX 1
#define K2_AT 0
#define SLP 15
#define PASS9 0
#define MERGE7 0
#define EARLY_VOTE 1
#define EREL_FROM 4
#define PRE9 0
#define MAXCL 66
#define SMID_TOP 88
constexpr int NOTILES = 60;
constexpr float QSCALE = 0.08838834764831845f * 1.4426950408889634f;
constexpr float L_MIN = 9.5367431640625e-07f;
constexpr float L_MAX = 1.152921504606846976e18f;

constexpr uint32_t RING_SLOTS = 6, RING_BYTES = 16384;
constexpr uint32_t XB = 15360;
constexpr uint32_t BB = 20480;
constexpr uint32_t OFF_Q = RING_SLOTS * RING_BYTES;
constexpr uint32_t OFF_P = OFF_Q + 4 * XB;
constexpr uint32_t OFF_INV = OFF_P + 4 * XB;
constexpr uint32_t OFF_L2 = OFF_INV + 1280;
constexpr uint32_t OFF_BAR = OFF_L2 + 4096;
constexpr uint32_t BAR_RFULL = OFF_BAR, BAR_REMPTY = BAR_RFULL + 48, BAR_XFULL = BAR_REMPTY + 48,
    BAR_XEMPTY = BAR_XFULL + 64, BAR_BFULL = BAR_XEMPTY + 32, BAR_BEMPTY = BAR_BFULL + 48, BAR_STAGE = BAR_BEMPTY + 48;
constexpr uint32_t BAR_ROLE = BAR_STAGE + 16, BAR_LSUM = BAR_ROLE + 24, BAR_INV = BAR_LSUM + 16;
constexpr uint32_t OFF_TR = BAR_INV + 16;
constexpr uint32_t SMEM_BYTES = OFF_TR + 1024;

constexpr uint32_t HI128 = (1u << 30) | (1024 >> 4);
constexpr uint32_t HI64 = (2u << 30) | (512 >> 4);
constexpr uint32_t HI64A = (2u << 30) | (1024 >> 4), LBO64A = (512u >> 4) << 16;

__device__ __nv_bfloat16 g_o[HD * NROWS];
__device__ unsigned g_cnt[67 * 8];
#define TS(i)
#define TI(i)
#define TRL(i)
#define TR(i)
#define TG(i)

struct Params {
  const __nv_bfloat16 *x, *k, *v, *wq;
  __nv_bfloat16 *out, *o;
};

__device__ __forceinline__ void wg_fence() { asm volatile("wgmma.fence.sync.aligned;" ::: "memory"); }
__device__ __forceinline__ void wg_commit() { asm volatile("wgmma.commit_group.sync.aligned;" ::: "memory"); }
template <int N> __device__ __forceinline__ void wg_wait() { asm volatile("wgmma.wait_group.sync.aligned %0;" ::"n"(N) : "memory"); }
template <int N> __device__ __forceinline__ void reg_fence(float (&r)[N]) {
#pragma unroll
  for (int i = 0; i < N; i++) asm volatile("" : "+f"(r[i])::"memory");
}
template <int TA, int TB>
__device__ __forceinline__ void wgmma_n120(float (&d)[60], uint32_t a_lo, uint32_t a_hi, uint32_t b_lo, uint32_t b_hi, int acc) {
  asm volatile(
      "{\n.reg .pred p;\n.reg .b64 da, db;\nsetp.ne.b32 p, %64, 0;\n"
      "mov.b64 da, {%60, %61};\nmov.b64 db, {%62, %63};\n"
      "wgmma.mma_async.sync.aligned.m64n120k16.f32.bf16.bf16 {"
      "%0, %1, %2, %3, %4, %5, %6, %7, %8, %9, %10, %11, %12, %13, %14, %15, %16, %17, %18, %19, %20, %21, %22, %23, "
      "%24, %25, %26, %27, %28, %29, %30, %31, %32, %33, %34, %35, %36, %37, %38, %39, %40, %41, %42, %43, %44, %45, "
      "%46, %47, %48, %49, %50, %51, %52, %53, %54, %55, %56, %57, %58, %59"
      "}, da, db, p, 1, 1, %65, %66;\n}\n"
      : "+f"(d[0]), "+f"(d[1]), "+f"(d[2]), "+f"(d[3]), "+f"(d[4]), "+f"(d[5]), "+f"(d[6]), "+f"(d[7]), "+f"(d[8]),
        "+f"(d[9]), "+f"(d[10]), "+f"(d[11]), "+f"(d[12]), "+f"(d[13]), "+f"(d[14]), "+f"(d[15]), "+f"(d[16]),
        "+f"(d[17]), "+f"(d[18]), "+f"(d[19]), "+f"(d[20]), "+f"(d[21]), "+f"(d[22]), "+f"(d[23]), "+f"(d[24]),
        "+f"(d[25]), "+f"(d[26]), "+f"(d[27]), "+f"(d[28]), "+f"(d[29]), "+f"(d[30]), "+f"(d[31]), "+f"(d[32]),
        "+f"(d[33]), "+f"(d[34]), "+f"(d[35]), "+f"(d[36]), "+f"(d[37]), "+f"(d[38]), "+f"(d[39]), "+f"(d[40]),
        "+f"(d[41]), "+f"(d[42]), "+f"(d[43]), "+f"(d[44]), "+f"(d[45]), "+f"(d[46]), "+f"(d[47]), "+f"(d[48]),
        "+f"(d[49]), "+f"(d[50]), "+f"(d[51]), "+f"(d[52]), "+f"(d[53]), "+f"(d[54]), "+f"(d[55]), "+f"(d[56]),
        "+f"(d[57]), "+f"(d[58]), "+f"(d[59])
      : "r"(a_lo), "r"(a_hi), "r"(b_lo), "r"(b_hi), "r"(acc), "n"(TA), "n"(TB));
}

template <int TA, int TB>
__device__ __forceinline__ void wgmma_n160(float (&d)[80], uint32_t a_lo, uint32_t a_hi, uint32_t b_lo, uint32_t b_hi, int acc) {
  asm volatile(
      "{\n.reg .pred p;\n.reg .b64 da, db;\nsetp.ne.b32 p, %84, 0;\n"
      "mov.b64 da, {%80, %81};\nmov.b64 db, {%82, %83};\n"
      "wgmma.mma_async.sync.aligned.m64n160k16.f32.bf16.bf16 {"
      "%0, %1, %2, %3, %4, %5, %6, %7, %8, %9, %10, %11, %12, %13, %14, %15, %16, %17, %18, %19, %20, %21, %22, %23, "
      "%24, %25, %26, %27, %28, %29, %30, %31, %32, %33, %34, %35, %36, %37, %38, %39, %40, %41, %42, %43, %44, %45, "
      "%46, %47, %48, %49, %50, %51, %52, %53, %54, %55, %56, %57, %58, %59, %60, %61, %62, %63, %64, %65, %66, %67, "
      "%68, %69, %70, %71, %72, %73, %74, %75, %76, %77, %78, %79"
      "}, da, db, p, 1, 1, %85, %86;\n}\n"
      : "+f"(d[0]), "+f"(d[1]), "+f"(d[2]), "+f"(d[3]), "+f"(d[4]), "+f"(d[5]), "+f"(d[6]), "+f"(d[7]), "+f"(d[8]),
        "+f"(d[9]), "+f"(d[10]), "+f"(d[11]), "+f"(d[12]), "+f"(d[13]), "+f"(d[14]), "+f"(d[15]), "+f"(d[16]),
        "+f"(d[17]), "+f"(d[18]), "+f"(d[19]), "+f"(d[20]), "+f"(d[21]), "+f"(d[22]), "+f"(d[23]), "+f"(d[24]),
        "+f"(d[25]), "+f"(d[26]), "+f"(d[27]), "+f"(d[28]), "+f"(d[29]), "+f"(d[30]), "+f"(d[31]), "+f"(d[32]),
        "+f"(d[33]), "+f"(d[34]), "+f"(d[35]), "+f"(d[36]), "+f"(d[37]), "+f"(d[38]), "+f"(d[39]), "+f"(d[40]),
        "+f"(d[41]), "+f"(d[42]), "+f"(d[43]), "+f"(d[44]), "+f"(d[45]), "+f"(d[46]), "+f"(d[47]), "+f"(d[48]),
        "+f"(d[49]), "+f"(d[50]), "+f"(d[51]), "+f"(d[52]), "+f"(d[53]), "+f"(d[54]), "+f"(d[55]), "+f"(d[56]),
        "+f"(d[57]), "+f"(d[58]), "+f"(d[59]), "+f"(d[60]), "+f"(d[61]), "+f"(d[62]), "+f"(d[63]), "+f"(d[64]),
        "+f"(d[65]), "+f"(d[66]), "+f"(d[67]), "+f"(d[68]), "+f"(d[69]), "+f"(d[70]), "+f"(d[71]), "+f"(d[72]),
        "+f"(d[73]), "+f"(d[74]), "+f"(d[75]), "+f"(d[76]), "+f"(d[77]), "+f"(d[78]), "+f"(d[79])
      : "r"(a_lo), "r"(a_hi), "r"(b_lo), "r"(b_hi), "r"(acc), "n"(TA), "n"(TB));
}
__device__ __forceinline__ void mbar_init(uint32_t bar, int cnt) { asm volatile("mbarrier.init.shared::cta.b64 [%0], %1;" ::"r"(bar), "r"(cnt)); }
__device__ __forceinline__ void mbar_expect(uint32_t bar, uint32_t bytes) {
  asm volatile("mbarrier.arrive.expect_tx.shared::cta.b64 _, [%0], %1;" ::"r"(bar), "r"(bytes) : "memory");
}
__device__ __forceinline__ uint32_t mapa(uint32_t addr, uint32_t cta) {
  uint32_t r; asm("mapa.shared::cluster.u32 %0, %1, %2;" : "=r"(r) : "r"(addr), "r"(cta)); return r;
}
__device__ __forceinline__ void mbar_expect_cl(uint32_t cbar, uint32_t bytes) {
  asm volatile("mbarrier.arrive.expect_tx.shared::cluster.b64 _, [%0], %1;" ::"r"(cbar), "r"(bytes) : "memory");
}
__device__ __forceinline__ void mbar_arrive(uint32_t bar) { asm volatile("mbarrier.arrive.shared::cta.b64 _, [%0];" ::"r"(bar) : "memory"); }
__device__ __forceinline__ void mbar_arrive_cl(uint32_t cbar) { asm volatile("mbarrier.arrive.shared::cluster.b64 _, [%0];" ::"r"(cbar) : "memory"); }
__device__ __forceinline__ void warp_arrive(uint32_t bar) {
  asm volatile("{\n.reg .pred p;\nelect.sync _|p, 0xffffffff;\n@p mbarrier.arrive.shared::cta.b64 _, [%0];\n}\n" ::"r"(bar) : "memory");
}
__device__ __forceinline__ void warp_arrive_cl(uint32_t cbar) {
  asm volatile("{\n.reg .pred p;\nelect.sync _|p, 0xffffffff;\n@p mbarrier.arrive.shared::cluster.b64 _, [%0];\n}\n" ::"r"(cbar) : "memory");
}
__device__ __forceinline__ void mbar_wait(uint32_t bar, uint32_t parity) {
  asm volatile(
      "{\n.reg .pred p;\n.reg .u32 n;\n"
      "mbarrier.try_wait.parity.shared::cta.b64 p, [%0], %1;\n@p bra WAIT_DONE;\n"
      "mov.u32 n, 0;\n"
      "WAIT_LOOP:\n"
      "mbarrier.try_wait.parity.shared::cta.b64 p, [%0], %1;\n@p bra WAIT_DONE;\n"
      "add.u32 n, n, 1;\nsetp.lt.u32 p, n, 0x4000000;\n@p bra WAIT_LOOP;\ntrap;\n"
      "WAIT_DONE:\n}\n" ::"r"(bar), "r"(parity) : "memory");
}
__device__ __forceinline__ void mbar_sleep(uint32_t bar, uint32_t parity) {
  asm volatile(
      "{\n.reg .pred p;\n.reg .u32 n;\nmov.u32 n, 0;\n"
      "WAIT_LOOP:\n"
      "mbarrier.try_wait.parity.shared::cta.b64 p, [%0], %1, 4000;\n@p bra WAIT_DONE;\n"
      "add.u32 n, n, 1;\nsetp.lt.u32 p, n, 0x400000;\n@p bra WAIT_LOOP;\ntrap;\n"
      "WAIT_DONE:\n}\n" ::"r"(bar), "r"(parity) : "memory");
}
__device__ __forceinline__ void mbar_wait_cl(uint32_t bar, uint32_t parity) {
  asm volatile(
      "{\n.reg .pred p;\n.reg .u32 n;\nmov.u32 n, 0;\n"
      "WAIT_LOOP:\n"
      "mbarrier.try_wait.parity.acquire.cluster.shared::cta.b64 p, [%0], %1;\n@p bra WAIT_DONE;\n"
      "add.u32 n, n, 1;\nsetp.lt.u32 p, n, 0x4000000;\n@p bra WAIT_LOOP;\ntrap;\n"
      "WAIT_DONE:\n}\n" ::"r"(bar), "r"(parity) : "memory");
}
__device__ __forceinline__ void tma3d(uint32_t dst, const CUtensorMap* m, int c0, int c1, int c2, uint32_t bar) {
  asm volatile("cp.async.bulk.tensor.3d.shared::cluster.global.mbarrier::complete_tx::bytes [%0], [%1, {%3, %4, %5}], [%2];"
               ::"r"(dst), "l"(m), "r"(bar), "r"(c0), "r"(c1), "r"(c2) : "memory");
}
__device__ __forceinline__ void tma3d_hint(uint32_t dst, const CUtensorMap* m, int c0, int c1, int c2, uint32_t bar, uint64_t pol) {
  asm volatile("cp.async.bulk.tensor.3d.shared::cluster.global.mbarrier::complete_tx::bytes.L2::cache_hint [%0], [%1, {%3, %4, %5}], [%2], %6;"
               ::"r"(dst), "l"(m), "r"(bar), "r"(c0), "r"(c1), "r"(c2), "l"(pol) : "memory");
}
__device__ __forceinline__ void tma2d_mc(uint32_t dst, const CUtensorMap* m, int c0, int c1, uint32_t bar) {
  asm volatile("cp.async.bulk.tensor.2d.shared::cluster.global.mbarrier::complete_tx::bytes.multicast::cluster [%0], [%1, {%3, %4}], [%2], %5;"
               ::"r"(dst), "l"(m), "r"(bar), "r"(c0), "r"(c1), "h"((uint16_t)3) : "memory");
}
__device__ __forceinline__ void tma3d_mc(uint32_t dst, const CUtensorMap* m, int c0, int c1, int c2, uint32_t bar) {
  asm volatile("cp.async.bulk.tensor.3d.shared::cluster.global.mbarrier::complete_tx::bytes.multicast::cluster [%0], [%1, {%3, %4, %5}], [%2], %6;"
               ::"r"(dst), "l"(m), "r"(bar), "r"(c0), "r"(c1), "r"(c2), "h"((uint16_t)3) : "memory");
}
__device__ __forceinline__ void l2_prefetch(const void* p, uint32_t bytes) {
  asm volatile("cp.async.bulk.prefetch.L2.global [%0], %1;" ::"l"(p), "r"(bytes) : "memory");
}
__device__ __forceinline__ void fence_async_smem() { asm volatile("fence.proxy.async.shared::cta;" ::: "memory"); }
__device__ __forceinline__ void bar_sync(int wg) {
  if (wg == 0) asm volatile("bar.sync 1, 128;" ::: "memory");
  else asm volatile("bar.sync 2, 128;" ::: "memory");
}
__device__ __forceinline__ bool bar_red_or(int id, bool v) {
  uint32_t r;
  asm volatile("{\n.reg .pred p, q;\nsetp.ne.u32 p, %2, 0;\nbar.red.or.pred q, %1, 128, p;\nselp.u32 %0, 1, 0, q;\n}\n"
               : "=r"(r) : "r"(1 + id), "r"((uint32_t)v) : "memory");
  return r != 0;
}
__device__ __forceinline__ uint32_t hfma2(uint32_t a, uint32_t b, uint32_t c) { uint32_t r; asm("fma.rn.bf16x2 %0, %1, %2, %3;" : "=r"(r) : "r"(a), "r"(b), "r"(c)); return r; }
__device__ __forceinline__ float ex2(float x) { float y; asm("ex2.approx.ftz.f32 %0, %1;" : "=f"(y) : "f"(x)); return y; }
__device__ __forceinline__ uint32_t pack(float lo, float hi) { uint32_t r; asm("cvt.rn.bf16x2.f32 %0, %1, %2;" : "=r"(r) : "f"(hi), "f"(lo)); return r; }
__device__ __forceinline__ void stsm4t(uint32_t a, uint32_t r0, uint32_t r1, uint32_t r2, uint32_t r3) {
  asm volatile("stmatrix.sync.aligned.m8n8.x4.trans.shared.b16 [%0], {%1,%2,%3,%4};" ::"r"(a), "r"(r0), "r"(r1), "r"(r2), "r"(r3) : "memory");
}
__device__ __forceinline__ void stsm2t(uint32_t a, uint32_t r0, uint32_t r1) {
  asm volatile("stmatrix.sync.aligned.m8n8.x2.trans.shared.b16 [%0], {%1,%2};" ::"r"(a), "r"(r0), "r"(r1) : "memory");
}
__device__ __forceinline__ void mma16816(float (&d)[4], const uint32_t (&a)[4], uint32_t b0, uint32_t b1) {
  asm volatile("mma.sync.aligned.m16n8k16.row.col.f32.bf16.bf16.f32 {%0,%1,%2,%3}, {%4,%5,%6,%7}, {%8,%9}, {%0,%1,%2,%3};"
               : "+f"(d[0]), "+f"(d[1]), "+f"(d[2]), "+f"(d[3]) : "r"(a[0]), "r"(a[1]), "r"(a[2]), "r"(a[3]), "r"(b0), "r"(b1));
}

__device__ __forceinline__ uint32_t fresh_tid() { uint32_t t; asm volatile("mov.u32 %0, %tid.x;" : "=r"(t)); return t; }

template <int V> struct IC { static constexpr int value = V; };

struct Ring {
  uint32_t slot = 0, phase = 0;
  __device__ __forceinline__ void next() { if (++slot == RING_SLOTS) { slot = 0; phase ^= 1; } }
};

__device__ __forceinline__ void mma_tn(float (&o0)[60], float (&o1)[60], uint32_t a, uint32_t b, int acc) {
#pragma unroll
  for (int k = 0; k < 4; k++) {
    wgmma_n120<1, 0>(o0, a + k * 128, HI128, b + k * 2, HI128, k == 0 ? acc : 1);
    wgmma_n120<1, 0>(o1, a + 512 + k * 128, HI128, b + k * 2, HI128, k == 0 ? acc : 1);
  }
}
__device__ __forceinline__ void mma_tn_split(float (&o0)[60], float (&o1)[60], uint32_t a, uint32_t b) {
#pragma unroll
  for (int k = 0; k < 4; k++) wgmma_n120<1, 0>(o0, a + k * 128, HI128, b + k * 2, HI128, 1);
  wg_commit();
#pragma unroll
  for (int k = 0; k < 4; k++) wgmma_n120<1, 0>(o1, a + 512 + k * 128, HI128, b + k * 2, HI128, 1);
  wg_commit();
}
__device__ __forceinline__ void mma_qk(float (&s)[60], uint32_t a, uint32_t q) {
#pragma unroll
  for (int k = 0; k < 8; k++)
    wgmma_n120<0, 0>(s, a + (k >> 2) * 512 + (k & 3) * 2, HI128, q + (k >> 2) * (XB >> 4) + (k & 3) * 2, HI128, k != 0);
}
template <int J0, int J1, bool FIRST = false>
__device__ __forceinline__ void exp_store(const float (&s)[60], float (&l)[30], uint32_t dst) {
#pragma unroll
  for (int j = J0; j < J1; j += 2) {
    uint32_t p[4];
#pragma unroll
    for (int jj = 0; jj < 2; jj++) {
      if (j + jj < 15) {
        const int c = j + jj;
        float e0 = ex2(s[4 * c]), e1 = ex2(s[4 * c + 1]), e2 = ex2(s[4 * c + 2]), e3 = ex2(s[4 * c + 3]);
        if (FIRST) { l[2 * c] = e0 + e2; l[2 * c + 1] = e1 + e3; }
        else { l[2 * c] += e0; l[2 * c + 1] += e1; l[2 * c] += e2; l[2 * c + 1] += e3; }
        p[2 * jj] = pack(e0, e1); p[2 * jj + 1] = pack(e2, e3);
      }
    }
    if (j + 1 < 15) stsm4t(dst + j * 1024, p[0], p[1], p[2], p[3]);
    else stsm2t(dst + j * 1024, p[0], p[1]);
  }
}

__device__ __forceinline__ int o_pos(int b, int wg, int r) {
  const int j = r >> 3, q = (r >> 1) & 3, c = r & 1, o = b & 1, base = (b >> 1) * 480;
  if (j < 12) return base + (o * 9 + wg * 3 + (j >> 2)) * 32 + q * 8 + (j & 3) * 2 + c;
  if (j < 14) return base + (6 + 2 * o) * 32 + wg * 16 + q * 4 + (j - 12) * 2 + c;
  return base + 7 * 32 + (o * 2 + wg) * 8 + q * 2 + c;
}
__device__ __forceinline__ int o_row(int p) {
  const int pair = p / 480, a = (p - pair * 480) >> 5, in = p & 31, c = p & 1;
  int tile, row;
  if (a == 7) { tile = in >> 3; row = 112 + (in & 7); }
  else if (a == 6 || a == 8) { tile = a - 6 + (in >> 4); row = (12 + ((in >> 1) & 1)) * 8 + ((in >> 2) & 3) * 2 + c; }
  else { const int f = a > 8 ? a - 3 : a; tile = f / 3; row = ((f - tile * 3) * 4 + ((in >> 1) & 3)) * 8 + (in >> 3) * 2 + c; }
  return pair * 480 + tile * 120 + row;
}
__device__ __forceinline__ uint32_t o_idx(int k, int p) {
  return ((k >> 3) * (NROWS / 32) + (p >> 5)) * 256 + (k & 7) * 32 + ((((p >> 3) & 3) ^ ((k & 7) >> 1)) << 3) + (p & 7);
}

__device__ __forceinline__ void slow_path(const Params& P, int b, int h, int wg, int w, int lane) {
  const int g = lane >> 2, q = lane & 3, row0 = wg * 120;
  const uint16_t* wq = reinterpret_cast<const uint16_t*>(P.wq) + h * DH + g;
  const __nv_bfloat16* kp = P.k + (size_t)(b * NH + h) * SK * DH;
  const uint16_t* vp = reinterpret_cast<const uint16_t*>(P.v) + (size_t)(b * NH + h) * SK * DH + g;
#pragma unroll 1
  for (int t = w; t < 8; t += 4) {
    const int r0 = 16 * t + g, r1 = r0 + 8;
    const __nv_bfloat16* x0 = P.x + (size_t)(b * SQ + row0 + r0) * DM + 2 * q;
    const __nv_bfloat16* x1 = P.x + (size_t)(b * SQ + row0 + min(r1, 119)) * DM + 2 * q;
    float o[16][4];
#pragma unroll
    for (int n = 0; n < 16; n++) o[n][0] = o[n][1] = o[n][2] = o[n][3] = 0.f;
#pragma unroll 1
    for (int k0 = 0; k0 < DM; k0 += 16) {
      uint32_t a[4] = {*(const uint32_t*)(x0 + k0), *(const uint32_t*)(x1 + k0), *(const uint32_t*)(x0 + k0 + 8), *(const uint32_t*)(x1 + k0 + 8)};
      const uint16_t* wr = wq + (size_t)(k0 + 2 * q) * HD;
#pragma unroll
      for (int n = 0; n < 16; n++) {
        if ((n & 3) == 0) __syncwarp();
        mma16816(o[n], a, wr[8 * n] | ((uint32_t)wr[8 * n + HD] << 16), wr[8 * n + 8 * HD] | ((uint32_t)wr[8 * n + 9 * HD] << 16));
      }
    }
    uint32_t qa[8][4];
#pragma unroll
    for (int k = 0; k < 8; k++) {
      qa[k][0] = pack(o[2 * k][0] * QSCALE, o[2 * k][1] * QSCALE);
      qa[k][1] = pack(o[2 * k][2] * QSCALE, o[2 * k][3] * QSCALE);
      qa[k][2] = pack(o[2 * k + 1][0] * QSCALE, o[2 * k + 1][1] * QSCALE);
      qa[k][3] = pack(o[2 * k + 1][2] * QSCALE, o[2 * k + 1][3] * QSCALE);
    }
#pragma unroll
    for (int n = 0; n < 16; n++) o[n][0] = o[n][1] = o[n][2] = o[n][3] = 0.f;
    float m0 = -INFINITY, m1 = -INFINITY, l0 = 0.f, l1 = 0.f;
#pragma unroll 1
    for (int key0 = 0; key0 < SK; key0 += 16) {
      float s[2][4];
#pragma unroll
      for (int nt = 0; nt < 2; nt++) {
        s[nt][0] = s[nt][1] = s[nt][2] = s[nt][3] = 0.f;
        const __nv_bfloat16* kr = kp + (size_t)(key0 + 8 * nt + g) * DH + 2 * q;
#pragma unroll
        for (int k = 0; k < 8; k++) mma16816(s[nt], qa[k], *(const uint32_t*)(kr + 16 * k), *(const uint32_t*)(kr + 16 * k + 8));
      }
      float n0 = fmaxf(fmaxf(s[0][0], s[0][1]), fmaxf(s[1][0], s[1][1])), n1 = fmaxf(fmaxf(s[0][2], s[0][3]), fmaxf(s[1][2], s[1][3]));
      n0 = fmaxf(n0, __shfl_xor_sync(~0u, n0, 1)); n1 = fmaxf(n1, __shfl_xor_sync(~0u, n1, 1));
      n0 = fmaxf(n0, __shfl_xor_sync(~0u, n0, 2)); n1 = fmaxf(n1, __shfl_xor_sync(~0u, n1, 2));
      n0 = fmaxf(n0, m0); n1 = fmaxf(n1, m1);
      const float z0 = n0 == -INFINITY ? 0.f : n0, z1 = n1 == -INFINITY ? 0.f : n1;
      const float c0 = ex2(m0 - z0), c1 = ex2(m1 - z1);
      m0 = n0; m1 = n1;
#pragma unroll
      for (int nt = 0; nt < 2; nt++) {
        s[nt][0] = ex2(s[nt][0] - z0); s[nt][1] = ex2(s[nt][1] - z0);
        s[nt][2] = ex2(s[nt][2] - z1); s[nt][3] = ex2(s[nt][3] - z1);
      }
      l0 = l0 * c0 + s[0][0] + s[0][1] + s[1][0] + s[1][1];
      l1 = l1 * c1 + s[0][2] + s[0][3] + s[1][2] + s[1][3];
      uint32_t pa[4] = {pack(s[0][0], s[0][1]), pack(s[0][2], s[0][3]), pack(s[1][0], s[1][1]), pack(s[1][2], s[1][3])};
      const uint16_t* vr = vp + (size_t)(key0 + 2 * q) * DH;
#pragma unroll
      for (int n = 0; n < 16; n++) {
        if ((n & 3) == 0) __syncwarp();
        o[n][0] *= c0; o[n][1] *= c0; o[n][2] *= c1; o[n][3] *= c1;
        mma16816(o[n], pa, vr[8 * n] | ((uint32_t)vr[8 * n + DH] << 16), vr[8 * n + 8 * DH] | ((uint32_t)vr[8 * n + 9 * DH] << 16));
      }
    }
    l0 += __shfl_xor_sync(~0u, l0, 1); l1 += __shfl_xor_sync(~0u, l1, 1);
    l0 += __shfl_xor_sync(~0u, l0, 2); l1 += __shfl_xor_sync(~0u, l1, 2);
    const float i0 = 1.f / l0, i1 = 1.f / l1;
    __nv_bfloat16* oc0 = P.o + o_idx(h * DH + 2 * q, o_pos(b, wg, r0));
    __nv_bfloat16* oc1 = P.o + o_idx(h * DH + 2 * q, o_pos(b, wg, min(r1, 119)));
#pragma unroll
    for (int n = 0; n < 16; n++) {
      oc0[8 * n * NROWS] = __float2bfloat16(o[n][0] * i0);
      oc0[8 * n * NROWS + 32] = __float2bfloat16(o[n][1] * i0);
      if (r1 < 120) {
        oc1[8 * n * NROWS] = __float2bfloat16(o[n][2] * i1);
        oc1[8 * n * NROWS + 32] = __float2bfloat16(o[n][3] * i1);
      }
    }
  }
}

__device__ __forceinline__ int bk(int ks) { return B_ORDER && ks < 48 ? 32 - (ks & 48) + (ks & 15) : ks; }
__device__ __forceinline__ uint32_t x_slot(uint32_t wg, uint32_t j) { return j < 2 ? (2 * wg + j) * XB : (2 * j + wg) * XB; }
__device__ __forceinline__ int row_block(int t) { return t >= 44 ? (t >> 2) - 11 : (t >> 2) + 4; }
__device__ __forceinline__ int unit_batch(int u) { return (u & 63) >> 2; }
__device__ __forceinline__ int unit_head(int u, int rank) { return (u >> 6) * 8 + (u & 3) * 2 + rank; }

template <int NCL>
__global__ void __cluster_dims__(2, 1, 1) __launch_bounds__(384, 1)
fused_attn_kernel(const __grid_constant__ CUtensorMap tm_x, const __grid_constant__ CUtensorMap tm_wq,
                  const __grid_constant__ CUtensorMap tm_k, const __grid_constant__ CUtensorMap tm_v,
                  const __grid_constant__ CUtensorMap tm_o, const __grid_constant__ CUtensorMap tm_wo,
                  const __grid_constant__ Params P) {
  extern __shared__ uint8_t smem_raw[];
  const uint32_t sb = ((uint32_t)__cvta_generic_to_shared(smem_raw) + 1023) & ~1023u;
  if (threadIdx.x == 0) TS(152);
  const int warp = __shfl_sync(~0u, threadIdx.x >> 5, 0);
  const int lane = threadIdx.x & 31;
  const int rank = blockIdx.x & 1, cl = blockIdx.x >> 1, ncl = NCL ? NCL : gridDim.x >> 1;

  const int nsingle = NCL == 66 ? 44 : NOTILES;
  auto role = [&]() {
    mbar_wait(sb + BAR_ROLE + 16, 0);
    int id;
    asm volatile("ld.shared.u32 %0, [%1];" : "=r"(id) : "r"(sb + BAR_ROLE + 8) : "memory");
    return id;
  };

  if (EARLY && threadIdx.x == 128) asm volatile("prefetch.tensormap [%0];" ::"l"(&tm_x) : "memory");
  if (threadIdx.x == 0) {
    if (EARLY) asm volatile("prefetch.tensormap [%0];" ::"l"(&tm_wq) : "memory");
    for (int i = 0; i < 6; i++) {
      mbar_init(sb + BAR_RFULL + 8 * i, 1); mbar_init(sb + BAR_REMPTY + 8 * i, 8);
      mbar_init(sb + BAR_BFULL + 8 * i, 1); mbar_init(sb + BAR_BEMPTY + 8 * i, 16);
    }
    for (int i = 0; i < 8; i++) mbar_init(sb + BAR_XFULL + 8 * i, 1);
    for (int i = 0; i < 4; i++) mbar_init(sb + BAR_XEMPTY + 8 * i, 8);
    for (int i = 0; i < 2; i++) { mbar_init(sb + BAR_STAGE + 8 * i, 4); mbar_init(sb + BAR_LSUM + 8 * i, 4); mbar_init(sb + BAR_INV + 8 * i, 1); }
    mbar_init(sb + BAR_ROLE, 1); mbar_init(sb + BAR_ROLE + 16, 1);
    asm volatile("fence.mbarrier_init.release.cluster;" ::: "memory");
  }
  __syncwarp();
  asm volatile("barrier.cluster.arrive.relaxed.aligned;" ::: "memory");
  auto first_w = [&](int s) {
    mbar_expect(sb + BAR_RFULL + 8 * s, RING_BYTES);
    tma3d(sb + s * RING_BYTES, &tm_wq, 0, s * 64, 2 * unit_head(cl, rank), sb + BAR_RFULL + 8 * s);
  };
  if (EARLY && threadIdx.x == 0) first_w(0);
  __syncwarp();
  asm volatile("barrier.cluster.wait.aligned;" ::: "memory");
  if (EARLY && threadIdx.x == 128) {
#pragma unroll 1
    for (int s = 0; s < EARLY_X; s++) {
      const uint32_t fb = sb + BAR_XFULL + 32 * rank + 8 * s;
      mbar_expect(fb, XB);
      mbar_expect_cl(mapa(fb, rank ^ 1), XB);
      tma2d_mc(sb + OFF_Q + x_slot(rank, s), &tm_x, s * 64, unit_batch(cl) * SQ + rank * 120, fb);
      if (s + 1 < EARLY_W) first_w(s + 1);
    }
  }
  __syncwarp();
  if (threadIdx.x == 0) TS(153);

  if (warp >= 8) {
    asm volatile("setmaxnreg.dec.sync.aligned.u32 24;");
    if (warp == 8) {
      uint64_t pol;
      asm volatile("createpolicy.fractional.L2::evict_first.b64 %0, 1.0;" : "=l"(pol));
      Ring r;
      if (EARLY) r.slot = EARLY_W;
      auto load = [&](const CUtensorMap* m, int c1, int c2, bool ef) {
        if (SLP & 8) mbar_sleep(sb + BAR_REMPTY + 8 * r.slot, r.phase ^ 1); else mbar_wait(sb + BAR_REMPTY + 8 * r.slot, r.phase ^ 1);
        if (lane == 0) {
          mbar_expect(sb + BAR_RFULL + 8 * r.slot, RING_BYTES);
          if (ef) tma3d_hint(sb + r.slot * RING_BYTES, m, 0, c1, c2, sb + BAR_RFULL + 8 * r.slot, pol);
          else tma3d(sb + r.slot * RING_BYTES, m, 0, c1, c2, sb + BAR_RFULL + 8 * r.slot);
        }
        r.next();
      };
      const int rot = ROT * (blockIdx.x * 5 + (blockIdx.x >> 4));
      auto pause = [&](int u0) {
        if (PAUSE_NS && NCL == 66 && u0 == PAUSE_AT * 66) {
          const int id = role();
          if (id >= 44 && id < 58) {
            unsigned t0, t1;
            asm volatile("mov.u32 %0, %globaltimer_lo;" : "=r"(t0));
            do { __nanosleep(200); asm volatile("mov.u32 %0, %globaltimer_lo;" : "=r"(t1)); } while (t1 - t0 < PAUSE_NS + (id - 44) * PAUSE_SPREAD);
          }
        }
      };
      for (int u0 = 0;; u0 += ncl) {
        const int u = __shfl_sync(~0u, (u0 >= 3 * ncl ? role() : cl) + u0, 0);
        if (u >= NUNITS) break;
        if (PAUSE_J < 0) pause(u0);
        const int h = unit_head(u, rank);
        const int krow = (unit_batch(u) * NH + h) * SK;
#pragma unroll 1
        for (int s = EARLY && u0 == 0 ? EARLY_W : 0; s < 10; s++) {
          if (u0 == 0 && s == 0 && lane == 0) TS(154);
          load(&tm_wq, s * 64, 2 * h, false);
          if (u0 == 0 && s == 0 && lane == 0) TS(155);
          const int sp = u0 == 0 ? s - PF_HOLD : s;
          if (sp >= 0 && sp < PF_N && lane == 0) l2_prefetch(P.v + (size_t)(krow + ((PF_J0 + sp * PF_STEP + rot) & 15) * 64) * DH, 16384);
        }
#pragma unroll 1
        for (int j = 0; j <= 16; j++) {
          if (j == PAUSE_J) pause(u0);
          if (j < 16) load(&tm_k, krow + ((j + rot) & 15) * 64, 0, true);
          if (j == 1 + DPRO) load(&tm_v, krow + (rot & 15) * 64, 0, true);
          if (j > 1) load(&tm_v, krow + ((j - 1 + rot) & 15) * 64, 0, true);
        }
      }
      const int id = __shfl_sync(~0u, role(), 0);
      const bool dbl = NCL == 66 && id >= 58;
      for (int t = dbl ? 2 * id - 72 : id; t < (dbl ? NOTILES : nsingle); t += ncl) {
        const int row0 = row_block(t) * 256 + rank * 128;
        const int b0 = (row0 & ~31) / SQ, b1 = (row0 + 127) / SQ;
#pragma unroll 1
        for (int ks = 0; ks < 64; ks++) {
          if (dbl ? (ks & 15) == 0 : ks == 0 || ks == 48) {
            const unsigned* c = &g_cnt[((lane & 1 ? b1 : b0) * 4 + (ks || dbl ? ks >> 4 : min(lane >> 1, 2))) * 8];
            unsigned v, n = 0;
            do {
              asm volatile("ld.acquire.gpu.global.u32 %0, [%1];" : "=r"(v) : "l"(c) : "memory");
              if (++n > (1u << 26)) __trap();
            } while (v < 16);
            __syncwarp();
            asm volatile("fence.proxy.async.global;" ::: "memory");
          }
          mbar_wait(sb + BAR_REMPTY + 8 * r.slot, r.phase ^ 1);
          if (lane == 0) {
            mbar_expect(sb + BAR_RFULL + 8 * r.slot, RING_BYTES);
            asm volatile("cp.async.bulk.tensor.4d.shared::cluster.global.mbarrier::complete_tx::bytes.L2::cache_hint [%0], [%1, {%3, %3, %4, %5}], [%2], %6;"
                         ::"r"(sb + r.slot * RING_BYTES), "l"(&tm_o), "r"(sb + BAR_RFULL + 8 * r.slot), "r"(0), "r"((dbl ? ks : bk(ks)) * 8), "r"(row0 >> 6), "l"(pol) : "memory");
          }
          r.next();
        }
      }
      if (lane == 0 && atomicAdd(&g_cnt[64 * 8], 1) == gridDim.x - 1) {
        for (int i = 0; i < 67; i++) g_cnt[i * 8] = 0;
      }
    } else if (warp == 9) {
      if (lane == 0) {
        uint32_t it = 0;
        for (;; it++) {
          const int u = (it >= 3 ? role() : cl) + it * ncl;
          if (u >= NUNITS) break;
          const int row = unit_batch(u) * SQ + rank * 120;
#pragma unroll 1
          for (int s = EARLY && it == 0 ? EARLY_X : 0; s < 10; s++) {
            const uint32_t j = s & 3, par = ((s >> 2) + (j < 2 ? it : 0)) & 1;
            if ((SLP & 4) && s == 0) mbar_sleep(sb + BAR_XEMPTY, par ^ 1);
            mbar_wait(sb + BAR_XEMPTY + 8 * j, par ^ 1);
            const uint32_t fb = sb + BAR_XFULL + 32 * rank + 8 * j;
            mbar_expect(fb, XB);
            mbar_expect_cl(mapa(fb, rank ^ 1), XB);
            tma2d_mc(sb + OFF_Q + x_slot(rank, j), &tm_x, s * 64, row, fb);
          }
        }
        const int id = role();
        const bool dbl = NCL == 66 && id >= 58;
        uint32_t slot = rank, phase = 0;
        if (WO_PF0 && dbl)
          asm volatile("cp.async.bulk.prefetch.tensor.3d.L2.global [%0, {%1, %2, %3}];" ::"l"(&tm_wo), "r"(0), "r"((2 + ((id >> 1) & 3)) * 64), "r"(((2 * id - 72 + rank) & 3) * 5) : "memory");
        if ((SLP & 4) && (dbl || id < nsingle)) mbar_sleep(sb + BAR_BEMPTY + 8 * rank, 0);
        for (int t = dbl ? 2 * id - 72 + rank : id; t < (dbl ? NOTILES : nsingle); t += ncl) {
#pragma unroll 1
          for (int ks = dbl ? 0 : rank; ks < 64; ks += dbl ? 1 : 2) {
            mbar_wait(sb + BAR_BEMPTY + 8 * slot, phase);
            const uint32_t fb = sb + BAR_BFULL + 8 * slot;
            mbar_expect(fb, BB);
            mbar_expect_cl(mapa(fb, rank ^ 1), BB);
            tma3d_mc(sb + OFF_Q + slot * BB, &tm_wo, 0, (dbl ? ks : bk(ks)) * 64, (t & 3) * 5, fb);
            if (WO_PF && dbl && ks + WO_PF < 64 && (ks & 3) == ((id >> 1) & 3))
              asm volatile("cp.async.bulk.prefetch.tensor.3d.L2.global [%0, {%1, %2, %3}];" ::"l"(&tm_wo), "r"(0), "r"((ks + WO_PF) * 64), "r"((t & 3) * 5) : "memory");
            slot += 2;
            if (slot >= 6) { slot -= 6; phase ^= 1; }
          }
        }
      }
    } else {
      const int wg = warp - 10;
      {
        mbar_wait(sb + BAR_RFULL, 0);
        const __nv_bfloat16* xs = P.x + (size_t)(unit_batch(cl) * SQ + ((cl & 3) * 2 + rank) * 30 + min(lane, 29)) * DM + 256 + wg * 64;
#pragma unroll
        for (int i = 0; i < 3; i++) asm volatile("prefetch.global.L2 [%0];" ::"l"(xs + i * 128));
        if (lane < 16) asm volatile("prefetch.global.L2 [%0];" ::"l"(P.wq + (size_t)(384 + unit_batch(cl) * 16 + lane) * HD + unit_head(cl, rank) * DH + wg * 64));
      }
      auto take_role = [&]() {
          if (wg == 0 && rank == 0 && lane == 0) {
            int id = cl;
            if (NCL == 66) {
              uint32_t smid;
              asm("mov.u32 %0, %smid;" : "=r"(smid));
              id = smid >= SMID_TOP ? 65 - atomicAdd(&g_cnt[65 * 8], 1) : atomicAdd(&g_cnt[66 * 8], 1);
            }
    #pragma unroll
            for (int c = 0; c < 2; c++) {
              const uint32_t a = mapa(sb + BAR_ROLE, c);
              asm volatile("st.shared::cluster.u32 [%0 + 8], %1;\nmbarrier.arrive.release.cluster.shared::cluster.b64 _, [%0];" ::"r"(a), "r"(id) : "memory");
            }
          }
          if (wg == 0 && lane == 0) {
            mbar_wait_cl(sb + BAR_ROLE, 0);
            mbar_arrive(sb + BAR_ROLE + 16);
          }
      };
      if (ROLE_AT < 0) { take_role(); __syncwarp(); }
      for (uint32_t it = 0;; it++) {
        const int u = __shfl_sync(~0u, (it >= 3 ? role() : cl) + it * ncl, 0);
        if (u >= NUNITS) break;
        if (SLP & 1) mbar_sleep(sb + BAR_LSUM + 8 * wg, it & 1); else mbar_wait(sb + BAR_LSUM + 8 * wg, it & 1);
        float l4[4], v[4];
        const uint32_t a = sb + OFF_L2 + wg * 2048 + lane * 16;
        asm volatile("ld.shared.v4.f32 {%0, %1, %2, %3}, [%4];" : "=f"(l4[0]), "=f"(l4[1]), "=f"(l4[2]), "=f"(l4[3]) : "r"(a) : "memory");
#pragma unroll
        for (int g = 1; g < 4; g++) {
          asm volatile("ld.shared.v4.f32 {%0, %1, %2, %3}, [%4];" : "=f"(v[0]), "=f"(v[1]), "=f"(v[2]), "=f"(v[3]) : "r"(a + g * 512) : "memory");
#pragma unroll
          for (int c = 0; c < 4; c++) l4[c] += v[c];
        }
#pragma unroll
        for (int c = 0; c < 4; c++) {
          float inv;
          asm("rcp.approx.ftz.f32 %0, %1;" : "=f"(inv) : "f"(l4[c]));
          l4[c] = l4[c] >= L_MIN && l4[c] <= L_MAX ? inv : __uint_as_float(0x7FFFFFFFu);
        }
        const uint32_t h0 = pack(l4[0], l4[1]), h1 = pack(l4[2], l4[3]);
        const uint32_t e0 = pack(l4[0] - __uint_as_float(h0 << 16), l4[1] - __uint_as_float(h0 & 0xFFFF0000u));
        const uint32_t e1 = pack(l4[2] - __uint_as_float(h1 << 16), l4[3] - __uint_as_float(h1 & 0xFFFF0000u));
        asm volatile("st.shared.v4.u32 [%0], {%1, %2, %3, %4};" ::"r"(sb + OFF_INV + wg * 640 + (lane & 3) * 144 + (lane >> 2) * 16), "r"(h0), "r"(e0), "r"(h1), "r"(e1) : "memory");
        __syncwarp();
        if (lane == 0) {
          mbar_arrive(sb + BAR_INV + 8 * wg);
          if ((int)it == ROLE_AT) {
            take_role();
          }
          if (SLP & 2) mbar_sleep(sb + BAR_STAGE + 8 * wg, it & 1); else mbar_wait(sb + BAR_STAGE + 8 * wg, it & 1);
          __threadfence();
          asm volatile("red.relaxed.gpu.global.add.u32 [%0], 1;" ::"l"(&g_cnt[(unit_batch(u) * 4 + (u >> 6)) * 8]) : "memory");
        }
        __syncwarp();
      }
    }
  } else {
    asm volatile("setmaxnreg.inc.sync.aligned.u32 240;");
    const int wg = warp >> 2, w = warp & 3;
    const uint32_t qreg = sb + OFF_Q + wg * 2 * XB, preg = sb + OFF_P + (2 + wg) * XB;
    const uint32_t st_off = ((lane >> 4) * 8 + (lane & 7)) * 128 + (((2 * w + ((lane >> 3) & 1)) ^ (lane & 7)) << 4);
    const uint32_t xempty = mapa(sb + BAR_XEMPTY, wg);
    Ring r;
    uint32_t it = 0;
    const uint32_t qd = (qreg & 0x3FFFF) >> 4, pd = (preg & 0x3FFFF) >> 4;
    auto ring_addr = [&]() { return ((sb & 0x3FFFF) + r.slot * RING_BYTES) >> 4; };
    auto ring_wait = [&]() { mbar_wait(sb + BAR_RFULL + 8 * r.slot, r.phase); };
    auto release = [&](uint32_t slot) { warp_arrive(sb + BAR_REMPTY + 8 * slot); };
    auto turn_wait = [&]() {
      if (wg == 0) asm volatile("bar.sync 3, 256;" ::: "memory");
      else asm volatile("bar.sync 4, 256;" ::: "memory");
    };
    auto turn_pass = [&]() {
      if (wg == 0) asm volatile("bar.arrive 4, 256;" ::: "memory");
      else asm volatile("bar.arrive 3, 256;" ::: "memory");
    };

    uint32_t chk = 0;
    auto load_inv = [&](uint32_t (&iv)[30], uint32_t parity) {
      const int lane = fresh_tid() & 31;
      mbar_wait(sb + BAR_INV + 8 * wg, parity);
      chk = 0;
#pragma unroll
      for (int j = 0; j < 7; j++)
        asm volatile("ld.shared.v4.u32 {%0, %1, %2, %3}, [%4];" : "=r"(iv[4 * j]), "=r"(iv[4 * j + 1]), "=r"(iv[4 * j + 2]), "=r"(iv[4 * j + 3])
                     : "r"(sb + OFF_INV + wg * 640 + (lane & 3) * 144 + j * 16) : "memory");
      asm volatile("ld.shared.v2.u32 {%0, %1}, [%2];" : "=r"(iv[28]), "=r"(iv[29]) : "r"(sb + OFF_INV + wg * 640 + (lane & 3) * 144 + 112) : "memory");
    };
    auto norm = [&](uint32_t (&n)[8], const uint32_t (&po)[60], const uint32_t (&iv)[30], auto part) {
      constexpr int k = decltype(part)::value >> 1, j0 = (decltype(part)::value & 1) * 8;
#pragma unroll
      for (int j = 0; j < 8; j++)
        n[j] = j0 + j < 15 ? hfma2(po[15 * k + (j0 + j) % 15], iv[2 * ((j0 + j) % 15)], hfma2(po[15 * k + (j0 + j) % 15], iv[2 * ((j0 + j) % 15) + 1], 0x80008000u)) : 0x3F803F80u;
#pragma unroll
      for (int j = 0; j < 8; j += 2) chk = hfma2(n[j], n[j + 1], chk);
    };
    int od1, od2;
    auto store = [&](const uint32_t (&n)[8], const char* optr, auto part) {
      constexpr int k = decltype(part)::value >> 1, off = (8 * (k & 1) + 64 * (k >> 1)) * NROWS * 2;
      if ((decltype(part)::value & 1) == 0)
        asm volatile(
            "{\n.reg .pred p;\nsetp.ne.u64 p, %8, 0;\n"
            "@p st.global.v4.u32 [%8 + %9], {%0, %1, %2, %3};\n@p st.global.v4.u32 [%8 + %9 + 512], {%4, %5, %6, %7};\n}\n"
            ::"r"(n[0]), "r"(n[1]), "r"(n[2]), "r"(n[3]), "r"(n[4]), "r"(n[5]), "r"(n[6]), "r"(n[7]), "l"(optr), "n"(off) : "memory");
      else
        asm volatile(
            "{\n.reg .pred p;\n.reg .b64 b, c;\nsetp.ne.u64 p, %7, 0;\nmad.wide.s32 b, %9, 1, %7;\nmad.wide.s32 c, %10, 1, %7;\n"
            "@p st.global.v4.u32 [%7 + %8 + 1024], {%0, %1, %2, %3};\n@p st.global.v2.u32 [b + %8], {%4, %5};\n@p st.global.u32 [c + %8], %6;\n}\n"
            ::"r"(n[0]), "r"(n[1]), "r"(n[2]), "r"(n[3]), "r"(n[4]), "r"(n[5]), "r"(n[6]), "l"(optr), "n"(off), "r"(od1), "r"(od2) : "memory");
    };
    auto put = [&](const uint32_t (&po)[60], const uint32_t (&iv)[30], const char* optr, auto part) {
      uint32_t n[8];
      norm(n, po, iv, part);
      store(n, optr, part);
    };
    auto out_ptr = [&](int u) {
      const int lane = fresh_tid() & 31;
      const int k = unit_head(u, rank) * DH + 16 * w + (lane >> 2), b = unit_batch(u), q = lane & 3;
      const uint32_t i0 = o_idx(k, o_pos(b, wg, 2 * q));
      od1 = 2 * (int)(o_idx(k, o_pos(b, wg, 96 + 2 * q)) - i0);
      od2 = 2 * (int)(o_idx(k, o_pos(b, wg, 112 + 2 * q)) - i0);
      return reinterpret_cast<const char*>(P.o + i0);
    };
    auto unsafe = [&](bool valid) {
      const bool b = valid && ((chk & 0x7F80u) == 0x7F80u || (chk & 0x7F800000u) == 0x7F800000u);
      return __any_sync(~0u, bar_red_or(wg, b));
    };
    auto publish = [&]() { __syncwarp(); warp_arrive(sb + BAR_STAGE + 8 * wg); };

    uint32_t po[60];
#pragma unroll
    for (int i = 0; i < 60; i++) po[i] = 0;
    int id = 0;
    bool more;
    do {
      float o0[60], o1[60];
      uint32_t prev = 0;
      auto qstep = [&](int s, int acc) {
        const uint32_t j = s & 3, par = ((s >> 2) + (j < 2 ? it : 0)) & 1;
        TR(it * 160 + 3 * s);
        ring_wait();
        TR(it * 160 + 3 * s + 1);
        mbar_wait(sb + BAR_XFULL + 32 * wg + 8 * j, par);
        TR(it * 160 + 3 * s + 2);
        if (s >= ALT_FROM) turn_wait();
        TI(s);
        wg_fence();
        mma_tn(o0, o1, ring_addr(), ((sb & 0x3FFFF) + OFF_Q + x_slot(wg, j)) >> 4, acc);
        wg_commit();
        if ((s >= ALT_FROM && !(MERGE7 && s == 7)) || (s == ALT_FROM - 1 && wg == 1)) turn_pass();
        if (s > 0 && s <= EREL_FROM) {
          wg_wait<1>();
          release(prev);
          if (s <= 6) warp_arrive_cl(xempty + 8 * ((s - 1) & 3));
        }
        prev = r.slot;
        r.next();
      };
      auto qdone = [&](int s) {
        if (s >= EREL_FROM) {
          wg_wait<0>();
          release(prev);
          if (s <= 5) warp_arrive_cl(xempty + 8 * (s & 3));
        }
      };
      qstep(0, 0);
      qstep(1, 1);
      const int up = (it > 3 ? id : cl) + ((int)it - 1) * ncl;
      const char* optr = out_ptr(up);
      if (it == 0) optr = nullptr;
      uint32_t n7[8];
      {
        uint32_t iv[30];
        load_inv(iv, (it + 1) & 1); put(po, iv, optr, IC<0>());
        auto extra = [&](int s) { if (LATE_AT == 10 + s) put(po, iv, optr, IC<7>()); };
        qstep(2, 1); put(po, iv, optr, IC<1>()); extra(2); qdone(2);
        qstep(3, 1); put(po, iv, optr, IC<2>()); extra(3); qdone(3);
        qstep(4, 1); put(po, iv, optr, IC<3>()); extra(4); qdone(4);
        qstep(5, 1); put(po, iv, optr, IC<4>()); extra(5); qdone(5);
        qstep(6, 1); put(po, iv, optr, IC<5>()); extra(6);
        if (MERGE7) { put(po, iv, optr, IC<6>()); if (LATE_AT < 10) norm(n7, po, iv, IC<7>()); }
        qdone(6);
        qstep(7, 1);
        if (!MERGE7) { put(po, iv, optr, IC<6>()); if (LATE_AT < 10) norm(n7, po, iv, IC<7>()); qdone(7); }
        if (LATE_AT == 3 || (LATE_AT == 5 && wg == 1)) store(n7, optr, IC<7>());
      }
      TR(it * 160 + 24);
      const uint32_t a8 = ring_addr(), slot8 = r.slot;
      ring_wait();
      r.next();
      TR(it * 160 + 25);
      mbar_wait(sb + BAR_XFULL + 32 * wg, it & 1);
      TR(it * 160 + 26);
      auto wait9 = [&]() {
        TR(it * 160 + 27);
        ring_wait();
        TR(it * 160 + 28);
        mbar_wait(sb + BAR_XFULL + 32 * wg + 8, it & 1);
        TR(it * 160 + 29);
      };
      if (PRE9 == 1 || (PRE9 == 2 && wg == 1)) wait9();
      if (PRE9 == 3) ring_wait();
      if (!MERGE7) turn_wait();
      TI(8);
      wg_fence();
      mma_tn(o0, o1, a8, qd, 1);
      wg_commit();
      if (PRE9 == 0 || (PRE9 == 2 && wg == 0)) wait9();
      if (PRE9 == 3) mbar_wait(sb + BAR_XFULL + 32 * wg + 8, it & 1);
      TI(9);
      if (PRE9 != 1) wg_fence();
      mma_tn_split(o0, o1, ring_addr(), qd + (XB >> 4));
      if (PASS9 == 0 || (PASS9 == 3 && wg == 0) || (PASS9 == 4 && wg == 1)) turn_pass();
      wg_wait<2>();
      if (PASS9 == 1) turn_pass();
      if (EREL_FROM > 7 || MERGE7) release(prev);
      release(slot8);
      if (LATE_AT == 4 || (LATE_AT == 5 && wg == 0)) store(n7, optr, IC<7>());
      auto put_q = [&](const float (&o)[60], uint32_t dst) {
#pragma unroll
        for (int j = 0; j < 14; j += 2)
          stsm4t(dst + j * 1024, pack(o[4 * j] * QSCALE, o[4 * j + 1] * QSCALE), pack(o[4 * j + 2] * QSCALE, o[4 * j + 3] * QSCALE),
                 pack(o[4 * j + 4] * QSCALE, o[4 * j + 5] * QSCALE), pack(o[4 * j + 6] * QSCALE, o[4 * j + 7] * QSCALE));
        stsm2t(dst + 14 * 1024, pack(o[56] * QSCALE, o[57] * QSCALE), pack(o[58] * QSCALE, o[59] * QSCALE));
      };
      wg_wait<1>();
      if (PASS9 == 2 || (PASS9 == 3 && wg == 1) || (PASS9 == 4 && wg == 0)) turn_pass();
      reg_fence(o0);
      bool redo;
      if (EARLY_VOTE) redo = unsafe(it > 0); else bar_sync(wg);
      put_q(o0, qreg + st_off);
      wg_wait<0>();
      reg_fence(o1);
      release(r.slot);
      r.next();
      TR(it * 160 + 30);
      bar_sync(wg);
      put_q(o1, qreg + XB + st_off);
      fence_async_smem();
      if (!EARLY_VOTE) redo = unsafe(it > 0);
      if (redo) {
        slow_path(P, unit_batch(up), unit_head(up, rank), wg, w, fresh_tid() & 31);
        optr = nullptr;
        if (!DPRO) {
#pragma unroll
          for (int i = 0; i < 60; i++) o0[i] = o1[i] = 0.f;
        }
      }
      TR(it * 160 + 32); TG(it * 160 + 142);

      float sc[60], l[30];
      uint32_t slot0 = r.slot;
      ring_wait();
      TR(it * 160 + 33);
      turn_wait();
      TI(10);
      wg_fence();
      mma_qk(sc, ring_addr(), qd);
      wg_commit();
      r.next();
      uint32_t slot1 = r.slot;
      ring_wait();
      TI(11);
      wg_fence();
      mma_qk(o1, ring_addr(), qd);
      wg_commit();
      r.next();
      turn_pass();
      if (LATE_AT == 0) store(n7, optr, IC<7>());
      wg_wait<1>();
      reg_fence(sc);
      TR(it * 160 + 35);
      release(slot0);
      exp_store<0, 15, true>(sc, l, preg + st_off);
      TR(it * 160 + 38); TG(it * 160 + 43);
      slot0 = r.slot;
      if (K2_AT > 0) {
        wg_wait<0>();
        reg_fence(o1);
        release(slot1);
        exp_store<0, K2_AT>(o1, l, preg - 2 * XB + st_off);
      }
      ring_wait();
      TI(12);
      wg_fence();
      mma_qk(sc, ring_addr(), qd);
      wg_commit();
      r.next();
      if (K2_AT == 0) {
        wg_wait<1>();
        reg_fence(o1);
        release(slot1);
      }
      TR(it * 160 + 41);
      exp_store<K2_AT, 15>(o1, l, preg - 2 * XB + st_off);
      fence_async_smem();
      TR(it * 160 + 44);
      slot1 = r.slot;
      ring_wait();
      turn_wait();
      TI(13);
      wg_fence();
      mma_tn(o0, o1, ring_addr(), pd, 0);
      wg_commit();
      r.next();
      ring_wait();
      wg_fence();
      mma_tn(o0, o1, ring_addr(), pd - (2 * XB >> 4), 1);
      wg_commit();
      turn_pass();
      if (LATE_AT == 1) store(n7, optr, IC<7>());
      if (it > 0) publish();
      if (it >= 2) id = __shfl_sync(~0u, role(), 0);
      wg_wait<1>();
      reg_fence(sc);
      release(slot0);
      release(slot1);
      bar_sync(wg);
      TR(it * 160 + 47);
      exp_store<0, VREL>(sc, l, preg + st_off);
      wg_wait<0>();
      reg_fence(o0); reg_fence(o1);
      release(r.slot);
      r.next();
      exp_store<VREL, 15>(sc, l, preg + st_off);
      fence_async_smem();
      more = id + ((int)it + 1) * ncl < NUNITS;
      const bool gemm = id < nsingle || (NCL == 66 && id >= 58);
#pragma unroll 1
      for (int s = DPRO ? 3 : 1; s < 16; s++) {
        const uint32_t kslot = r.slot;
        TR(it * 160 + 32 + 6 * s); TG(it * 160 + 37 + 6 * s);
        if (s == 8) TRL(it * 160 + 139);
        ring_wait();
        TR(it * 160 + 33 + 6 * s);
        turn_wait();
        TI(11 + s);
        wg_fence();
        mma_qk(sc, ring_addr(), qd);
        wg_commit();
        r.next();
        TR(it * 160 + 36 + 6 * s);
        ring_wait();
        TR(it * 160 + 34 + 6 * s);
        wg_fence();
        mma_tn(o0, o1, ring_addr(), pd - ((s - 1) & 1) * (2 * XB >> 4), DPRO || s != 1);
        wg_commit();
        if (wg == 0 || s < 15) turn_pass();
        wg_wait<1>();
        reg_fence(sc);
        TR(it * 160 + 35 + 6 * s);
        release(kslot);
        if (s == 15) {
          if (more) { warp_arrive_cl(xempty); warp_arrive_cl(xempty + 8); }
          else if (gemm) for (int i = 0; i < 3; i++) warp_arrive_cl(mapa(sb + BAR_BEMPTY + 8 * i, i & 1));
        }
        exp_store<0, VREL>(sc, l, preg - (s & 1) * 2 * XB + st_off);
        wg_wait<0>();
        reg_fence(o0); reg_fence(o1);
        release(r.slot);
        r.next();
        exp_store<VREL, 15>(sc, l, preg - (s & 1) * 2 * XB + st_off);
        fence_async_smem();
      }
      const uint32_t tid = fresh_tid();
      bar_sync(wg);
      TR(it * 160 + 128);
      ring_wait();
      TI(27);
      wg_fence();
      mma_tn_split(o0, o1, ring_addr(), pd - (2 * XB >> 4));
      {
        float a[16], b[8], c[4];
        const bool b4 = tid & 16, b3 = tid & 8, b2 = tid & 4;
#pragma unroll
        for (int i = 0; i < 16; i++) {
          const float hi = i < 14 ? l[(16 + i) % 30] : 1.f;
          a[i] = (b4 ? hi : l[i]) + __shfl_xor_sync(~0u, b4 ? l[i] : hi, 16);
        }
#pragma unroll
        for (int i = 0; i < 8; i++) b[i] = (b3 ? a[8 + i] : a[i]) + __shfl_xor_sync(~0u, b3 ? a[i] : a[8 + i], 8);
#pragma unroll
        for (int i = 0; i < 4; i++) c[i] = (b2 ? b[4 + i] : b[i]) + __shfl_xor_sync(~0u, b2 ? b[i] : b[4 + i], 4);
        asm volatile("st.shared.v4.f32 [%0], {%1, %2, %3, %4};" ::"r"(sb + OFF_L2 + tid * 16), "f"(c[0]), "f"(c[1]),
                     "f"(c[2]), "f"(c[3]) : "memory");
        __syncwarp();
        warp_arrive(sb + BAR_LSUM + 8 * wg);
      }
      TR(it * 160 + 132);
      TR(it * 160 + 133);
      wg_wait<1>();
      reg_fence(o0);
      TR(it * 160 + 134);
#pragma unroll
      for (int j = 0; j < 15; j++) { po[j] = pack(o0[4 * j], o0[4 * j + 1]); po[15 + j] = pack(o0[4 * j + 2], o0[4 * j + 3]); }
      wg_wait<0>();
      reg_fence(o1);
      release(r.slot);
      r.next();
      if (more) { warp_arrive_cl(xempty + 16); warp_arrive_cl(xempty + 24); }
      else if (gemm) for (int i = 3; i < 6; i++) warp_arrive_cl(mapa(sb + BAR_BEMPTY + 8 * i, i & 1));
      TR(it * 160 + 130);
#pragma unroll
      for (int j = 0; j < 15; j++) { po[30 + j] = pack(o1[4 * j], o1[4 * j + 1]); po[45 + j] = pack(o1[4 * j + 2], o1[4 * j + 3]); }
      TR(it * 160 + 131); TG(it * 160 + 143);
      it++;
    } while (more);
    const bool gemm = id < nsingle || (NCL == 66 && id >= 58);
    const int u = (it > 3 ? id : cl) + ((int)it - 1) * ncl;
    uint32_t pb[60];
#pragma unroll
    for (int i = 0; i < 60; i++) pb[i] = NCL != 66 ? po[i] ^ (gridDim.y - 1) : po[i];

    uint32_t bslot = 0, bphase = 0;
    auto out_row = [&](int lane) {
      const int row = lane & 15;
      return sb + wg * 8192 + (row < 12 ? w * RING_BYTES + row * 656 : (4 + (w >> 1)) * RING_BYTES + ((w & 1) * 4 + row - 12) * 656);
    };
    auto out_stage = [&](const float (&acc)[80], uint32_t col_off) {
      const int lane = fresh_tid() & 31;
      const uint32_t sa = out_row(lane) + col_off + (lane >> 4) * 16;
#pragma unroll
      for (int j = 0; j < 20; j += 2)
        asm volatile("stmatrix.sync.aligned.m8n8.x4.shared.b16 [%0], {%1,%2,%3,%4};" ::"r"(sa + j * 16), "r"(pack(acc[4 * j], acc[4 * j + 1])),
                     "r"(pack(acc[4 * j + 2], acc[4 * j + 3])), "r"(pack(acc[4 * j + 4], acc[4 * j + 5])), "r"(pack(acc[4 * j + 6], acc[4 * j + 7])) : "memory");
    };
    auto out_store = [&](int t, uint32_t bytes) {
      const int lane = fresh_tid() & 31;
      if (EPI_MIX && wg == 1) {
        __syncwarp();
#pragma unroll 1
        for (int h = 0; h < 2; h++) {
          const int row = h * 8 + (lane >> 2);
          const uint32_t src = out_row(row) + (lane & 3) * 16;
          char* dst = reinterpret_cast<char*>(P.out + (size_t)o_row(row_block(t) * 256 + rank * 128 + 64 + w * 16 + row) * DM + (t & 3) * 160) + (lane & 3) * 16;
#pragma unroll 1
          for (uint32_t c = 0; c < bytes; c += 320) {
            uint4 v[5];
#pragma unroll
            for (int i = 0; i < 5; i++)
              asm volatile("ld.shared.v4.u32 {%0, %1, %2, %3}, [%4];" : "=r"(v[i].x), "=r"(v[i].y), "=r"(v[i].z), "=r"(v[i].w) : "r"(src + c + i * 64) : "memory");
#pragma unroll
            for (int i = 0; i < 5; i++) *reinterpret_cast<uint4*>(dst + c + i * 64) = v[i];
          }
        }
        return;
      }
      fence_async_smem();
      __syncwarp();
      if (lane < 16) {
        __nv_bfloat16* dst = P.out + (size_t)o_row(row_block(t) * 256 + rank * 128 + wg * 64 + w * 16 + lane) * DM + (t & 3) * 160;
        asm volatile("cp.async.bulk.global.shared::cta.bulk_group [%0], [%1], %2;" ::"l"(dst), "r"(out_row(lane)), "r"(bytes) : "memory");
        asm volatile("cp.async.bulk.commit_group;" ::: "memory");
        asm volatile("cp.async.bulk.wait_group.read 0;" ::: "memory");
      }
    };
    for (int t = id; t == id || (NCL != 66 && t < nsingle); t += ncl) {
      float acc[80];
      uint32_t prev = 0, bprev = 0;
      const bool tile = t < nsingle;
      const bool last = NCL == 66 || t + ncl >= nsingle;
      auto bstep = [&](int ks, int accf) {
        if (!(ks & 3)) TR(640 + ks / 2); if ((ks & 7) == 0) TG(144 + (ks >> 3));
        ring_wait();
        mbar_wait(sb + BAR_BFULL + 8 * bslot, bphase);
        if (!(ks & 3)) TR(641 + ks / 2);
        wg_fence();
        const uint32_t a = ring_addr() + wg * 512, bd = (((sb & 0x3FFFF) + OFF_Q + bslot * BB) >> 4) | ((4096u >> 4) << 16);
#pragma unroll
        for (int k = 0; k < 4; k++) wgmma_n160<1, 1>(acc, a + LBO64A + k * 128, HI64A, bd + k * 64, HI64, k == 0 ? accf : 1);
        wg_commit();
        if (ks > 0) {
          wg_wait<1>();
          release(prev);
          if (ks < 59 || !last) warp_arrive_cl(mapa(sb + BAR_BEMPTY + 8 * bprev, bprev & 1));
        }
        prev = r.slot; bprev = bslot;
        r.next();
        if (++bslot == 6) { bslot = 0; bphase ^= 1; }
      };
      const char* optr;
      uint32_t iv[30], n3[8], n4[8], n5[8], n6[8], n7[8];
      if (tile) {
        bstep(0, 0);
        bstep(1, 1);
        optr = out_ptr(u);
        if (t != id) optr = nullptr;
        load_inv(iv, (it + 1) & 1);
#pragma unroll 1
        for (int ks = 2; ks < 17; ks++) {
          bstep(ks, 1);
          switch (ks) {
            case 2: put(pb, iv, optr, IC<0>()); break;
            case 4: put(pb, iv, optr, IC<1>()); break;
            case 6: put(pb, iv, optr, IC<2>()); break;
            case 8: put(pb, iv, optr, IC<3>()); break;
            case 10: put(pb, iv, optr, IC<4>()); break;
            case 12: put(pb, iv, optr, IC<5>()); break;
            case 14: put(pb, iv, optr, IC<6>()); break;
            case 16: put(pb, iv, optr, IC<7>()); break;
            default: break;
          }
        }
        wg_wait<0>();
        reg_fence(acc);
#pragma unroll
        for (int i = 0; i < 8; i++) n3[i] = n4[i] = n5[i] = n6[i] = n7[i] = 0;
      } else {
        Ring r2 = r;
        auto first = [&](int ks) {
          if (ks == 0) { TR(640); TG(144); }
          if (gemm) { mbar_wait(sb + BAR_RFULL + 8 * r2.slot, r2.phase); mbar_wait(sb + BAR_BFULL + 16 * ks, 0); }
          wg_fence();
          const uint32_t a = (((sb & 0x3FFFF) + r2.slot * RING_BYTES) >> 4) + wg * 512;
          const uint32_t bd = (((sb & 0x3FFFF) + OFF_Q + 2 * ks * BB) >> 4) | ((4096u >> 4) << 16);
#pragma unroll
          for (int k = 0; k < 4; k++) wgmma_n160<1, 1>(acc, a + LBO64A + k * 128, HI64A, bd + k * 64, HI64, k + ks != 0);
          wg_commit();
          if (ks > 0) {
            wg_wait<1>();
            if (gemm) warp_arrive_cl(mapa(sb + BAR_BEMPTY + 16 * (ks - 1), 0));
          }
          r2.next();
        };
        first(0);
        optr = out_ptr(u);
        load_inv(iv, (it + 1) & 1);
        put(pb, iv, optr, IC<0>());
        first(1);
        put(pb, iv, optr, IC<1>());
        norm(n3, pb, iv, IC<3>()); norm(n4, pb, iv, IC<4>());
        first(2);
        put(pb, iv, optr, IC<2>());
        norm(n5, pb, iv, IC<5>()); norm(n6, pb, iv, IC<6>()); norm(n7, pb, iv, IC<7>());
        wg_wait<0>();
        reg_fence(acc);
      }
      if (unsafe(t == id)) {
        slow_path(P, unit_batch(u), unit_head(u, rank), wg, w, fresh_tid() & 31);
        optr = nullptr;
#pragma unroll
        for (int i = 0; i < 8; i++) n3[i] = n4[i] = n5[i] = n6[i] = n7[i] = 0;
      }
      if (tile && t == id) publish();
      if (!tile) {
        if (gemm) {
          float ac1[80];
          auto half = [&](float (&ac)[80], bool rel, int accf) {
            mbar_wait(sb + BAR_BFULL + 8 * bslot, bphase);
            wg_fence();
            const uint32_t a = ring_addr() + wg * 512, bd = (((sb & 0x3FFFF) + OFF_Q + bslot * BB) >> 4) | ((4096u >> 4) << 16);
#pragma unroll
            for (int k = 0; k < 4; k++) wgmma_n160<1, 1>(ac, a + LBO64A + k * 128, HI64A, bd + k * 64, HI64, k == 0 ? accf : 1);
            wg_commit();
            wg_wait<1>();
            if (rel) warp_arrive_cl(mapa(sb + BAR_BEMPTY + 8 * bprev, bprev & 1));
            bprev = bslot;
          };
          auto dstep = [&](int ks) {
            if (!(ks & 3)) TR(640 + ks / 2); if ((ks & 7) == 0) TG(144 + (ks >> 3));
            ring_wait();
            if (!(ks & 3)) TR(641 + ks / 2);
            half(acc, ks < 62, 1);
            release(prev);
            bslot++;
            half(ac1, ks < 61, 1);
            if (++bslot == 6) { bslot = 0; bphase ^= 1; }
            prev = r.slot; r.next();
          };
          bprev = 4; bslot = 1;
          half(ac1, true, 0);
          prev = r.slot; r.next(); bslot = 3;
          half(ac1, true, 1);
          release(prev); prev = r.slot; r.next(); bslot = 5;
          store(n3, optr, IC<3>());
          half(ac1, true, 1);
          release(prev); prev = r.slot; r.next(); bslot = 0; bphase = 1;
#pragma unroll 1
          for (int ks = 3; ks < 7; ks++) {
            dstep(ks);
            switch (ks) {
              case 3: store(n4, optr, IC<4>()); break;
              case 4: store(n5, optr, IC<5>()); break;
              case 5: store(n6, optr, IC<6>()); break;
              default: store(n7, optr, IC<7>()); break;
            }
          }
          publish();
#pragma unroll 1
          for (int ks = 7; ks < 64; ks++) {
            if (wg == 1 && ks == 62) turn_wait();
            dstep(ks);
          }
          if (wg == 0) turn_pass();
          wg_wait<0>();
          reg_fence(acc); reg_fence(ac1);
          TRL(158); TG(156);
          bar_sync(wg);
          out_stage(acc, 0);
          out_stage(ac1, 320);
          out_store(2 * id - 72, 640);
        } else {
          store(n3, optr, IC<3>()); store(n4, optr, IC<4>()); store(n5, optr, IC<5>()); store(n6, optr, IC<6>()); store(n7, optr, IC<7>());
          publish();
        }
        break;
      }
#pragma unroll 1
      for (int ks = 17; ks < 64; ks++) {
        if (END_SKEW && wg == 1 && ks == 64 - END_SKEW) turn_wait();
        bstep(ks, 1);
      }
      if (END_SKEW && wg == 0) turn_pass();
      wg_wait<0>();
      reg_fence(acc);
      release(prev);
      if (!last) warp_arrive_cl(mapa(sb + BAR_BEMPTY + 8 * bprev, bprev & 1));
      TRL(158); TG(156);
      const int pos0 = row_block(t) * 256 + rank * 128 + wg * 64 + w * 16;
      if (last) {
        bar_sync(wg);
        out_stage(acc, 0);
        out_store(t, 320);
      } else {
        const int lane = fresh_tid() & 31;
        __nv_bfloat16* op0 = P.out + (size_t)o_row(pos0 + (lane >> 2)) * DM + (t & 3) * 160 + (lane & 3) * 2;
        __nv_bfloat16* op1 = P.out + (size_t)o_row(pos0 + (lane >> 2) + 8) * DM + (t & 3) * 160 + (lane & 3) * 2;
#pragma unroll
        for (int j = 0; j < 20; j++) {
          *reinterpret_cast<uint32_t*>(op0 + j * 8) = pack(acc[4 * j], acc[4 * j + 1]);
          *reinterpret_cast<uint32_t*>(op1 + j * 8) = pack(acc[4 * j + 2], acc[4 * j + 3]);
        }
      }
#pragma unroll
      for (int i = 0; i < 60; i++) pb[i] = 0;
    }
    TRL(159);
  }
}

typedef CUresult (*EncodeFn)(CUtensorMap*, CUtensorMapDataType, cuuint32_t, void*, const cuuint64_t*, const cuuint64_t*,
                             const cuuint32_t*, const cuuint32_t*, CUtensorMapInterleave, CUtensorMapSwizzle,
                             CUtensorMapL2promotion, CUtensorMapFloatOOBfill);

void make_map(EncodeFn enc, CUtensorMap* m, const void* p, int rank, const cuuint64_t* dims, const cuuint64_t* strides,
              const cuuint32_t* box, CUtensorMapSwizzle sw, CUtensorMapL2promotion promo) {
  cuuint32_t es[4] = {1, 1, 1, 1};
  enc(m, CU_TENSOR_MAP_DATA_TYPE_BFLOAT16, rank, const_cast<void*>(p), dims, strides, box, es, CU_TENSOR_MAP_INTERLEAVE_NONE, sw,
      promo, CU_TENSOR_MAP_FLOAT_OOB_FILL_NONE);
}

}

extern "C" void kernel_launch(void* const* d_in, const int* in_sizes, int n_in, void* d_out, int out_size) {
  static EncodeFn enc = nullptr;
  static int nclusters = 0;
  static void* o_ptr = nullptr;
  if (!enc) {
    cudaDriverEntryPointQueryResult qr;
    cudaGetDriverEntryPoint("cuTensorMapEncodeTiled", (void**)&enc, cudaEnableDefault, &qr);
    cudaFuncSetAttribute(fused_attn_kernel<66>, cudaFuncAttributeMaxDynamicSharedMemorySize, SMEM_BYTES);
    cudaFuncSetAttribute(fused_attn_kernel<0>, cudaFuncAttributeMaxDynamicSharedMemorySize, SMEM_BYTES);
    cudaGetSymbolAddress(&o_ptr, g_o);
    cudaLaunchConfig_t cfg = {};
    cfg.gridDim = 128; cfg.blockDim = 384; cfg.dynamicSmemBytes = SMEM_BYTES;
    cudaLaunchAttribute at; at.id = cudaLaunchAttributeClusterDimension;
    at.val.clusterDim.x = 2; at.val.clusterDim.y = 1; at.val.clusterDim.z = 1;
    cfg.attrs = &at; cfg.numAttrs = 1;
    int n = 0;
    cudaOccupancyMaxActiveClusters(&n, fused_attn_kernel<66>, &cfg);
    nclusters = n >= 66 ? MAXCL : (n >= 64 || n <= 0 ? 64 : n);
  }
  const __nv_bfloat16* x = (const __nv_bfloat16*)d_in[0];
  const __nv_bfloat16* k = (const __nv_bfloat16*)d_in[1];
  const __nv_bfloat16* v = (const __nv_bfloat16*)d_in[2];
  const __nv_bfloat16* wq = (const __nv_bfloat16*)d_in[3];
  const __nv_bfloat16* wo = (const __nv_bfloat16*)d_in[4];
  CUtensorMap tm_x, tm_wq, tm_k, tm_v, tm_o, tm_wo;
  const auto S128 = CU_TENSOR_MAP_SWIZZLE_128B;
  const auto P128 = CU_TENSOR_MAP_L2_PROMOTION_L2_128B, P256 = CU_TENSOR_MAP_L2_PROMOTION_L2_256B;
  { cuuint64_t d[2] = {DM, NB * SQ}, s[1] = {DM * 2}; cuuint32_t b[2] = {64, 120}; make_map(enc, &tm_x, x, 2, d, s, b, S128, X_PROMO); }
  { cuuint64_t d[3] = {64, DM, HD / 64}, s[2] = {HD * 2, 128}; cuuint32_t b[3] = {64, 64, 2}; make_map(enc, &tm_wq, wq, 3, d, s, b, S128, P256); }
  { cuuint64_t d[3] = {64, NB * NH * SK, 2}, s[2] = {DH * 2, 128}; cuuint32_t b[3] = {64, 64, 2};
    make_map(enc, &tm_k, k, 3, d, s, b, S128, P128); make_map(enc, &tm_v, v, 3, d, s, b, S128, P128); }
  { cuuint64_t d[4] = {256, 2, HD / 8, NROWS / 64}, s[3] = {512, NROWS * 16, 1024}; cuuint32_t b[4] = {256, 2, 8, 2};
    make_map(enc, &tm_o, o_ptr, 4, d, s, b, CU_TENSOR_MAP_SWIZZLE_NONE, P256); }
  { cuuint64_t d[3] = {32, HD, DM / 32}, s[2] = {DM * 2, 64}; cuuint32_t b[3] = {32, 64, 5};
    make_map(enc, &tm_wo, wo, 3, d, s, b, CU_TENSOR_MAP_SWIZZLE_64B, P128); }
  Params P{x, k, v, wq, (__nv_bfloat16*)d_out, (__nv_bfloat16*)o_ptr};
  if (nclusters == 66) fused_attn_kernel<66><<<132, 384, SMEM_BYTES>>>(tm_x, tm_wq, tm_k, tm_v, tm_o, tm_wo, P);
  else fused_attn_kernel<0><<<2 * nclusters, 384, SMEM_BYTES>>>(tm_x, tm_wq, tm_k, tm_v, tm_o, tm_wo, P);
}
```

```cpp
#include <cuda_runtime.h>
#include <cuda.h>
#include <cuda_bf16.h>
#include <stdint.h>

namespace {

constexpr int NB = 16, SQ = 240, DM = 640, NH = 32, SK = 1024, DH = 128, HD = NH * DH;
constexpr int NROWS = NB * SQ;
constexpr int NUNITS = 256;
#define DPRO 1
#define LATE_AT 0
#define ALT_FROM 4
#define END_SKEW 5
#define VREL 6
#define PF_HOLD 6
#define PF_N 4
#define PF_J0 3
#define PF_STEP 3
#define ROT 0
#define O_EF 1
#define B_ORDER 1
#define WO_PF 6
#define ROLE_AT 0
#define PAUSE_NS 11000
#define PAUSE_AT 2
#define EARLY 1
#define EARLY_X 2
#define EARLY_W 2
#define X_PROMO P128
#define PAUSE_J -1
#define PAUSE_SPREAD 0
#define WO_PF0 1
#define EPI_MIX 1
#define K2_AT 0
#define SLP 15
#define PASS9 0
#define LSUM_AT 0
#define PUT_FROM 1
#define EARLY_VOTE 1
#define EREL_FROM 4
#define PRE9 0
#define MAXCL 66
#define SMID_TOP 88
constexpr int NOTILES = 60;
constexpr float QSCALE = 0.08838834764831845f * 1.4426950408889634f;
constexpr float L_MIN = 9.5367431640625e-07f;
constexpr float L_MAX = 1.152921504606846976e18f;

constexpr uint32_t RING_SLOTS = 6, RING_BYTES = 16384;
constexpr uint32_t XB = 15360;
constexpr uint32_t BB = 20480;
constexpr uint32_t OFF_Q = RING_SLOTS * RING_BYTES;
constexpr uint32_t OFF_P = OFF_Q + 4 * XB;
constexpr uint32_t OFF_INV = OFF_P + 4 * XB;
constexpr uint32_t OFF_L2 = OFF_INV + 1280;
constexpr uint32_t OFF_BAR = OFF_L2 + 4096;
constexpr uint32_t BAR_RFULL = OFF_BAR, BAR_REMPTY = BAR_RFULL + 48, BAR_XFULL = BAR_REMPTY + 48,
    BAR_XEMPTY = BAR_XFULL + 64, BAR_BFULL = BAR_XEMPTY + 32, BAR_BEMPTY = BAR_BFULL + 48, BAR_STAGE = BAR_BEMPTY + 48;
constexpr uint32_t BAR_ROLE = BAR_STAGE + 16, BAR_LSUM = BAR_ROLE + 24, BAR_INV = BAR_LSUM + 16;
constexpr uint32_t OFF_TR = BAR_INV + 16;
constexpr uint32_t SMEM_BYTES = OFF_TR + 1024;

constexpr uint32_t HI128 = (1u << 30) | (1024 >> 4);
constexpr uint32_t HI64 = (2u << 30) | (512 >> 4);
constexpr uint32_t HI64A = (2u << 30) | (1024 >> 4), LBO64A = (512u >> 4) << 16;

__device__ __nv_bfloat16 g_o[HD * NROWS];
__device__ unsigned g_cnt[67 * 8];
#define TS(i)
#define TI(i)
#define TRL(i)
#define TR(i)
#define TG(i)

struct Params {
  const __nv_bfloat16 *x, *k, *v, *wq;
  __nv_bfloat16 *out, *o;
};

__device__ __forceinline__ void wg_fence() { asm volatile("wgmma.fence.sync.aligned;" ::: "memory"); }
__device__ __forceinline__ void wg_commit() { asm volatile("wgmma.commit_group.sync.aligned;" ::: "memory"); }
template <int N> __device__ __forceinline__ void wg_wait() { asm volatile("wgmma.wait_group.sync.aligned %0;" ::"n"(N) : "memory"); }
template <int N> __device__ __forceinline__ void reg_fence(float (&r)[N]) {
#pragma unroll
  for (int i = 0; i < N; i++) asm volatile("" : "+f"(r[i])::"memory");
}
template <int TA, int TB>
__device__ __forceinline__ void wgmma_n120(float (&d)[60], uint32_t a_lo, uint32_t a_hi, uint32_t b_lo, uint32_t b_hi, int acc) {
  asm volatile(
      "{\n.reg .pred p;\n.reg .b64 da, db;\nsetp.ne.b32 p, %64, 0;\n"
      "mov.b64 da, {%60, %61};\nmov.b64 db, {%62, %63};\n"
      "wgmma.mma_async.sync.aligned.m64n120k16.f32.bf16.bf16 {"
      "%0, %1, %2, %3, %4, %5, %6, %7, %8, %9, %10, %11, %12, %13, %14, %15, %16, %17, %18, %19, %20, %21, %22, %23, "
      "%24, %25, %26, %27, %28, %29, %30, %31, %32, %33, %34, %35, %36, %37, %38, %39, %40, %41, %42, %43, %44, %45, "
      "%46, %47, %48, %49, %50, %51, %52, %53, %54, %55, %56, %57, %58, %59"
      "}, da, db, p, 1, 1, %65, %66;\n}\n"
      : "+f"(d[0]), "+f"(d[1]), "+f"(d[2]), "+f"(d[3]), "+f"(d[4]), "+f"(d[5]), "+f"(d[6]), "+f"(d[7]), "+f"(d[8]),
        "+f"(d[9]), "+f"(d[10]), "+f"(d[11]), "+f"(d[12]), "+f"(d[13]), "+f"(d[14]), "+f"(d[15]), "+f"(d[16]),
        "+f"(d[17]), "+f"(d[18]), "+f"(d[19]), "+f"(d[20]), "+f"(d[21]), "+f"(d[22]), "+f"(d[23]), "+f"(d[24]),
        "+f"(d[25]), "+f"(d[26]), "+f"(d[27]), "+f"(d[28]), "+f"(d[29]), "+f"(d[30]), "+f"(d[31]), "+f"(d[32]),
        "+f"(d[33]), "+f"(d[34]), "+f"(d[35]), "+f"(d[36]), "+f"(d[37]), "+f"(d[38]), "+f"(d[39]), "+f"(d[40]),
        "+f"(d[41]), "+f"(d[42]), "+f"(d[43]), "+f"(d[44]), "+f"(d[45]), "+f"(d[46]), "+f"(d[47]), "+f"(d[48]),
        "+f"(d[49]), "+f"(d[50]), "+f"(d[51]), "+f"(d[52]), "+f"(d[53]), "+f"(d[54]), "+f"(d[55]), "+f"(d[56]),
        "+f"(d[57]), "+f"(d[58]), "+f"(d[59])
      : "r"(a_lo), "r"(a_hi), "r"(b_lo), "r"(b_hi), "r"(acc), "n"(TA), "n"(TB));
}

template <int TA, int TB>
__device__ __forceinline__ void wgmma_n160(float (&d)[80], uint32_t a_lo, uint32_t a_hi, uint32_t b_lo, uint32_t b_hi, int acc) {
  asm volatile(
      "{\n.reg .pred p;\n.reg .b64 da, db;\nsetp.ne.b32 p, %84, 0;\n"
      "mov.b64 da, {%80, %81};\nmov.b64 db, {%82, %83};\n"
      "wgmma.mma_async.sync.aligned.m64n160k16.f32.bf16.bf16 {"
      "%0, %1, %2, %3, %4, %5, %6, %7, %8, %9, %10, %11, %12, %13, %14, %15, %16, %17, %18, %19, %20, %21, %22, %23, "
      "%24, %25, %26, %27, %28, %29, %30, %31, %32, %33, %34, %35, %36, %37, %38, %39, %40, %41, %42, %43, %44, %45, "
      "%46, %47, %48, %49, %50, %51, %52, %53, %54, %55, %56, %57, %58, %59, %60, %61, %62, %63, %64, %65, %66, %67, "
      "%68, %69, %70, %71, %72, %73, %74, %75, %76, %77, %78, %79"
      "}, da, db, p, 1, 1, %85, %86;\n}\n"
      : "+f"(d[0]), "+f"(d[1]), "+f"(d[2]), "+f"(d[3]), "+f"(d[4]), "+f"(d[5]), "+f"(d[6]), "+f"(d[7]), "+f"(d[8]),
        "+f"(d[9]), "+f"(d[10]), "+f"(d[11]), "+f"(d[12]), "+f"(d[13]), "+f"(d[14]), "+f"(d[15]), "+f"(d[16]),
        "+f"(d[17]), "+f"(d[18]), "+f"(d[19]), "+f"(d[20]), "+f"(d[21]), "+f"(d[22]), "+f"(d[23]), "+f"(d[24]),
        "+f"(d[25]), "+f"(d[26]), "+f"(d[27]), "+f"(d[28]), "+f"(d[29]), "+f"(d[30]), "+f"(d[31]), "+f"(d[32]),
        "+f"(d[33]), "+f"(d[34]), "+f"(d[35]), "+f"(d[36]), "+f"(d[37]), "+f"(d[38]), "+f"(d[39]), "+f"(d[40]),
        "+f"(d[41]), "+f"(d[42]), "+f"(d[43]), "+f"(d[44]), "+f"(d[45]), "+f"(d[46]), "+f"(d[47]), "+f"(d[48]),
        "+f"(d[49]), "+f"(d[50]), "+f"(d[51]), "+f"(d[52]), "+f"(d[53]), "+f"(d[54]), "+f"(d[55]), "+f"(d[56]),
        "+f"(d[57]), "+f"(d[58]), "+f"(d[59]), "+f"(d[60]), "+f"(d[61]), "+f"(d[62]), "+f"(d[63]), "+f"(d[64]),
        "+f"(d[65]), "+f"(d[66]), "+f"(d[67]), "+f"(d[68]), "+f"(d[69]), "+f"(d[70]), "+f"(d[71]), "+f"(d[72]),
        "+f"(d[73]), "+f"(d[74]), "+f"(d[75]), "+f"(d[76]), "+f"(d[77]), "+f"(d[78]), "+f"(d[79])
      : "r"(a_lo), "r"(a_hi), "r"(b_lo), "r"(b_hi), "r"(acc), "n"(TA), "n"(TB));
}
__device__ __forceinline__ void mbar_init(uint32_t bar, int cnt) { asm volatile("mbarrier.init.shared::cta.b64 [%0], %1;" ::"r"(bar), "r"(cnt)); }
__device__ __forceinline__ void mbar_expect(uint32_t bar, uint32_t bytes) {
  asm volatile("mbarrier.arrive.expect_tx.shared::cta.b64 _, [%0], %1;" ::"r"(bar), "r"(bytes) : "memory");
}
__device__ __forceinline__ uint32_t mapa(uint32_t addr, uint32_t cta) {
  uint32_t r; asm("mapa.shared::cluster.u32 %0, %1, %2;" : "=r"(r) : "r"(addr), "r"(cta)); return r;
}
__device__ __forceinline__ void mbar_expect_cl(uint32_t cbar, uint32_t bytes) {
  asm volatile("mbarrier.arrive.expect_tx.shared::cluster.b64 _, [%0], %1;" ::"r"(cbar), "r"(bytes) : "memory");
}
__device__ __forceinline__ void mbar_arrive(uint32_t bar) { asm volatile("mbarrier.arrive.shared::cta.b64 _, [%0];" ::"r"(bar) : "memory"); }
__device__ __forceinline__ void mbar_arrive_cl(uint32_t cbar) { asm volatile("mbarrier.arrive.shared::cluster.b64 _, [%0];" ::"r"(cbar) : "memory"); }
__device__ __forceinline__ void warp_arrive(uint32_t bar) {
  asm volatile("{\n.reg .pred p;\nelect.sync _|p, 0xffffffff;\n@p mbarrier.arrive.shared::cta.b64 _, [%0];\n}\n" ::"r"(bar) : "memory");
}
__device__ __forceinline__ void warp_arrive_cl(uint32_t cbar) {
  asm volatile("{\n.reg .pred p;\nelect.sync _|p, 0xffffffff;\n@p mbarrier.arrive.shared::cluster.b64 _, [%0];\n}\n" ::"r"(cbar) : "memory");
}
__device__ __forceinline__ void mbar_wait(uint32_t bar, uint32_t parity) {
  asm volatile(
      "{\n.reg .pred p;\n.reg .u32 n;\n"
      "mbarrier.try_wait.parity.shared::cta.b64 p, [%0], %1;\n@p bra WAIT_DONE;\n"
      "mov.u32 n, 0;\n"
      "WAIT_LOOP:\n"
      "mbarrier.try_wait.parity.shared::cta.b64 p, [%0], %1;\n@p bra WAIT_DONE;\n"
      "add.u32 n, n, 1;\nsetp.lt.u32 p, n, 0x4000000;\n@p bra WAIT_LOOP;\ntrap;\n"
      "WAIT_DONE:\n}\n" ::"r"(bar), "r"(parity) : "memory");
}
__device__ __forceinline__ void mbar_sleep(uint32_t bar, uint32_t parity) {
  asm volatile(
      "{\n.reg .pred p;\n.reg .u32 n;\nmov.u32 n, 0;\n"
      "WAIT_LOOP:\n"
      "mbarrier.try_wait.parity.shared::cta.b64 p, [%0], %1, 4000;\n@p bra WAIT_DONE;\n"
      "add.u32 n, n, 1;\nsetp.lt.u32 p, n, 0x400000;\n@p bra WAIT_LOOP;\ntrap;\n"
      "WAIT_DONE:\n}\n" ::"r"(bar), "r"(parity) : "memory");
}
__device__ __forceinline__ void mbar_wait_cl(uint32_t bar, uint32_t parity) {
  asm volatile(
      "{\n.reg .pred p;\n.reg .u32 n;\nmov.u32 n, 0;\n"
      "WAIT_LOOP:\n"
      "mbarrier.try_wait.parity.acquire.cluster.shared::cta.b64 p, [%0], %1;\n@p bra WAIT_DONE;\n"
      "add.u32 n, n, 1;\nsetp.lt.u32 p, n, 0x4000000;\n@p bra WAIT_LOOP;\ntrap;\n"
      "WAIT_DONE:\n}\n" ::"r"(bar), "r"(parity) : "memory");
}
__device__ __forceinline__ void tma3d(uint32_t dst, const CUtensorMap* m, int c0, int c1, int c2, uint32_t bar) {
  asm volatile("cp.async.bulk.tensor.3d.shared::cluster.global.mbarrier::complete_tx::bytes [%0], [%1, {%3, %4, %5}], [%2];"
               ::"r"(dst), "l"(m), "r"(bar), "r"(c0), "r"(c1), "r"(c2) : "memory");
}
__device__ __forceinline__ void tma3d_hint(uint32_t dst, const CUtensorMap* m, int c0, int c1, int c2, uint32_t bar, uint64_t pol) {
  asm volatile("cp.async.bulk.tensor.3d.shared::cluster.global.mbarrier::complete_tx::bytes.L2::cache_hint [%0], [%1, {%3, %4, %5}], [%2], %6;"
               ::"r"(dst), "l"(m), "r"(bar), "r"(c0), "r"(c1), "r"(c2), "l"(pol) : "memory");
}
__device__ __forceinline__ void tma2d_mc(uint32_t dst, const CUtensorMap* m, int c0, int c1, uint32_t bar) {
  asm volatile("cp.async.bulk.tensor.2d.shared::cluster.global.mbarrier::complete_tx::bytes.multicast::cluster [%0], [%1, {%3, %4}], [%2], %5;"
               ::"r"(dst), "l"(m), "r"(bar), "r"(c0), "r"(c1), "h"((uint16_t)3) : "memory");
}
__device__ __forceinline__ void tma3d_mc(uint32_t dst, const CUtensorMap* m, int c0, int c1, int c2, uint32_t bar) {
  asm volatile("cp.async.bulk.tensor.3d.shared::cluster.global.mbarrier::complete_tx::bytes.multicast::cluster [%0], [%1, {%3, %4, %5}], [%2], %6;"
               ::"r"(dst), "l"(m), "r"(bar), "r"(c0), "r"(c1), "r"(c2), "h"((uint16_t)3) : "memory");
}
__device__ __forceinline__ void l2_prefetch(const void* p, uint32_t bytes) {
  asm volatile("cp.async.bulk.prefetch.L2.global [%0], %1;" ::"l"(p), "r"(bytes) : "memory");
}
__device__ __forceinline__ void fence_async_smem() { asm volatile("fence.proxy.async.shared::cta;" ::: "memory"); }
__device__ __forceinline__ void bar_sync(int wg) {
  if (wg == 0) asm volatile("bar.sync 1, 128;" ::: "memory");
  else asm volatile("bar.sync 2, 128;" ::: "memory");
}
__device__ __forceinline__ bool bar_red_or(int id, bool v) {
  uint32_t r;
  asm volatile("{\n.reg .pred p, q;\nsetp.ne.u32 p, %2, 0;\nbar.red.or.pred q, %1, 128, p;\nselp.u32 %0, 1, 0, q;\n}\n"
               : "=r"(r) : "r"(1 + id), "r"((uint32_t)v) : "memory");
  return r != 0;
}
__device__ __forceinline__ uint32_t hfma2(uint32_t a, uint32_t b, uint32_t c) { uint32_t r; asm("fma.rn.bf16x2 %0, %1, %2, %3;" : "=r"(r) : "r"(a), "r"(b), "r"(c)); return r; }
__device__ __forceinline__ float ex2(float x) { float y; asm("ex2.approx.ftz.f32 %0, %1;" : "=f"(y) : "f"(x)); return y; }
__device__ __forceinline__ uint32_t pack(float lo, float hi) { uint32_t r; asm("cvt.rn.bf16x2.f32 %0, %1, %2;" : "=r"(r) : "f"(hi), "f"(lo)); return r; }
__device__ __forceinline__ void stsm4t(uint32_t a, uint32_t r0, uint32_t r1, uint32_t r2, uint32_t r3) {
  asm volatile("stmatrix.sync.aligned.m8n8.x4.trans.shared.b16 [%0], {%1,%2,%3,%4};" ::"r"(a), "r"(r0), "r"(r1), "r"(r2), "r"(r3) : "memory");
}
__device__ __forceinline__ void stsm2t(uint32_t a, uint32_t r0, uint32_t r1) {
  asm volatile("stmatrix.sync.aligned.m8n8.x2.trans.shared.b16 [%0], {%1,%2};" ::"r"(a), "r"(r0), "r"(r1) : "memory");
}
__device__ __forceinline__ void mma16816(float (&d)[4], const uint32_t (&a)[4], uint32_t b0, uint32_t b1) {
  asm volatile("mma.sync.aligned.m16n8k16.row.col.f32.bf16.bf16.f32 {%0,%1,%2,%3}, {%4,%5,%6,%7}, {%8,%9}, {%0,%1,%2,%3};"
               : "+f"(d[0]), "+f"(d[1]), "+f"(d[2]), "+f"(d[3]) : "r"(a[0]), "r"(a[1]), "r"(a[2]), "r"(a[3]), "r"(b0), "r"(b1));
}

__device__ __forceinline__ uint32_t fresh_tid() { uint32_t t; asm volatile("mov.u32 %0, %tid.x;" : "=r"(t)); return t; }

template <int V> struct IC { static constexpr int value = V; };

struct Ring {
  uint32_t slot = 0, phase = 0;
  __device__ __forceinline__ void next() { if (++slot == RING_SLOTS) { slot = 0; phase ^= 1; } }
};

__device__ __forceinline__ void mma_tn(float (&o0)[60], float (&o1)[60], uint32_t a, uint32_t b, int acc) {
#pragma unroll
  for (int k = 0; k < 4; k++) {
    wgmma_n120<1, 0>(o0, a + k * 128, HI128, b + k * 2, HI128, k == 0 ? acc : 1);
    wgmma_n120<1, 0>(o1, a + 512 + k * 128, HI128, b + k * 2, HI128, k == 0 ? acc : 1);
  }
}
__device__ __forceinline__ void mma_tn_split(float (&o0)[60], float (&o1)[60], uint32_t a, uint32_t b) {
#pragma unroll
  for (int k = 0; k < 4; k++) wgmma_n120<1, 0>(o0, a + k * 128, HI128, b + k * 2, HI128, 1);
  wg_commit();
#pragma unroll
  for (int k = 0; k < 4; k++) wgmma_n120<1, 0>(o1, a + 512 + k * 128, HI128, b + k * 2, HI128, 1);
  wg_commit();
}
__device__ __forceinline__ void mma_qk(float (&s)[60], uint32_t a, uint32_t q) {
#pragma unroll
  for (int k = 0; k < 8; k++)
    wgmma_n120<0, 0>(s, a + (k >> 2) * 512 + (k & 3) * 2, HI128, q + (k >> 2) * (XB >> 4) + (k & 3) * 2, HI128, k != 0);
}
template <int J0, int J1, bool FIRST = false>
__device__ __forceinline__ void exp_store(const float (&s)[60], float (&l)[30], uint32_t dst) {
#pragma unroll
  for (int j = J0; j < J1; j += 2) {
    uint32_t p[4];
#pragma unroll
    for (int jj = 0; jj < 2; jj++) {
      if (j + jj < 15) {
        const int c = j + jj;
        float e0 = ex2(s[4 * c]), e1 = ex2(s[4 * c + 1]), e2 = ex2(s[4 * c + 2]), e3 = ex2(s[4 * c + 3]);
        if (FIRST) { l[2 * c] = e0 + e2; l[2 * c + 1] = e1 + e3; }
        else { l[2 * c] += e0; l[2 * c + 1] += e1; l[2 * c] += e2; l[2 * c + 1] += e3; }
        p[2 * jj] = pack(e0, e1); p[2 * jj + 1] = pack(e2, e3);
      }
    }
    if (j + 1 < 15) stsm4t(dst + j * 1024, p[0], p[1], p[2], p[3]);
    else stsm2t(dst + j * 1024, p[0], p[1]);
  }
}

__device__ __forceinline__ int o_pos(int b, int wg, int r) {
  const int j = r >> 3, q = (r >> 1) & 3, c = r & 1, o = b & 1, base = (b >> 1) * 480;
  if (j < 12) return base + (o * 9 + wg * 3 + (j >> 2)) * 32 + q * 8 + (j & 3) * 2 + c;
  if (j < 14) return base + (6 + 2 * o) * 32 + wg * 16 + q * 4 + (j - 12) * 2 + c;
  return base + 7 * 32 + (o * 2 + wg) * 8 + q * 2 + c;
}
__device__ __forceinline__ int o_row(int p) {
  const int pair = p / 480, a = (p - pair * 480) >> 5, in = p & 31, c = p & 1;
  int tile, row;
  if (a == 7) { tile = in >> 3; row = 112 + (in & 7); }
  else if (a == 6 || a == 8) { tile = a - 6 + (in >> 4); row = (12 + ((in >> 1) & 1)) * 8 + ((in >> 2) & 3) * 2 + c; }
  else { const int f = a > 8 ? a - 3 : a; tile = f / 3; row = ((f - tile * 3) * 4 + ((in >> 1) & 3)) * 8 + (in >> 3) * 2 + c; }
  return pair * 480 + tile * 120 + row;
}
__device__ __forceinline__ uint32_t o_idx(int k, int p) {
  return ((k >> 3) * (NROWS / 32) + (p >> 5)) * 256 + (k & 7) * 32 + ((((p >> 3) & 3) ^ ((k & 7) >> 1)) << 3) + (p & 7);
}

__device__ __forceinline__ void slow_path(const Params& P, int b, int h, int wg, int w, int lane) {
  const int g = lane >> 2, q = lane & 3, row0 = wg * 120;
  const uint16_t* wq = reinterpret_cast<const uint16_t*>(P.wq) + h * DH + g;
  const __nv_bfloat16* kp = P.k + (size_t)(b * NH + h) * SK * DH;
  const uint16_t* vp = reinterpret_cast<const uint16_t*>(P.v) + (size_t)(b * NH + h) * SK * DH + g;
#pragma unroll 1
  for (int t = w; t < 8; t += 4) {
    const int r0 = 16 * t + g, r1 = r0 + 8;
    const __nv_bfloat16* x0 = P.x + (size_t)(b * SQ + row0 + r0) * DM + 2 * q;
    const __nv_bfloat16* x1 = P.x + (size_t)(b * SQ + row0 + min(r1, 119)) * DM + 2 * q;
    float o[16][4];
#pragma unroll
    for (int n = 0; n < 16; n++) o[n][0] = o[n][1] = o[n][2] = o[n][3] = 0.f;
#pragma unroll 1
    for (int k0 = 0; k0 < DM; k0 += 16) {
      uint32_t a[4] = {*(const uint32_t*)(x0 + k0), *(const uint32_t*)(x1 + k0), *(const uint32_t*)(x0 + k0 + 8), *(const uint32_t*)(x1 + k0 + 8)};
      const uint16_t* wr = wq + (size_t)(k0 + 2 * q) * HD;
#pragma unroll
      for (int n = 0; n < 16; n++) {
        if ((n & 3) == 0) __syncwarp();
        mma16816(o[n], a, wr[8 * n] | ((uint32_t)wr[8 * n + HD] << 16), wr[8 * n + 8 * HD] | ((uint32_t)wr[8 * n + 9 * HD] << 16));
      }
    }
    uint32_t qa[8][4];
#pragma unroll
    for (int k = 0; k < 8; k++) {
      qa[k][0] = pack(o[2 * k][0] * QSCALE, o[2 * k][1] * QSCALE);
      qa[k][1] = pack(o[2 * k][2] * QSCALE, o[2 * k][3] * QSCALE);
      qa[k][2] = pack(o[2 * k + 1][0] * QSCALE, o[2 * k + 1][1] * QSCALE);
      qa[k][3] = pack(o[2 * k + 1][2] * QSCALE, o[2 * k + 1][3] * QSCALE);
    }
#pragma unroll
    for (int n = 0; n < 16; n++) o[n][0] = o[n][1] = o[n][2] = o[n][3] = 0.f;
    float m0 = -INFINITY, m1 = -INFINITY, l0 = 0.f, l1 = 0.f;
#pragma unroll 1
    for (int key0 = 0; key0 < SK; key0 += 16) {
      float s[2][4];
#pragma unroll
      for (int nt = 0; nt < 2; nt++) {
        s[nt][0] = s[nt][1] = s[nt][2] = s[nt][3] = 0.f;
        const __nv_bfloat16* kr = kp + (size_t)(key0 + 8 * nt + g) * DH + 2 * q;
#pragma unroll
        for (int k = 0; k < 8; k++) mma16816(s[nt], qa[k], *(const uint32_t*)(kr + 16 * k), *(const uint32_t*)(kr + 16 * k + 8));
      }
      float n0 = fmaxf(fmaxf(s[0][0], s[0][1]), fmaxf(s[1][0], s[1][1])), n1 = fmaxf(fmaxf(s[0][2], s[0][3]), fmaxf(s[1][2], s[1][3]));
      n0 = fmaxf(n0, __shfl_xor_sync(~0u, n0, 1)); n1 = fmaxf(n1, __shfl_xor_sync(~0u, n1, 1));
      n0 = fmaxf(n0, __shfl_xor_sync(~0u, n0, 2)); n1 = fmaxf(n1, __shfl_xor_sync(~0u, n1, 2));
      n0 = fmaxf(n0, m0); n1 = fmaxf(n1, m1);
      const float z0 = n0 == -INFINITY ? 0.f : n0, z1 = n1 == -INFINITY ? 0.f : n1;
      const float c0 = ex2(m0 - z0), c1 = ex2(m1 - z1);
      m0 = n0; m1 = n1;
#pragma unroll
      for (int nt = 0; nt < 2; nt++) {
        s[nt][0] = ex2(s[nt][0] - z0); s[nt][1] = ex2(s[nt][1] - z0);
        s[nt][2] = ex2(s[nt][2] - z1); s[nt][3] = ex2(s[nt][3] - z1);
      }
      l0 = l0 * c0 + s[0][0] + s[0][1] + s[1][0] + s[1][1];
      l1 = l1 * c1 + s[0][2] + s[0][3] + s[1][2] + s[1][3];
      uint32_t pa[4] = {pack(s[0][0], s[0][1]), pack(s[0][2], s[0][3]), pack(s[1][0], s[1][1]), pack(s[1][2], s[1][3])};
      const uint16_t* vr = vp + (size_t)(key0 + 2 * q) * DH;
#pragma unroll
      for (int n = 0; n < 16; n++) {
        if ((n & 3) == 0) __syncwarp();
        o[n][0] *= c0; o[n][1] *= c0; o[n][2] *= c1; o[n][3] *= c1;
        mma16816(o[n], pa, vr[8 * n] | ((uint32_t)vr[8 * n + DH] << 16), vr[8 * n + 8 * DH] | ((uint32_t)vr[8 * n + 9 * DH] << 16));
      }
    }
    l0 += __shfl_xor_sync(~0u, l0, 1); l1 += __shfl_xor_sync(~0u, l1, 1);
    l0 += __shfl_xor_sync(~0u, l0, 2); l1 += __shfl_xor_sync(~0u, l1, 2);
    const float i0 = 1.f / l0, i1 = 1.f / l1;
    __nv_bfloat16* oc0 = P.o + o_idx(h * DH + 2 * q, o_pos(b, wg, r0));
    __nv_bfloat16* oc1 = P.o + o_idx(h * DH + 2 * q, o_pos(b, wg, min(r1, 119)));
#pragma unroll
    for (int n = 0; n < 16; n++) {
      oc0[8 * n * NROWS] = __float2bfloat16(o[n][0] * i0);
      oc0[8 * n * NROWS + 32] = __float2bfloat16(o[n][1] * i0);
      if (r1 < 120) {
        oc1[8 * n * NROWS] = __float2bfloat16(o[n][2] * i1);
        oc1[8 * n * NROWS + 32] = __float2bfloat16(o[n][3] * i1);
      }
    }
  }
}

__device__ __forceinline__ int bk(int ks) { return B_ORDER && ks < 48 ? 32 - (ks & 48) + (ks & 15) : ks; }
__device__ __forceinline__ uint32_t x_slot(uint32_t wg, uint32_t j) { return j < 2 ? (2 * wg + j) * XB : (2 * j + wg) * XB; }
__device__ __forceinline__ int row_block(int t) { return t >= 44 ? (t >> 2) - 11 : (t >> 2) + 4; }
__device__ __forceinline__ int unit_batch(int u) { return (u & 63) >> 2; }
__device__ __forceinline__ int unit_head(int u, int rank) { return (u >> 6) * 8 + (u & 3) * 2 + rank; }

template <int NCL>
__global__ void __cluster_dims__(2, 1, 1) __launch_bounds__(384, 1)
fused_attn_kernel(const __grid_constant__ CUtensorMap tm_x, const __grid_constant__ CUtensorMap tm_wq,
                  const __grid_constant__ CUtensorMap tm_k, const __grid_constant__ CUtensorMap tm_v,
                  const __grid_constant__ CUtensorMap tm_o, const __grid_constant__ CUtensorMap tm_wo,
                  const __grid_constant__ Params P) {
  extern __shared__ uint8_t smem_raw[];
  const uint32_t sb = ((uint32_t)__cvta_generic_to_shared(smem_raw) + 1023) & ~1023u;
  if (threadIdx.x == 0) TS(152);
  const int warp = __shfl_sync(~0u, threadIdx.x >> 5, 0);
  const int lane = threadIdx.x & 31;
  const int rank = blockIdx.x & 1, cl = blockIdx.x >> 1, ncl = NCL ? NCL : gridDim.x >> 1;

  const int nsingle = NCL == 66 ? 44 : NOTILES;
  auto role = [&]() {
    mbar_wait(sb + BAR_ROLE + 16, 0);
    int id;
    asm volatile("ld.shared.u32 %0, [%1];" : "=r"(id) : "r"(sb + BAR_ROLE + 8) : "memory");
    return id;
  };

  if (EARLY && threadIdx.x == 128) asm volatile("prefetch.tensormap [%0];" ::"l"(&tm_x) : "memory");
  if (threadIdx.x == 0) {
    if (EARLY) asm volatile("prefetch.tensormap [%0];" ::"l"(&tm_wq) : "memory");
    for (int i = 0; i < 6; i++) {
      mbar_init(sb + BAR_RFULL + 8 * i, 1); mbar_init(sb + BAR_REMPTY + 8 * i, 8);
      mbar_init(sb + BAR_BFULL + 8 * i, 1); mbar_init(sb + BAR_BEMPTY + 8 * i, 16);
    }
    for (int i = 0; i < 8; i++) mbar_init(sb + BAR_XFULL + 8 * i, 1);
    for (int i = 0; i < 4; i++) mbar_init(sb + BAR_XEMPTY + 8 * i, 8);
    for (int i = 0; i < 2; i++) { mbar_init(sb + BAR_STAGE + 8 * i, 4); mbar_init(sb + BAR_LSUM + 8 * i, 4); mbar_init(sb + BAR_INV + 8 * i, 1); }
    mbar_init(sb + BAR_ROLE, 1); mbar_init(sb + BAR_ROLE + 16, 1);
    asm volatile("fence.mbarrier_init.release.cluster;" ::: "memory");
  }
  __syncwarp();
  asm volatile("barrier.cluster.arrive.relaxed.aligned;" ::: "memory");
  auto first_w = [&](int s) {
    mbar_expect(sb + BAR_RFULL + 8 * s, RING_BYTES);
    tma3d(sb + s * RING_BYTES, &tm_wq, 0, s * 64, 2 * unit_head(cl, rank), sb + BAR_RFULL + 8 * s);
  };
  if (EARLY && threadIdx.x == 0) first_w(0);
  __syncwarp();
  asm volatile("barrier.cluster.wait.aligned;" ::: "memory");
  if (EARLY && threadIdx.x == 128) {
#pragma unroll 1
    for (int s = 0; s < EARLY_X; s++) {
      const uint32_t fb = sb + BAR_XFULL + 32 * rank + 8 * s;
      mbar_expect(fb, XB);
      mbar_expect_cl(mapa(fb, rank ^ 1), XB);
      tma2d_mc(sb + OFF_Q + x_slot(rank, s), &tm_x, s * 64, unit_batch(cl) * SQ + rank * 120, fb);
      if (s + 1 < EARLY_W) first_w(s + 1);
    }
  }
  __syncwarp();
  if (threadIdx.x == 0) TS(153);

  if (warp >= 8) {
    asm volatile("setmaxnreg.dec.sync.aligned.u32 24;");
    if (warp == 8) {
      uint64_t pol;
      asm volatile("createpolicy.fractional.L2::evict_first.b64 %0, 1.0;" : "=l"(pol));
      Ring r;
      if (EARLY) r.slot = EARLY_W;
      auto load = [&](const CUtensorMap* m, int c1, int c2, bool ef) {
        if (SLP & 8) mbar_sleep(sb + BAR_REMPTY + 8 * r.slot, r.phase ^ 1); else mbar_wait(sb + BAR_REMPTY + 8 * r.slot, r.phase ^ 1);
        if (lane == 0) {
          mbar_expect(sb + BAR_RFULL + 8 * r.slot, RING_BYTES);
          if (ef) tma3d_hint(sb + r.slot * RING_BYTES, m, 0, c1, c2, sb + BAR_RFULL + 8 * r.slot, pol);
          else tma3d(sb + r.slot * RING_BYTES, m, 0, c1, c2, sb + BAR_RFULL + 8 * r.slot);
        }
        r.next();
      };
      const int rot = ROT * (blockIdx.x * 5 + (blockIdx.x >> 4));
      auto pause = [&](int u0) {
        if (PAUSE_NS && NCL == 66 && u0 == PAUSE_AT * 66) {
          const int id = role();
          if (id >= 44 && id < 58) {
            unsigned t0, t1;
            asm volatile("mov.u32 %0, %globaltimer_lo;" : "=r"(t0));
            do { __nanosleep(200); asm volatile("mov.u32 %0, %globaltimer_lo;" : "=r"(t1)); } while (t1 - t0 < PAUSE_NS + (id - 44) * PAUSE_SPREAD);
          }
        }
      };
      for (int u0 = 0;; u0 += ncl) {
        const int u = __shfl_sync(~0u, (u0 >= 3 * ncl ? role() : cl) + u0, 0);
        if (u >= NUNITS) break;
        if (PAUSE_J < 0) pause(u0);
        const int h = unit_head(u, rank);
        const int krow = (unit_batch(u) * NH + h) * SK;
#pragma unroll 1
        for (int s = EARLY && u0 == 0 ? EARLY_W : 0; s < 10; s++) {
          if (u0 == 0 && s == 0 && lane == 0) TS(154);
          load(&tm_wq, s * 64, 2 * h, false);
          if (u0 == 0 && s == 0 && lane == 0) TS(155);
          const int sp = u0 == 0 ? s - PF_HOLD : s;
          if (sp >= 0 && sp < PF_N && lane == 0) l2_prefetch(P.v + (size_t)(krow + ((PF_J0 + sp * PF_STEP + rot) & 15) * 64) * DH, 16384);
        }
#pragma unroll 1
        for (int j = 0; j <= 16; j++) {
          if (j == PAUSE_J) pause(u0);
          if (j < 16) load(&tm_k, krow + ((j + rot) & 15) * 64, 0, true);
          if (j == 1 + DPRO) load(&tm_v, krow + (rot & 15) * 64, 0, true);
          if (j > 1) load(&tm_v, krow + ((j - 1 + rot) & 15) * 64, 0, true);
        }
      }
      const int id = __shfl_sync(~0u, role(), 0);
      const bool dbl = NCL == 66 && id >= 58;
      for (int t = dbl ? 2 * id - 72 : id; t < (dbl ? NOTILES : nsingle); t += ncl) {
        const int row0 = row_block(t) * 256 + rank * 128;
        const int b0 = (row0 & ~31) / SQ, b1 = (row0 + 127) / SQ;
#pragma unroll 1
        for (int ks = 0; ks < 64; ks++) {
          if (dbl ? (ks & 15) == 0 : ks == 0 || ks == 48) {
            const unsigned* c = &g_cnt[((lane & 1 ? b1 : b0) * 4 + (ks || dbl ? ks >> 4 : min(lane >> 1, 2))) * 8];
            unsigned v, n = 0;
            do {
              asm volatile("ld.acquire.gpu.global.u32 %0, [%1];" : "=r"(v) : "l"(c) : "memory");
              if (++n > (1u << 26)) __trap();
            } while (v < 16);
            __syncwarp();
            asm volatile("fence.proxy.async.global;" ::: "memory");
          }
          mbar_wait(sb + BAR_REMPTY + 8 * r.slot, r.phase ^ 1);
          if (lane == 0) {
            mbar_expect(sb + BAR_RFULL + 8 * r.slot, RING_BYTES);
            asm volatile("cp.async.bulk.tensor.4d.shared::cluster.global.mbarrier::complete_tx::bytes.L2::cache_hint [%0], [%1, {%3, %3, %4, %5}], [%2], %6;"
                         ::"r"(sb + r.slot * RING_BYTES), "l"(&tm_o), "r"(sb + BAR_RFULL + 8 * r.slot), "r"(0), "r"((dbl ? ks : bk(ks)) * 8), "r"(row0 >> 6), "l"(pol) : "memory");
          }
          r.next();
        }
      }
      if (lane == 0 && atomicAdd(&g_cnt[64 * 8], 1) == gridDim.x - 1) {
        for (int i = 0; i < 67; i++) g_cnt[i * 8] = 0;
      }
    } else if (warp == 9) {
      if (lane == 0) {
        uint32_t it = 0;
        for (;; it++) {
          const int u = (it >= 3 ? role() : cl) + it * ncl;
          if (u >= NUNITS) break;
          const int row = unit_batch(u) * SQ + rank * 120;
#pragma unroll 1
          for (int s = EARLY && it == 0 ? EARLY_X : 0; s < 10; s++) {
            const uint32_t j = s & 3, par = ((s >> 2) + (j < 2 ? it : 0)) & 1;
            if ((SLP & 4) && s == 0) mbar_sleep(sb + BAR_XEMPTY, par ^ 1);
            mbar_wait(sb + BAR_XEMPTY + 8 * j, par ^ 1);
            const uint32_t fb = sb + BAR_XFULL + 32 * rank + 8 * j;
            mbar_expect(fb, XB);
            mbar_expect_cl(mapa(fb, rank ^ 1), XB);
            tma2d_mc(sb + OFF_Q + x_slot(rank, j), &tm_x, s * 64, row, fb);
          }
        }
        const int id = role();
        const bool dbl = NCL == 66 && id >= 58;
        uint32_t slot = rank, phase = 0;
        if (WO_PF0 && dbl)
          asm volatile("cp.async.bulk.prefetch.tensor.3d.L2.global [%0, {%1, %2, %3}];" ::"l"(&tm_wo), "r"(0), "r"((2 + ((id >> 1) & 3)) * 64), "r"(((2 * id - 72 + rank) & 3) * 5) : "memory");
        if ((SLP & 4) && (dbl || id < nsingle)) mbar_sleep(sb + BAR_BEMPTY + 8 * rank, 0);
        for (int t = dbl ? 2 * id - 72 + rank : id; t < (dbl ? NOTILES : nsingle); t += ncl) {
#pragma unroll 1
          for (int ks = dbl ? 0 : rank; ks < 64; ks += dbl ? 1 : 2) {
            mbar_wait(sb + BAR_BEMPTY + 8 * slot, phase);
            const uint32_t fb = sb + BAR_BFULL + 8 * slot;
            mbar_expect(fb, BB);
            mbar_expect_cl(mapa(fb, rank ^ 1), BB);
            tma3d_mc(sb + OFF_Q + slot * BB, &tm_wo, 0, (dbl ? ks : bk(ks)) * 64, (t & 3) * 5, fb);
            if (WO_PF && dbl && ks + WO_PF < 64 && (ks & 3) == ((id >> 1) & 3))
              asm volatile("cp.async.bulk.prefetch.tensor.3d.L2.global [%0, {%1, %2, %3}];" ::"l"(&tm_wo), "r"(0), "r"((ks + WO_PF) * 64), "r"((t & 3) * 5) : "memory");
            slot += 2;
            if (slot >= 6) { slot -= 6; phase ^= 1; }
          }
        }
      }
    } else {
      const int wg = warp - 10;
      {
        mbar_wait(sb + BAR_RFULL, 0);
        const __nv_bfloat16* xs = P.x + (size_t)(unit_batch(cl) * SQ + ((cl & 3) * 2 + rank) * 30 + min(lane, 29)) * DM + 256 + wg * 64;
#pragma unroll
        for (int i = 0; i < 3; i++) asm volatile("prefetch.global.L2 [%0];" ::"l"(xs + i * 128));
        if (lane < 16) asm volatile("prefetch.global.L2 [%0];" ::"l"(P.wq + (size_t)(384 + unit_batch(cl) * 16 + lane) * HD + unit_head(cl, rank) * DH + wg * 64));
      }
      auto take_role = [&]() {
          if (wg == 0 && rank == 0 && lane == 0) {
            int id = cl;
            if (NCL == 66) {
              uint32_t smid;
              asm("mov.u32 %0, %smid;" : "=r"(smid));
              id = smid >= SMID_TOP ? 65 - atomicAdd(&g_cnt[65 * 8], 1) : atomicAdd(&g_cnt[66 * 8], 1);
            }
    #pragma unroll
            for (int c = 0; c < 2; c++) {
              const uint32_t a = mapa(sb + BAR_ROLE, c);
              asm volatile("st.shared::cluster.u32 [%0 + 8], %1;\nmbarrier.arrive.release.cluster.shared::cluster.b64 _, [%0];" ::"r"(a), "r"(id) : "memory");
            }
          }
          if (wg == 0 && lane == 0) {
            mbar_wait_cl(sb + BAR_ROLE, 0);
            mbar_arrive(sb + BAR_ROLE + 16);
          }
      };
      if (ROLE_AT < 0) { take_role(); __syncwarp(); }
      for (uint32_t it = 0;; it++) {
        const int u = __shfl_sync(~0u, (it >= 3 ? role() : cl) + it * ncl, 0);
        if (u >= NUNITS) break;
        if (SLP & 1) mbar_sleep(sb + BAR_LSUM + 8 * wg, it & 1); else mbar_wait(sb + BAR_LSUM + 8 * wg, it & 1);
        float l4[4], v[4];
        const uint32_t a = sb + OFF_L2 + wg * 2048 + lane * 16;
        asm volatile("ld.shared.v4.f32 {%0, %1, %2, %3}, [%4];" : "=f"(l4[0]), "=f"(l4[1]), "=f"(l4[2]), "=f"(l4[3]) : "r"(a) : "memory");
#pragma unroll
        for (int g = 1; g < 4; g++) {
          asm volatile("ld.shared.v4.f32 {%0, %1, %2, %3}, [%4];" : "=f"(v[0]), "=f"(v[1]), "=f"(v[2]), "=f"(v[3]) : "r"(a + g * 512) : "memory");
#pragma unroll
          for (int c = 0; c < 4; c++) l4[c] += v[c];
        }
#pragma unroll
        for (int c = 0; c < 4; c++) {
          float inv;
          asm("rcp.approx.ftz.f32 %0, %1;" : "=f"(inv) : "f"(l4[c]));
          l4[c] = l4[c] >= L_MIN && l4[c] <= L_MAX ? inv : __uint_as_float(0x7FFFFFFFu);
        }
        const uint32_t h0 = pack(l4[0], l4[1]), h1 = pack(l4[2], l4[3]);
        const uint32_t e0 = pack(l4[0] - __uint_as_float(h0 << 16), l4[1] - __uint_as_float(h0 & 0xFFFF0000u));
        const uint32_t e1 = pack(l4[2] - __uint_as_float(h1 << 16), l4[3] - __uint_as_float(h1 & 0xFFFF0000u));
        asm volatile("st.shared.v4.u32 [%0], {%1, %2, %3, %4};" ::"r"(sb + OFF_INV + wg * 640 + (lane & 3) * 144 + (lane >> 2) * 16), "r"(h0), "r"(e0), "r"(h1), "r"(e1) : "memory");
        __syncwarp();
        if (lane == 0) {
          mbar_arrive(sb + BAR_INV + 8 * wg);
          if ((int)it == ROLE_AT) {
            take_role();
          }
          if (SLP & 2) mbar_sleep(sb + BAR_STAGE + 8 * wg, it & 1); else mbar_wait(sb + BAR_STAGE + 8 * wg, it & 1);
          __threadfence();
          asm volatile("red.relaxed.gpu.global.add.u32 [%0], 1;" ::"l"(&g_cnt[(unit_batch(u) * 4 + (u >> 6)) * 8]) : "memory");
        }
        __syncwarp();
      }
    }
  } else {
    asm volatile("setmaxnreg.inc.sync.aligned.u32 240;");
    const int wg = warp >> 2, w = warp & 3;
    const uint32_t qreg = sb + OFF_Q + wg * 2 * XB, preg = sb + OFF_P + (2 + wg) * XB;
    const uint32_t st_off = ((lane >> 4) * 8 + (lane & 7)) * 128 + (((2 * w + ((lane >> 3) & 1)) ^ (lane & 7)) << 4);
    const uint32_t xempty = mapa(sb + BAR_XEMPTY, wg);
    Ring r;
    uint32_t it = 0;
    const uint32_t qd = (qreg & 0x3FFFF) >> 4, pd = (preg & 0x3FFFF) >> 4;
    auto ring_addr = [&]() { return ((sb & 0x3FFFF) + r.slot * RING_BYTES) >> 4; };
    auto ring_wait = [&]() { mbar_wait(sb + BAR_RFULL + 8 * r.slot, r.phase); };
    auto release = [&](uint32_t slot) { warp_arrive(sb + BAR_REMPTY + 8 * slot); };
    auto turn_wait = [&]() {
      if (wg == 0) asm volatile("bar.sync 3, 256;" ::: "memory");
      else asm volatile("bar.sync 4, 256;" ::: "memory");
    };
    auto turn_pass = [&]() {
      if (wg == 0) asm volatile("bar.arrive 4, 256;" ::: "memory");
      else asm volatile("bar.arrive 3, 256;" ::: "memory");
    };

    uint32_t chk = 0;
    auto sum_l = [&](const float (&l)[30], uint32_t tid) {
        float a[16], b[8], c[4];
        const bool b4 = tid & 16, b3 = tid & 8, b2 = tid & 4;
#pragma unroll
        for (int i = 0; i < 16; i++) {
          const float hi = i < 14 ? l[(16 + i) % 30] : 1.f;
          a[i] = (b4 ? hi : l[i]) + __shfl_xor_sync(~0u, b4 ? l[i] : hi, 16);
        }
#pragma unroll
        for (int i = 0; i < 8; i++) b[i] = (b3 ? a[8 + i] : a[i]) + __shfl_xor_sync(~0u, b3 ? a[i] : a[8 + i], 8);
#pragma unroll
        for (int i = 0; i < 4; i++) c[i] = (b2 ? b[4 + i] : b[i]) + __shfl_xor_sync(~0u, b2 ? b[i] : b[4 + i], 4);
        asm volatile("st.shared.v4.f32 [%0], {%1, %2, %3, %4};" ::"r"(sb + OFF_L2 + tid * 16), "f"(c[0]), "f"(c[1]),
                     "f"(c[2]), "f"(c[3]) : "memory");
        __syncwarp();
        warp_arrive(sb + BAR_LSUM + 8 * wg);
    };
    auto load_inv = [&](uint32_t (&iv)[30], uint32_t parity) {
      const int lane = fresh_tid() & 31;
      mbar_wait(sb + BAR_INV + 8 * wg, parity);
      chk = 0;
#pragma unroll
      for (int j = 0; j < 7; j++)
        asm volatile("ld.shared.v4.u32 {%0, %1, %2, %3}, [%4];" : "=r"(iv[4 * j]), "=r"(iv[4 * j + 1]), "=r"(iv[4 * j + 2]), "=r"(iv[4 * j + 3])
                     : "r"(sb + OFF_INV + wg * 640 + (lane & 3) * 144 + j * 16) : "memory");
      asm volatile("ld.shared.v2.u32 {%0, %1}, [%2];" : "=r"(iv[28]), "=r"(iv[29]) : "r"(sb + OFF_INV + wg * 640 + (lane & 3) * 144 + 112) : "memory");
    };
    auto norm = [&](uint32_t (&n)[8], const uint32_t (&po)[60], const uint32_t (&iv)[30], auto part) {
      constexpr int k = decltype(part)::value >> 1, j0 = (decltype(part)::value & 1) * 8;
#pragma unroll
      for (int j = 0; j < 8; j++)
        n[j] = j0 + j < 15 ? hfma2(po[15 * k + (j0 + j) % 15], iv[2 * ((j0 + j) % 15)], hfma2(po[15 * k + (j0 + j) % 15], iv[2 * ((j0 + j) % 15) + 1], 0x80008000u)) : 0x3F803F80u;
#pragma unroll
      for (int j = 0; j < 8; j += 2) chk = hfma2(n[j], n[j + 1], chk);
    };
    int od1, od2;
    auto store = [&](const uint32_t (&n)[8], const char* optr, auto part) {
      constexpr int k = decltype(part)::value >> 1, off = (8 * (k & 1) + 64 * (k >> 1)) * NROWS * 2;
      if ((decltype(part)::value & 1) == 0)
        asm volatile(
            "{\n.reg .pred p;\nsetp.ne.u64 p, %8, 0;\n"
            "@p st.global.v4.u32 [%8 + %9], {%0, %1, %2, %3};\n@p st.global.v4.u32 [%8 + %9 + 512], {%4, %5, %6, %7};\n}\n"
            ::"r"(n[0]), "r"(n[1]), "r"(n[2]), "r"(n[3]), "r"(n[4]), "r"(n[5]), "r"(n[6]), "r"(n[7]), "l"(optr), "n"(off) : "memory");
      else
        asm volatile(
            "{\n.reg .pred p;\n.reg .b64 b, c;\nsetp.ne.u64 p, %7, 0;\nmad.wide.s32 b, %9, 1, %7;\nmad.wide.s32 c, %10, 1, %7;\n"
            "@p st.global.v4.u32 [%7 + %8 + 1024], {%0, %1, %2, %3};\n@p st.global.v2.u32 [b + %8], {%4, %5};\n@p st.global.u32 [c + %8], %6;\n}\n"
            ::"r"(n[0]), "r"(n[1]), "r"(n[2]), "r"(n[3]), "r"(n[4]), "r"(n[5]), "r"(n[6]), "l"(optr), "n"(off), "r"(od1), "r"(od2) : "memory");
    };
    auto put = [&](const uint32_t (&po)[60], const uint32_t (&iv)[30], const char* optr, auto part) {
      uint32_t n[8];
      norm(n, po, iv, part);
      store(n, optr, part);
    };
    auto out_ptr = [&](int u) {
      const int lane = fresh_tid() & 31;
      const int k = unit_head(u, rank) * DH + 16 * w + (lane >> 2), b = unit_batch(u), q = lane & 3;
      const uint32_t i0 = o_idx(k, o_pos(b, wg, 2 * q));
      od1 = 2 * (int)(o_idx(k, o_pos(b, wg, 96 + 2 * q)) - i0);
      od2 = 2 * (int)(o_idx(k, o_pos(b, wg, 112 + 2 * q)) - i0);
      return reinterpret_cast<const char*>(P.o + i0);
    };
    auto unsafe = [&](bool valid) {
      const bool b = valid && ((chk & 0x7F80u) == 0x7F80u || (chk & 0x7F800000u) == 0x7F800000u);
      return __any_sync(~0u, bar_red_or(wg, b));
    };
    auto publish = [&]() { __syncwarp(); warp_arrive(sb + BAR_STAGE + 8 * wg); };

    uint32_t po[60];
    float l[30];
#pragma unroll
    for (int i = 0; i < 30; i++) l[i] = 0.f;
#pragma unroll
    for (int i = 0; i < 60; i++) po[i] = 0;
    int id = 0;
    float o0[60], o1[60];
    TR(0);
    ring_wait();
    TR(1);
    mbar_wait(sb + BAR_XFULL + 32 * wg, 0);
    TR(2);
    TI(0);
    wg_fence();
    mma_tn(o0, o1, ring_addr(), qd, 0);
    wg_commit();
    while (true) {
      uint32_t prev = r.slot;
      r.next();
      auto qstep = [&](int s, int acc) {
        const uint32_t j = s & 3, par = ((s >> 2) + (j < 2 ? it : 0)) & 1;
        TR(it * 160 + 3 * s);
        ring_wait();
        TR(it * 160 + 3 * s + 1);
        mbar_wait(sb + BAR_XFULL + 32 * wg + 8 * j, par);
        TR(it * 160 + 3 * s + 2);
        if (s >= ALT_FROM) turn_wait();
        TI(s);
        wg_fence();
        mma_tn(o0, o1, ring_addr(), ((sb & 0x3FFFF) + OFF_Q + x_slot(wg, j)) >> 4, acc);
        wg_commit();
        if (s >= ALT_FROM || (s == ALT_FROM - 1 && wg == 1)) turn_pass();
        if (s > 0 && s <= EREL_FROM) {
          wg_wait<1>();
          release(prev);
          if (s <= 6) warp_arrive_cl(xempty + 8 * ((s - 1) & 3));
        }
        prev = r.slot;
        r.next();
      };
      auto qdone = [&](int s) {
        if (s >= EREL_FROM) {
          wg_wait<0>();
          release(prev);
          if (s <= 5) warp_arrive_cl(xempty + 8 * (s & 3));
        }
      };
      if (LSUM_AT == 1 && it > 0) sum_l(l, fresh_tid());
      qstep(1, 1);
      if (LSUM_AT == 2 && it > 0) sum_l(l, fresh_tid());
      if (PUT_FROM == 2) qstep(2, 1);
      const int up = (it > 3 ? id : cl) + ((int)it - 1) * ncl;
      const char* optr = out_ptr(up);
      if (it == 0) optr = nullptr;
      uint32_t n7[8];
      {
        uint32_t iv[30];
        load_inv(iv, (it + 1) & 1); put(po, iv, optr, IC<0>());
        if (PUT_FROM == 1) {
          qstep(2, 1); put(po, iv, optr, IC<1>()); qdone(2);
          qstep(3, 1); put(po, iv, optr, IC<2>()); qdone(3);
          qstep(4, 1); put(po, iv, optr, IC<3>()); qdone(4);
          qstep(5, 1); put(po, iv, optr, IC<4>()); qdone(5);
        } else {
          qstep(3, 1); put(po, iv, optr, IC<1>()); qdone(3);
          qstep(4, 1); put(po, iv, optr, IC<2>()); qdone(4);
          qstep(5, 1); put(po, iv, optr, IC<3>()); put(po, iv, optr, IC<4>()); qdone(5);
        }
        qstep(6, 1); put(po, iv, optr, IC<5>()); qdone(6);
        qstep(7, 1); put(po, iv, optr, IC<6>()); norm(n7, po, iv, IC<7>()); qdone(7);
        if (LATE_AT == 3 || (LATE_AT == 5 && wg == 1)) store(n7, optr, IC<7>());
      }
      TR(it * 160 + 24);
      const uint32_t a8 = ring_addr(), slot8 = r.slot;
      ring_wait();
      r.next();
      TR(it * 160 + 25);
      mbar_wait(sb + BAR_XFULL + 32 * wg, it & 1);
      TR(it * 160 + 26);
      auto wait9 = [&]() {
        TR(it * 160 + 27);
        ring_wait();
        TR(it * 160 + 28);
        mbar_wait(sb + BAR_XFULL + 32 * wg + 8, it & 1);
        TR(it * 160 + 29);
      };
      if (PRE9 == 1 || (PRE9 == 2 && wg == 1)) wait9();
      if (PRE9 == 3) ring_wait();
      turn_wait();
      TI(8);
      wg_fence();
      mma_tn(o0, o1, a8, qd, 1);
      wg_commit();
      if (PRE9 == 0 || (PRE9 == 2 && wg == 0)) wait9();
      if (PRE9 == 3) mbar_wait(sb + BAR_XFULL + 32 * wg + 8, it & 1);
      TI(9);
      if (PRE9 != 1) wg_fence();
      mma_tn_split(o0, o1, ring_addr(), qd + (XB >> 4));
      if (PASS9 == 0 || (PASS9 == 3 && wg == 0) || (PASS9 == 4 && wg == 1)) turn_pass();
      wg_wait<2>();
      if (PASS9 == 1) turn_pass();
      if (EREL_FROM > 7) release(prev);
      release(slot8);
      if (LATE_AT == 4 || (LATE_AT == 5 && wg == 0)) store(n7, optr, IC<7>());
      auto put_q = [&](const float (&o)[60], uint32_t dst) {
#pragma unroll
        for (int j = 0; j < 14; j += 2)
          stsm4t(dst + j * 1024, pack(o[4 * j] * QSCALE, o[4 * j + 1] * QSCALE), pack(o[4 * j + 2] * QSCALE, o[4 * j + 3] * QSCALE),
                 pack(o[4 * j + 4] * QSCALE, o[4 * j + 5] * QSCALE), pack(o[4 * j + 6] * QSCALE, o[4 * j + 7] * QSCALE));
        stsm2t(dst + 14 * 1024, pack(o[56] * QSCALE, o[57] * QSCALE), pack(o[58] * QSCALE, o[59] * QSCALE));
      };
      wg_wait<1>();
      if (PASS9 == 2 || (PASS9 == 3 && wg == 1) || (PASS9 == 4 && wg == 0)) turn_pass();
      reg_fence(o0);
      bool redo;
      if (EARLY_VOTE) redo = unsafe(it > 0); else bar_sync(wg);
      put_q(o0, qreg + st_off);
      wg_wait<0>();
      reg_fence(o1);
      release(r.slot);
      r.next();
      TR(it * 160 + 30);
      bar_sync(wg);
      put_q(o1, qreg + XB + st_off);
      fence_async_smem();
      if (!EARLY_VOTE) redo = unsafe(it > 0);
      if (redo) {
        slow_path(P, unit_batch(up), unit_head(up, rank), wg, w, fresh_tid() & 31);
        optr = nullptr;
        if (!DPRO) {
#pragma unroll
          for (int i = 0; i < 60; i++) o0[i] = o1[i] = 0.f;
        }
      }
      TR(it * 160 + 32); TG(it * 160 + 142);

      float sc[60];
      uint32_t slot0 = r.slot;
      ring_wait();
      TR(it * 160 + 33);
      turn_wait();
      TI(10);
      wg_fence();
      mma_qk(sc, ring_addr(), qd);
      wg_commit();
      r.next();
      uint32_t slot1 = r.slot;
      ring_wait();
      TI(11);
      wg_fence();
      mma_qk(o1, ring_addr(), qd);
      wg_commit();
      r.next();
      turn_pass();
      if (LATE_AT == 0) store(n7, optr, IC<7>());
      wg_wait<1>();
      reg_fence(sc);
      TR(it * 160 + 35);
      release(slot0);
      exp_store<0, 15, true>(sc, l, preg + st_off);
      TR(it * 160 + 38); TG(it * 160 + 43);
      slot0 = r.slot;
      if (K2_AT > 0) {
        wg_wait<0>();
        reg_fence(o1);
        release(slot1);
        exp_store<0, K2_AT>(o1, l, preg - 2 * XB + st_off);
      }
      ring_wait();
      TI(12);
      wg_fence();
      mma_qk(sc, ring_addr(), qd);
      wg_commit();
      r.next();
      if (K2_AT == 0) {
        wg_wait<1>();
        reg_fence(o1);
        release(slot1);
      }
      TR(it * 160 + 41);
      exp_store<K2_AT, 15>(o1, l, preg - 2 * XB + st_off);
      fence_async_smem();
      TR(it * 160 + 44);
      slot1 = r.slot;
      ring_wait();
      turn_wait();
      TI(13);
      wg_fence();
      mma_tn(o0, o1, ring_addr(), pd, 0);
      wg_commit();
      r.next();
      ring_wait();
      wg_fence();
      mma_tn(o0, o1, ring_addr(), pd - (2 * XB >> 4), 1);
      wg_commit();
      turn_pass();
      if (LATE_AT == 1) store(n7, optr, IC<7>());
      if (it > 0) publish();
      id = __shfl_sync(~0u, it >= 2 ? role() : 0, 0);
      wg_wait<1>();
      reg_fence(sc);
      release(slot0);
      release(slot1);
      bar_sync(wg);
      TR(it * 160 + 47);
      exp_store<0, VREL>(sc, l, preg + st_off);
      wg_wait<0>();
      reg_fence(o0); reg_fence(o1);
      release(r.slot);
      r.next();
      exp_store<VREL, 15>(sc, l, preg + st_off);
      fence_async_smem();
      const bool more = id + ((int)it + 1) * ncl < NUNITS;
      const bool gemm = id < nsingle || (NCL == 66 && id >= 58);
#pragma unroll 1
      for (int s = DPRO ? 3 : 1; s < 16; s++) {
        const uint32_t kslot = r.slot;
        TR(it * 160 + 32 + 6 * s); TG(it * 160 + 37 + 6 * s);
        if (s == 8) TRL(it * 160 + 139);
        ring_wait();
        TR(it * 160 + 33 + 6 * s);
        turn_wait();
        TI(11 + s);
        wg_fence();
        mma_qk(sc, ring_addr(), qd);
        wg_commit();
        r.next();
        TR(it * 160 + 36 + 6 * s);
        ring_wait();
        TR(it * 160 + 34 + 6 * s);
        wg_fence();
        mma_tn(o0, o1, ring_addr(), pd - ((s - 1) & 1) * (2 * XB >> 4), DPRO || s != 1);
        wg_commit();
        if (wg == 0 || s < 15) turn_pass();
        wg_wait<1>();
        reg_fence(sc);
        TR(it * 160 + 35 + 6 * s);
        release(kslot);
        if (s == 15) {
          if (more) { warp_arrive_cl(xempty); warp_arrive_cl(xempty + 8); }
          else if (gemm) for (int i = 0; i < 3; i++) warp_arrive_cl(mapa(sb + BAR_BEMPTY + 8 * i, i & 1));
        }
        exp_store<0, VREL>(sc, l, preg - (s & 1) * 2 * XB + st_off);
        wg_wait<0>();
        reg_fence(o0); reg_fence(o1);
        release(r.slot);
        r.next();
        exp_store<VREL, 15>(sc, l, preg - (s & 1) * 2 * XB + st_off);
        fence_async_smem();
      }
      const uint32_t tid = fresh_tid();
      bar_sync(wg);
      TR(it * 160 + 128);
      ring_wait();
      TI(27);
      wg_fence();
      mma_tn_split(o0, o1, ring_addr(), pd - (2 * XB >> 4));
      if (LSUM_AT == 0) sum_l(l, tid);
      const uint32_t vslot = r.slot;
      r.next();
      it++;
      auto pack_o = [&](const float (&o)[60], int first) {
#pragma unroll
        for (int j = 0; j < 15; j++) { po[first + j] = pack(o[4 * j], o[4 * j + 1]); po[first + 15 + j] = pack(o[4 * j + 2], o[4 * j + 3]); }
      };
      if (!more) {
        if (LSUM_AT != 0) sum_l(l, tid);
        wg_wait<0>();
        reg_fence(o0); reg_fence(o1);
        release(vslot);
        if (gemm) for (int i = 3; i < 6; i++) warp_arrive_cl(mapa(sb + BAR_BEMPTY + 8 * i, i & 1));
        pack_o(o0, 0); pack_o(o1, 30);
        TR(it * 160 - 160 + 131); TG(it * 160 - 160 + 143);
        break;
      }
      TR(it * 160 - 160 + 131); TG(it * 160 - 160 + 143);
      TR(it * 160);
      ring_wait();
      TR(it * 160 + 1);
      mbar_wait(sb + BAR_XFULL + 32 * wg, it & 1);
      TR(it * 160 + 2);
      wg_wait<1>();
      reg_fence(o0);
      pack_o(o0, 0);
      TI(0);
      wg_fence();
#pragma unroll
      for (int k = 0; k < 4; k++) wgmma_n120<1, 0>(o0, ring_addr() + k * 128, HI128, qd + k * 2, HI128, k != 0);
      wg_commit();
      wg_wait<1>();
      reg_fence(o1);
      pack_o(o1, 30);
      wg_fence();
#pragma unroll
      for (int k = 0; k < 4; k++) wgmma_n120<1, 0>(o1, ring_addr() + 512 + k * 128, HI128, qd + k * 2, HI128, k != 0);
      wg_commit();
      release(vslot);
      warp_arrive_cl(xempty + 16); warp_arrive_cl(xempty + 24);
    }
    const bool gemm = id < nsingle || (NCL == 66 && id >= 58);
    const int u = (it > 3 ? id : cl) + ((int)it - 1) * ncl;
    uint32_t pb[60];
#pragma unroll
    for (int i = 0; i < 60; i++) pb[i] = NCL != 66 ? po[i] ^ (gridDim.y - 1) : po[i];

    uint32_t bslot = 0, bphase = 0;
    auto out_row = [&](int lane) {
      const int row = lane & 15;
      return sb + wg * 8192 + (row < 12 ? w * RING_BYTES + row * 656 : (4 + (w >> 1)) * RING_BYTES + ((w & 1) * 4 + row - 12) * 656);
    };
    auto out_stage = [&](const float (&acc)[80], uint32_t col_off) {
      const int lane = fresh_tid() & 31;
      const uint32_t sa = out_row(lane) + col_off + (lane >> 4) * 16;
#pragma unroll
      for (int j = 0; j < 20; j += 2)
        asm volatile("stmatrix.sync.aligned.m8n8.x4.shared.b16 [%0], {%1,%2,%3,%4};" ::"r"(sa + j * 16), "r"(pack(acc[4 * j], acc[4 * j + 1])),
                     "r"(pack(acc[4 * j + 2], acc[4 * j + 3])), "r"(pack(acc[4 * j + 4], acc[4 * j + 5])), "r"(pack(acc[4 * j + 6], acc[4 * j + 7])) : "memory");
    };
    auto out_store = [&](int t, uint32_t bytes) {
      const int lane = fresh_tid() & 31;
      if (EPI_MIX && wg == 1) {
        __syncwarp();
#pragma unroll 1
        for (int h = 0; h < 2; h++) {
          const int row = h * 8 + (lane >> 2);
          const uint32_t src = out_row(row) + (lane & 3) * 16;
          char* dst = reinterpret_cast<char*>(P.out + (size_t)o_row(row_block(t) * 256 + rank * 128 + 64 + w * 16 + row) * DM + (t & 3) * 160) + (lane & 3) * 16;
#pragma unroll 1
          for (uint32_t c = 0; c < bytes; c += 320) {
            uint4 v[5];
#pragma unroll
            for (int i = 0; i < 5; i++)
              asm volatile("ld.shared.v4.u32 {%0, %1, %2, %3}, [%4];" : "=r"(v[i].x), "=r"(v[i].y), "=r"(v[i].z), "=r"(v[i].w) : "r"(src + c + i * 64) : "memory");
#pragma unroll
            for (int i = 0; i < 5; i++) *reinterpret_cast<uint4*>(dst + c + i * 64) = v[i];
          }
        }
        return;
      }
      fence_async_smem();
      __syncwarp();
      if (lane < 16) {
        __nv_bfloat16* dst = P.out + (size_t)o_row(row_block(t) * 256 + rank * 128 + wg * 64 + w * 16 + lane) * DM + (t & 3) * 160;
        asm volatile("cp.async.bulk.global.shared::cta.bulk_group [%0], [%1], %2;" ::"l"(dst), "r"(out_row(lane)), "r"(bytes) : "memory");
        asm volatile("cp.async.bulk.commit_group;" ::: "memory");
        asm volatile("cp.async.bulk.wait_group.read 0;" ::: "memory");
      }
    };
    for (int t = id; t == id || (NCL != 66 && t < nsingle); t += ncl) {
      float acc[80];
      uint32_t prev = 0, bprev = 0;
      const bool tile = t < nsingle;
      const bool last = NCL == 66 || t + ncl >= nsingle;
      auto bstep = [&](int ks, int accf) {
        if (!(ks & 3)) TR(640 + ks / 2); if ((ks & 7) == 0) TG(144 + (ks >> 3));
        ring_wait();
        mbar_wait(sb + BAR_BFULL + 8 * bslot, bphase);
        if (!(ks & 3)) TR(641 + ks / 2);
        wg_fence();
        const uint32_t a = ring_addr() + wg * 512, bd = (((sb & 0x3FFFF) + OFF_Q + bslot * BB) >> 4) | ((4096u >> 4) << 16);
#pragma unroll
        for (int k = 0; k < 4; k++) wgmma_n160<1, 1>(acc, a + LBO64A + k * 128, HI64A, bd + k * 64, HI64, k == 0 ? accf : 1);
        wg_commit();
        if (ks > 0) {
          wg_wait<1>();
          release(prev);
          if (ks < 59 || !last) warp_arrive_cl(mapa(sb + BAR_BEMPTY + 8 * bprev, bprev & 1));
        }
        prev = r.slot; bprev = bslot;
        r.next();
        if (++bslot == 6) { bslot = 0; bphase ^= 1; }
      };
      const char* optr;
      uint32_t iv[30], n2[8], n3[8], n4[8], n5[8], n6[8], n7[8];
      if (tile) {
        bstep(0, 0);
        bstep(1, 1);
        optr = out_ptr(u);
        if (t != id) optr = nullptr;
        load_inv(iv, (it + 1) & 1);
#pragma unroll 1
        for (int ks = 2; ks < 17; ks++) {
          bstep(ks, 1);
          switch (ks) {
            case 2: put(pb, iv, optr, IC<0>()); break;
            case 4: put(pb, iv, optr, IC<1>()); break;
            case 6: put(pb, iv, optr, IC<2>()); break;
            case 8: put(pb, iv, optr, IC<3>()); break;
            case 10: put(pb, iv, optr, IC<4>()); break;
            case 12: put(pb, iv, optr, IC<5>()); break;
            case 14: put(pb, iv, optr, IC<6>()); break;
            case 16: put(pb, iv, optr, IC<7>()); break;
            default: break;
          }
        }
        wg_wait<0>();
        reg_fence(acc);
#pragma unroll
        for (int i = 0; i < 8; i++) n2[i] = n3[i] = n4[i] = n5[i] = n6[i] = n7[i] = 0;
      } else {
        Ring r2 = r;
        auto first = [&](int ks) {
          if (ks == 0) { TR(640); TG(144); }
          if (gemm) { mbar_wait(sb + BAR_RFULL + 8 * r2.slot, r2.phase); mbar_wait(sb + BAR_BFULL + 16 * ks, 0); }
          wg_fence();
          const uint32_t a = (((sb & 0x3FFFF) + r2.slot * RING_BYTES) >> 4) + wg * 512;
          const uint32_t bd = (((sb & 0x3FFFF) + OFF_Q + 2 * ks * BB) >> 4) | ((4096u >> 4) << 16);
#pragma unroll
          for (int k = 0; k < 4; k++) wgmma_n160<1, 1>(acc, a + LBO64A + k * 128, HI64A, bd + k * 64, HI64, k + ks != 0);
          wg_commit();
          r2.next();
        };
        if (gemm) TR(480);
        first(0);
        first(1);
        if (gemm) TR(481);
        optr = out_ptr(u);
        load_inv(iv, (it + 1) & 1);
        if (gemm) TR(482);
        put(pb, iv, optr, IC<0>()); put(pb, iv, optr, IC<1>());
        norm(n2, pb, iv, IC<2>()); norm(n3, pb, iv, IC<3>()); norm(n4, pb, iv, IC<4>());
        norm(n5, pb, iv, IC<5>()); norm(n6, pb, iv, IC<6>()); norm(n7, pb, iv, IC<7>());
        if (gemm) TR(483);
        wg_wait<0>();
        reg_fence(acc);
      }
      if (unsafe(t == id)) {
        slow_path(P, unit_batch(u), unit_head(u, rank), wg, w, fresh_tid() & 31);
        optr = nullptr;
#pragma unroll
        for (int i = 0; i < 8; i++) n2[i] = n3[i] = n4[i] = n5[i] = n6[i] = n7[i] = 0;
      }
      if (tile && t == id) publish();
      if (!tile) {
        if (gemm) {
          float ac1[80];
          auto half = [&](float (&ac)[80], bool rel, int accf) {
            mbar_wait(sb + BAR_BFULL + 8 * bslot, bphase);
            wg_fence();
            const uint32_t a = ring_addr() + wg * 512, bd = (((sb & 0x3FFFF) + OFF_Q + bslot * BB) >> 4) | ((4096u >> 4) << 16);
#pragma unroll
            for (int k = 0; k < 4; k++) wgmma_n160<1, 1>(ac, a + LBO64A + k * 128, HI64A, bd + k * 64, HI64, k == 0 ? accf : 1);
            wg_commit();
            wg_wait<1>();
            if (rel) warp_arrive_cl(mapa(sb + BAR_BEMPTY + 8 * bprev, bprev & 1));
            bprev = bslot;
          };
          auto dstep = [&](int ks) {
            if (!(ks & 3)) TR(640 + ks / 2); if ((ks & 7) == 0) TG(144 + (ks >> 3));
            ring_wait();
            if (!(ks & 3)) TR(641 + ks / 2);
            half(acc, ks < 62, 1);
            release(prev);
            bslot++;
            half(ac1, ks < 61, 1);
            if (++bslot == 6) { bslot = 0; bphase ^= 1; }
            prev = r.slot; r.next();
          };
          TR(484);
          warp_arrive_cl(mapa(sb + BAR_BEMPTY, 0));
          bprev = 2; bslot = 1;
          half(ac1, true, 0);
          prev = r.slot; r.next(); bslot = 3;
          half(ac1, true, 1);
          release(prev); prev = r.slot; r.next(); bslot = 4;
          TR(485);
#pragma unroll 1
          for (int ks = 2; ks < 8; ks++) {
            dstep(ks);
            switch (ks) {
              case 2: store(n2, optr, IC<2>()); break;
              case 3: store(n3, optr, IC<3>()); break;
              case 4: store(n4, optr, IC<4>()); break;
              case 5: store(n5, optr, IC<5>()); break;
              case 6: store(n6, optr, IC<6>()); break;
              default: store(n7, optr, IC<7>()); break;
            }
          }
          publish();
#pragma unroll 1
          for (int ks = 8; ks < 64; ks++) {
            if (wg == 1 && ks == 62) turn_wait();
            dstep(ks);
          }
          if (wg == 0) turn_pass();
          wg_wait<0>();
          reg_fence(acc); reg_fence(ac1);
          TRL(158); TG(156);
          bar_sync(wg);
          out_stage(acc, 0);
          out_stage(ac1, 320);
          out_store(2 * id - 72, 640);
        } else {
          store(n2, optr, IC<2>()); store(n3, optr, IC<3>()); store(n4, optr, IC<4>()); store(n5, optr, IC<5>()); store(n6, optr, IC<6>()); store(n7, optr, IC<7>());
          publish();
        }
        break;
      }
#pragma unroll 1
      for (int ks = 17; ks < 64; ks++) {
        if (END_SKEW && wg == 1 && ks == 64 - END_SKEW) turn_wait();
        bstep(ks, 1);
      }
      if (END_SKEW && wg == 0) turn_pass();
      wg_wait<0>();
      reg_fence(acc);
      release(prev);
      if (!last) warp_arrive_cl(mapa(sb + BAR_BEMPTY + 8 * bprev, bprev & 1));
      TRL(158); TG(156);
      const int pos0 = row_block(t) * 256 + rank * 128 + wg * 64 + w * 16;
      if (last) {
        bar_sync(wg);
        out_stage(acc, 0);
        out_store(t, 320);
      } else {
        const int lane = fresh_tid() & 31;
        __nv_bfloat16* op0 = P.out + (size_t)o_row(pos0 + (lane >> 2)) * DM + (t & 3) * 160 + (lane & 3) * 2;
        __nv_bfloat16* op1 = P.out + (size_t)o_row(pos0 + (lane >> 2) + 8) * DM + (t & 3) * 160 + (lane & 3) * 2;
#pragma unroll
        for (int j = 0; j < 20; j++) {
          *reinterpret_cast<uint32_t*>(op0 + j * 8) = pack(acc[4 * j], acc[4 * j + 1]);
          *reinterpret_cast<uint32_t*>(op1 + j * 8) = pack(acc[4 * j + 2], acc[4 * j + 3]);
        }
      }
#pragma unroll
      for (int i = 0; i < 60; i++) pb[i] = 0;
    }
    TRL(159);
  }
}

typedef CUresult (*EncodeFn)(CUtensorMap*, CUtensorMapDataType, cuuint32_t, void*, const cuuint64_t*, const cuuint64_t*,
                             const cuuint32_t*, const cuuint32_t*, CUtensorMapInterleave, CUtensorMapSwizzle,
                             CUtensorMapL2promotion, CUtensorMapFloatOOBfill);

void make_map(EncodeFn enc, CUtensorMap* m, const void* p, int rank, const cuuint64_t* dims, const cuuint64_t* strides,
              const cuuint32_t* box, CUtensorMapSwizzle sw, CUtensorMapL2promotion promo) {
  cuuint32_t es[4] = {1, 1, 1, 1};
  enc(m, CU_TENSOR_MAP_DATA_TYPE_BFLOAT16, rank, const_cast<void*>(p), dims, strides, box, es, CU_TENSOR_MAP_INTERLEAVE_NONE, sw,
      promo, CU_TENSOR_MAP_FLOAT_OOB_FILL_NONE);
}

}

extern "C" void kernel_launch(void* const* d_in, const int* in_sizes, int n_in, void* d_out, int out_size) {
  static EncodeFn enc = nullptr;
  static int nclusters = 0;
  static void* o_ptr = nullptr;
  if (!enc) {
    cudaDriverEntryPointQueryResult qr;
    cudaGetDriverEntryPoint("cuTensorMapEncodeTiled", (void**)&enc, cudaEnableDefault, &qr);
    cudaFuncSetAttribute(fused_attn_kernel<66>, cudaFuncAttributeMaxDynamicSharedMemorySize, SMEM_BYTES);
    cudaFuncSetAttribute(fused_attn_kernel<0>, cudaFuncAttributeMaxDynamicSharedMemorySize, SMEM_BYTES);
    cudaGetSymbolAddress(&o_ptr, g_o);
    cudaLaunchConfig_t cfg = {};
    cfg.gridDim = 128; cfg.blockDim = 384; cfg.dynamicSmemBytes = SMEM_BYTES;
    cudaLaunchAttribute at; at.id = cudaLaunchAttributeClusterDimension;
    at.val.clusterDim.x = 2; at.val.clusterDim.y = 1; at.val.clusterDim.z = 1;
    cfg.attrs = &at; cfg.numAttrs = 1;
    int n = 0;
    cudaOccupancyMaxActiveClusters(&n, fused_attn_kernel<66>, &cfg);
    nclusters = n >= 66 ? MAXCL : (n >= 64 || n <= 0 ? 64 : n);
  }
  const __nv_bfloat16* x = (const __nv_bfloat16*)d_in[0];
  const __nv_bfloat16* k = (const __nv_bfloat16*)d_in[1];
  const __nv_bfloat16* v = (const __nv_bfloat16*)d_in[2];
  const __nv_bfloat16* wq = (const __nv_bfloat16*)d_in[3];
  const __nv_bfloat16* wo = (const __nv_bfloat16*)d_in[4];
  CUtensorMap tm_x, tm_wq, tm_k, tm_v, tm_o, tm_wo;
  const auto S128 = CU_TENSOR_MAP_SWIZZLE_128B;
  const auto P128 = CU_TENSOR_MAP_L2_PROMOTION_L2_128B, P256 = CU_TENSOR_MAP_L2_PROMOTION_L2_256B;
  { cuuint64_t d[2] = {DM, NB * SQ}, s[1] = {DM * 2}; cuuint32_t b[2] = {64, 120}; make_map(enc, &tm_x, x, 2, d, s, b, S128, X_PROMO); }
  { cuuint64_t d[3] = {64, DM, HD / 64}, s[2] = {HD * 2, 128}; cuuint32_t b[3] = {64, 64, 2}; make_map(enc, &tm_wq, wq, 3, d, s, b, S128, P256); }
  { cuuint64_t d[3] = {64, NB * NH * SK, 2}, s[2] = {DH * 2, 128}; cuuint32_t b[3] = {64, 64, 2};
    make_map(enc, &tm_k, k, 3, d, s, b, S128, P128); make_map(enc, &tm_v, v, 3, d, s, b, S128, P128); }
  { cuuint64_t d[4] = {256, 2, HD / 8, NROWS / 64}, s[3] = {512, NROWS * 16, 1024}; cuuint32_t b[4] = {256, 2, 8, 2};
    make_map(enc, &tm_o, o_ptr, 4, d, s, b, CU_TENSOR_MAP_SWIZZLE_NONE, P256); }
  { cuuint64_t d[3] = {32, HD, DM / 32}, s[2] = {DM * 2, 64}; cuuint32_t b[3] = {32, 64, 5};
    make_map(enc, &tm_wo, wo, 3, d, s, b, CU_TENSOR_MAP_SWIZZLE_64B, P128); }
  Params P{x, k, v, wq, (__nv_bfloat16*)d_out, (__nv_bfloat16*)o_ptr};
  if (nclusters == 66) fused_attn_kernel<66><<<132, 384, SMEM_BYTES>>>(tm_x, tm_wq, tm_k, tm_v, tm_o, tm_wo, P);
  else fused_attn_kernel<0><<<2 * nclusters, 384, SMEM_BYTES>>>(tm_x, tm_wq, tm_k, tm_v, tm_o, tm_wo, P);
}
```

```cpp
#include <cuda_runtime.h>
#include <cuda.h>
#include <cuda_bf16.h>
#include <stdint.h>

namespace {

constexpr int NB = 16, SQ = 240, DM = 640, NH = 32, SK = 1024, DH = 128, HD = NH * DH;
constexpr int NROWS = NB * SQ;
constexpr int NUNITS = 256;
#define DPRO 1
#define LATE_AT 0
#define ALT_FROM 4
#define END_SKEW 5
#define VREL 6
#define PF_HOLD 6
#define PF_N 4
#define PF_J0 3
#define PF_STEP 3
#define ROT 0
#define O_EF 1
#define B_ORDER 1
#define WO_PF 6
#define ROLE_AT 0
#define PAUSE_NS 11000
#define PAUSE_AT 2
#define EARLY 1
#define EARLY_X 2
#define EARLY_W 2
#define X_PROMO P128
#define PAUSE_J -1
#define PAUSE_SPREAD 0
#define WO_PF0 1
#define EPI_MIX 1
#define K2_AT 0
#define SLP 15
#define PASS9 0
#define LSUM_AT 0
#define PUT_FROM 1
#define EARLY_VOTE 1
#define EREL_FROM 4
#define PRE9 0
#define MAXCL 66
#define SMID_TOP 88
constexpr int NOTILES = 60;
constexpr float QSCALE = 0.08838834764831845f * 1.4426950408889634f;
constexpr float L_MIN = 9.5367431640625e-07f;
constexpr float L_MAX = 1.152921504606846976e18f;

constexpr uint32_t RING_SLOTS = 6, RING_BYTES = 16384;
constexpr uint32_t XB = 15360;
constexpr uint32_t BB = 20480;
constexpr uint32_t OFF_Q = RING_SLOTS * RING_BYTES;
constexpr uint32_t OFF_P = OFF_Q + 4 * XB;
constexpr uint32_t OFF_INV = OFF_P + 4 * XB;
constexpr uint32_t OFF_L2 = OFF_INV + 1280;
constexpr uint32_t OFF_BAR = OFF_L2 + 4096;
constexpr uint32_t BAR_RFULL = OFF_BAR, BAR_REMPTY = BAR_RFULL + 48, BAR_XFULL = BAR_REMPTY + 48,
    BAR_XEMPTY = BAR_XFULL + 64, BAR_BFULL = BAR_XEMPTY + 32, BAR_BEMPTY = BAR_BFULL + 48, BAR_STAGE = BAR_BEMPTY + 48;
constexpr uint32_t BAR_ROLE = BAR_STAGE + 16, BAR_LSUM = BAR_ROLE + 24, BAR_INV = BAR_LSUM + 16;
constexpr uint32_t OFF_TR = BAR_INV + 16;
constexpr uint32_t SMEM_BYTES = OFF_TR + 1024;

constexpr uint32_t HI128 = (1u << 30) | (1024 >> 4);
constexpr uint32_t HI64 = (2u << 30) | (512 >> 4);
constexpr uint32_t HI64A = (2u << 30) | (1024 >> 4), LBO64A = (512u >> 4) << 16;

__device__ __nv_bfloat16 g_o[HD * NROWS];
__device__ unsigned g_cnt[67 * 8];
#define TS(i)
#define TI(i)
#define TRL(i)
#define TR(i)
#define TG(i)

struct Params {
  const __nv_bfloat16 *x, *k, *v, *wq;
  __nv_bfloat16 *out, *o;
};

__device__ __forceinline__ void wg_fence() { asm volatile("wgmma.fence.sync.aligned;" ::: "memory"); }
__device__ __forceinline__ void wg_commit() { asm volatile("wgmma.commit_group.sync.aligned;" ::: "memory"); }
template <int N> __device__ __forceinline__ void wg_wait() { asm volatile("wgmma.wait_group.sync.aligned %0;" ::"n"(N) : "memory"); }
template <int N> __device__ __forceinline__ void reg_fence(float (&r)[N]) {
#pragma unroll
  for (int i = 0; i < N; i++) asm volatile("" : "+f"(r[i])::"memory");
}
template <int TA, int TB>
__device__ __forceinline__ void wgmma_n120(float (&d)[60], uint32_t a_lo, uint32_t a_hi, uint32_t b_lo, uint32_t b_hi, int acc) {
  asm volatile(
      "{\n.reg .pred p;\n.reg .b64 da, db;\nsetp.ne.b32 p, %64, 0;\n"
      "mov.b64 da, {%60, %61};\nmov.b64 db, {%62, %63};\n"
      "wgmma.mma_async.sync.aligned.m64n120k16.f32.bf16.bf16 {"
      "%0, %1, %2, %3, %4, %5, %6, %7, %8, %9, %10, %11, %12, %13, %14, %15, %16, %17, %18, %19, %20, %21, %22, %23, "
      "%24, %25, %26, %27, %28, %29, %30, %31, %32, %33, %34, %35, %36, %37, %38, %39, %40, %41, %42, %43, %44, %45, "
      "%46, %47, %48, %49, %50, %51, %52, %53, %54, %55, %56, %57, %58, %59"
      "}, da, db, p, 1, 1, %65, %66;\n}\n"
      : "+f"(d[0]), "+f"(d[1]), "+f"(d[2]), "+f"(d[3]), "+f"(d[4]), "+f"(d[5]), "+f"(d[6]), "+f"(d[7]), "+f"(d[8]),
        "+f"(d[9]), "+f"(d[10]), "+f"(d[11]), "+f"(d[12]), "+f"(d[13]), "+f"(d[14]), "+f"(d[15]), "+f"(d[16]),
        "+f"(d[17]), "+f"(d[18]), "+f"(d[19]), "+f"(d[20]), "+f"(d[21]), "+f"(d[22]), "+f"(d[23]), "+f"(d[24]),
        "+f"(d[25]), "+f"(d[26]), "+f"(d[27]), "+f"(d[28]), "+f"(d[29]), "+f"(d[30]), "+f"(d[31]), "+f"(d[32]),
        "+f"(d[33]), "+f"(d[34]), "+f"(d[35]), "+f"(d[36]), "+f"(d[37]), "+f"(d[38]), "+f"(d[39]), "+f"(d[40]),
        "+f"(d[41]), "+f"(d[42]), "+f"(d[43]), "+f"(d[44]), "+f"(d[45]), "+f"(d[46]), "+f"(d[47]), "+f"(d[48]),
        "+f"(d[49]), "+f"(d[50]), "+f"(d[51]), "+f"(d[52]), "+f"(d[53]), "+f"(d[54]), "+f"(d[55]), "+f"(d[56]),
        "+f"(d[57]), "+f"(d[58]), "+f"(d[59])
      : "r"(a_lo), "r"(a_hi), "r"(b_lo), "r"(b_hi), "r"(acc), "n"(TA), "n"(TB));
}

template <int TA, int TB>
__device__ __forceinline__ void wgmma_n160(float (&d)[80], uint32_t a_lo, uint32_t a_hi, uint32_t b_lo, uint32_t b_hi, int acc) {
  asm volatile(
      "{\n.reg .pred p;\n.reg .b64 da, db;\nsetp.ne.b32 p, %84, 0;\n"
      "mov.b64 da, {%80, %81};\nmov.b64 db, {%82, %83};\n"
      "wgmma.mma_async.sync.aligned.m64n160k16.f32.bf16.bf16 {"
      "%0, %1, %2, %3, %4, %5, %6, %7, %8, %9, %10, %11, %12, %13, %14, %15, %16, %17, %18, %19, %20, %21, %22, %23, "
      "%24, %25, %26, %27, %28, %29, %30, %31, %32, %33, %34, %35, %36, %37, %38, %39, %40, %41, %42, %43, %44, %45, "
      "%46, %47, %48, %49, %50, %51, %52, %53, %54, %55, %56, %57, %58, %59, %60, %61, %62, %63, %64, %65, %66, %67, "
      "%68, %69, %70, %71, %72, %73, %74, %75, %76, %77, %78, %79"
      "}, da, db, p, 1, 1, %85, %86;\n}\n"
      : "+f"(d[0]), "+f"(d[1]), "+f"(d[2]), "+f"(d[3]), "+f"(d[4]), "+f"(d[5]), "+f"(d[6]), "+f"(d[7]), "+f"(d[8]),
        "+f"(d[9]), "+f"(d[10]), "+f"(d[11]), "+f"(d[12]), "+f"(d[13]), "+f"(d[14]), "+f"(d[15]), "+f"(d[16]),
        "+f"(d[17]), "+f"(d[18]), "+f"(d[19]), "+f"(d[20]), "+f"(d[21]), "+f"(d[22]), "+f"(d[23]), "+f"(d[24]),
        "+f"(d[25]), "+f"(d[26]), "+f"(d[27]), "+f"(d[28]), "+f"(d[29]), "+f"(d[30]), "+f"(d[31]), "+f"(d[32]),
        "+f"(d[33]), "+f"(d[34]), "+f"(d[35]), "+f"(d[36]), "+f"(d[37]), "+f"(d[38]), "+f"(d[39]), "+f"(d[40]),
        "+f"(d[41]), "+f"(d[42]), "+f"(d[43]), "+f"(d[44]), "+f"(d[45]), "+f"(d[46]), "+f"(d[47]), "+f"(d[48]),
        "+f"(d[49]), "+f"(d[50]), "+f"(d[51]), "+f"(d[52]), "+f"(d[53]), "+f"(d[54]), "+f"(d[55]), "+f"(d[56]),
        "+f"(d[57]), "+f"(d[58]), "+f"(d[59]), "+f"(d[60]), "+f"(d[61]), "+f"(d[62]), "+f"(d[63]), "+f"(d[64]),
        "+f"(d[65]), "+f"(d[66]), "+f"(d[67]), "+f"(d[68]), "+f"(d[69]), "+f"(d[70]), "+f"(d[71]), "+f"(d[72]),
        "+f"(d[73]), "+f"(d[74]), "+f"(d[75]), "+f"(d[76]), "+f"(d[77]), "+f"(d[78]), "+f"(d[79])
      : "r"(a_lo), "r"(a_hi), "r"(b_lo), "r"(b_hi), "r"(acc), "n"(TA), "n"(TB));
}
__device__ __forceinline__ void mbar_init(uint32_t bar, int cnt) { asm volatile("mbarrier.init.shared::cta.b64 [%0], %1;" ::"r"(bar), "r"(cnt)); }
__device__ __forceinline__ void mbar_expect(uint32_t bar, uint32_t bytes) {
  asm volatile("mbarrier.arrive.expect_tx.shared::cta.b64 _, [%0], %1;" ::"r"(bar), "r"(bytes) : "memory");
}
__device__ __forceinline__ uint32_t mapa(uint32_t addr, uint32_t cta) {
  uint32_t r; asm("mapa.shared::cluster.u32 %0, %1, %2;" : "=r"(r) : "r"(addr), "r"(cta)); return r;
}
__device__ __forceinline__ void mbar_expect_cl(uint32_t cbar, uint32_t bytes) {
  asm volatile("mbarrier.arrive.expect_tx.shared::cluster.b64 _, [%0], %1;" ::"r"(cbar), "r"(bytes) : "memory");
}
__device__ __forceinline__ void mbar_arrive(uint32_t bar) { asm volatile("mbarrier.arrive.shared::cta.b64 _, [%0];" ::"r"(bar) : "memory"); }
__device__ __forceinline__ void mbar_arrive_cl(uint32_t cbar) { asm volatile("mbarrier.arrive.shared::cluster.b64 _, [%0];" ::"r"(cbar) : "memory"); }
__device__ __forceinline__ void warp_arrive(uint32_t bar) {
  asm volatile("{\n.reg .pred p;\nelect.sync _|p, 0xffffffff;\n@p mbarrier.arrive.shared::cta.b64 _, [%0];\n}\n" ::"r"(bar) : "memory");
}
__device__ __forceinline__ void warp_arrive_cl(uint32_t cbar) {
  asm volatile("{\n.reg .pred p;\nelect.sync _|p, 0xffffffff;\n@p mbarrier.arrive.shared::cluster.b64 _, [%0];\n}\n" ::"r"(cbar) : "memory");
}
__device__ __forceinline__ void mbar_wait(uint32_t bar, uint32_t parity) {
  asm volatile(
      "{\n.reg .pred p;\n.reg .u32 n;\n"
      "mbarrier.try_wait.parity.shared::cta.b64 p, [%0], %1;\n@p bra WAIT_DONE;\n"
      "mov.u32 n, 0;\n"
      "WAIT_LOOP:\n"
      "mbarrier.try_wait.parity.shared::cta.b64 p, [%0], %1;\n@p bra WAIT_DONE;\n"
      "add.u32 n, n, 1;\nsetp.lt.u32 p, n, 0x4000000;\n@p bra WAIT_LOOP;\ntrap;\n"
      "WAIT_DONE:\n}\n" ::"r"(bar), "r"(parity) : "memory");
}
__device__ __forceinline__ void mbar_sleep(uint32_t bar, uint32_t parity) {
  asm volatile(
      "{\n.reg .pred p;\n.reg .u32 n;\nmov.u32 n, 0;\n"
      "WAIT_LOOP:\n"
      "mbarrier.try_wait.parity.shared::cta.b64 p, [%0], %1, 4000;\n@p bra WAIT_DONE;\n"
      "add.u32 n, n, 1;\nsetp.lt.u32 p, n, 0x400000;\n@p bra WAIT_LOOP;\ntrap;\n"
      "WAIT_DONE:\n}\n" ::"r"(bar), "r"(parity) : "memory");
}
__device__ __forceinline__ void mbar_wait_cl(uint32_t bar, uint32_t parity) {
  asm volatile(
      "{\n.reg .pred p;\n.reg .u32 n;\nmov.u32 n, 0;\n"
      "WAIT_LOOP:\n"
      "mbarrier.try_wait.parity.acquire.cluster.shared::cta.b64 p, [%0], %1;\n@p bra WAIT_DONE;\n"
      "add.u32 n, n, 1;\nsetp.lt.u32 p, n, 0x4000000;\n@p bra WAIT_LOOP;\ntrap;\n"
      "WAIT_DONE:\n}\n" ::"r"(bar), "r"(parity) : "memory");
}
__device__ __forceinline__ void tma3d(uint32_t dst, const CUtensorMap* m, int c0, int c1, int c2, uint32_t bar) {
  asm volatile("cp.async.bulk.tensor.3d.shared::cluster.global.mbarrier::complete_tx::bytes [%0], [%1, {%3, %4, %5}], [%2];"
               ::"r"(dst), "l"(m), "r"(bar), "r"(c0), "r"(c1), "r"(c2) : "memory");
}
__device__ __forceinline__ void tma3d_hint(uint32_t dst, const CUtensorMap* m, int c0, int c1, int c2, uint32_t bar, uint64_t pol) {
  asm volatile("cp.async.bulk.tensor.3d.shared::cluster.global.mbarrier::complete_tx::bytes.L2::cache_hint [%0], [%1, {%3, %4, %5}], [%2], %6;"
               ::"r"(dst), "l"(m), "r"(bar), "r"(c0), "r"(c1), "r"(c2), "l"(pol) : "memory");
}
__device__ __forceinline__ void tma2d_mc(uint32_t dst, const CUtensorMap* m, int c0, int c1, uint32_t bar) {
  asm volatile("cp.async.bulk.tensor.2d.shared::cluster.global.mbarrier::complete_tx::bytes.multicast::cluster [%0], [%1, {%3, %4}], [%2], %5;"
               ::"r"(dst), "l"(m), "r"(bar), "r"(c0), "r"(c1), "h"((uint16_t)3) : "memory");
}
__device__ __forceinline__ void tma3d_mc(uint32_t dst, const CUtensorMap* m, int c0, int c1, int c2, uint32_t bar) {
  asm volatile("cp.async.bulk.tensor.3d.shared::cluster.global.mbarrier::complete_tx::bytes.multicast::cluster [%0], [%1, {%3, %4, %5}], [%2], %6;"
               ::"r"(dst), "l"(m), "r"(bar), "r"(c0), "r"(c1), "r"(c2), "h"((uint16_t)3) : "memory");
}
__device__ __forceinline__ void l2_prefetch(const void* p, uint32_t bytes) {
  asm volatile("cp.async.bulk.prefetch.L2.global [%0], %1;" ::"l"(p), "r"(bytes) : "memory");
}
__device__ __forceinline__ void fence_async_smem() { asm volatile("fence.proxy.async.shared::cta;" ::: "memory"); }
__device__ __forceinline__ void bar_sync(int wg) {
  if (wg == 0) asm volatile("bar.sync 1, 128;" ::: "memory");
  else asm volatile("bar.sync 2, 128;" ::: "memory");
}
__device__ __forceinline__ bool bar_red_or(int id, bool v) {
  uint32_t r;
  asm volatile("{\n.reg .pred p, q;\nsetp.ne.u32 p, %2, 0;\nbar.red.or.pred q, %1, 128, p;\nselp.u32 %0, 1, 0, q;\n}\n"
               : "=r"(r) : "r"(1 + id), "r"((uint32_t)v) : "memory");
  return r != 0;
}
__device__ __forceinline__ uint32_t hfma2(uint32_t a, uint32_t b, uint32_t c) { uint32_t r; asm("fma.rn.bf16x2 %0, %1, %2, %3;" : "=r"(r) : "r"(a), "r"(b), "r"(c)); return r; }
__device__ __forceinline__ float ex2(float x) { float y; asm("ex2.approx.ftz.f32 %0, %1;" : "=f"(y) : "f"(x)); return y; }
__device__ __forceinline__ uint32_t pack(float lo, float hi) { uint32_t r; asm("cvt.rn.bf16x2.f32 %0, %1, %2;" : "=r"(r) : "f"(hi), "f"(lo)); return r; }
__device__ __forceinline__ void stsm4t(uint32_t a, uint32_t r0, uint32_t r1, uint32_t r2, uint32_t r3) {
  asm volatile("stmatrix.sync.aligned.m8n8.x4.trans.shared.b16 [%0], {%1,%2,%3,%4};" ::"r"(a), "r"(r0), "r"(r1), "r"(r2), "r"(r3) : "memory");
}
__device__ __forceinline__ void stsm2t(uint32_t a, uint32_t r0, uint32_t r1) {
  asm volatile("stmatrix.sync.aligned.m8n8.x2.trans.shared.b16 [%0], {%1,%2};" ::"r"(a), "r"(r0), "r"(r1) : "memory");
}
__device__ __forceinline__ void mma16816(float (&d)[4], const uint32_t (&a)[4], uint32_t b0, uint32_t b1) {
  asm volatile("mma.sync.aligned.m16n8k16.row.col.f32.bf16.bf16.f32 {%0,%1,%2,%3}, {%4,%5,%6,%7}, {%8,%9}, {%0,%1,%2,%3};"
               : "+f"(d[0]), "+f"(d[1]), "+f"(d[2]), "+f"(d[3]) : "r"(a[0]), "r"(a[1]), "r"(a[2]), "r"(a[3]), "r"(b0), "r"(b1));
}

__device__ __forceinline__ uint32_t fresh_tid() { uint32_t t; asm volatile("mov.u32 %0, %tid.x;" : "=r"(t)); return t; }

template <int V> struct IC { static constexpr int value = V; };

struct Ring {
  uint32_t slot = 0, phase = 0;
  __device__ __forceinline__ void next() { if (++slot == RING_SLOTS) { slot = 0; phase ^= 1; } }
};

__device__ __forceinline__ void mma_tn(float (&o0)[60], float (&o1)[60], uint32_t a, uint32_t b, int acc) {
#pragma unroll
  for (int k = 0; k < 4; k++) {
    wgmma_n120<1, 0>(o0, a + k * 128, HI128, b + k * 2, HI128, k == 0 ? acc : 1);
    wgmma_n120<1, 0>(o1, a + 512 + k * 128, HI128, b + k * 2, HI128, k == 0 ? acc : 1);
  }
}
__device__ __forceinline__ void mma_tn_split(float (&o0)[60], float (&o1)[60], uint32_t a, uint32_t b) {
#pragma unroll
  for (int k = 0; k < 4; k++) wgmma_n120<1, 0>(o0, a + k * 128, HI128, b + k * 2, HI128, 1);
  wg_commit();
#pragma unroll
  for (int k = 0; k < 4; k++) wgmma_n120<1, 0>(o1, a + 512 + k * 128, HI128, b + k * 2, HI128, 1);
  wg_commit();
}
__device__ __forceinline__ void mma_qk(float (&s)[60], uint32_t a, uint32_t q) {
#pragma unroll
  for (int k = 0; k < 8; k++)
    wgmma_n120<0, 0>(s, a + (k >> 2) * 512 + (k & 3) * 2, HI128, q + (k >> 2) * (XB >> 4) + (k & 3) * 2, HI128, k != 0);
}
template <int J0, int J1, bool FIRST = false>
__device__ __forceinline__ void exp_store(const float (&s)[60], float (&l)[30], uint32_t dst) {
#pragma unroll
  for (int j = J0; j < J1; j += 2) {
    uint32_t p[4];
#pragma unroll
    for (int jj = 0; jj < 2; jj++) {
      if (j + jj < 15) {
        const int c = j + jj;
        float e0 = ex2(s[4 * c]), e1 = ex2(s[4 * c + 1]), e2 = ex2(s[4 * c + 2]), e3 = ex2(s[4 * c + 3]);
        if (FIRST) { l[2 * c] = e0 + e2; l[2 * c + 1] = e1 + e3; }
        else { l[2 * c] += e0; l[2 * c + 1] += e1; l[2 * c] += e2; l[2 * c + 1] += e3; }
        p[2 * jj] = pack(e0, e1); p[2 * jj + 1] = pack(e2, e3);
      }
    }
    if (j + 1 < 15) stsm4t(dst + j * 1024, p[0], p[1], p[2], p[3]);
    else stsm2t(dst + j * 1024, p[0], p[1]);
  }
}

__device__ __forceinline__ int o_pos(int b, int wg, int r) {
  const int j = r >> 3, q = (r >> 1) & 3, c = r & 1, o = b & 1, base = (b >> 1) * 480;
  if (j < 12) return base + (o * 9 + wg * 3 + (j >> 2)) * 32 + q * 8 + (j & 3) * 2 + c;
  if (j < 14) return base + (6 + 2 * o) * 32 + wg * 16 + q * 4 + (j - 12) * 2 + c;
  return base + 7 * 32 + (o * 2 + wg) * 8 + q * 2 + c;
}
__device__ __forceinline__ int o_row(int p) {
  const int pair = p / 480, a = (p - pair * 480) >> 5, in = p & 31, c = p & 1;
  int tile, row;
  if (a == 7) { tile = in >> 3; row = 112 + (in & 7); }
  else if (a == 6 || a == 8) { tile = a - 6 + (in >> 4); row = (12 + ((in >> 1) & 1)) * 8 + ((in >> 2) & 3) * 2 + c; }
  else { const int f = a > 8 ? a - 3 : a; tile = f / 3; row = ((f - tile * 3) * 4 + ((in >> 1) & 3)) * 8 + (in >> 3) * 2 + c; }
  return pair * 480 + tile * 120 + row;
}
__device__ __forceinline__ uint32_t o_idx(int k, int p) {
  return ((k >> 3) * (NROWS / 32) + (p >> 5)) * 256 + (k & 7) * 32 + ((((p >> 3) & 3) ^ ((k & 7) >> 1)) << 3) + (p & 7);
}

__device__ __forceinline__ void slow_path(const Params& P, int b, int h, int wg, int w, int lane) {
  const int g = lane >> 2, q = lane & 3, row0 = wg * 120;
  const uint16_t* wq = reinterpret_cast<const uint16_t*>(P.wq) + h * DH + g;
  const __nv_bfloat16* kp = P.k + (size_t)(b * NH + h) * SK * DH;
  const uint16_t* vp = reinterpret_cast<const uint16_t*>(P.v) + (size_t)(b * NH + h) * SK * DH + g;
#pragma unroll 1
  for (int t = w; t < 8; t += 4) {
    const int r0 = 16 * t + g, r1 = r0 + 8;
    const __nv_bfloat16* x0 = P.x + (size_t)(b * SQ + row0 + r0) * DM + 2 * q;
    const __nv_bfloat16* x1 = P.x + (size_t)(b * SQ + row0 + min(r1, 119)) * DM + 2 * q;
    float o[16][4];
#pragma unroll
    for (int n = 0; n < 16; n++) o[n][0] = o[n][1] = o[n][2] = o[n][3] = 0.f;
#pragma unroll 1
    for (int k0 = 0; k0 < DM; k0 += 16) {
      uint32_t a[4] = {*(const uint32_t*)(x0 + k0), *(const uint32_t*)(x1 + k0), *(const uint32_t*)(x0 + k0 + 8), *(const uint32_t*)(x1 + k0 + 8)};
      const uint16_t* wr = wq + (size_t)(k0 + 2 * q) * HD;
#pragma unroll
      for (int n = 0; n < 16; n++) {
        if ((n & 3) == 0) __syncwarp();
        mma16816(o[n], a, wr[8 * n] | ((uint32_t)wr[8 * n + HD] << 16), wr[8 * n + 8 * HD] | ((uint32_t)wr[8 * n + 9 * HD] << 16));
      }
    }
    uint32_t qa[8][4];
#pragma unroll
    for (int k = 0; k < 8; k++) {
      qa[k][0] = pack(o[2 * k][0] * QSCALE, o[2 * k][1] * QSCALE);
      qa[k][1] = pack(o[2 * k][2] * QSCALE, o[2 * k][3] * QSCALE);
      qa[k][2] = pack(o[2 * k + 1][0] * QSCALE, o[2 * k + 1][1] * QSCALE);
      qa[k][3] = pack(o[2 * k + 1][2] * QSCALE, o[2 * k + 1][3] * QSCALE);
    }
#pragma unroll
    for (int n = 0; n < 16; n++) o[n][0] = o[n][1] = o[n][2] = o[n][3] = 0.f;
    float m0 = -INFINITY, m1 = -INFINITY, l0 = 0.f, l1 = 0.f;
#pragma unroll 1
    for (int key0 = 0; key0 < SK; key0 += 16) {
      float s[2][4];
#pragma unroll
      for (int nt = 0; nt < 2; nt++) {
        s[nt][0] = s[nt][1] = s[nt][2] = s[nt][3] = 0.f;
        const __nv_bfloat16* kr = kp + (size_t)(key0 + 8 * nt + g) * DH + 2 * q;
#pragma unroll
        for (int k = 0; k < 8; k++) mma16816(s[nt], qa[k], *(const uint32_t*)(kr + 16 * k), *(const uint32_t*)(kr + 16 * k + 8));
      }
      float n0 = fmaxf(fmaxf(s[0][0], s[0][1]), fmaxf(s[1][0], s[1][1])), n1 = fmaxf(fmaxf(s[0][2], s[0][3]), fmaxf(s[1][2], s[1][3]));
      n0 = fmaxf(n0, __shfl_xor_sync(~0u, n0, 1)); n1 = fmaxf(n1, __shfl_xor_sync(~0u, n1, 1));
      n0 = fmaxf(n0, __shfl_xor_sync(~0u, n0, 2)); n1 = fmaxf(n1, __shfl_xor_sync(~0u, n1, 2));
      n0 = fmaxf(n0, m0); n1 = fmaxf(n1, m1);
      const float z0 = n0 == -INFINITY ? 0.f : n0, z1 = n1 == -INFINITY ? 0.f : n1;
      const float c0 = ex2(m0 - z0), c1 = ex2(m1 - z1);
      m0 = n0; m1 = n1;
#pragma unroll
      for (int nt = 0; nt < 2; nt++) {
        s[nt][0] = ex2(s[nt][0] - z0); s[nt][1] = ex2(s[nt][1] - z0);
        s[nt][2] = ex2(s[nt][2] - z1); s[nt][3] = ex2(s[nt][3] - z1);
      }
      l0 = l0 * c0 + s[0][0] + s[0][1] + s[1][0] + s[1][1];
      l1 = l1 * c1 + s[0][2] + s[0][3] + s[1][2] + s[1][3];
      uint32_t pa[4] = {pack(s[0][0], s[0][1]), pack(s[0][2], s[0][3]), pack(s[1][0], s[1][1]), pack(s[1][2], s[1][3])};
      const uint16_t* vr = vp + (size_t)(key0 + 2 * q) * DH;
#pragma unroll
      for (int n = 0; n < 16; n++) {
        if ((n & 3) == 0) __syncwarp();
        o[n][0] *= c0; o[n][1] *= c0; o[n][2] *= c1; o[n][3] *= c1;
        mma16816(o[n], pa, vr[8 * n] | ((uint32_t)vr[8 * n + DH] << 16), vr[8 * n + 8 * DH] | ((uint32_t)vr[8 * n + 9 * DH] << 16));
      }
    }
    l0 += __shfl_xor_sync(~0u, l0, 1); l1 += __shfl_xor_sync(~0u, l1, 1);
    l0 += __shfl_xor_sync(~0u, l0, 2); l1 += __shfl_xor_sync(~0u, l1, 2);
    const float i0 = 1.f / l0, i1 = 1.f / l1;
    __nv_bfloat16* oc0 = P.o + o_idx(h * DH + 2 * q, o_pos(b, wg, r0));
    __nv_bfloat16* oc1 = P.o + o_idx(h * DH + 2 * q, o_pos(b, wg, min(r1, 119)));
#pragma unroll
    for (int n = 0; n < 16; n++) {
      oc0[8 * n * NROWS] = __float2bfloat16(o[n][0] * i0);
      oc0[8 * n * NROWS + 32] = __float2bfloat16(o[n][1] * i0);
      if (r1 < 120) {
        oc1[8 * n * NROWS] = __float2bfloat16(o[n][2] * i1);
        oc1[8 * n * NROWS + 32] = __float2bfloat16(o[n][3] * i1);
      }
    }
  }
}

__device__ __forceinline__ int bk(int ks) { return B_ORDER && ks < 48 ? 32 - (ks & 48) + (ks & 15) : ks; }
__device__ __forceinline__ uint32_t x_slot(uint32_t wg, uint32_t j) { return j < 2 ? (2 * wg + j) * XB : (2 * j + wg) * XB; }
__device__ __forceinline__ int row_block(int t) { return t >= 44 ? (t >> 2) - 11 : (t >> 2) + 4; }
__device__ __forceinline__ int unit_batch(int u) { return (u & 63) >> 2; }
__device__ __forceinline__ int unit_head(int u, int rank) { return (u >> 6) * 8 + (u & 3) * 2 + rank; }

template <int NCL>
__global__ void __cluster_dims__(2, 1, 1) __launch_bounds__(384, 1)
fused_attn_kernel(const __grid_constant__ CUtensorMap tm_x, const __grid_constant__ CUtensorMap tm_wq,
                  const __grid_constant__ CUtensorMap tm_k, const __grid_constant__ CUtensorMap tm_v,
                  const __grid_constant__ CUtensorMap tm_o, const __grid_constant__ CUtensorMap tm_wo,
                  const __grid_constant__ Params P) {
  extern __shared__ uint8_t smem_raw[];
  const uint32_t sb = ((uint32_t)__cvta_generic_to_shared(smem_raw) + 1023) & ~1023u;
  if (threadIdx.x == 0) TS(152);
  const int warp = __shfl_sync(~0u, threadIdx.x >> 5, 0);
  const int lane = threadIdx.x & 31;
  const int rank = blockIdx.x & 1, cl = blockIdx.x >> 1, ncl = NCL ? NCL : gridDim.x >> 1;

  const int nsingle = NCL == 66 ? 44 : NOTILES;
  auto role = [&]() {
    mbar_wait(sb + BAR_ROLE + 16, 0);
    int id;
    asm volatile("ld.shared.u32 %0, [%1];" : "=r"(id) : "r"(sb + BAR_ROLE + 8) : "memory");
    return id;
  };

  if (EARLY && threadIdx.x == 128) asm volatile("prefetch.tensormap [%0];" ::"l"(&tm_x) : "memory");
  if (threadIdx.x == 0) {
    if (EARLY) asm volatile("prefetch.tensormap [%0];" ::"l"(&tm_wq) : "memory");
    for (int i = 0; i < 6; i++) {
      mbar_init(sb + BAR_RFULL + 8 * i, 1); mbar_init(sb + BAR_REMPTY + 8 * i, 8);
      mbar_init(sb + BAR_BFULL + 8 * i, 1); mbar_init(sb + BAR_BEMPTY + 8 * i, 16);
    }
    for (int i = 0; i < 8; i++) mbar_init(sb + BAR_XFULL + 8 * i, 1);
    for (int i = 0; i < 4; i++) mbar_init(sb + BAR_XEMPTY + 8 * i, 8);
    for (int i = 0; i < 2; i++) { mbar_init(sb + BAR_STAGE + 8 * i, 4); mbar_init(sb + BAR_LSUM + 8 * i, 4); mbar_init(sb + BAR_INV + 8 * i, 1); }
    mbar_init(sb + BAR_ROLE, 1); mbar_init(sb + BAR_ROLE + 16, 1);
    asm volatile("fence.mbarrier_init.release.cluster;" ::: "memory");
  }
  __syncwarp();
  asm volatile("barrier.cluster.arrive.relaxed.aligned;" ::: "memory");
  auto first_w = [&](int s) {
    mbar_expect(sb + BAR_RFULL + 8 * s, RING_BYTES);
    tma3d(sb + s * RING_BYTES, &tm_wq, 0, s * 64, 2 * unit_head(cl, rank), sb + BAR_RFULL + 8 * s);
  };
  if (EARLY && threadIdx.x == 0) first_w(0);
  __syncwarp();
  asm volatile("barrier.cluster.wait.aligned;" ::: "memory");
  if (EARLY && threadIdx.x == 128) {
#pragma unroll 1
    for (int s = 0; s < EARLY_X; s++) {
      const uint32_t fb = sb + BAR_XFULL + 32 * rank + 8 * s;
      mbar_expect(fb, XB);
      mbar_expect_cl(mapa(fb, rank ^ 1), XB);
      tma2d_mc(sb + OFF_Q + x_slot(rank, s), &tm_x, s * 64, unit_batch(cl) * SQ + rank * 120, fb);
      if (s + 1 < EARLY_W) first_w(s + 1);
    }
  }
  __syncwarp();
  if (threadIdx.x == 0) TS(153);

  if (warp >= 8) {
    asm volatile("setmaxnreg.dec.sync.aligned.u32 24;");
    if (warp == 8) {
      uint64_t pol;
      asm volatile("createpolicy.fractional.L2::evict_first.b64 %0, 1.0;" : "=l"(pol));
      Ring r;
      if (EARLY) r.slot = EARLY_W;
      auto load = [&](const CUtensorMap* m, int c1, int c2, bool ef) {
        if (SLP & 8) mbar_sleep(sb + BAR_REMPTY + 8 * r.slot, r.phase ^ 1); else mbar_wait(sb + BAR_REMPTY + 8 * r.slot, r.phase ^ 1);
        if (lane == 0) {
          mbar_expect(sb + BAR_RFULL + 8 * r.slot, RING_BYTES);
          if (ef) tma3d_hint(sb + r.slot * RING_BYTES, m, 0, c1, c2, sb + BAR_RFULL + 8 * r.slot, pol);
          else tma3d(sb + r.slot * RING_BYTES, m, 0, c1, c2, sb + BAR_RFULL + 8 * r.slot);
        }
        r.next();
      };
      const int rot = ROT * (blockIdx.x * 5 + (blockIdx.x >> 4));
      auto pause = [&](int u0) {
        if (PAUSE_NS && NCL == 66 && u0 == PAUSE_AT * 66) {
          const int id = role();
          if (id >= 44 && id < 58) {
            unsigned t0, t1;
            asm volatile("mov.u32 %0, %globaltimer_lo;" : "=r"(t0));
            do { __nanosleep(200); asm volatile("mov.u32 %0, %globaltimer_lo;" : "=r"(t1)); } while (t1 - t0 < PAUSE_NS + (id - 44) * PAUSE_SPREAD);
          }
        }
      };
      for (int u0 = 0;; u0 += ncl) {
        const int u = __shfl_sync(~0u, (u0 >= 3 * ncl ? role() : cl) + u0, 0);
        if (u >= NUNITS) break;
        if (PAUSE_J < 0) pause(u0);
        const int h = unit_head(u, rank);
        const int krow = (unit_batch(u) * NH + h) * SK;
#pragma unroll 1
        for (int s = EARLY && u0 == 0 ? EARLY_W : 0; s < 10; s++) {
          if (u0 == 0 && s == 0 && lane == 0) TS(154);
          load(&tm_wq, s * 64, 2 * h, false);
          if (u0 == 0 && s == 0 && lane == 0) TS(155);
          const int sp = u0 == 0 ? s - PF_HOLD : s;
          if (sp >= 0 && sp < PF_N && lane == 0) l2_prefetch(P.v + (size_t)(krow + ((PF_J0 + sp * PF_STEP + rot) & 15) * 64) * DH, 16384);
        }
#pragma unroll 1
        for (int j = 0; j <= 16; j++) {
          if (j == PAUSE_J) pause(u0);
          if (j < 16) load(&tm_k, krow + ((j + rot) & 15) * 64, 0, true);
          if (j == 1 + DPRO) load(&tm_v, krow + (rot & 15) * 64, 0, true);
          if (j > 1) load(&tm_v, krow + ((j - 1 + rot) & 15) * 64, 0, true);
        }
      }
      const int id = __shfl_sync(~0u, role(), 0);
      const bool dbl = NCL == 66 && id >= 58;
      for (int t = dbl ? 2 * id - 72 : id; t < (dbl ? NOTILES : nsingle); t += ncl) {
        const int row0 = row_block(t) * 256 + rank * 128;
        const int b0 = (row0 & ~31) / SQ, b1 = (row0 + 127) / SQ;
#pragma unroll 1
        for (int ks = 0; ks < 64; ks++) {
          if (dbl ? (ks & 15) == 0 : ks == 0 || ks == 48) {
            const unsigned* c = &g_cnt[((lane & 1 ? b1 : b0) * 4 + (ks || dbl ? ks >> 4 : min(lane >> 1, 2))) * 8];
            unsigned v, n = 0;
            do {
              asm volatile("ld.acquire.gpu.global.u32 %0, [%1];" : "=r"(v) : "l"(c) : "memory");
              if (++n > (1u << 26)) __trap();
            } while (v < 16);
            __syncwarp();
            asm volatile("fence.proxy.async.global;" ::: "memory");
          }
          mbar_wait(sb + BAR_REMPTY + 8 * r.slot, r.phase ^ 1);
          if (lane == 0) {
            mbar_expect(sb + BAR_RFULL + 8 * r.slot, RING_BYTES);
            asm volatile("cp.async.bulk.tensor.4d.shared::cluster.global.mbarrier::complete_tx::bytes.L2::cache_hint [%0], [%1, {%3, %3, %4, %5}], [%2], %6;"
                         ::"r"(sb + r.slot * RING_BYTES), "l"(&tm_o), "r"(sb + BAR_RFULL + 8 * r.slot), "r"(0), "r"((dbl ? ks : bk(ks)) * 8), "r"(row0 >> 6), "l"(pol) : "memory");
          }
          r.next();
        }
      }
      if (lane == 0 && atomicAdd(&g_cnt[64 * 8], 1) == gridDim.x - 1) {
        for (int i = 0; i < 67; i++) g_cnt[i * 8] = 0;
      }
    } else if (warp == 9) {
      if (lane == 0) {
        uint32_t it = 0;
        for (;; it++) {
          const int u = (it >= 3 ? role() : cl) + it * ncl;
          if (u >= NUNITS) break;
          const int row = unit_batch(u) * SQ + rank * 120;
#pragma unroll 1
          for (int s = EARLY && it == 0 ? EARLY_X : 0; s < 10; s++) {
            const uint32_t j = s & 3, par = ((s >> 2) + (j < 2 ? it : 0)) & 1;
            if ((SLP & 4) && s == 0) mbar_sleep(sb + BAR_XEMPTY, par ^ 1);
            mbar_wait(sb + BAR_XEMPTY + 8 * j, par ^ 1);
            const uint32_t fb = sb + BAR_XFULL + 32 * rank + 8 * j;
            mbar_expect(fb, XB);
            mbar_expect_cl(mapa(fb, rank ^ 1), XB);
            tma2d_mc(sb + OFF_Q + x_slot(rank, j), &tm_x, s * 64, row, fb);
          }
        }
        const int id = role();
        const bool dbl = NCL == 66 && id >= 58;
        uint32_t slot = rank, phase = 0;
        if (WO_PF0 && dbl)
          asm volatile("cp.async.bulk.prefetch.tensor.3d.L2.global [%0, {%1, %2, %3}];" ::"l"(&tm_wo), "r"(0), "r"((2 + ((id >> 1) & 3)) * 64), "r"(((2 * id - 72 + rank) & 3) * 5) : "memory");
        if ((SLP & 4) && (dbl || id < nsingle)) mbar_sleep(sb + BAR_BEMPTY + 8 * rank, 0);
        for (int t = dbl ? 2 * id - 72 + rank : id; t < (dbl ? NOTILES : nsingle); t += ncl) {
#pragma unroll 1
          for (int ks = dbl ? 0 : rank; ks < 64; ks += dbl ? 1 : 2) {
            mbar_wait(sb + BAR_BEMPTY + 8 * slot, phase);
            const uint32_t fb = sb + BAR_BFULL + 8 * slot;
            mbar_expect(fb, BB);
            mbar_expect_cl(mapa(fb, rank ^ 1), BB);
            tma3d_mc(sb + OFF_Q + slot * BB, &tm_wo, 0, (dbl ? ks : bk(ks)) * 64, (t & 3) * 5, fb);
            if (WO_PF && dbl && ks + WO_PF < 64 && (ks & 3) == ((id >> 1) & 3))
              asm volatile("cp.async.bulk.prefetch.tensor.3d.L2.global [%0, {%1, %2, %3}];" ::"l"(&tm_wo), "r"(0), "r"((ks + WO_PF) * 64), "r"((t & 3) * 5) : "memory");
            slot += 2;
            if (slot >= 6) { slot -= 6; phase ^= 1; }
          }
        }
      }
    } else {
      const int wg = warp - 10;
      {
        mbar_wait(sb + BAR_RFULL, 0);
        const __nv_bfloat16* xs = P.x + (size_t)(unit_batch(cl) * SQ + ((cl & 3) * 2 + rank) * 30 + min(lane, 29)) * DM + 256 + wg * 64;
#pragma unroll
        for (int i = 0; i < 3; i++) asm volatile("prefetch.global.L2 [%0];" ::"l"(xs + i * 128));
        if (lane < 16) asm volatile("prefetch.global.L2 [%0];" ::"l"(P.wq + (size_t)(384 + unit_batch(cl) * 16 + lane) * HD + unit_head(cl, rank) * DH + wg * 64));
      }
      auto take_role = [&]() {
          if (wg == 0 && rank == 0 && lane == 0) {
            int id = cl;
            if (NCL == 66) {
              uint32_t smid;
              asm("mov.u32 %0, %smid;" : "=r"(smid));
              id = smid >= SMID_TOP ? 65 - atomicAdd(&g_cnt[65 * 8], 1) : atomicAdd(&g_cnt[66 * 8], 1);
            }
    #pragma unroll
            for (int c = 0; c < 2; c++) {
              const uint32_t a = mapa(sb + BAR_ROLE, c);
              asm volatile("st.shared::cluster.u32 [%0 + 8], %1;\nmbarrier.arrive.release.cluster.shared::cluster.b64 _, [%0];" ::"r"(a), "r"(id) : "memory");
            }
          }
          if (wg == 0 && lane == 0) {
            mbar_wait_cl(sb + BAR_ROLE, 0);
            mbar_arrive(sb + BAR_ROLE + 16);
          }
      };
      if (ROLE_AT < 0) { take_role(); __syncwarp(); }
      for (uint32_t it = 0;; it++) {
        const int u = __shfl_sync(~0u, (it >= 3 ? role() : cl) + it * ncl, 0);
        if (u >= NUNITS) break;
        if (SLP & 1) mbar_sleep(sb + BAR_LSUM + 8 * wg, it & 1); else mbar_wait(sb + BAR_LSUM + 8 * wg, it & 1);
        float l4[4], v[4];
        const uint32_t a = sb + OFF_L2 + wg * 2048 + lane * 16;
        asm volatile("ld.shared.v4.f32 {%0, %1, %2, %3}, [%4];" : "=f"(l4[0]), "=f"(l4[1]), "=f"(l4[2]), "=f"(l4[3]) : "r"(a) : "memory");
#pragma unroll
        for (int g = 1; g < 4; g++) {
          asm volatile("ld.shared.v4.f32 {%0, %1, %2, %3}, [%4];" : "=f"(v[0]), "=f"(v[1]), "=f"(v[2]), "=f"(v[3]) : "r"(a + g * 512) : "memory");
#pragma unroll
          for (int c = 0; c < 4; c++) l4[c] += v[c];
        }
#pragma unroll
        for (int c = 0; c < 4; c++) {
          float inv;
          asm("rcp.approx.ftz.f32 %0, %1;" : "=f"(inv) : "f"(l4[c]));
          l4[c] = l4[c] >= L_MIN && l4[c] <= L_MAX ? inv : __uint_as_float(0x7FFFFFFFu);
        }
        const uint32_t h0 = pack(l4[0], l4[1]), h1 = pack(l4[2], l4[3]);
        const uint32_t e0 = pack(l4[0] - __uint_as_float(h0 << 16), l4[1] - __uint_as_float(h0 & 0xFFFF0000u));
        const uint32_t e1 = pack(l4[2] - __uint_as_float(h1 << 16), l4[3] - __uint_as_float(h1 & 0xFFFF0000u));
        asm volatile("st.shared.v4.u32 [%0], {%1, %2, %3, %4};" ::"r"(sb + OFF_INV + wg * 640 + (lane & 3) * 144 + (lane >> 2) * 16), "r"(h0), "r"(e0), "r"(h1), "r"(e1) : "memory");
        __syncwarp();
        if (lane == 0) {
          mbar_arrive(sb + BAR_INV + 8 * wg);
          if ((int)it == ROLE_AT) {
            take_role();
          }
          if (SLP & 2) mbar_sleep(sb + BAR_STAGE + 8 * wg, it & 1); else mbar_wait(sb + BAR_STAGE + 8 * wg, it & 1);
          __threadfence();
          asm volatile("red.relaxed.gpu.global.add.u32 [%0], 1;" ::"l"(&g_cnt[(unit_batch(u) * 4 + (u >> 6)) * 8]) : "memory");
        }
        __syncwarp();
      }
    }
  } else {
    asm volatile("setmaxnreg.inc.sync.aligned.u32 240;");
    const int wg = warp >> 2, w = warp & 3;
    const uint32_t qreg = sb + OFF_Q + wg * 2 * XB, preg = sb + OFF_P + (2 + wg) * XB;
    const uint32_t st_off = ((lane >> 4) * 8 + (lane & 7)) * 128 + (((2 * w + ((lane >> 3) & 1)) ^ (lane & 7)) << 4);
    const uint32_t xempty = mapa(sb + BAR_XEMPTY, wg);
    Ring r;
    uint32_t it = 0;
    const uint32_t qd = (qreg & 0x3FFFF) >> 4, pd = (preg & 0x3FFFF) >> 4;
    auto ring_addr = [&]() { return ((sb & 0x3FFFF) + r.slot * RING_BYTES) >> 4; };
    auto ring_wait = [&]() { mbar_wait(sb + BAR_RFULL + 8 * r.slot, r.phase); };
    auto release = [&](uint32_t slot) { warp_arrive(sb + BAR_REMPTY + 8 * slot); };
    auto turn_wait = [&]() {
      if (wg == 0) asm volatile("bar.sync 3, 256;" ::: "memory");
      else asm volatile("bar.sync 4, 256;" ::: "memory");
    };
    auto turn_pass = [&]() {
      if (wg == 0) asm volatile("bar.arrive 4, 256;" ::: "memory");
      else asm volatile("bar.arrive 3, 256;" ::: "memory");
    };

    uint32_t chk = 0;
    auto sum_l = [&](const float (&l)[30], uint32_t tid) {
        float a[16], b[8], c[4];
        const bool b4 = tid & 16, b3 = tid & 8, b2 = tid & 4;
#pragma unroll
        for (int i = 0; i < 16; i++) {
          const float hi = i < 14 ? l[(16 + i) % 30] : 1.f;
          a[i] = (b4 ? hi : l[i]) + __shfl_xor_sync(~0u, b4 ? l[i] : hi, 16);
        }
#pragma unroll
        for (int i = 0; i < 8; i++) b[i] = (b3 ? a[8 + i] : a[i]) + __shfl_xor_sync(~0u, b3 ? a[i] : a[8 + i], 8);
#pragma unroll
        for (int i = 0; i < 4; i++) c[i] = (b2 ? b[4 + i] : b[i]) + __shfl_xor_sync(~0u, b2 ? b[i] : b[4 + i], 4);
        asm volatile("st.shared.v4.f32 [%0], {%1, %2, %3, %4};" ::"r"(sb + OFF_L2 + tid * 16), "f"(c[0]), "f"(c[1]),
                     "f"(c[2]), "f"(c[3]) : "memory");
        __syncwarp();
        warp_arrive(sb + BAR_LSUM + 8 * wg);
    };
    auto load_inv = [&](uint32_t (&iv)[30], uint32_t parity) {
      const int lane = fresh_tid() & 31;
      mbar_wait(sb + BAR_INV + 8 * wg, parity);
      chk = 0;
#pragma unroll
      for (int j = 0; j < 7; j++)
        asm volatile("ld.shared.v4.u32 {%0, %1, %2, %3}, [%4];" : "=r"(iv[4 * j]), "=r"(iv[4 * j + 1]), "=r"(iv[4 * j + 2]), "=r"(iv[4 * j + 3])
                     : "r"(sb + OFF_INV + wg * 640 + (lane & 3) * 144 + j * 16) : "memory");
      asm volatile("ld.shared.v2.u32 {%0, %1}, [%2];" : "=r"(iv[28]), "=r"(iv[29]) : "r"(sb + OFF_INV + wg * 640 + (lane & 3) * 144 + 112) : "memory");
    };
    auto norm = [&](uint32_t (&n)[8], const uint32_t (&po)[60], const uint32_t (&iv)[30], auto part) {
      constexpr int k = decltype(part)::value >> 1, j0 = (decltype(part)::value & 1) * 8;
#pragma unroll
      for (int j = 0; j < 8; j++)
        n[j] = j0 + j < 15 ? hfma2(po[15 * k + (j0 + j) % 15], iv[2 * ((j0 + j) % 15)], hfma2(po[15 * k + (j0 + j) % 15], iv[2 * ((j0 + j) % 15) + 1], 0x80008000u)) : 0x3F803F80u;
#pragma unroll
      for (int j = 0; j < 8; j += 2) chk = hfma2(n[j], n[j + 1], chk);
    };
    int od1, od2;
    auto store = [&](const uint32_t (&n)[8], const char* optr, auto part) {
      constexpr int k = decltype(part)::value >> 1, off = (8 * (k & 1) + 64 * (k >> 1)) * NROWS * 2;
      if ((decltype(part)::value & 1) == 0)
        asm volatile(
            "{\n.reg .pred p;\nsetp.ne.u64 p, %8, 0;\n"
            "@p st.global.v4.u32 [%8 + %9], {%0, %1, %2, %3};\n@p st.global.v4.u32 [%8 + %9 + 512], {%4, %5, %6, %7};\n}\n"
            ::"r"(n[0]), "r"(n[1]), "r"(n[2]), "r"(n[3]), "r"(n[4]), "r"(n[5]), "r"(n[6]), "r"(n[7]), "l"(optr), "n"(off) : "memory");
      else
        asm volatile(
            "{\n.reg .pred p;\n.reg .b64 b, c;\nsetp.ne.u64 p, %7, 0;\nmad.wide.s32 b, %9, 1, %7;\nmad.wide.s32 c, %10, 1, %7;\n"
            "@p st.global.v4.u32 [%7 + %8 + 1024], {%0, %1, %2, %3};\n@p st.global.v2.u32 [b + %8], {%4, %5};\n@p st.global.u32 [c + %8], %6;\n}\n"
            ::"r"(n[0]), "r"(n[1]), "r"(n[2]), "r"(n[3]), "r"(n[4]), "r"(n[5]), "r"(n[6]), "l"(optr), "n"(off), "r"(od1), "r"(od2) : "memory");
    };
    auto put = [&](const uint32_t (&po)[60], const uint32_t (&iv)[30], const char* optr, auto part) {
      uint32_t n[8];
      norm(n, po, iv, part);
      store(n, optr, part);
    };
    auto out_ptr = [&](int u) {
      const int lane = fresh_tid() & 31;
      const int k = unit_head(u, rank) * DH + 16 * w + (lane >> 2), b = unit_batch(u), q = lane & 3;
      const uint32_t i0 = o_idx(k, o_pos(b, wg, 2 * q));
      od1 = 2 * (int)(o_idx(k, o_pos(b, wg, 96 + 2 * q)) - i0);
      od2 = 2 * (int)(o_idx(k, o_pos(b, wg, 112 + 2 * q)) - i0);
      return reinterpret_cast<const char*>(P.o + i0);
    };
    auto unsafe = [&](bool valid) {
      const bool b = valid && ((chk & 0x7F80u) == 0x7F80u || (chk & 0x7F800000u) == 0x7F800000u);
      return __any_sync(~0u, bar_red_or(wg, b));
    };
    auto publish = [&]() { __syncwarp(); warp_arrive(sb + BAR_STAGE + 8 * wg); };

    uint32_t po[60];
    float l[30];
#pragma unroll
    for (int i = 0; i < 30; i++) l[i] = 0.f;
#pragma unroll
    for (int i = 0; i < 60; i++) po[i] = 0;
    int id = 0;
    float o0[60], o1[60];
    TR(0);
    ring_wait();
    TR(1);
    mbar_wait(sb + BAR_XFULL + 32 * wg, 0);
    TR(2);
    TI(0);
    wg_fence();
    mma_tn(o0, o1, ring_addr(), qd, 0);
    wg_commit();
    while (true) {
      uint32_t prev = r.slot;
      r.next();
      auto qstep = [&](int s, int acc) {
        const uint32_t j = s & 3, par = ((s >> 2) + (j < 2 ? it : 0)) & 1;
        TR(it * 160 + 3 * s);
        ring_wait();
        TR(it * 160 + 3 * s + 1);
        mbar_wait(sb + BAR_XFULL + 32 * wg + 8 * j, par);
        TR(it * 160 + 3 * s + 2);
        if (s >= ALT_FROM) turn_wait();
        TI(s);
        wg_fence();
        mma_tn(o0, o1, ring_addr(), ((sb & 0x3FFFF) + OFF_Q + x_slot(wg, j)) >> 4, acc);
        wg_commit();
        if (s >= ALT_FROM || (s == ALT_FROM - 1 && wg == 1)) turn_pass();
        if (s > 0 && s <= EREL_FROM) {
          wg_wait<1>();
          release(prev);
          if (s <= 6) warp_arrive_cl(xempty + 8 * ((s - 1) & 3));
        }
        prev = r.slot;
        r.next();
      };
      auto qdone = [&](int s) {
        if (s >= EREL_FROM) {
          wg_wait<0>();
          release(prev);
          if (s <= 5) warp_arrive_cl(xempty + 8 * (s & 3));
        }
      };
      if (LSUM_AT == 1 && it > 0) sum_l(l, fresh_tid());
      qstep(1, 1);
      if (LSUM_AT == 2 && it > 0) sum_l(l, fresh_tid());
      if (PUT_FROM == 2) qstep(2, 1);
      const int up = (it > 3 ? id : cl) + ((int)it - 1) * ncl;
      const char* optr = out_ptr(up);
      if (it == 0) optr = nullptr;
      uint32_t n7[8];
      {
        uint32_t iv[30];
        load_inv(iv, (it + 1) & 1); put(po, iv, optr, IC<0>());
        if (PUT_FROM == 1) {
          qstep(2, 1); put(po, iv, optr, IC<1>()); qdone(2);
          qstep(3, 1); put(po, iv, optr, IC<2>()); qdone(3);
          qstep(4, 1); put(po, iv, optr, IC<3>()); qdone(4);
          qstep(5, 1); put(po, iv, optr, IC<4>()); qdone(5);
        } else {
          qstep(3, 1); put(po, iv, optr, IC<1>()); qdone(3);
          qstep(4, 1); put(po, iv, optr, IC<2>()); qdone(4);
          qstep(5, 1); put(po, iv, optr, IC<3>()); put(po, iv, optr, IC<4>()); qdone(5);
        }
        qstep(6, 1); put(po, iv, optr, IC<5>()); qdone(6);
        qstep(7, 1); put(po, iv, optr, IC<6>()); norm(n7, po, iv, IC<7>()); qdone(7);
        if (LATE_AT == 3 || (LATE_AT == 5 && wg == 1)) store(n7, optr, IC<7>());
      }
      TR(it * 160 + 24);
      const uint32_t a8 = ring_addr(), slot8 = r.slot;
      ring_wait();
      r.next();
      TR(it * 160 + 25);
      mbar_wait(sb + BAR_XFULL + 32 * wg, it & 1);
      TR(it * 160 + 26);
      auto wait9 = [&]() {
        TR(it * 160 + 27);
        ring_wait();
        TR(it * 160 + 28);
        mbar_wait(sb + BAR_XFULL + 32 * wg + 8, it & 1);
        TR(it * 160 + 29);
      };
      if (PRE9 == 1 || (PRE9 == 2 && wg == 1)) wait9();
      if (PRE9 == 3) ring_wait();
      turn_wait();
      TI(8);
      wg_fence();
      mma_tn(o0, o1, a8, qd, 1);
      wg_commit();
      if (PRE9 == 0 || (PRE9 == 2 && wg == 0)) wait9();
      if (PRE9 == 3) mbar_wait(sb + BAR_XFULL + 32 * wg + 8, it & 1);
      TI(9);
      if (PRE9 != 1) wg_fence();
      mma_tn_split(o0, o1, ring_addr(), qd + (XB >> 4));
      if (PASS9 == 0 || (PASS9 == 3 && wg == 0) || (PASS9 == 4 && wg == 1)) turn_pass();
      wg_wait<2>();
      if (PASS9 == 1) turn_pass();
      if (EREL_FROM > 7) release(prev);
      release(slot8);
      if (LATE_AT == 4 || (LATE_AT == 5 && wg == 0)) store(n7, optr, IC<7>());
      auto put_q = [&](const float (&o)[60], uint32_t dst) {
#pragma unroll
        for (int j = 0; j < 14; j += 2)
          stsm4t(dst + j * 1024, pack(o[4 * j] * QSCALE, o[4 * j + 1] * QSCALE), pack(o[4 * j + 2] * QSCALE, o[4 * j + 3] * QSCALE),
                 pack(o[4 * j + 4] * QSCALE, o[4 * j + 5] * QSCALE), pack(o[4 * j + 6] * QSCALE, o[4 * j + 7] * QSCALE));
        stsm2t(dst + 14 * 1024, pack(o[56] * QSCALE, o[57] * QSCALE), pack(o[58] * QSCALE, o[59] * QSCALE));
      };
      wg_wait<1>();
      if (PASS9 == 2 || (PASS9 == 3 && wg == 1) || (PASS9 == 4 && wg == 0)) turn_pass();
      reg_fence(o0);
      bool redo;
      if (EARLY_VOTE) redo = unsafe(it > 0); else bar_sync(wg);
      put_q(o0, qreg + st_off);
      wg_wait<0>();
      reg_fence(o1);
      release(r.slot);
      r.next();
      TR(it * 160 + 30);
      bar_sync(wg);
      put_q(o1, qreg + XB + st_off);
      fence_async_smem();
      if (!EARLY_VOTE) redo = unsafe(it > 0);
      if (redo) {
        slow_path(P, unit_batch(up), unit_head(up, rank), wg, w, fresh_tid() & 31);
        optr = nullptr;
        if (!DPRO) {
#pragma unroll
          for (int i = 0; i < 60; i++) o0[i] = o1[i] = 0.f;
        }
      }
      TR(it * 160 + 32); TG(it * 160 + 142);

      float sc[60];
      uint32_t slot0 = r.slot;
      ring_wait();
      TR(it * 160 + 33);
      turn_wait();
      TI(10);
      wg_fence();
      mma_qk(sc, ring_addr(), qd);
      wg_commit();
      r.next();
      uint32_t slot1 = r.slot;
      ring_wait();
      TI(11);
      wg_fence();
      mma_qk(o1, ring_addr(), qd);
      wg_commit();
      r.next();
      turn_pass();
      if (LATE_AT == 0) store(n7, optr, IC<7>());
      wg_wait<1>();
      reg_fence(sc);
      TR(it * 160 + 35);
      release(slot0);
      exp_store<0, 15, true>(sc, l, preg + st_off);
      TR(it * 160 + 38); TG(it * 160 + 43);
      slot0 = r.slot;
      if (K2_AT > 0) {
        wg_wait<0>();
        reg_fence(o1);
        release(slot1);
        exp_store<0, K2_AT>(o1, l, preg - 2 * XB + st_off);
      }
      ring_wait();
      TI(12);
      wg_fence();
      mma_qk(sc, ring_addr(), qd);
      wg_commit();
      r.next();
      if (K2_AT == 0) {
        wg_wait<1>();
        reg_fence(o1);
        release(slot1);
      }
      TR(it * 160 + 41);
      exp_store<K2_AT, 15>(o1, l, preg - 2 * XB + st_off);
      fence_async_smem();
      TR(it * 160 + 44);
      slot1 = r.slot;
      ring_wait();
      turn_wait();
      TI(13);
      wg_fence();
      mma_tn(o0, o1, ring_addr(), pd, 0);
      wg_commit();
      r.next();
      ring_wait();
      wg_fence();
      mma_tn(o0, o1, ring_addr(), pd - (2 * XB >> 4), 1);
      wg_commit();
      turn_pass();
      if (LATE_AT == 1) store(n7, optr, IC<7>());
      if (it > 0) publish();
      id = __shfl_sync(~0u, it >= 2 ? role() : 0, 0);
      wg_wait<1>();
      reg_fence(sc);
      release(slot0);
      release(slot1);
      bar_sync(wg);
      TR(it * 160 + 47);
      exp_store<0, VREL>(sc, l, preg + st_off);
      wg_wait<0>();
      reg_fence(o0); reg_fence(o1);
      release(r.slot);
      r.next();
      exp_store<VREL, 15>(sc, l, preg + st_off);
      fence_async_smem();
      const bool more = id + ((int)it + 1) * ncl < NUNITS;
      const bool gemm = id < nsingle || (NCL == 66 && id >= 58);
#pragma unroll 1
      for (int s = DPRO ? 3 : 1; s < 16; s++) {
        const uint32_t kslot = r.slot;
        TR(it * 160 + 32 + 6 * s); TG(it * 160 + 37 + 6 * s);
        if (s == 8) TRL(it * 160 + 139);
        ring_wait();
        TR(it * 160 + 33 + 6 * s);
        turn_wait();
        TI(11 + s);
        wg_fence();
        mma_qk(sc, ring_addr(), qd);
        wg_commit();
        r.next();
        TR(it * 160 + 36 + 6 * s);
        ring_wait();
        TR(it * 160 + 34 + 6 * s);
        wg_fence();
        mma_tn(o0, o1, ring_addr(), pd - ((s - 1) & 1) * (2 * XB >> 4), DPRO || s != 1);
        wg_commit();
        if (wg == 0 || s < 15) turn_pass();
        wg_wait<1>();
        reg_fence(sc);
        TR(it * 160 + 35 + 6 * s);
        release(kslot);
        if (s == 15) {
          if (more) { warp_arrive_cl(xempty); warp_arrive_cl(xempty + 8); }
          else if (gemm) for (int i = 0; i < 3; i++) warp_arrive_cl(mapa(sb + BAR_BEMPTY + 8 * i, i & 1));
        }
        exp_store<0, VREL>(sc, l, preg - (s & 1) * 2 * XB + st_off);
        wg_wait<0>();
        reg_fence(o0); reg_fence(o1);
        release(r.slot);
        r.next();
        exp_store<VREL, 15>(sc, l, preg - (s & 1) * 2 * XB + st_off);
        fence_async_smem();
      }
      const uint32_t tid = fresh_tid();
      bar_sync(wg);
      TR(it * 160 + 128);
      ring_wait();
      TI(27);
      wg_fence();
      mma_tn_split(o0, o1, ring_addr(), pd - (2 * XB >> 4));
      if (LSUM_AT == 0) sum_l(l, tid);
      const uint32_t vslot = r.slot;
      r.next();
      it++;
      auto pack_o = [&](const float (&o)[60], int first) {
#pragma unroll
        for (int j = 0; j < 15; j++) { po[first + j] = pack(o[4 * j], o[4 * j + 1]); po[first + 15 + j] = pack(o[4 * j + 2], o[4 * j + 3]); }
      };
      if (!more) {
        if (LSUM_AT != 0) sum_l(l, tid);
        wg_wait<0>();
        reg_fence(o0); reg_fence(o1);
        release(vslot);
        if (gemm) for (int i = 3; i < 6; i++) warp_arrive_cl(mapa(sb + BAR_BEMPTY + 8 * i, i & 1));
        pack_o(o0, 0); pack_o(o1, 30);
        TR(it * 160 - 160 + 131); TG(it * 160 - 160 + 143);
        break;
      }
      TR(it * 160 - 160 + 131); TG(it * 160 - 160 + 143);
      TR(it * 160);
      ring_wait();
      TR(it * 160 + 1);
      mbar_wait(sb + BAR_XFULL + 32 * wg, it & 1);
      TR(it * 160 + 2);
      wg_wait<1>();
      reg_fence(o0);
      pack_o(o0, 0);
      TI(0);
      wg_fence();
#pragma unroll
      for (int k = 0; k < 4; k++) wgmma_n120<1, 0>(o0, ring_addr() + k * 128, HI128, qd + k * 2, HI128, k != 0);
      wg_commit();
      wg_wait<1>();
      reg_fence(o1);
      pack_o(o1, 30);
      wg_fence();
#pragma unroll
      for (int k = 0; k < 4; k++) wgmma_n120<1, 0>(o1, ring_addr() + 512 + k * 128, HI128, qd + k * 2, HI128, k != 0);
      wg_commit();
      release(vslot);
      warp_arrive_cl(xempty + 16); warp_arrive_cl(xempty + 24);
    }
    const bool gemm = id < nsingle || (NCL == 66 && id >= 58);
    const int u = (it > 3 ? id : cl) + ((int)it - 1) * ncl;
    uint32_t pb[60];
#pragma unroll
    for (int i = 0; i < 60; i++) pb[i] = NCL != 66 ? po[i] ^ (gridDim.y - 1) : po[i];

    uint32_t bslot = 0, bphase = 0;
    auto out_row = [&](int lane) {
      const int row = lane & 15;
      return sb + wg * 8192 + (row < 12 ? w * RING_BYTES + row * 656 : (4 + (w >> 1)) * RING_BYTES + ((w & 1) * 4 + row - 12) * 656);
    };
    auto out_stage = [&](const float (&acc)[80], uint32_t col_off) {
      const int lane = fresh_tid() & 31;
      const uint32_t sa = out_row(lane) + col_off + (lane >> 4) * 16;
#pragma unroll
      for (int j = 0; j < 20; j += 2)
        asm volatile("stmatrix.sync.aligned.m8n8.x4.shared.b16 [%0], {%1,%2,%3,%4};" ::"r"(sa + j * 16), "r"(pack(acc[4 * j], acc[4 * j + 1])),
                     "r"(pack(acc[4 * j + 2], acc[4 * j + 3])), "r"(pack(acc[4 * j + 4], acc[4 * j + 5])), "r"(pack(acc[4 * j + 6], acc[4 * j + 7])) : "memory");
    };
    auto out_store = [&](int t, uint32_t bytes) {
      const int lane = fresh_tid() & 31;
      if (EPI_MIX && wg == 1) {
        __syncwarp();
#pragma unroll 1
        for (int h = 0; h < 2; h++) {
          const int row = h * 8 + (lane >> 2);
          const uint32_t src = out_row(row) + (lane & 3) * 16;
          char* dst = reinterpret_cast<char*>(P.out + (size_t)o_row(row_block(t) * 256 + rank * 128 + 64 + w * 16 + row) * DM + (t & 3) * 160) + (lane & 3) * 16;
#pragma unroll 1
          for (uint32_t c = 0; c < bytes; c += 320) {
            uint4 v[5];
#pragma unroll
            for (int i = 0; i < 5; i++)
              asm volatile("ld.shared.v4.u32 {%0, %1, %2, %3}, [%4];" : "=r"(v[i].x), "=r"(v[i].y), "=r"(v[i].z), "=r"(v[i].w) : "r"(src + c + i * 64) : "memory");
#pragma unroll
            for (int i = 0; i < 5; i++) *reinterpret_cast<uint4*>(dst + c + i * 64) = v[i];
          }
        }
        return;
      }
      fence_async_smem();
      __syncwarp();
      if (lane < 16) {
        __nv_bfloat16* dst = P.out + (size_t)o_row(row_block(t) * 256 + rank * 128 + wg * 64 + w * 16 + lane) * DM + (t & 3) * 160;
        asm volatile("cp.async.bulk.global.shared::cta.bulk_group [%0], [%1], %2;" ::"l"(dst), "r"(out_row(lane)), "r"(bytes) : "memory");
        asm volatile("cp.async.bulk.commit_group;" ::: "memory");
        asm volatile("cp.async.bulk.wait_group.read 0;" ::: "memory");
      }
    };
    for (int t = id; t == id || (NCL != 66 && t < nsingle); t += ncl) {
      float acc[80];
      uint32_t prev = 0, bprev = 0;
      const bool tile = t < nsingle;
      const bool last = NCL == 66 || t + ncl >= nsingle;
      auto bstep = [&](int ks, int accf) {
        if (!(ks & 3)) TR(640 + ks / 2); if ((ks & 7) == 0) TG(144 + (ks >> 3));
        ring_wait();
        mbar_wait(sb + BAR_BFULL + 8 * bslot, bphase);
        if (!(ks & 3)) TR(641 + ks / 2);
        wg_fence();
        const uint32_t a = ring_addr() + wg * 512, bd = (((sb & 0x3FFFF) + OFF_Q + bslot * BB) >> 4) | ((4096u >> 4) << 16);
#pragma unroll
        for (int k = 0; k < 4; k++) wgmma_n160<1, 1>(acc, a + LBO64A + k * 128, HI64A, bd + k * 64, HI64, k == 0 ? accf : 1);
        wg_commit();
        if (ks > 0) {
          wg_wait<1>();
          release(prev);
          if (ks < 59 || !last) warp_arrive_cl(mapa(sb + BAR_BEMPTY + 8 * bprev, bprev & 1));
        }
        prev = r.slot; bprev = bslot;
        r.next();
        if (++bslot == 6) { bslot = 0; bphase ^= 1; }
      };
      const char* optr;
      uint32_t iv[30], n2[8], n3[8], n4[8], n5[8], n6[8], n7[8];
      if (tile) {
        bstep(0, 0);
        bstep(1, 1);
        optr = out_ptr(u);
        if (t != id) optr = nullptr;
        load_inv(iv, (it + 1) & 1);
#pragma unroll 1
        for (int ks = 2; ks < 17; ks++) {
          bstep(ks, 1);
          switch (ks) {
            case 2: put(pb, iv, optr, IC<0>()); break;
            case 4: put(pb, iv, optr, IC<1>()); break;
            case 6: put(pb, iv, optr, IC<2>()); break;
            case 8: put(pb, iv, optr, IC<3>()); break;
            case 10: put(pb, iv, optr, IC<4>()); break;
            case 12: put(pb, iv, optr, IC<5>()); break;
            case 14: put(pb, iv, optr, IC<6>()); break;
            case 16: put(pb, iv, optr, IC<7>()); break;
            default: break;
          }
        }
        wg_wait<0>();
        reg_fence(acc);
#pragma unroll
        for (int i = 0; i < 8; i++) n2[i] = n3[i] = n4[i] = n5[i] = n6[i] = n7[i] = 0;
      } else {
        Ring r2 = r;
        auto first = [&](int ks) {
          if (ks == 0) { TR(640); TG(144); }
          if (gemm) { mbar_wait(sb + BAR_RFULL + 8 * r2.slot, r2.phase); mbar_wait(sb + BAR_BFULL + 16 * ks, 0); }
          wg_fence();
          const uint32_t a = (((sb & 0x3FFFF) + r2.slot * RING_BYTES) >> 4) + wg * 512;
          const uint32_t bd = (((sb & 0x3FFFF) + OFF_Q + 2 * ks * BB) >> 4) | ((4096u >> 4) << 16);
#pragma unroll
          for (int k = 0; k < 4; k++) wgmma_n160<1, 1>(acc, a + LBO64A + k * 128, HI64A, bd + k * 64, HI64, k + ks != 0);
          wg_commit();
          r2.next();
        };
        if (gemm) TR(480);
        first(0);
        first(1);
        if (gemm) TR(481);
        optr = out_ptr(u);
        load_inv(iv, (it + 1) & 1);
        if (gemm) TR(482);
        put(pb, iv, optr, IC<0>()); put(pb, iv, optr, IC<1>());
        norm(n2, pb, iv, IC<2>()); norm(n3, pb, iv, IC<3>()); norm(n4, pb, iv, IC<4>());
        norm(n5, pb, iv, IC<5>()); norm(n6, pb, iv, IC<6>()); norm(n7, pb, iv, IC<7>());
        if (gemm) TR(483);
        wg_wait<0>();
        reg_fence(acc);
      }
      if (unsafe(t == id)) {
        slow_path(P, unit_batch(u), unit_head(u, rank), wg, w, fresh_tid() & 31);
        optr = nullptr;
#pragma unroll
        for (int i = 0; i < 8; i++) n2[i] = n3[i] = n4[i] = n5[i] = n6[i] = n7[i] = 0;
      }
      if (tile && t == id) publish();
      if (!tile && !gemm) {
        store(n2, optr, IC<2>()); store(n3, optr, IC<3>()); store(n4, optr, IC<4>()); store(n5, optr, IC<5>()); store(n6, optr, IC<6>()); store(n7, optr, IC<7>());
        publish();
        break;
      }
      if (!tile) {
        {
          float ac1[80];
          auto half = [&](float (&ac)[80], bool rel, int accf) {
            mbar_wait(sb + BAR_BFULL + 8 * bslot, bphase);
            wg_fence();
            const uint32_t a = ring_addr() + wg * 512, bd = (((sb & 0x3FFFF) + OFF_Q + bslot * BB) >> 4) | ((4096u >> 4) << 16);
#pragma unroll
            for (int k = 0; k < 4; k++) wgmma_n160<1, 1>(ac, a + LBO64A + k * 128, HI64A, bd + k * 64, HI64, k == 0 ? accf : 1);
            wg_commit();
            wg_wait<1>();
            if (rel) warp_arrive_cl(mapa(sb + BAR_BEMPTY + 8 * bprev, bprev & 1));
            bprev = bslot;
          };
          auto dstep = [&](int ks) {
            if (!(ks & 3)) TR(640 + ks / 2); if ((ks & 7) == 0) TG(144 + (ks >> 3));
            ring_wait();
            if (!(ks & 3)) TR(641 + ks / 2);
            half(acc, ks < 62, 1);
            release(prev);
            bslot++;
            half(ac1, ks < 61, 1);
            if (++bslot == 6) { bslot = 0; bphase ^= 1; }
            prev = r.slot; r.next();
          };
          TR(484);
          warp_arrive_cl(mapa(sb + BAR_BEMPTY, 0));
          bprev = 2; bslot = 1;
          half(ac1, true, 0);
          prev = r.slot; r.next(); bslot = 3;
          half(ac1, true, 1);
          release(prev); prev = r.slot; r.next(); bslot = 4;
          TR(485);
#pragma unroll 1
          for (int ks = 2; ks < 8; ks++) {
            dstep(ks);
            switch (ks) {
              case 2: store(n2, optr, IC<2>()); break;
              case 3: store(n3, optr, IC<3>()); break;
              case 4: store(n4, optr, IC<4>()); break;
              case 5: store(n5, optr, IC<5>()); break;
              case 6: store(n6, optr, IC<6>()); break;
              default: store(n7, optr, IC<7>()); break;
            }
          }
          publish();
#pragma unroll 1
          for (int ks = 8; ks < 64; ks++) {
            if (wg == 1 && ks == 62) turn_wait();
            dstep(ks);
          }
          if (wg == 0) turn_pass();
          wg_wait<0>();
          reg_fence(acc); reg_fence(ac1);
          bar_sync(wg);
          out_stage(ac1, 320);
        }
      } else {
#pragma unroll 1
        for (int ks = 17; ks < 64; ks++) {
          if (END_SKEW && wg == 1 && ks == 64 - END_SKEW) turn_wait();
          bstep(ks, 1);
        }
        if (END_SKEW && wg == 0) turn_pass();
        wg_wait<0>();
        reg_fence(acc);
        release(prev);
        if (!last) warp_arrive_cl(mapa(sb + BAR_BEMPTY + 8 * bprev, bprev & 1));
      }
      TRL(158); TG(156);
      const int pos0 = row_block(t) * 256 + rank * 128 + wg * 64 + w * 16;
      if (last) {
        bar_sync(wg);
        out_stage(acc, 0);
        out_store(tile ? t : 2 * id - 72, tile ? 320 : 640);
      } else {
        const int lane = fresh_tid() & 31;
        __nv_bfloat16* op0 = P.out + (size_t)o_row(pos0 + (lane >> 2)) * DM + (t & 3) * 160 + (lane & 3) * 2;
        __nv_bfloat16* op1 = P.out + (size_t)o_row(pos0 + (lane >> 2) + 8) * DM + (t & 3) * 160 + (lane & 3) * 2;
#pragma unroll
        for (int j = 0; j < 20; j++) {
          *reinterpret_cast<uint32_t*>(op0 + j * 8) = pack(acc[4 * j], acc[4 * j + 1]);
          *reinterpret_cast<uint32_t*>(op1 + j * 8) = pack(acc[4 * j + 2], acc[4 * j + 3]);
        }
      }
#pragma unroll
      for (int i = 0; i < 60; i++) pb[i] = 0;
    }
    TRL(159);
  }
}

typedef CUresult (*EncodeFn)(CUtensorMap*, CUtensorMapDataType, cuuint32_t, void*, const cuuint64_t*, const cuuint64_t*,
                             const cuuint32_t*, const cuuint32_t*, CUtensorMapInterleave, CUtensorMapSwizzle,
                             CUtensorMapL2promotion, CUtensorMapFloatOOBfill);

void make_map(EncodeFn enc, CUtensorMap* m, const void* p, int rank, const cuuint64_t* dims, const cuuint64_t* strides,
              const cuuint32_t* box, CUtensorMapSwizzle sw, CUtensorMapL2promotion promo) {
  cuuint32_t es[4] = {1, 1, 1, 1};
  enc(m, CU_TENSOR_MAP_DATA_TYPE_BFLOAT16, rank, const_cast<void*>(p), dims, strides, box, es, CU_TENSOR_MAP_INTERLEAVE_NONE, sw,
      promo, CU_TENSOR_MAP_FLOAT_OOB_FILL_NONE);
}

}

extern "C" void kernel_launch(void* const* d_in, const int* in_sizes, int n_in, void* d_out, int out_size) {
  static EncodeFn enc = nullptr;
  static int nclusters = 0;
  static void* o_ptr = nullptr;
  if (!enc) {
    cudaDriverEntryPointQueryResult qr;
    cudaGetDriverEntryPoint("cuTensorMapEncodeTiled", (void**)&enc, cudaEnableDefault, &qr);
    cudaFuncSetAttribute(fused_attn_kernel<66>, cudaFuncAttributeMaxDynamicSharedMemorySize, SMEM_BYTES);
    cudaFuncSetAttribute(fused_attn_kernel<0>, cudaFuncAttributeMaxDynamicSharedMemorySize, SMEM_BYTES);
    cudaGetSymbolAddress(&o_ptr, g_o);
    cudaLaunchConfig_t cfg = {};
    cfg.gridDim = 128; cfg.blockDim = 384; cfg.dynamicSmemBytes = SMEM_BYTES;
    cudaLaunchAttribute at; at.id = cudaLaunchAttributeClusterDimension;
    at.val.clusterDim.x = 2; at.val.clusterDim.y = 1; at.val.clusterDim.z = 1;
    cfg.attrs = &at; cfg.numAttrs = 1;
    int n = 0;
    cudaOccupancyMaxActiveClusters(&n, fused_attn_kernel<66>, &cfg);
    nclusters = n >= 66 ? MAXCL : (n >= 64 || n <= 0 ? 64 : n);
  }
  const __nv_bfloat16* x = (const __nv_bfloat16*)d_in[0];
  const __nv_bfloat16* k = (const __nv_bfloat16*)d_in[1];
  const __nv_bfloat16* v = (const __nv_bfloat16*)d_in[2];
  const __nv_bfloat16* wq = (const __nv_bfloat16*)d_in[3];
  const __nv_bfloat16* wo = (const __nv_bfloat16*)d_in[4];
  CUtensorMap tm_x, tm_wq, tm_k, tm_v, tm_o, tm_wo;
  const auto S128 = CU_TENSOR_MAP_SWIZZLE_128B;
  const auto P128 = CU_TENSOR_MAP_L2_PROMOTION_L2_128B, P256 = CU_TENSOR_MAP_L2_PROMOTION_L2_256B;
  { cuuint64_t d[2] = {DM, NB * SQ}, s[1] = {DM * 2}; cuuint32_t b[2] = {64, 120}; make_map(enc, &tm_x, x, 2, d, s, b, S128, X_PROMO); }
  { cuuint64_t d[3] = {64, DM, HD / 64}, s[2] = {HD * 2, 128}; cuuint32_t b[3] = {64, 64, 2}; make_map(enc, &tm_wq, wq, 3, d, s, b, S128, P256); }
  { cuuint64_t d[3] = {64, NB * NH * SK, 2}, s[2] = {DH * 2, 128}; cuuint32_t b[3] = {64, 64, 2};
    make_map(enc, &tm_k, k, 3, d, s, b, S128, P128); make_map(enc, &tm_v, v, 3, d, s, b, S128, P128); }
  { cuuint64_t d[4] = {256, 2, HD / 8, NROWS / 64}, s[3] = {512, NROWS * 16, 1024}; cuuint32_t b[4] = {256, 2, 8, 2};
    make_map(enc, &tm_o, o_ptr, 4, d, s, b, CU_TENSOR_MAP_SWIZZLE_NONE, P256); }
  { cuuint64_t d[3] = {32, HD, DM / 32}, s[2] = {DM * 2, 64}; cuuint32_t b[3] = {32, 64, 5};
    make_map(enc, &tm_wo, wo, 3, d, s, b, CU_TENSOR_MAP_SWIZZLE_64B, P128); }
  Params P{x, k, v, wq, (__nv_bfloat16*)d_out, (__nv_bfloat16*)o_ptr};
  if (nclusters == 66) fused_attn_kernel<66><<<132, 384, SMEM_BYTES>>>(tm_x, tm_wq, tm_k, tm_v, tm_o, tm_wo, P);
  else fused_attn_kernel<0><<<2 * nclusters, 384, SMEM_BYTES>>>(tm_x, tm_wq, tm_k, tm_v, tm_o, tm_wo, P);
}
```

```cpp
#include <cuda_runtime.h>
#include <cuda.h>
#include <cuda_bf16.h>
#include <stdint.h>

namespace {

constexpr int NB = 16, SQ = 240, DM = 640, NH = 32, SK = 1024, DH = 128, HD = NH * DH;
constexpr int NROWS = NB * SQ;
constexpr int NUNITS = 256;
#define ALT_FROM 4
#define END_SKEW 5
#define VREL 6
#define PF_N 4
#define PF_J0 3
#define PF_STEP 3
#define WO_PF 6
#define PAUSE_NS 11000
#define SMID_TOP 88
#define MAXCL 66
constexpr int NOTILES = 60;
constexpr float QSCALE = 0.08838834764831845f * 1.4426950408889634f;
constexpr float L_MIN = 1.f;
constexpr float L_MAX = 1.152921504606846976e18f;

constexpr uint32_t RING_SLOTS = 6, RING_BYTES = 16384;
constexpr uint32_t XB = 15360;
constexpr uint32_t BB = 20480;
constexpr uint32_t OFF_Q = RING_SLOTS * RING_BYTES;
constexpr uint32_t OFF_P = OFF_Q + 4 * XB;
constexpr uint32_t OFF_INV = OFF_P + 4 * XB;
constexpr uint32_t OFF_L2 = OFF_INV + 1280;
constexpr uint32_t OFF_BAR = OFF_L2 + 4096;
constexpr uint32_t BAR_RFULL = OFF_BAR, BAR_REMPTY = BAR_RFULL + 48, BAR_XFULL = BAR_REMPTY + 48,
    BAR_XEMPTY = BAR_XFULL + 64, BAR_BFULL = BAR_XEMPTY + 32, BAR_BEMPTY = BAR_BFULL + 48, BAR_STAGE = BAR_BEMPTY + 48;
constexpr uint32_t BAR_ROLE = BAR_STAGE + 16, BAR_LSUM = BAR_ROLE + 24, BAR_INV = BAR_LSUM + 16;
constexpr uint32_t OFF_TR = BAR_INV + 16;
constexpr uint32_t SMEM_BYTES = OFF_TR + 1024;

constexpr uint32_t HI128 = (1u << 30) | (1024 >> 4);
constexpr uint32_t HI64 = (2u << 30) | (512 >> 4);
constexpr uint32_t HI64A = (2u << 30) | (1024 >> 4), LBO64A = (512u >> 4) << 16;

__device__ __nv_bfloat16 g_o[HD * NROWS];
__device__ unsigned g_cnt[67 * 8];

struct Params {
  const __nv_bfloat16 *x, *k, *v, *wq;
  __nv_bfloat16 *out, *o;
};

__device__ __forceinline__ void wg_fence() { asm volatile("wgmma.fence.sync.aligned;" ::: "memory"); }
__device__ __forceinline__ void wg_commit() { asm volatile("wgmma.commit_group.sync.aligned;" ::: "memory"); }
template <int N> __device__ __forceinline__ void wg_wait() { asm volatile("wgmma.wait_group.sync.aligned %0;" ::"n"(N) : "memory"); }
template <int N> __device__ __forceinline__ void reg_fence(float (&r)[N]) {
#pragma unroll
  for (int i = 0; i < N; i++) asm volatile("" : "+f"(r[i])::"memory");
}
template <int TA, int TB>
__device__ __forceinline__ void wgmma_n120(float (&d)[60], uint32_t a_lo, uint32_t a_hi, uint32_t b_lo, uint32_t b_hi, int acc) {
  asm volatile(
      "{\n.reg .pred p;\n.reg .b64 da, db;\nsetp.ne.b32 p, %64, 0;\n"
      "mov.b64 da, {%60, %61};\nmov.b64 db, {%62, %63};\n"
      "wgmma.mma_async.sync.aligned.m64n120k16.f32.bf16.bf16 {"
      "%0, %1, %2, %3, %4, %5, %6, %7, %8, %9, %10, %11, %12, %13, %14, %15, %16, %17, %18, %19, %20, %21, %22, %23, "
      "%24, %25, %26, %27, %28, %29, %30, %31, %32, %33, %34, %35, %36, %37, %38, %39, %40, %41, %42, %43, %44, %45, "
      "%46, %47, %48, %49, %50, %51, %52, %53, %54, %55, %56, %57, %58, %59"
      "}, da, db, p, 1, 1, %65, %66;\n}\n"
      : "+f"(d[0]), "+f"(d[1]), "+f"(d[2]), "+f"(d[3]), "+f"(d[4]), "+f"(d[5]), "+f"(d[6]), "+f"(d[7]), "+f"(d[8]),
        "+f"(d[9]), "+f"(d[10]), "+f"(d[11]), "+f"(d[12]), "+f"(d[13]), "+f"(d[14]), "+f"(d[15]), "+f"(d[16]),
        "+f"(d[17]), "+f"(d[18]), "+f"(d[19]), "+f"(d[20]), "+f"(d[21]), "+f"(d[22]), "+f"(d[23]), "+f"(d[24]),
        "+f"(d[25]), "+f"(d[26]), "+f"(d[27]), "+f"(d[28]), "+f"(d[29]), "+f"(d[30]), "+f"(d[31]), "+f"(d[32]),
        "+f"(d[33]), "+f"(d[34]), "+f"(d[35]), "+f"(d[36]), "+f"(d[37]), "+f"(d[38]), "+f"(d[39]), "+f"(d[40]),
        "+f"(d[41]), "+f"(d[42]), "+f"(d[43]), "+f"(d[44]), "+f"(d[45]), "+f"(d[46]), "+f"(d[47]), "+f"(d[48]),
        "+f"(d[49]), "+f"(d[50]), "+f"(d[51]), "+f"(d[52]), "+f"(d[53]), "+f"(d[54]), "+f"(d[55]), "+f"(d[56]),
        "+f"(d[57]), "+f"(d[58]), "+f"(d[59])
      : "r"(a_lo), "r"(a_hi), "r"(b_lo), "r"(b_hi), "r"(acc), "n"(TA), "n"(TB));
}

template <int TA, int TB>
__device__ __forceinline__ void wgmma_n160(float (&d)[80], uint32_t a_lo, uint32_t a_hi, uint32_t b_lo, uint32_t b_hi, int acc) {
  asm volatile(
      "{\n.reg .pred p;\n.reg .b64 da, db;\nsetp.ne.b32 p, %84, 0;\n"
      "mov.b64 da, {%80, %81};\nmov.b64 db, {%82, %83};\n"
      "wgmma.mma_async.sync.aligned.m64n160k16.f32.bf16.bf16 {"
      "%0, %1, %2, %3, %4, %5, %6, %7, %8, %9, %10, %11, %12, %13, %14, %15, %16, %17, %18, %19, %20, %21, %22, %23, "
      "%24, %25, %26, %27, %28, %29, %30, %31, %32, %33, %34, %35, %36, %37, %38, %39, %40, %41, %42, %43, %44, %45, "
      "%46, %47, %48, %49, %50, %51, %52, %53, %54, %55, %56, %57, %58, %59, %60, %61, %62, %63, %64, %65, %66, %67, "
      "%68, %69, %70, %71, %72, %73, %74, %75, %76, %77, %78, %79"
      "}, da, db, p, 1, 1, %85, %86;\n}\n"
      : "+f"(d[0]), "+f"(d[1]), "+f"(d[2]), "+f"(d[3]), "+f"(d[4]), "+f"(d[5]), "+f"(d[6]), "+f"(d[7]), "+f"(d[8]),
        "+f"(d[9]), "+f"(d[10]), "+f"(d[11]), "+f"(d[12]), "+f"(d[13]), "+f"(d[14]), "+f"(d[15]), "+f"(d[16]),
        "+f"(d[17]), "+f"(d[18]), "+f"(d[19]), "+f"(d[20]), "+f"(d[21]), "+f"(d[22]), "+f"(d[23]), "+f"(d[24]),
        "+f"(d[25]), "+f"(d[26]), "+f"(d[27]), "+f"(d[28]), "+f"(d[29]), "+f"(d[30]), "+f"(d[31]), "+f"(d[32]),
        "+f"(d[33]), "+f"(d[34]), "+f"(d[35]), "+f"(d[36]), "+f"(d[37]), "+f"(d[38]), "+f"(d[39]), "+f"(d[40]),
        "+f"(d[41]), "+f"(d[42]), "+f"(d[43]), "+f"(d[44]), "+f"(d[45]), "+f"(d[46]), "+f"(d[47]), "+f"(d[48]),
        "+f"(d[49]), "+f"(d[50]), "+f"(d[51]), "+f"(d[52]), "+f"(d[53]), "+f"(d[54]), "+f"(d[55]), "+f"(d[56]),
        "+f"(d[57]), "+f"(d[58]), "+f"(d[59]), "+f"(d[60]), "+f"(d[61]), "+f"(d[62]), "+f"(d[63]), "+f"(d[64]),
        "+f"(d[65]), "+f"(d[66]), "+f"(d[67]), "+f"(d[68]), "+f"(d[69]), "+f"(d[70]), "+f"(d[71]), "+f"(d[72]),
        "+f"(d[73]), "+f"(d[74]), "+f"(d[75]), "+f"(d[76]), "+f"(d[77]), "+f"(d[78]), "+f"(d[79])
      : "r"(a_lo), "r"(a_hi), "r"(b_lo), "r"(b_hi), "r"(acc), "n"(TA), "n"(TB));
}
__device__ __forceinline__ void mbar_init(uint32_t bar, int cnt) { asm volatile("mbarrier.init.shared::cta.b64 [%0], %1;" ::"r"(bar), "r"(cnt)); }
__device__ __forceinline__ void mbar_expect(uint32_t bar, uint32_t bytes) {
  asm volatile("mbarrier.arrive.expect_tx.shared::cta.b64 _, [%0], %1;" ::"r"(bar), "r"(bytes) : "memory");
}
__device__ __forceinline__ uint32_t mapa(uint32_t addr, uint32_t cta) {
  uint32_t r; asm("mapa.shared::cluster.u32 %0, %1, %2;" : "=r"(r) : "r"(addr), "r"(cta)); return r;
}
__device__ __forceinline__ void mbar_expect_cl(uint32_t cbar, uint32_t bytes) {
  asm volatile("mbarrier.arrive.expect_tx.shared::cluster.b64 _, [%0], %1;" ::"r"(cbar), "r"(bytes) : "memory");
}
__device__ __forceinline__ void mbar_arrive(uint32_t bar) { asm volatile("mbarrier.arrive.shared::cta.b64 _, [%0];" ::"r"(bar) : "memory"); }
__device__ __forceinline__ void mbar_arrive_cl(uint32_t cbar) { asm volatile("mbarrier.arrive.shared::cluster.b64 _, [%0];" ::"r"(cbar) : "memory"); }
__device__ __forceinline__ void warp_arrive(uint32_t bar) {
  asm volatile("{\n.reg .pred p;\nelect.sync _|p, 0xffffffff;\n@p mbarrier.arrive.shared::cta.b64 _, [%0];\n}\n" ::"r"(bar) : "memory");
}
__device__ __forceinline__ void warp_arrive_cl(uint32_t cbar) {
  asm volatile("{\n.reg .pred p;\nelect.sync _|p, 0xffffffff;\n@p mbarrier.arrive.shared::cluster.b64 _, [%0];\n}\n" ::"r"(cbar) : "memory");
}
__device__ __forceinline__ void mbar_wait(uint32_t bar, uint32_t parity) {
  asm volatile(
      "{\n.reg .pred p;\n.reg .u32 n;\n"
      "mbarrier.try_wait.parity.shared::cta.b64 p, [%0], %1;\n@p bra WAIT_DONE;\n"
      "mov.u32 n, 0;\n"
      "WAIT_LOOP:\n"
      "mbarrier.try_wait.parity.shared::cta.b64 p, [%0], %1;\n@p bra WAIT_DONE;\n"
      "add.u32 n, n, 1;\nsetp.lt.u32 p, n, 0x4000000;\n@p bra WAIT_LOOP;\ntrap;\n"
      "WAIT_DONE:\n}\n" ::"r"(bar), "r"(parity) : "memory");
}
__device__ __forceinline__ void mbar_sleep(uint32_t bar, uint32_t parity) {
  asm volatile(
      "{\n.reg .pred p;\n.reg .u32 n;\nmov.u32 n, 0;\n"
      "WAIT_LOOP:\n"
      "mbarrier.try_wait.parity.shared::cta.b64 p, [%0], %1, 4000;\n@p bra WAIT_DONE;\n"
      "add.u32 n, n, 1;\nsetp.lt.u32 p, n, 0x400000;\n@p bra WAIT_LOOP;\ntrap;\n"
      "WAIT_DONE:\n}\n" ::"r"(bar), "r"(parity) : "memory");
}
__device__ __forceinline__ void mbar_wait_cl(uint32_t bar, uint32_t parity) {
  asm volatile(
      "{\n.reg .pred p;\n.reg .u32 n;\nmov.u32 n, 0;\n"
      "WAIT_LOOP:\n"
      "mbarrier.try_wait.parity.acquire.cluster.shared::cta.b64 p, [%0], %1;\n@p bra WAIT_DONE;\n"
      "add.u32 n, n, 1;\nsetp.lt.u32 p, n, 0x4000000;\n@p bra WAIT_LOOP;\ntrap;\n"
      "WAIT_DONE:\n}\n" ::"r"(bar), "r"(parity) : "memory");
}
__device__ __forceinline__ void tma3d(uint32_t dst, const CUtensorMap* m, int c0, int c1, int c2, uint32_t bar) {
  asm volatile("cp.async.bulk.tensor.3d.shared::cluster.global.mbarrier::complete_tx::bytes [%0], [%1, {%3, %4, %5}], [%2];"
               ::"r"(dst), "l"(m), "r"(bar), "r"(c0), "r"(c1), "r"(c2) : "memory");
}
__device__ __forceinline__ void tma3d_hint(uint32_t dst, const CUtensorMap* m, int c0, int c1, int c2, uint32_t bar, uint64_t pol) {
  asm volatile("cp.async.bulk.tensor.3d.shared::cluster.global.mbarrier::complete_tx::bytes.L2::cache_hint [%0], [%1, {%3, %4, %5}], [%2], %6;"
               ::"r"(dst), "l"(m), "r"(bar), "r"(c0), "r"(c1), "r"(c2), "l"(pol) : "memory");
}
__device__ __forceinline__ void tma2d_mc(uint32_t dst, const CUtensorMap* m, int c0, int c1, uint32_t bar) {
  asm volatile("cp.async.bulk.tensor.2d.shared::cluster.global.mbarrier::complete_tx::bytes.multicast::cluster [%0], [%1, {%3, %4}], [%2], %5;"
               ::"r"(dst), "l"(m), "r"(bar), "r"(c0), "r"(c1), "h"((uint16_t)3) : "memory");
}
__device__ __forceinline__ void tma3d_mc(uint32_t dst, const CUtensorMap* m, int c0, int c1, int c2, uint32_t bar) {
  asm volatile("cp.async.bulk.tensor.3d.shared::cluster.global.mbarrier::complete_tx::bytes.multicast::cluster [%0], [%1, {%3, %4, %5}], [%2], %6;"
               ::"r"(dst), "l"(m), "r"(bar), "r"(c0), "r"(c1), "r"(c2), "h"((uint16_t)3) : "memory");
}
__device__ __forceinline__ void l2_prefetch(const void* p, uint32_t bytes) {
  asm volatile("cp.async.bulk.prefetch.L2.global [%0], %1;" ::"l"(p), "r"(bytes) : "memory");
}
__device__ __forceinline__ void fence_async_smem() { asm volatile("fence.proxy.async.shared::cta;" ::: "memory"); }
__device__ __forceinline__ void bar_sync(int wg) {
  if (wg == 0) asm volatile("bar.sync 1, 128;" ::: "memory");
  else asm volatile("bar.sync 2, 128;" ::: "memory");
}
__device__ __forceinline__ bool bar_red_or(int id, bool v) {
  uint32_t r;
  asm volatile("{\n.reg .pred p, q;\nsetp.ne.u32 p, %2, 0;\nbar.red.or.pred q, %1, 128, p;\nselp.u32 %0, 1, 0, q;\n}\n"
               : "=r"(r) : "r"(1 + id), "r"((uint32_t)v) : "memory");
  return r != 0;
}
__device__ __forceinline__ uint32_t hfma2(uint32_t a, uint32_t b, uint32_t c) { uint32_t r; asm("fma.rn.bf16x2 %0, %1, %2, %3;" : "=r"(r) : "r"(a), "r"(b), "r"(c)); return r; }
__device__ __forceinline__ float ex2(float x) { float y; asm("ex2.approx.ftz.f32 %0, %1;" : "=f"(y) : "f"(x)); return y; }
__device__ __forceinline__ uint32_t pack(float lo, float hi) { uint32_t r; asm("cvt.rn.bf16x2.f32 %0, %1, %2;" : "=r"(r) : "f"(hi), "f"(lo)); return r; }
__device__ __forceinline__ void stsm4t(uint32_t a, uint32_t r0, uint32_t r1, uint32_t r2, uint32_t r3) {
  asm volatile("stmatrix.sync.aligned.m8n8.x4.trans.shared.b16 [%0], {%1,%2,%3,%4};" ::"r"(a), "r"(r0), "r"(r1), "r"(r2), "r"(r3) : "memory");
}
__device__ __forceinline__ void stsm2t(uint32_t a, uint32_t r0, uint32_t r1) {
  asm volatile("stmatrix.sync.aligned.m8n8.x2.trans.shared.b16 [%0], {%1,%2};" ::"r"(a), "r"(r0), "r"(r1) : "memory");
}
__device__ __forceinline__ void mma16816(float (&d)[4], const uint32_t (&a)[4], uint32_t b0, uint32_t b1) {
  asm volatile("mma.sync.aligned.m16n8k16.row.col.f32.bf16.bf16.f32 {%0,%1,%2,%3}, {%4,%5,%6,%7}, {%8,%9}, {%0,%1,%2,%3};"
               : "+f"(d[0]), "+f"(d[1]), "+f"(d[2]), "+f"(d[3]) : "r"(a[0]), "r"(a[1]), "r"(a[2]), "r"(a[3]), "r"(b0), "r"(b1));
}

__device__ __forceinline__ uint32_t fresh_tid() { uint32_t t; asm volatile("mov.u32 %0, %tid.x;" : "=r"(t)); return t; }

template <int V> struct IC { static constexpr int value = V; };

struct Ring {
  uint32_t slot = 0, phase = 0;
  __device__ __forceinline__ void next() { if (++slot == RING_SLOTS) { slot = 0; phase ^= 1; } }
};

__device__ __forceinline__ void mma_tn(float (&o0)[60], float (&o1)[60], uint32_t a, uint32_t b, int acc) {
#pragma unroll
  for (int k = 0; k < 4; k++) {
    wgmma_n120<1, 0>(o0, a + k * 128, HI128, b + k * 2, HI128, k == 0 ? acc : 1);
    wgmma_n120<1, 0>(o1, a + 512 + k * 128, HI128, b + k * 2, HI128, k == 0 ? acc : 1);
  }
}
__device__ __forceinline__ void mma_tn_split(float (&o0)[60], float (&o1)[60], uint32_t a, uint32_t b) {
#pragma unroll
  for (int k = 0; k < 4; k++) wgmma_n120<1, 0>(o0, a + k * 128, HI128, b + k * 2, HI128, 1);
  wg_commit();
#pragma unroll
  for (int k = 0; k < 4; k++) wgmma_n120<1, 0>(o1, a + 512 + k * 128, HI128, b + k * 2, HI128, 1);
  wg_commit();
}
__device__ __forceinline__ void mma_qk(float (&s)[60], uint32_t a, uint32_t q) {
#pragma unroll
  for (int k = 0; k < 8; k++)
    wgmma_n120<0, 0>(s, a + (k >> 2) * 512 + (k & 3) * 2, HI128, q + (k >> 2) * (XB >> 4) + (k & 3) * 2, HI128, k != 0);
}
template <int J0, int J1, bool FIRST = false>
__device__ __forceinline__ void exp_store(const float (&s)[60], float (&l)[30], uint32_t dst) {
#pragma unroll
  for (int j = J0; j < J1; j += 2) {
    uint32_t p[4];
#pragma unroll
    for (int jj = 0; jj < 2; jj++) {
      if (j + jj < 15) {
        const int c = j + jj;
        float e0 = ex2(s[4 * c]), e1 = ex2(s[4 * c + 1]), e2 = ex2(s[4 * c + 2]), e3 = ex2(s[4 * c + 3]);
        if (FIRST) { l[2 * c] = e0 + e2; l[2 * c + 1] = e1 + e3; }
        else { l[2 * c] += e0; l[2 * c + 1] += e1; l[2 * c] += e2; l[2 * c + 1] += e3; }
        p[2 * jj] = pack(e0, e1); p[2 * jj + 1] = pack(e2, e3);
      }
    }
    if (j + 1 < 15) stsm4t(dst + j * 1024, p[0], p[1], p[2], p[3]);
    else stsm2t(dst + j * 1024, p[0], p[1]);
  }
}

__device__ __forceinline__ int o_pos(int b, int wg, int r) {
  const int j = r >> 3, q = (r >> 1) & 3, c = r & 1, o = b & 1, base = (b >> 1) * 480;
  if (j < 12) return base + (o * 9 + wg * 3 + (j >> 2)) * 32 + q * 8 + (j & 3) * 2 + c;
  if (j < 14) return base + (6 + 2 * o) * 32 + wg * 16 + q * 4 + (j - 12) * 2 + c;
  return base + 7 * 32 + (o * 2 + wg) * 8 + q * 2 + c;
}
__device__ __forceinline__ int o_row(int p) {
  const int pair = p / 480, a = (p - pair * 480) >> 5, in = p & 31, c = p & 1;
  int tile, row;
  if (a == 7) { tile = in >> 3; row = 112 + (in & 7); }
  else if (a == 6 || a == 8) { tile = a - 6 + (in >> 4); row = (12 + ((in >> 1) & 1)) * 8 + ((in >> 2) & 3) * 2 + c; }
  else { const int f = a > 8 ? a - 3 : a; tile = f / 3; row = ((f - tile * 3) * 4 + ((in >> 1) & 3)) * 8 + (in >> 3) * 2 + c; }
  return pair * 480 + tile * 120 + row;
}
__device__ __forceinline__ uint32_t o_idx(int k, int p) {
  return ((k >> 3) * (NROWS / 32) + (p >> 5)) * 256 + (k & 7) * 32 + ((((p >> 3) & 3) ^ ((k & 7) >> 1)) << 3) + (p & 7);
}

__device__ __forceinline__ void slow_path(const Params& P, int b, int h, int wg, int w, int lane) {
  const int g = lane >> 2, q = lane & 3, row0 = wg * 120;
  const uint16_t* wq = reinterpret_cast<const uint16_t*>(P.wq) + h * DH + g;
  const __nv_bfloat16* kp = P.k + (size_t)(b * NH + h) * SK * DH;
  const uint16_t* vp = reinterpret_cast<const uint16_t*>(P.v) + (size_t)(b * NH + h) * SK * DH + g;
#pragma unroll 1
  for (int t = w; t < 8; t += 4) {
    const int r0 = 16 * t + g, r1 = r0 + 8;
    const __nv_bfloat16* x0 = P.x + (size_t)(b * SQ + row0 + r0) * DM + 2 * q;
    const __nv_bfloat16* x1 = P.x + (size_t)(b * SQ + row0 + min(r1, 119)) * DM + 2 * q;
    float o[16][4];
#pragma unroll
    for (int n = 0; n < 16; n++) o[n][0] = o[n][1] = o[n][2] = o[n][3] = 0.f;
#pragma unroll 1
    for (int k0 = 0; k0 < DM; k0 += 16) {
      uint32_t a[4] = {*(const uint32_t*)(x0 + k0), *(const uint32_t*)(x1 + k0), *(const uint32_t*)(x0 + k0 + 8), *(const uint32_t*)(x1 + k0 + 8)};
      const uint16_t* wr = wq + (size_t)(k0 + 2 * q) * HD;
#pragma unroll
      for (int n = 0; n < 16; n++) {
        if ((n & 3) == 0) __syncwarp();
        mma16816(o[n], a, wr[8 * n] | ((uint32_t)wr[8 * n + HD] << 16), wr[8 * n + 8 * HD] | ((uint32_t)wr[8 * n + 9 * HD] << 16));
      }
    }
    uint32_t qa[8][4];
#pragma unroll
    for (int k = 0; k < 8; k++) {
      qa[k][0] = pack(o[2 * k][0] * QSCALE, o[2 * k][1] * QSCALE);
      qa[k][1] = pack(o[2 * k][2] * QSCALE, o[2 * k][3] * QSCALE);
      qa[k][2] = pack(o[2 * k + 1][0] * QSCALE, o[2 * k + 1][1] * QSCALE);
      qa[k][3] = pack(o[2 * k + 1][2] * QSCALE, o[2 * k + 1][3] * QSCALE);
    }
#pragma unroll
    for (int n = 0; n < 16; n++) o[n][0] = o[n][1] = o[n][2] = o[n][3] = 0.f;
    float m0 = -INFINITY, m1 = -INFINITY, l0 = 0.f, l1 = 0.f;
#pragma unroll 1
    for (int key0 = 0; key0 < SK; key0 += 16) {
      float s[2][4];
#pragma unroll
      for (int nt = 0; nt < 2; nt++) {
        s[nt][0] = s[nt][1] = s[nt][2] = s[nt][3] = 0.f;
        const __nv_bfloat16* kr = kp + (size_t)(key0 + 8 * nt + g) * DH + 2 * q;
#pragma unroll
        for (int k = 0; k < 8; k++) mma16816(s[nt], qa[k], *(const uint32_t*)(kr + 16 * k), *(const uint32_t*)(kr + 16 * k + 8));
      }
      float n0 = fmaxf(fmaxf(s[0][0], s[0][1]), fmaxf(s[1][0], s[1][1])), n1 = fmaxf(fmaxf(s[0][2], s[0][3]), fmaxf(s[1][2], s[1][3]));
      n0 = fmaxf(n0, __shfl_xor_sync(~0u, n0, 1)); n1 = fmaxf(n1, __shfl_xor_sync(~0u, n1, 1));
      n0 = fmaxf(n0, __shfl_xor_sync(~0u, n0, 2)); n1 = fmaxf(n1, __shfl_xor_sync(~0u, n1, 2));
      n0 = fmaxf(n0, m0); n1 = fmaxf(n1, m1);
      const float z0 = n0 == -INFINITY ? 0.f : n0, z1 = n1 == -INFINITY ? 0.f : n1;
      const float c0 = ex2(m0 - z0), c1 = ex2(m1 - z1);
      m0 = n0; m1 = n1;
#pragma unroll
      for (int nt = 0; nt < 2; nt++) {
        s[nt][0] = ex2(s[nt][0] - z0); s[nt][1] = ex2(s[nt][1] - z0);
        s[nt][2] = ex2(s[nt][2] - z1); s[nt][3] = ex2(s[nt][3] - z1);
      }
      l0 = l0 * c0 + s[0][0] + s[0][1] + s[1][0] + s[1][1];
      l1 = l1 * c1 + s[0][2] + s[0][3] + s[1][2] + s[1][3];
      uint32_t pa[4] = {pack(s[0][0], s[0][1]), pack(s[0][2], s[0][3]), pack(s[1][0], s[1][1]), pack(s[1][2], s[1][3])};
      const uint16_t* vr = vp + (size_t)(key0 + 2 * q) * DH;
#pragma unroll
      for (int n = 0; n < 16; n++) {
        if ((n & 3) == 0) __syncwarp();
        o[n][0] *= c0; o[n][1] *= c0; o[n][2] *= c1; o[n][3] *= c1;
        mma16816(o[n], pa, vr[8 * n] | ((uint32_t)vr[8 * n + DH] << 16), vr[8 * n + 8 * DH] | ((uint32_t)vr[8 * n + 9 * DH] << 16));
      }
    }
    l0 += __shfl_xor_sync(~0u, l0, 1); l1 += __shfl_xor_sync(~0u, l1, 1);
    l0 += __shfl_xor_sync(~0u, l0, 2); l1 += __shfl_xor_sync(~0u, l1, 2);
    const float i0 = 1.f / l0, i1 = 1.f / l1;
    __nv_bfloat16* oc0 = P.o + o_idx(h * DH + 2 * q, o_pos(b, wg, r0));
    __nv_bfloat16* oc1 = P.o + o_idx(h * DH + 2 * q, o_pos(b, wg, min(r1, 119)));
#pragma unroll
    for (int n = 0; n < 16; n++) {
      oc0[8 * n * NROWS] = __float2bfloat16(o[n][0] * i0);
      oc0[8 * n * NROWS + 32] = __float2bfloat16(o[n][1] * i0);
      if (r1 < 120) {
        oc1[8 * n * NROWS] = __float2bfloat16(o[n][2] * i1);
        oc1[8 * n * NROWS + 32] = __float2bfloat16(o[n][3] * i1);
      }
    }
  }
}

__device__ __forceinline__ int bk(int ks) { return ks < 48 ? 32 - (ks & 48) + (ks & 15) : ks; }
__device__ __forceinline__ uint32_t x_slot(uint32_t wg, uint32_t j) { return j < 2 ? (2 * wg + j) * XB : (2 * j + wg) * XB; }
__device__ __forceinline__ int row_block(int t) { return t >= 44 ? (t >> 2) - 11 : (t >> 2) + 4; }
__device__ __forceinline__ int unit_batch(int u) { return (u & 63) >> 2; }
__device__ __forceinline__ int unit_head(int u, int rank) { return (u >> 6) * 8 + (u & 3) * 2 + rank; }

template <int NCL>
__global__ void __cluster_dims__(2, 1, 1) __launch_bounds__(384, 1)
fused_attn_kernel(const __grid_constant__ CUtensorMap tm_x, const __grid_constant__ CUtensorMap tm_wq,
                  const __grid_constant__ CUtensorMap tm_k, const __grid_constant__ CUtensorMap tm_v,
                  const __grid_constant__ CUtensorMap tm_o, const __grid_constant__ CUtensorMap tm_wo,
                  const __grid_constant__ Params P) {
  extern __shared__ uint8_t smem_raw[];
  const uint32_t sb = ((uint32_t)__cvta_generic_to_shared(smem_raw) + 1023) & ~1023u;
  const int warp = __shfl_sync(~0u, threadIdx.x >> 5, 0);
  const int lane = threadIdx.x & 31;
  const int rank = blockIdx.x & 1, cl = blockIdx.x >> 1, ncl = NCL ? NCL : gridDim.x >> 1;

  const int nsingle = NCL == 66 ? 44 : NOTILES;
  auto role = [&]() {
    mbar_wait(sb + BAR_ROLE + 16, 0);
    int id;
    asm volatile("ld.shared.u32 %0, [%1];" : "=r"(id) : "r"(sb + BAR_ROLE + 8) : "memory");
    return id;
  };

  if (threadIdx.x == 128) asm volatile("prefetch.tensormap [%0];" ::"l"(&tm_x) : "memory");
  if (threadIdx.x == 0) {
    asm volatile("prefetch.tensormap [%0];" ::"l"(&tm_wq) : "memory");
    for (int i = 0; i < 6; i++) {
      mbar_init(sb + BAR_RFULL + 8 * i, 1); mbar_init(sb + BAR_REMPTY + 8 * i, 8);
      mbar_init(sb + BAR_BFULL + 8 * i, 1); mbar_init(sb + BAR_BEMPTY + 8 * i, 16);
    }
    for (int i = 0; i < 8; i++) mbar_init(sb + BAR_XFULL + 8 * i, 1);
    for (int i = 0; i < 4; i++) mbar_init(sb + BAR_XEMPTY + 8 * i, 8);
    for (int i = 0; i < 2; i++) { mbar_init(sb + BAR_STAGE + 8 * i, 4); mbar_init(sb + BAR_LSUM + 8 * i, 4); mbar_init(sb + BAR_INV + 8 * i, 1); }
    mbar_init(sb + BAR_ROLE, 1); mbar_init(sb + BAR_ROLE + 16, 1);
    asm volatile("fence.mbarrier_init.release.cluster;" ::: "memory");
  }
  __syncwarp();
  asm volatile("barrier.cluster.arrive.relaxed.aligned;" ::: "memory");
  auto first_w = [&](int s) {
    mbar_expect(sb + BAR_RFULL + 8 * s, RING_BYTES);
    tma3d(sb + s * RING_BYTES, &tm_wq, 0, s * 64, 2 * unit_head(cl, rank), sb + BAR_RFULL + 8 * s);
  };
  if (threadIdx.x == 0) first_w(0);
  __syncwarp();
  asm volatile("barrier.cluster.wait.aligned;" ::: "memory");
  if (threadIdx.x == 128) {
#pragma unroll 1
    for (int s = 0; s < 2; s++) {
      const uint32_t fb = sb + BAR_XFULL + 32 * rank + 8 * s;
      mbar_expect(fb, XB);
      mbar_expect_cl(mapa(fb, rank ^ 1), XB);
      tma2d_mc(sb + OFF_Q + x_slot(rank, s), &tm_x, s * 64, unit_batch(cl) * SQ + rank * 120, fb);
      if (s == 0) first_w(1);
    }
  }
  __syncwarp();

  if (warp >= 8) {
    asm volatile("setmaxnreg.dec.sync.aligned.u32 24;");
    if (warp == 8) {
      uint64_t pol;
      asm volatile("createpolicy.fractional.L2::evict_first.b64 %0, 1.0;" : "=l"(pol));
      Ring r;
      r.slot = 2;
      auto load = [&](const CUtensorMap* m, int c1, int c2, bool ef) {
        mbar_sleep(sb + BAR_REMPTY + 8 * r.slot, r.phase ^ 1);
        if (lane == 0) {
          mbar_expect(sb + BAR_RFULL + 8 * r.slot, RING_BYTES);
          if (ef) tma3d_hint(sb + r.slot * RING_BYTES, m, 0, c1, c2, sb + BAR_RFULL + 8 * r.slot, pol);
          else tma3d(sb + r.slot * RING_BYTES, m, 0, c1, c2, sb + BAR_RFULL + 8 * r.slot);
        }
        r.next();
      };
      for (int u0 = 0;; u0 += ncl) {
        const int u = __shfl_sync(~0u, (u0 >= 3 * ncl ? role() : cl) + u0, 0);
        if (u >= NUNITS) break;
        if (NCL == 66 && u0 == 2 * 66) {
          const int id = role();
          if (id >= 44 && id < 58) {
            unsigned t0, t1;
            asm volatile("mov.u32 %0, %globaltimer_lo;" : "=r"(t0));
            do { __nanosleep(200); asm volatile("mov.u32 %0, %globaltimer_lo;" : "=r"(t1)); } while (t1 - t0 < PAUSE_NS);
          }
        }
        const int h = unit_head(u, rank);
        const int krow = (unit_batch(u) * NH + h) * SK;
#pragma unroll 1
        for (int s = u0 == 0 ? 2 : 0; s < 10; s++) {
          load(&tm_wq, s * 64, 2 * h, false);
          const int sp = u0 == 0 ? s - 6 : s;
          if (sp >= 0 && sp < PF_N && lane == 0) l2_prefetch(P.v + (size_t)(krow + (PF_J0 + sp * PF_STEP) * 64) * DH, 16384);
        }
#pragma unroll 1
        for (int j = 0; j <= 16; j++) {
          if (j < 16) load(&tm_k, krow + j * 64, 0, true);
          if (j == 2) load(&tm_v, krow, 0, true);
          if (j > 1) load(&tm_v, krow + (j - 1) * 64, 0, true);
        }
      }
      const int id = __shfl_sync(~0u, role(), 0);
      const bool dbl = NCL == 66 && id >= 58;
      for (int t = dbl ? 2 * id - 72 : id; t < (dbl ? NOTILES : nsingle); t += ncl) {
        const int row0 = row_block(t) * 256 + rank * 128;
        const int b0 = row0 / SQ, b1 = (row0 + 127) / SQ;
#pragma unroll 1
        for (int ks = 0; ks < 64; ks++) {
          if (dbl ? (ks & 15) == 0 : ks == 0 || ks == 48) {
            const unsigned* c = &g_cnt[((lane & 1 ? b1 : b0) * 4 + (ks || dbl ? ks >> 4 : min(lane >> 1, 2))) * 8];
            unsigned v, n = 0;
            do {
              asm volatile("ld.acquire.gpu.global.u32 %0, [%1];" : "=r"(v) : "l"(c) : "memory");
              if (++n > (1u << 26)) __trap();
            } while (v < 16);
            __syncwarp();
            asm volatile("fence.proxy.async.global;" ::: "memory");
          }
          mbar_wait(sb + BAR_REMPTY + 8 * r.slot, r.phase ^ 1);
          if (lane == 0) {
            mbar_expect(sb + BAR_RFULL + 8 * r.slot, RING_BYTES);
            asm volatile("cp.async.bulk.tensor.4d.shared::cluster.global.mbarrier::complete_tx::bytes.L2::cache_hint [%0], [%1, {%3, %3, %4, %5}], [%2], %6;"
                         ::"r"(sb + r.slot * RING_BYTES), "l"(&tm_o), "r"(sb + BAR_RFULL + 8 * r.slot), "r"(0), "r"((dbl ? ks : bk(ks)) * 8), "r"(row0 >> 6), "l"(pol) : "memory");
          }
          r.next();
        }
      }
      if (lane == 0 && atomicAdd(&g_cnt[64 * 8], 1) == gridDim.x - 1) {
        for (int i = 0; i < 67; i++) g_cnt[i * 8] = 0;
      }
    } else if (warp == 9) {
      if (lane == 0) {
        uint32_t it = 0;
        for (;; it++) {
          const int u = (it >= 3 ? role() : cl) + it * ncl;
          if (u >= NUNITS) break;
          const int row = unit_batch(u) * SQ + rank * 120;
#pragma unroll 1
          for (int s = it == 0 ? 2 : 0; s < 10; s++) {
            const uint32_t j = s & 3, par = ((s >> 2) + (j < 2 ? it : 0)) & 1;
            if (s == 0) mbar_sleep(sb + BAR_XEMPTY, par ^ 1);
            mbar_wait(sb + BAR_XEMPTY + 8 * j, par ^ 1);
            const uint32_t fb = sb + BAR_XFULL + 32 * rank + 8 * j;
            mbar_expect(fb, XB);
            mbar_expect_cl(mapa(fb, rank ^ 1), XB);
            tma2d_mc(sb + OFF_Q + x_slot(rank, j), &tm_x, s * 64, row, fb);
          }
        }
        const int id = role();
        const bool dbl = NCL == 66 && id >= 58;
        uint32_t slot = rank, phase = 0;
        if (dbl)
          asm volatile("cp.async.bulk.prefetch.tensor.3d.L2.global [%0, {%1, %2, %3}];" ::"l"(&tm_wo), "r"(0), "r"((2 + ((id >> 1) & 3)) * 64), "r"(((2 * id - 72 + rank) & 3) * 5) : "memory");
        if (dbl || id < nsingle) mbar_sleep(sb + BAR_BEMPTY + 8 * rank, 0);
        for (int t = dbl ? 2 * id - 72 + rank : id; t < (dbl ? NOTILES : nsingle); t += ncl) {
#pragma unroll 1
          for (int ks = dbl ? 0 : rank; ks < 64; ks += dbl ? 1 : 2) {
            mbar_wait(sb + BAR_BEMPTY + 8 * slot, phase);
            const uint32_t fb = sb + BAR_BFULL + 8 * slot;
            mbar_expect(fb, BB);
            mbar_expect_cl(mapa(fb, rank ^ 1), BB);
            tma3d_mc(sb + OFF_Q + slot * BB, &tm_wo, 0, (dbl ? ks : bk(ks)) * 64, (t & 3) * 5, fb);
            if (dbl && ks + WO_PF < 64 && (ks & 3) == ((id >> 1) & 3))
              asm volatile("cp.async.bulk.prefetch.tensor.3d.L2.global [%0, {%1, %2, %3}];" ::"l"(&tm_wo), "r"(0), "r"((ks + WO_PF) * 64), "r"((t & 3) * 5) : "memory");
            slot += 2;
            if (slot >= 6) { slot -= 6; phase ^= 1; }
          }
        }
      }
    } else {
      const int wg = warp - 10;
      {
        mbar_wait(sb + BAR_RFULL, 0);
        const __nv_bfloat16* xs = P.x + (size_t)(unit_batch(cl) * SQ + ((cl & 3) * 2 + rank) * 30 + min(lane, 29)) * DM + 256 + wg * 64;
#pragma unroll
        for (int i = 0; i < 3; i++) asm volatile("prefetch.global.L2 [%0];" ::"l"(xs + i * 128));
        if (lane < 16) asm volatile("prefetch.global.L2 [%0];" ::"l"(P.wq + (size_t)(384 + unit_batch(cl) * 16 + lane) * HD + unit_head(cl, rank) * DH + wg * 64));
      }
      for (uint32_t it = 0;; it++) {
        const int u = __shfl_sync(~0u, (it >= 3 ? role() : cl) + it * ncl, 0);
        if (u >= NUNITS) break;
        mbar_sleep(sb + BAR_LSUM + 8 * wg, it & 1);
        float l4[4], v[4];
        const uint32_t a = sb + OFF_L2 + wg * 2048 + lane * 16;
        asm volatile("ld.shared.v4.f32 {%0, %1, %2, %3}, [%4];" : "=f"(l4[0]), "=f"(l4[1]), "=f"(l4[2]), "=f"(l4[3]) : "r"(a) : "memory");
#pragma unroll
        for (int g = 1; g < 4; g++) {
          asm volatile("ld.shared.v4.f32 {%0, %1, %2, %3}, [%4];" : "=f"(v[0]), "=f"(v[1]), "=f"(v[2]), "=f"(v[3]) : "r"(a + g * 512) : "memory");
#pragma unroll
          for (int c = 0; c < 4; c++) l4[c] += v[c];
        }
#pragma unroll
        for (int c = 0; c < 4; c++) {
          float inv;
          asm("rcp.approx.ftz.f32 %0, %1;" : "=f"(inv) : "f"(l4[c]));
          l4[c] = l4[c] >= L_MIN && l4[c] <= L_MAX ? inv : __uint_as_float(0x7FFFFFFFu);
        }
        const uint32_t h0 = pack(l4[0], l4[1]), h1 = pack(l4[2], l4[3]);
        const uint32_t e0 = pack(l4[0] - __uint_as_float(h0 << 16), l4[1] - __uint_as_float(h0 & 0xFFFF0000u));
        const uint32_t e1 = pack(l4[2] - __uint_as_float(h1 << 16), l4[3] - __uint_as_float(h1 & 0xFFFF0000u));
        asm volatile("st.shared.v4.u32 [%0], {%1, %2, %3, %4};" ::"r"(sb + OFF_INV + wg * 640 + (lane & 3) * 144 + (lane >> 2) * 16), "r"(h0), "r"(e0), "r"(h1), "r"(e1) : "memory");
        __syncwarp();
        if (lane == 0) {
          mbar_arrive(sb + BAR_INV + 8 * wg);
          if (it == 0 && wg == 0) {
            if (rank == 0) {
              int id = cl;
              if (NCL == 66) {
                uint32_t smid;
                asm("mov.u32 %0, %smid;" : "=r"(smid));
                id = smid >= SMID_TOP ? 65 - atomicAdd(&g_cnt[65 * 8], 1) : atomicAdd(&g_cnt[66 * 8], 1);
              }
#pragma unroll
              for (int c = 0; c < 2; c++) {
                const uint32_t a = mapa(sb + BAR_ROLE, c);
                asm volatile("st.shared::cluster.u32 [%0 + 8], %1;\nmbarrier.arrive.release.cluster.shared::cluster.b64 _, [%0];" ::"r"(a), "r"(id) : "memory");
              }
            }
            mbar_wait_cl(sb + BAR_ROLE, 0);
            mbar_arrive(sb + BAR_ROLE + 16);
          }
          mbar_sleep(sb + BAR_STAGE + 8 * wg, it & 1);
          __threadfence();
          asm volatile("red.relaxed.gpu.global.add.u32 [%0], 1;" ::"l"(&g_cnt[(unit_batch(u) * 4 + (u >> 6)) * 8]) : "memory");
        }
        __syncwarp();
      }
    }
  } else {
    asm volatile("setmaxnreg.inc.sync.aligned.u32 240;");
    const int wg = warp >> 2, w = warp & 3;
    const uint32_t qreg = sb + OFF_Q + wg * 2 * XB, preg = sb + OFF_P + (2 + wg) * XB;
    const uint32_t st_off = ((lane >> 4) * 8 + (lane & 7)) * 128 + (((2 * w + ((lane >> 3) & 1)) ^ (lane & 7)) << 4);
    const uint32_t xempty = mapa(sb + BAR_XEMPTY, wg);
    Ring r;
    uint32_t it = 0;
    const uint32_t qd = (qreg & 0x3FFFF) >> 4, pd = (preg & 0x3FFFF) >> 4;
    auto ring_addr = [&]() { return ((sb & 0x3FFFF) + r.slot * RING_BYTES) >> 4; };
    auto ring_wait = [&]() { mbar_wait(sb + BAR_RFULL + 8 * r.slot, r.phase); };
    auto release = [&](uint32_t slot) { warp_arrive(sb + BAR_REMPTY + 8 * slot); };
    auto turn_wait = [&]() {
      if (wg == 0) asm volatile("bar.sync 3, 256;" ::: "memory");
      else asm volatile("bar.sync 4, 256;" ::: "memory");
    };
    auto turn_pass = [&]() {
      if (wg == 0) asm volatile("bar.arrive 4, 256;" ::: "memory");
      else asm volatile("bar.arrive 3, 256;" ::: "memory");
    };

    uint32_t chk = 0;
    auto sum_l = [&](const float (&l)[30], uint32_t tid) {
      float a[16], b[8], c[4];
      const bool b4 = tid & 16, b3 = tid & 8, b2 = tid & 4;
#pragma unroll
      for (int i = 0; i < 16; i++) {
        const float hi = i < 14 ? l[(16 + i) % 30] : 1.f;
        a[i] = (b4 ? hi : l[i]) + __shfl_xor_sync(~0u, b4 ? l[i] : hi, 16);
      }
#pragma unroll
      for (int i = 0; i < 8; i++) b[i] = (b3 ? a[8 + i] : a[i]) + __shfl_xor_sync(~0u, b3 ? a[i] : a[8 + i], 8);
#pragma unroll
      for (int i = 0; i < 4; i++) c[i] = (b2 ? b[4 + i] : b[i]) + __shfl_xor_sync(~0u, b2 ? b[i] : b[4 + i], 4);
      asm volatile("st.shared.v4.f32 [%0], {%1, %2, %3, %4};" ::"r"(sb + OFF_L2 + tid * 16), "f"(c[0]), "f"(c[1]),
                   "f"(c[2]), "f"(c[3]) : "memory");
      __syncwarp();
      warp_arrive(sb + BAR_LSUM + 8 * wg);
    };
    auto load_inv = [&](uint32_t (&iv)[30], uint32_t parity) {
      const int lane = fresh_tid() & 31;
      mbar_wait(sb + BAR_INV + 8 * wg, parity);
      chk = 0;
#pragma unroll
      for (int j = 0; j < 7; j++)
        asm volatile("ld.shared.v4.u32 {%0, %1, %2, %3}, [%4];" : "=r"(iv[4 * j]), "=r"(iv[4 * j + 1]), "=r"(iv[4 * j + 2]), "=r"(iv[4 * j + 3])
                     : "r"(sb + OFF_INV + wg * 640 + (lane & 3) * 144 + j * 16) : "memory");
      asm volatile("ld.shared.v2.u32 {%0, %1}, [%2];" : "=r"(iv[28]), "=r"(iv[29]) : "r"(sb + OFF_INV + wg * 640 + (lane & 3) * 144 + 112) : "memory");
    };
    auto norm = [&](uint32_t (&n)[8], const uint32_t (&po)[60], const uint32_t (&iv)[30], auto part) {
      constexpr int k = decltype(part)::value >> 1, j0 = (decltype(part)::value & 1) * 8;
#pragma unroll
      for (int j = 0; j < 8; j++)
        n[j] = j0 + j < 15 ? hfma2(po[15 * k + (j0 + j) % 15], iv[2 * ((j0 + j) % 15)], hfma2(po[15 * k + (j0 + j) % 15], iv[2 * ((j0 + j) % 15) + 1], 0x80008000u)) : 0x3F803F80u;
#pragma unroll
      for (int j = 0; j < 8; j += 2) chk = hfma2(n[j], n[j + 1], chk);
    };
    int od1, od2;
    auto store = [&](const uint32_t (&n)[8], const char* optr, auto part) {
      constexpr int k = decltype(part)::value >> 1, off = (8 * (k & 1) + 64 * (k >> 1)) * NROWS * 2;
      if ((decltype(part)::value & 1) == 0)
        asm volatile(
            "{\n.reg .pred p;\nsetp.ne.u64 p, %8, 0;\n"
            "@p st.global.v4.u32 [%8 + %9], {%0, %1, %2, %3};\n@p st.global.v4.u32 [%8 + %9 + 512], {%4, %5, %6, %7};\n}\n"
            ::"r"(n[0]), "r"(n[1]), "r"(n[2]), "r"(n[3]), "r"(n[4]), "r"(n[5]), "r"(n[6]), "r"(n[7]), "l"(optr), "n"(off) : "memory");
      else
        asm volatile(
            "{\n.reg .pred p;\n.reg .b64 b, c;\nsetp.ne.u64 p, %7, 0;\nmad.wide.s32 b, %9, 1, %7;\nmad.wide.s32 c, %10, 1, %7;\n"
            "@p st.global.v4.u32 [%7 + %8 + 1024], {%0, %1, %2, %3};\n@p st.global.v2.u32 [b + %8], {%4, %5};\n@p st.global.u32 [c + %8], %6;\n}\n"
            ::"r"(n[0]), "r"(n[1]), "r"(n[2]), "r"(n[3]), "r"(n[4]), "r"(n[5]), "r"(n[6]), "l"(optr), "n"(off), "r"(od1), "r"(od2) : "memory");
    };
    auto put = [&](const uint32_t (&po)[60], const uint32_t (&iv)[30], const char* optr, auto part) {
      uint32_t n[8];
      norm(n, po, iv, part);
      store(n, optr, part);
    };
    auto out_ptr = [&](int u) {
      const int lane = fresh_tid() & 31;
      const int k = unit_head(u, rank) * DH + 16 * w + (lane >> 2), b = unit_batch(u), q = lane & 3;
      const uint32_t i0 = o_idx(k, o_pos(b, wg, 2 * q));
      od1 = 2 * (int)(o_idx(k, o_pos(b, wg, 96 + 2 * q)) - i0);
      od2 = 2 * (int)(o_idx(k, o_pos(b, wg, 112 + 2 * q)) - i0);
      return reinterpret_cast<const char*>(P.o + i0);
    };
    auto unsafe = [&](bool valid) {
      const bool b = valid && ((chk & 0x7F80u) == 0x7F80u || (chk & 0x7F800000u) == 0x7F800000u);
      return __any_sync(~0u, bar_red_or(wg, b));
    };
    auto publish = [&]() { __syncwarp(); warp_arrive(sb + BAR_STAGE + 8 * wg); };

    uint32_t po[60];
#pragma unroll
    for (int i = 0; i < 60; i++) po[i] = 0;
    int id = 0;
    float o0[60], o1[60];
    ring_wait();
    mbar_wait(sb + BAR_XFULL + 32 * wg, 0);
    wg_fence();
    mma_tn(o0, o1, ring_addr(), qd, 0);
    wg_commit();
    while (true) {
      uint32_t prev = r.slot;
      r.next();
      auto qstep = [&](int s) {
        const uint32_t j = s & 3, par = ((s >> 2) + (j < 2 ? it : 0)) & 1;
        ring_wait();
        mbar_wait(sb + BAR_XFULL + 32 * wg + 8 * j, par);
        if (s >= ALT_FROM) turn_wait();
        wg_fence();
        mma_tn(o0, o1, ring_addr(), ((sb & 0x3FFFF) + OFF_Q + x_slot(wg, j)) >> 4, 1);
        wg_commit();
        if (s >= ALT_FROM || (s == ALT_FROM - 1 && wg == 1)) turn_pass();
        if (s <= 4) {
          wg_wait<1>();
          release(prev);
          warp_arrive_cl(xempty + 8 * ((s - 1) & 3));
        }
        prev = r.slot;
        r.next();
      };
      auto qdone = [&](int s) {
        wg_wait<0>();
        release(prev);
        if (s <= 5) warp_arrive_cl(xempty + 8 * (s & 3));
      };
      qstep(1);
      const int up = (it > 3 ? id : cl) + ((int)it - 1) * ncl;
      const char* optr = out_ptr(up);
      if (it == 0) optr = nullptr;
      uint32_t n7[8];
      {
        uint32_t iv[30];
        load_inv(iv, (it + 1) & 1); put(po, iv, optr, IC<0>());
        qstep(2); put(po, iv, optr, IC<1>());
        qstep(3); put(po, iv, optr, IC<2>());
        qstep(4); put(po, iv, optr, IC<3>()); qdone(4);
        qstep(5); put(po, iv, optr, IC<4>()); qdone(5);
        qstep(6); put(po, iv, optr, IC<5>()); qdone(6);
        qstep(7); put(po, iv, optr, IC<6>()); norm(n7, po, iv, IC<7>()); qdone(7);
      }
      ring_wait();
      mbar_wait(sb + BAR_XFULL + 32 * wg, it & 1);
      turn_wait();
      wg_fence();
      mma_tn(o0, o1, ring_addr(), qd, 1);
      wg_commit();
      prev = r.slot;
      r.next();
      ring_wait();
      mbar_wait(sb + BAR_XFULL + 32 * wg + 8, it & 1);
      wg_fence();
      mma_tn_split(o0, o1, ring_addr(), qd + (XB >> 4));
      turn_pass();
      wg_wait<2>();
      release(prev);
      auto put_q = [&](const float (&o)[60], uint32_t dst) {
#pragma unroll
        for (int j = 0; j < 14; j += 2)
          stsm4t(dst + j * 1024, pack(o[4 * j] * QSCALE, o[4 * j + 1] * QSCALE), pack(o[4 * j + 2] * QSCALE, o[4 * j + 3] * QSCALE),
                 pack(o[4 * j + 4] * QSCALE, o[4 * j + 5] * QSCALE), pack(o[4 * j + 6] * QSCALE, o[4 * j + 7] * QSCALE));
        stsm2t(dst + 14 * 1024, pack(o[56] * QSCALE, o[57] * QSCALE), pack(o[58] * QSCALE, o[59] * QSCALE));
      };
      wg_wait<1>();
      reg_fence(o0);
      const bool redo = unsafe(it > 0);
      put_q(o0, qreg + st_off);
      wg_wait<0>();
      reg_fence(o1);
      release(r.slot);
      r.next();
      bar_sync(wg);
      put_q(o1, qreg + XB + st_off);
      fence_async_smem();
      if (redo) {
        slow_path(P, unit_batch(up), unit_head(up, rank), wg, w, fresh_tid() & 31);
        optr = nullptr;
      }

      float sc[60], l[30];
      uint32_t slot0 = r.slot;
      ring_wait();
      turn_wait();
      wg_fence();
      mma_qk(sc, ring_addr(), qd);
      wg_commit();
      r.next();
      uint32_t slot1 = r.slot;
      ring_wait();
      wg_fence();
      mma_qk(o1, ring_addr(), qd);
      wg_commit();
      r.next();
      turn_pass();
      store(n7, optr, IC<7>());
      wg_wait<1>();
      reg_fence(sc);
      release(slot0);
      exp_store<0, 15, true>(sc, l, preg + st_off);
      slot0 = r.slot;
      ring_wait();
      wg_fence();
      mma_qk(sc, ring_addr(), qd);
      wg_commit();
      r.next();
      wg_wait<1>();
      reg_fence(o1);
      release(slot1);
      exp_store<0, 15>(o1, l, preg - 2 * XB + st_off);
      fence_async_smem();
      slot1 = r.slot;
      ring_wait();
      turn_wait();
      wg_fence();
      mma_tn(o0, o1, ring_addr(), pd, 0);
      wg_commit();
      r.next();
      ring_wait();
      wg_fence();
      mma_tn(o0, o1, ring_addr(), pd - (2 * XB >> 4), 1);
      wg_commit();
      turn_pass();
      if (it > 0) publish();
      id = __shfl_sync(~0u, it >= 2 ? role() : 0, 0);
      wg_wait<1>();
      reg_fence(sc);
      release(slot0);
      release(slot1);
      bar_sync(wg);
      exp_store<0, VREL>(sc, l, preg + st_off);
      wg_wait<0>();
      reg_fence(o0); reg_fence(o1);
      release(r.slot);
      r.next();
      exp_store<VREL, 15>(sc, l, preg + st_off);
      fence_async_smem();
      const bool more = id + ((int)it + 1) * ncl < NUNITS;
      const bool gemm = id < nsingle || (NCL == 66 && id >= 58);
#pragma unroll 1
      for (int s = 3; s < 16; s++) {
        const uint32_t kslot = r.slot;
        ring_wait();
        turn_wait();
        wg_fence();
        mma_qk(sc, ring_addr(), qd);
        wg_commit();
        r.next();
        ring_wait();
        wg_fence();
        mma_tn(o0, o1, ring_addr(), pd - ((s - 1) & 1) * (2 * XB >> 4), 1);
        wg_commit();
        if (wg == 0 || s < 15) turn_pass();
        wg_wait<1>();
        reg_fence(sc);
        release(kslot);
        if (s == 15) {
          if (more) { warp_arrive_cl(xempty); warp_arrive_cl(xempty + 8); }
          else if (gemm) for (int i = 0; i < 3; i++) warp_arrive_cl(mapa(sb + BAR_BEMPTY + 8 * i, i & 1));
        }
        exp_store<0, VREL>(sc, l, preg - (s & 1) * 2 * XB + st_off);
        wg_wait<0>();
        reg_fence(o0); reg_fence(o1);
        release(r.slot);
        r.next();
        exp_store<VREL, 15>(sc, l, preg - (s & 1) * 2 * XB + st_off);
        fence_async_smem();
      }
      const uint32_t tid = fresh_tid();
      bar_sync(wg);
      ring_wait();
      wg_fence();
      mma_tn_split(o0, o1, ring_addr(), pd - (2 * XB >> 4));
      sum_l(l, tid);
      const uint32_t vslot = r.slot;
      r.next();
      it++;
      auto pack_o = [&](const float (&o)[60], int first) {
#pragma unroll
        for (int j = 0; j < 15; j++) { po[first + j] = pack(o[4 * j], o[4 * j + 1]); po[first + 15 + j] = pack(o[4 * j + 2], o[4 * j + 3]); }
      };
      if (!more) {
        wg_wait<0>();
        reg_fence(o0); reg_fence(o1);
        release(vslot);
        if (gemm) for (int i = 3; i < 6; i++) warp_arrive_cl(mapa(sb + BAR_BEMPTY + 8 * i, i & 1));
        pack_o(o0, 0); pack_o(o1, 30);
        break;
      }
      ring_wait();
      mbar_wait(sb + BAR_XFULL + 32 * wg, it & 1);
      wg_wait<1>();
      reg_fence(o0);
      pack_o(o0, 0);
      wg_fence();
#pragma unroll
      for (int k = 0; k < 4; k++) wgmma_n120<1, 0>(o0, ring_addr() + k * 128, HI128, qd + k * 2, HI128, k != 0);
      wg_commit();
      wg_wait<1>();
      reg_fence(o1);
      pack_o(o1, 30);
      wg_fence();
#pragma unroll
      for (int k = 0; k < 4; k++) wgmma_n120<1, 0>(o1, ring_addr() + 512 + k * 128, HI128, qd + k * 2, HI128, k != 0);
      wg_commit();
      release(vslot);
      warp_arrive_cl(xempty + 16); warp_arrive_cl(xempty + 24);
    }
    const bool gemm = id < nsingle || (NCL == 66 && id >= 58);
    const int u = (it > 3 ? id : cl) + ((int)it - 1) * ncl;
    uint32_t pb[60];
#pragma unroll
    for (int i = 0; i < 60; i++) pb[i] = NCL != 66 ? po[i] ^ (gridDim.y - 1) : po[i];

    uint32_t bslot = 0, bphase = 0;
    auto out_row = [&](int lane) {
      const int row = lane & 15;
      return sb + wg * 8192 + (row < 12 ? w * RING_BYTES + row * 656 : (4 + (w >> 1)) * RING_BYTES + ((w & 1) * 4 + row - 12) * 656);
    };
    auto out_stage = [&](const float (&acc)[80], uint32_t col_off) {
      const int lane = fresh_tid() & 31;
      const uint32_t sa = out_row(lane) + col_off + (lane >> 4) * 16;
#pragma unroll
      for (int j = 0; j < 20; j += 2)
        asm volatile("stmatrix.sync.aligned.m8n8.x4.shared.b16 [%0], {%1,%2,%3,%4};" ::"r"(sa + j * 16), "r"(pack(acc[4 * j], acc[4 * j + 1])),
                     "r"(pack(acc[4 * j + 2], acc[4 * j + 3])), "r"(pack(acc[4 * j + 4], acc[4 * j + 5])), "r"(pack(acc[4 * j + 6], acc[4 * j + 7])) : "memory");
    };
    auto out_store = [&](int t, uint32_t bytes) {
      const int lane = fresh_tid() & 31;
      if (wg == 1) {
        __syncwarp();
#pragma unroll 1
        for (int h = 0; h < 2; h++) {
          const int row = h * 8 + (lane >> 2);
          const uint32_t src = out_row(row) + (lane & 3) * 16;
          char* dst = reinterpret_cast<char*>(P.out + (size_t)o_row(row_block(t) * 256 + rank * 128 + 64 + w * 16 + row) * DM + (t & 3) * 160) + (lane & 3) * 16;
#pragma unroll 1
          for (uint32_t c = 0; c < bytes; c += 320) {
            uint4 v[5];
#pragma unroll
            for (int i = 0; i < 5; i++)
              asm volatile("ld.shared.v4.u32 {%0, %1, %2, %3}, [%4];" : "=r"(v[i].x), "=r"(v[i].y), "=r"(v[i].z), "=r"(v[i].w) : "r"(src + c + i * 64) : "memory");
#pragma unroll
            for (int i = 0; i < 5; i++) *reinterpret_cast<uint4*>(dst + c + i * 64) = v[i];
          }
        }
        return;
      }
      fence_async_smem();
      __syncwarp();
      if (lane < 16) {
        __nv_bfloat16* dst = P.out + (size_t)o_row(row_block(t) * 256 + rank * 128 + wg * 64 + w * 16 + lane) * DM + (t & 3) * 160;
        asm volatile("cp.async.bulk.global.shared::cta.bulk_group [%0], [%1], %2;" ::"l"(dst), "r"(out_row(lane)), "r"(bytes) : "memory");
        asm volatile("cp.async.bulk.commit_group;" ::: "memory");
        asm volatile("cp.async.bulk.wait_group.read 0;" ::: "memory");
      }
    };
    for (int t = id; t == id || (NCL != 66 && t < nsingle); t += ncl) {
      float acc[80];
      uint32_t prev = 0, bprev = 0;
      const bool tile = t < nsingle;
      const bool last = NCL == 66 || t + ncl >= nsingle;
      auto bstep = [&](int ks, int accf) {
        ring_wait();
        mbar_wait(sb + BAR_BFULL + 8 * bslot, bphase);
        wg_fence();
        const uint32_t a = ring_addr() + wg * 512, bd = (((sb & 0x3FFFF) + OFF_Q + bslot * BB) >> 4) | ((4096u >> 4) << 16);
#pragma unroll
        for (int k = 0; k < 4; k++) wgmma_n160<1, 1>(acc, a + LBO64A + k * 128, HI64A, bd + k * 64, HI64, k == 0 ? accf : 1);
        wg_commit();
        if (ks > 0) {
          wg_wait<1>();
          release(prev);
          if (ks < 59 || !last) warp_arrive_cl(mapa(sb + BAR_BEMPTY + 8 * bprev, bprev & 1));
        }
        prev = r.slot; bprev = bslot;
        r.next();
        if (++bslot == 6) { bslot = 0; bphase ^= 1; }
      };
      const char* optr;
      uint32_t iv[30], n2[8], n3[8], n4[8], n5[8], n6[8], n7[8];
      if (tile) {
        bstep(0, 0);
        bstep(1, 1);
        optr = out_ptr(u);
        if (t != id) optr = nullptr;
        load_inv(iv, (it + 1) & 1);
#pragma unroll 1
        for (int ks = 2; ks < 17; ks++) {
          bstep(ks, 1);
          switch (ks) {
            case 2: put(pb, iv, optr, IC<0>()); break;
            case 4: put(pb, iv, optr, IC<1>()); break;
            case 6: put(pb, iv, optr, IC<2>()); break;
            case 8: put(pb, iv, optr, IC<3>()); break;
            case 10: put(pb, iv, optr, IC<4>()); break;
            case 12: put(pb, iv, optr, IC<5>()); break;
            case 14: put(pb, iv, optr, IC<6>()); break;
            case 16: put(pb, iv, optr, IC<7>()); break;
            default: break;
          }
        }
        wg_wait<0>();
        reg_fence(acc);
#pragma unroll
        for (int i = 0; i < 8; i++) n2[i] = n3[i] = n4[i] = n5[i] = n6[i] = n7[i] = 0;
      } else {
        Ring r2 = r;
        auto first = [&](int ks) {
          if (gemm) { mbar_wait(sb + BAR_RFULL + 8 * r2.slot, r2.phase); mbar_wait(sb + BAR_BFULL + 16 * ks, 0); }
          wg_fence();
          const uint32_t a = (((sb & 0x3FFFF) + r2.slot * RING_BYTES) >> 4) + wg * 512;
          const uint32_t bd = (((sb & 0x3FFFF) + OFF_Q + 2 * ks * BB) >> 4) | ((4096u >> 4) << 16);
#pragma unroll
          for (int k = 0; k < 4; k++) wgmma_n160<1, 1>(acc, a + LBO64A + k * 128, HI64A, bd + k * 64, HI64, k + ks != 0);
          wg_commit();
          r2.next();
        };
        first(0);
        first(1);
        optr = out_ptr(u);
        load_inv(iv, (it + 1) & 1);
        put(pb, iv, optr, IC<0>()); put(pb, iv, optr, IC<1>());
        norm(n2, pb, iv, IC<2>()); norm(n3, pb, iv, IC<3>()); norm(n4, pb, iv, IC<4>());
        norm(n5, pb, iv, IC<5>()); norm(n6, pb, iv, IC<6>()); norm(n7, pb, iv, IC<7>());
        wg_wait<0>();
        reg_fence(acc);
      }
      if (unsafe(t == id)) {
        slow_path(P, unit_batch(u), unit_head(u, rank), wg, w, fresh_tid() & 31);
        optr = nullptr;
#pragma unroll
        for (int i = 0; i < 8; i++) n2[i] = n3[i] = n4[i] = n5[i] = n6[i] = n7[i] = 0;
      }
      if (tile && t == id) publish();
      if (!tile && !gemm) {
        store(n2, optr, IC<2>()); store(n3, optr, IC<3>()); store(n4, optr, IC<4>()); store(n5, optr, IC<5>()); store(n6, optr, IC<6>()); store(n7, optr, IC<7>());
        publish();
        break;
      }
      if (!tile) {
        float ac1[80];
        auto half = [&](float (&ac)[80], bool rel, int accf) {
          mbar_wait(sb + BAR_BFULL + 8 * bslot, bphase);
          wg_fence();
          const uint32_t a = ring_addr() + wg * 512, bd = (((sb & 0x3FFFF) + OFF_Q + bslot * BB) >> 4) | ((4096u >> 4) << 16);
#pragma unroll
          for (int k = 0; k < 4; k++) wgmma_n160<1, 1>(ac, a + LBO64A + k * 128, HI64A, bd + k * 64, HI64, k == 0 ? accf : 1);
          wg_commit();
          wg_wait<1>();
          if (rel) warp_arrive_cl(mapa(sb + BAR_BEMPTY + 8 * bprev, bprev & 1));
          bprev = bslot;
        };
        auto dstep = [&](int ks) {
          ring_wait();
          half(acc, ks < 62, 1);
          release(prev);
          bslot++;
          half(ac1, ks < 61, 1);
          if (++bslot == 6) { bslot = 0; bphase ^= 1; }
          prev = r.slot; r.next();
        };
        warp_arrive_cl(mapa(sb + BAR_BEMPTY, 0));
        bprev = 2; bslot = 1;
        half(ac1, true, 0);
        prev = r.slot; r.next(); bslot = 3;
        half(ac1, true, 1);
        release(prev); prev = r.slot; r.next(); bslot = 4;
#pragma unroll 1
        for (int ks = 2; ks < 8; ks++) {
          dstep(ks);
          switch (ks) {
            case 2: store(n2, optr, IC<2>()); break;
            case 3: store(n3, optr, IC<3>()); break;
            case 4: store(n4, optr, IC<4>()); break;
            case 5: store(n5, optr, IC<5>()); break;
            case 6: store(n6, optr, IC<6>()); break;
            default: store(n7, optr, IC<7>()); break;
          }
        }
        publish();
#pragma unroll 1
        for (int ks = 8; ks < 64; ks++) {
          if (wg == 1 && ks == 62) turn_wait();
          dstep(ks);
        }
        if (wg == 0) turn_pass();
        wg_wait<0>();
        reg_fence(acc); reg_fence(ac1);
        bar_sync(wg);
        out_stage(ac1, 320);
      } else {
#pragma unroll 1
        for (int ks = 17; ks < 64; ks++) {
          if (wg == 1 && ks == 64 - END_SKEW) turn_wait();
          bstep(ks, 1);
        }
        if (wg == 0) turn_pass();
        wg_wait<0>();
        reg_fence(acc);
        release(prev);
        if (!last) warp_arrive_cl(mapa(sb + BAR_BEMPTY + 8 * bprev, bprev & 1));
      }
      const int pos0 = row_block(t) * 256 + rank * 128 + wg * 64 + w * 16;
      if (last) {
        bar_sync(wg);
        out_stage(acc, 0);
        out_store(tile ? t : 2 * id - 72, tile ? 320 : 640);
      } else {
        const int lane = fresh_tid() & 31;
        __nv_bfloat16* op0 = P.out + (size_t)o_row(pos0 + (lane >> 2)) * DM + (t & 3) * 160 + (lane & 3) * 2;
        __nv_bfloat16* op1 = P.out + (size_t)o_row(pos0 + (lane >> 2) + 8) * DM + (t & 3) * 160 + (lane & 3) * 2;
#pragma unroll
        for (int j = 0; j < 20; j++) {
          *reinterpret_cast<uint32_t*>(op0 + j * 8) = pack(acc[4 * j], acc[4 * j + 1]);
          *reinterpret_cast<uint32_t*>(op1 + j * 8) = pack(acc[4 * j + 2], acc[4 * j + 3]);
        }
      }
#pragma unroll
      for (int i = 0; i < 60; i++) pb[i] = 0;
    }
  }
}

typedef CUresult (*EncodeFn)(CUtensorMap*, CUtensorMapDataType, cuuint32_t, void*, const cuuint64_t*, const cuuint64_t*,
                             const cuuint32_t*, const cuuint32_t*, CUtensorMapInterleave, CUtensorMapSwizzle,
                             CUtensorMapL2promotion, CUtensorMapFloatOOBfill);

void make_map(EncodeFn enc, CUtensorMap* m, const void* p, int rank, const cuuint64_t* dims, const cuuint64_t* strides,
              const cuuint32_t* box, CUtensorMapSwizzle sw, CUtensorMapL2promotion promo) {
  cuuint32_t es[4] = {1, 1, 1, 1};
  enc(m, CU_TENSOR_MAP_DATA_TYPE_BFLOAT16, rank, const_cast<void*>(p), dims, strides, box, es, CU_TENSOR_MAP_INTERLEAVE_NONE, sw,
      promo, CU_TENSOR_MAP_FLOAT_OOB_FILL_NONE);
}

}

extern "C" void kernel_launch(void* const* d_in, const int* in_sizes, int n_in, void* d_out, int out_size) {
  static EncodeFn enc = nullptr;
  static int nclusters = 0;
  static void* o_ptr = nullptr;
  if (!enc) {
    cudaDriverEntryPointQueryResult qr;
    cudaGetDriverEntryPoint("cuTensorMapEncodeTiled", (void**)&enc, cudaEnableDefault, &qr);
    cudaFuncSetAttribute(fused_attn_kernel<66>, cudaFuncAttributeMaxDynamicSharedMemorySize, SMEM_BYTES);
    cudaFuncSetAttribute(fused_attn_kernel<0>, cudaFuncAttributeMaxDynamicSharedMemorySize, SMEM_BYTES);
    cudaGetSymbolAddress(&o_ptr, g_o);
    cudaLaunchConfig_t cfg = {};
    cfg.gridDim = 128; cfg.blockDim = 384; cfg.dynamicSmemBytes = SMEM_BYTES;
    cudaLaunchAttribute at; at.id = cudaLaunchAttributeClusterDimension;
    at.val.clusterDim.x = 2; at.val.clusterDim.y = 1; at.val.clusterDim.z = 1;
    cfg.attrs = &at; cfg.numAttrs = 1;
    int n = 0;
    cudaOccupancyMaxActiveClusters(&n, fused_attn_kernel<66>, &cfg);
    nclusters = n >= 66 ? MAXCL : (n >= 64 || n <= 0 ? 64 : n);
  }
  const __nv_bfloat16* x = (const __nv_bfloat16*)d_in[0];
  const __nv_bfloat16* k = (const __nv_bfloat16*)d_in[1];
  const __nv_bfloat16* v = (const __nv_bfloat16*)d_in[2];
  const __nv_bfloat16* wq = (const __nv_bfloat16*)d_in[3];
  const __nv_bfloat16* wo = (const __nv_bfloat16*)d_in[4];
  CUtensorMap tm_x, tm_wq, tm_k, tm_v, tm_o, tm_wo;
  const auto S128 = CU_TENSOR_MAP_SWIZZLE_128B;
  const auto P128 = CU_TENSOR_MAP_L2_PROMOTION_L2_128B, P256 = CU_TENSOR_MAP_L2_PROMOTION_L2_256B;
  { cuuint64_t d[2] = {DM, NB * SQ}, s[1] = {DM * 2}; cuuint32_t b[2] = {64, 120}; make_map(enc, &tm_x, x, 2, d, s, b, S128, P128); }
  { cuuint64_t d[3] = {64, DM, HD / 64}, s[2] = {HD * 2, 128}; cuuint32_t b[3] = {64, 64, 2}; make_map(enc, &tm_wq, wq, 3, d, s, b, S128, P256); }
  { cuuint64_t d[3] = {64, NB * NH * SK, 2}, s[2] = {DH * 2, 128}; cuuint32_t b[3] = {64, 64, 2};
    make_map(enc, &tm_k, k, 3, d, s, b, S128, P128); make_map(enc, &tm_v, v, 3, d, s, b, S128, P128); }
  { cuuint64_t d[4] = {256, 2, HD / 8, NROWS / 64}, s[3] = {512, NROWS * 16, 1024}; cuuint32_t b[4] = {256, 2, 8, 2};
    make_map(enc, &tm_o, o_ptr, 4, d, s, b, CU_TENSOR_MAP_SWIZZLE_NONE, P256); }
  { cuuint64_t d[3] = {32, HD, DM / 32}, s[2] = {DM * 2, 64}; cuuint32_t b[3] = {32, 64, 5};
    make_map(enc, &tm_wo, wo, 3, d, s, b, CU_TENSOR_MAP_SWIZZLE_64B, P128); }
  Params P{x, k, v, wq, (__nv_bfloat16*)d_out, (__nv_bfloat16*)o_ptr};
  if (nclusters == 66) fused_attn_kernel<66><<<132, 384, SMEM_BYTES>>>(tm_x, tm_wq, tm_k, tm_v, tm_o, tm_wo, P);
  else fused_attn_kernel<0><<<2 * nclusters, 384, SMEM_BYTES>>>(tm_x, tm_wq, tm_k, tm_v, tm_o, tm_wo, P);
}
```

```cpp
#include <cuda_runtime.h>
#include <cuda.h>
#include <cuda_bf16.h>
#include <stdint.h>

namespace {

constexpr int NB = 16, SQ = 240, DM = 640, NH = 32, SK = 1024, DH = 128, HD = NH * DH;
constexpr int NROWS = NB * SQ;
constexpr int NUNITS = 256;
#define ALT_FROM 4
#define END_SKEW 5
#define VREL 6
#define PF_N 4
#define PF_J0 3
#define PF_STEP 3
#define WO_PF 6
#define PAUSE_NS 11000
#define SMID_TOP 88
#define EXPV 1
#define MAXCL 66
constexpr int NOTILES = 60;
constexpr float QSCALE = 0.08838834764831845f * 1.4426950408889634f;
constexpr float L_MIN = 1.f;
constexpr float L_MAX = 1.152921504606846976e18f;

constexpr uint32_t RING_SLOTS = 6, RING_BYTES = 16384;
constexpr uint32_t XB = 15360;
constexpr uint32_t BB = 20480;
constexpr uint32_t OFF_Q = RING_SLOTS * RING_BYTES;
constexpr uint32_t OFF_P = OFF_Q + 4 * XB;
constexpr uint32_t OFF_INV = OFF_P + 4 * XB;
constexpr uint32_t OFF_L2 = OFF_INV + 1280;
constexpr uint32_t OFF_BAR = OFF_L2 + 4096;
constexpr uint32_t BAR_RFULL = OFF_BAR, BAR_REMPTY = BAR_RFULL + 48, BAR_XFULL = BAR_REMPTY + 48,
    BAR_XEMPTY = BAR_XFULL + 64, BAR_BFULL = BAR_XEMPTY + 32, BAR_BEMPTY = BAR_BFULL + 48, BAR_STAGE = BAR_BEMPTY + 48;
constexpr uint32_t BAR_ROLE = BAR_STAGE + 16, BAR_LSUM = BAR_ROLE + 24, BAR_INV = BAR_LSUM + 16;
constexpr uint32_t OFF_TR = BAR_INV + 16;
constexpr uint32_t SMEM_BYTES = OFF_TR + 1024;

constexpr uint32_t HI128 = (1u << 30) | (1024 >> 4);
constexpr uint32_t HI64 = (2u << 30) | (512 >> 4);
constexpr uint32_t HI64A = (2u << 30) | (1024 >> 4), LBO64A = (512u >> 4) << 16;

__device__ __nv_bfloat16 g_o[HD * NROWS];
__device__ unsigned g_cnt[67 * 8];

struct Params {
  const __nv_bfloat16 *x, *k, *v, *wq;
  __nv_bfloat16 *out, *o;
};

__device__ __forceinline__ void wg_fence() { asm volatile("wgmma.fence.sync.aligned;" ::: "memory"); }
__device__ __forceinline__ void wg_commit() { asm volatile("wgmma.commit_group.sync.aligned;" ::: "memory"); }
template <int N> __device__ __forceinline__ void wg_wait() { asm volatile("wgmma.wait_group.sync.aligned %0;" ::"n"(N) : "memory"); }
template <int N> __device__ __forceinline__ void reg_fence(float (&r)[N]) {
#pragma unroll
  for (int i = 0; i < N; i++) asm volatile("" : "+f"(r[i])::"memory");
}
template <int TA, int TB>
__device__ __forceinline__ void wgmma_n120(float (&d)[60], uint32_t a_lo, uint32_t a_hi, uint32_t b_lo, uint32_t b_hi, int acc) {
  asm volatile(
      "{\n.reg .pred p;\n.reg .b64 da, db;\nsetp.ne.b32 p, %64, 0;\n"
      "mov.b64 da, {%60, %61};\nmov.b64 db, {%62, %63};\n"
      "wgmma.mma_async.sync.aligned.m64n120k16.f32.bf16.bf16 {"
      "%0, %1, %2, %3, %4, %5, %6, %7, %8, %9, %10, %11, %12, %13, %14, %15, %16, %17, %18, %19, %20, %21, %22, %23, "
      "%24, %25, %26, %27, %28, %29, %30, %31, %32, %33, %34, %35, %36, %37, %38, %39, %40, %41, %42, %43, %44, %45, "
      "%46, %47, %48, %49, %50, %51, %52, %53, %54, %55, %56, %57, %58, %59"
      "}, da, db, p, 1, 1, %65, %66;\n}\n"
      : "+f"(d[0]), "+f"(d[1]), "+f"(d[2]), "+f"(d[3]), "+f"(d[4]), "+f"(d[5]), "+f"(d[6]), "+f"(d[7]), "+f"(d[8]),
        "+f"(d[9]), "+f"(d[10]), "+f"(d[11]), "+f"(d[12]), "+f"(d[13]), "+f"(d[14]), "+f"(d[15]), "+f"(d[16]),
        "+f"(d[17]), "+f"(d[18]), "+f"(d[19]), "+f"(d[20]), "+f"(d[21]), "+f"(d[22]), "+f"(d[23]), "+f"(d[24]),
        "+f"(d[25]), "+f"(d[26]), "+f"(d[27]), "+f"(d[28]), "+f"(d[29]), "+f"(d[30]), "+f"(d[31]), "+f"(d[32]),
        "+f"(d[33]), "+f"(d[34]), "+f"(d[35]), "+f"(d[36]), "+f"(d[37]), "+f"(d[38]), "+f"(d[39]), "+f"(d[40]),
        "+f"(d[41]), "+f"(d[42]), "+f"(d[43]), "+f"(d[44]), "+f"(d[45]), "+f"(d[46]), "+f"(d[47]), "+f"(d[48]),
        "+f"(d[49]), "+f"(d[50]), "+f"(d[51]), "+f"(d[52]), "+f"(d[53]), "+f"(d[54]), "+f"(d[55]), "+f"(d[56]),
        "+f"(d[57]), "+f"(d[58]), "+f"(d[59])
      : "r"(a_lo), "r"(a_hi), "r"(b_lo), "r"(b_hi), "r"(acc), "n"(TA), "n"(TB));
}

template <int TA, int TB>
__device__ __forceinline__ void wgmma_n160(float (&d)[80], uint32_t a_lo, uint32_t a_hi, uint32_t b_lo, uint32_t b_hi, int acc) {
  asm volatile(
      "{\n.reg .pred p;\n.reg .b64 da, db;\nsetp.ne.b32 p, %84, 0;\n"
      "mov.b64 da, {%80, %81};\nmov.b64 db, {%82, %83};\n"
      "wgmma.mma_async.sync.aligned.m64n160k16.f32.bf16.bf16 {"
      "%0, %1, %2, %3, %4, %5, %6, %7, %8, %9, %10, %11, %12, %13, %14, %15, %16, %17, %18, %19, %20, %21, %22, %23, "
      "%24, %25, %26, %27, %28, %29, %30, %31, %32, %33, %34, %35, %36, %37, %38, %39, %40, %41, %42, %43, %44, %45, "
      "%46, %47, %48, %49, %50, %51, %52, %53, %54, %55, %56, %57, %58, %59, %60, %61, %62, %63, %64, %65, %66, %67, "
      "%68, %69, %70, %71, %72, %73, %74, %75, %76, %77, %78, %79"
      "}, da, db, p, 1, 1, %85, %86;\n}\n"
      : "+f"(d[0]), "+f"(d[1]), "+f"(d[2]), "+f"(d[3]), "+f"(d[4]), "+f"(d[5]), "+f"(d[6]), "+f"(d[7]), "+f"(d[8]),
        "+f"(d[9]), "+f"(d[10]), "+f"(d[11]), "+f"(d[12]), "+f"(d[13]), "+f"(d[14]), "+f"(d[15]), "+f"(d[16]),
        "+f"(d[17]), "+f"(d[18]), "+f"(d[19]), "+f"(d[20]), "+f"(d[21]), "+f"(d[22]), "+f"(d[23]), "+f"(d[24]),
        "+f"(d[25]), "+f"(d[26]), "+f"(d[27]), "+f"(d[28]), "+f"(d[29]), "+f"(d[30]), "+f"(d[31]), "+f"(d[32]),
        "+f"(d[33]), "+f"(d[34]), "+f"(d[35]), "+f"(d[36]), "+f"(d[37]), "+f"(d[38]), "+f"(d[39]), "+f"(d[40]),
        "+f"(d[41]), "+f"(d[42]), "+f"(d[43]), "+f"(d[44]), "+f"(d[45]), "+f"(d[46]), "+f"(d[47]), "+f"(d[48]),
        "+f"(d[49]), "+f"(d[50]), "+f"(d[51]), "+f"(d[52]), "+f"(d[53]), "+f"(d[54]), "+f"(d[55]), "+f"(d[56]),
        "+f"(d[57]), "+f"(d[58]), "+f"(d[59]), "+f"(d[60]), "+f"(d[61]), "+f"(d[62]), "+f"(d[63]), "+f"(d[64]),
        "+f"(d[65]), "+f"(d[66]), "+f"(d[67]), "+f"(d[68]), "+f"(d[69]), "+f"(d[70]), "+f"(d[71]), "+f"(d[72]),
        "+f"(d[73]), "+f"(d[74]), "+f"(d[75]), "+f"(d[76]), "+f"(d[77]), "+f"(d[78]), "+f"(d[79])
      : "r"(a_lo), "r"(a_hi), "r"(b_lo), "r"(b_hi), "r"(acc), "n"(TA), "n"(TB));
}
__device__ __forceinline__ void mbar_init(uint32_t bar, int cnt) { asm volatile("mbarrier.init.shared::cta.b64 [%0], %1;" ::"r"(bar), "r"(cnt)); }
__device__ __forceinline__ void mbar_expect(uint32_t bar, uint32_t bytes) {
  asm volatile("mbarrier.arrive.expect_tx.shared::cta.b64 _, [%0], %1;" ::"r"(bar), "r"(bytes) : "memory");
}
__device__ __forceinline__ uint32_t mapa(uint32_t addr, uint32_t cta) {
  uint32_t r; asm("mapa.shared::cluster.u32 %0, %1, %2;" : "=r"(r) : "r"(addr), "r"(cta)); return r;
}
__device__ __forceinline__ void mbar_expect_cl(uint32_t cbar, uint32_t bytes) {
  asm volatile("mbarrier.arrive.expect_tx.shared::cluster.b64 _, [%0], %1;" ::"r"(cbar), "r"(bytes) : "memory");
}
__device__ __forceinline__ void mbar_arrive(uint32_t bar) { asm volatile("mbarrier.arrive.shared::cta.b64 _, [%0];" ::"r"(bar) : "memory"); }
__device__ __forceinline__ void mbar_arrive_cl(uint32_t cbar) { asm volatile("mbarrier.arrive.shared::cluster.b64 _, [%0];" ::"r"(cbar) : "memory"); }
__device__ __forceinline__ void warp_arrive(uint32_t bar) {
  asm volatile("{\n.reg .pred p;\nelect.sync _|p, 0xffffffff;\n@p mbarrier.arrive.shared::cta.b64 _, [%0];\n}\n" ::"r"(bar) : "memory");
}
__device__ __forceinline__ void warp_arrive_cl(uint32_t cbar) {
  asm volatile("{\n.reg .pred p;\nelect.sync _|p, 0xffffffff;\n@p mbarrier.arrive.shared::cluster.b64 _, [%0];\n}\n" ::"r"(cbar) : "memory");
}
__device__ __forceinline__ void mbar_wait(uint32_t bar, uint32_t parity) {
  asm volatile(
      "{\n.reg .pred p;\n.reg .u32 n;\n"
      "mbarrier.try_wait.parity.shared::cta.b64 p, [%0], %1;\n@p bra WAIT_DONE;\n"
      "mov.u32 n, 0;\n"
      "WAIT_LOOP:\n"
      "mbarrier.try_wait.parity.shared::cta.b64 p, [%0], %1;\n@p bra WAIT_DONE;\n"
      "add.u32 n, n, 1;\nsetp.lt.u32 p, n, 0x4000000;\n@p bra WAIT_LOOP;\ntrap;\n"
      "WAIT_DONE:\n}\n" ::"r"(bar), "r"(parity) : "memory");
}
__device__ __forceinline__ void mbar_sleep(uint32_t bar, uint32_t parity) {
  asm volatile(
      "{\n.reg .pred p;\n.reg .u32 n;\nmov.u32 n, 0;\n"
      "WAIT_LOOP:\n"
      "mbarrier.try_wait.parity.shared::cta.b64 p, [%0], %1, 4000;\n@p bra WAIT_DONE;\n"
      "add.u32 n, n, 1;\nsetp.lt.u32 p, n, 0x400000;\n@p bra WAIT_LOOP;\ntrap;\n"
      "WAIT_DONE:\n}\n" ::"r"(bar), "r"(parity) : "memory");
}
__device__ __forceinline__ void mbar_wait_cl(uint32_t bar, uint32_t parity) {
  asm volatile(
      "{\n.reg .pred p;\n.reg .u32 n;\nmov.u32 n, 0;\n"
      "WAIT_LOOP:\n"
      "mbarrier.try_wait.parity.acquire.cluster.shared::cta.b64 p, [%0], %1;\n@p bra WAIT_DONE;\n"
      "add.u32 n, n, 1;\nsetp.lt.u32 p, n, 0x4000000;\n@p bra WAIT_LOOP;\ntrap;\n"
      "WAIT_DONE:\n}\n" ::"r"(bar), "r"(parity) : "memory");
}
__device__ __forceinline__ void tma3d(uint32_t dst, const CUtensorMap* m, int c0, int c1, int c2, uint32_t bar) {
  asm volatile("cp.async.bulk.tensor.3d.shared::cluster.global.mbarrier::complete_tx::bytes [%0], [%1, {%3, %4, %5}], [%2];"
               ::"r"(dst), "l"(m), "r"(bar), "r"(c0), "r"(c1), "r"(c2) : "memory");
}
__device__ __forceinline__ void tma3d_hint(uint32_t dst, const CUtensorMap* m, int c0, int c1, int c2, uint32_t bar, uint64_t pol) {
  asm volatile("cp.async.bulk.tensor.3d.shared::cluster.global.mbarrier::complete_tx::bytes.L2::cache_hint [%0], [%1, {%3, %4, %5}], [%2], %6;"
               ::"r"(dst), "l"(m), "r"(bar), "r"(c0), "r"(c1), "r"(c2), "l"(pol) : "memory");
}
__device__ __forceinline__ void tma2d_mc(uint32_t dst, const CUtensorMap* m, int c0, int c1, uint32_t bar) {
  asm volatile("cp.async.bulk.tensor.2d.shared::cluster.global.mbarrier::complete_tx::bytes.multicast::cluster [%0], [%1, {%3, %4}], [%2], %5;"
               ::"r"(dst), "l"(m), "r"(bar), "r"(c0), "r"(c1), "h"((uint16_t)3) : "memory");
}
__device__ __forceinline__ void tma3d_mc(uint32_t dst, const CUtensorMap* m, int c0, int c1, int c2, uint32_t bar) {
  asm volatile("cp.async.bulk.tensor.3d.shared::cluster.global.mbarrier::complete_tx::bytes.multicast::cluster [%0], [%1, {%3, %4, %5}], [%2], %6;"
               ::"r"(dst), "l"(m), "r"(bar), "r"(c0), "r"(c1), "r"(c2), "h"((uint16_t)3) : "memory");
}
__device__ __forceinline__ void l2_prefetch(const void* p, uint32_t bytes) {
  asm volatile("cp.async.bulk.prefetch.L2.global [%0], %1;" ::"l"(p), "r"(bytes) : "memory");
}
__device__ __forceinline__ void fence_async_smem() { asm volatile("fence.proxy.async.shared::cta;" ::: "memory"); }
__device__ __forceinline__ void bar_sync(int wg) {
  if (wg == 0) asm volatile("bar.sync 1, 128;" ::: "memory");
  else asm volatile("bar.sync 2, 128;" ::: "memory");
}
__device__ __forceinline__ bool bar_red_or(int id, bool v) {
  uint32_t r;
  asm volatile("{\n.reg .pred p, q;\nsetp.ne.u32 p, %2, 0;\nbar.red.or.pred q, %1, 128, p;\nselp.u32 %0, 1, 0, q;\n}\n"
               : "=r"(r) : "r"(1 + id), "r"((uint32_t)v) : "memory");
  return r != 0;
}
__device__ __forceinline__ uint32_t hfma2(uint32_t a, uint32_t b, uint32_t c) { uint32_t r; asm("fma.rn.bf16x2 %0, %1, %2, %3;" : "=r"(r) : "r"(a), "r"(b), "r"(c)); return r; }
__device__ __forceinline__ float ex2(float x) { float y; asm("ex2.approx.ftz.f32 %0, %1;" : "=f"(y) : "f"(x)); return y; }
__device__ __forceinline__ uint32_t pack(float lo, float hi) { uint32_t r; asm("cvt.rn.bf16x2.f32 %0, %1, %2;" : "=r"(r) : "f"(hi), "f"(lo)); return r; }
__device__ __forceinline__ void stsm4t(uint32_t a, uint32_t r0, uint32_t r1, uint32_t r2, uint32_t r3) {
  asm volatile("stmatrix.sync.aligned.m8n8.x4.trans.shared.b16 [%0], {%1,%2,%3,%4};" ::"r"(a), "r"(r0), "r"(r1), "r"(r2), "r"(r3) : "memory");
}
__device__ __forceinline__ void stsm2t(uint32_t a, uint32_t r0, uint32_t r1) {
  asm volatile("stmatrix.sync.aligned.m8n8.x2.trans.shared.b16 [%0], {%1,%2};" ::"r"(a), "r"(r0), "r"(r1) : "memory");
}
__device__ __forceinline__ void mma16816(float (&d)[4], const uint32_t (&a)[4], uint32_t b0, uint32_t b1) {
  asm volatile("mma.sync.aligned.m16n8k16.row.col.f32.bf16.bf16.f32 {%0,%1,%2,%3}, {%4,%5,%6,%7}, {%8,%9}, {%0,%1,%2,%3};"
               : "+f"(d[0]), "+f"(d[1]), "+f"(d[2]), "+f"(d[3]) : "r"(a[0]), "r"(a[1]), "r"(a[2]), "r"(a[3]), "r"(b0), "r"(b1));
}

__device__ __forceinline__ uint32_t fresh_tid() { uint32_t t; asm volatile("mov.u32 %0, %tid.x;" : "=r"(t)); return t; }

template <int V> struct IC { static constexpr int value = V; };

struct Ring {
  uint32_t slot = 0, phase = 0;
  __device__ __forceinline__ void next() { if (++slot == RING_SLOTS) { slot = 0; phase ^= 1; } }
};

__device__ __forceinline__ void mma_tn(float (&o0)[60], float (&o1)[60], uint32_t a, uint32_t b, int acc) {
#pragma unroll
  for (int k = 0; k < 4; k++) {
    wgmma_n120<1, 0>(o0, a + k * 128, HI128, b + k * 2, HI128, k == 0 ? acc : 1);
    wgmma_n120<1, 0>(o1, a + 512 + k * 128, HI128, b + k * 2, HI128, k == 0 ? acc : 1);
  }
}
__device__ __forceinline__ void mma_tn_split(float (&o0)[60], float (&o1)[60], uint32_t a, uint32_t b) {
#pragma unroll
  for (int k = 0; k < 4; k++) wgmma_n120<1, 0>(o0, a + k * 128, HI128, b + k * 2, HI128, 1);
  wg_commit();
#pragma unroll
  for (int k = 0; k < 4; k++) wgmma_n120<1, 0>(o1, a + 512 + k * 128, HI128, b + k * 2, HI128, 1);
  wg_commit();
}
__device__ __forceinline__ void mma_qk(float (&s)[60], uint32_t a, uint32_t q) {
#pragma unroll
  for (int k = 0; k < 8; k++)
    wgmma_n120<0, 0>(s, a + (k >> 2) * 512 + (k & 3) * 2, HI128, q + (k >> 2) * (XB >> 4) + (k & 3) * 2, HI128, k != 0);
}
template <int J0, int J1, bool FIRST = false>
__device__ __forceinline__ void exp_store(const float (&s)[60], float (&l)[30], uint32_t dst) {
#pragma unroll
  for (int c = J0; c < J1; c++) {
    const float e0 = ex2(s[4 * c]), e1 = ex2(s[4 * c + 1]), e2 = ex2(s[4 * c + 2]), e3 = ex2(s[4 * c + 3]);
    if (FIRST) { l[2 * c] = e0 + e2; l[2 * c + 1] = e1 + e3; }
    else if (EXPV == 1) { l[2 * c] += e0; l[2 * c + 1] += e1; l[2 * c] += e2; l[2 * c + 1] += e3; }
    else { l[2 * c] += e0 + e2; l[2 * c + 1] += e1 + e3; }
    stsm2t(dst + c * 1024, pack(e0, e1), pack(e2, e3));
  }
}

__device__ __forceinline__ int o_pos(int b, int wg, int r) {
  const int j = r >> 3, q = (r >> 1) & 3, c = r & 1, o = b & 1, base = (b >> 1) * 480;
  if (j < 12) return base + (o * 9 + wg * 3 + (j >> 2)) * 32 + q * 8 + (j & 3) * 2 + c;
  if (j < 14) return base + (6 + 2 * o) * 32 + wg * 16 + q * 4 + (j - 12) * 2 + c;
  return base + 7 * 32 + (o * 2 + wg) * 8 + q * 2 + c;
}
__device__ __forceinline__ int o_row(int p) {
  const int pair = p / 480, a = (p - pair * 480) >> 5, in = p & 31, c = p & 1;
  int tile, row;
  if (a == 7) { tile = in >> 3; row = 112 + (in & 7); }
  else if (a == 6 || a == 8) { tile = a - 6 + (in >> 4); row = (12 + ((in >> 1) & 1)) * 8 + ((in >> 2) & 3) * 2 + c; }
  else { const int f = a > 8 ? a - 3 : a; tile = f / 3; row = ((f - tile * 3) * 4 + ((in >> 1) & 3)) * 8 + (in >> 3) * 2 + c; }
  return pair * 480 + tile * 120 + row;
}
__device__ __forceinline__ uint32_t o_idx(int k, int p) {
  return ((k >> 3) * (NROWS / 32) + (p >> 5)) * 256 + (k & 7) * 32 + ((((p >> 3) & 3) ^ ((k & 7) >> 1)) << 3) + (p & 7);
}

__device__ __forceinline__ void slow_path(const Params& P, int b, int h, int wg, int w, int lane) {
  const int g = lane >> 2, q = lane & 3, row0 = wg * 120;
  const uint16_t* wq = reinterpret_cast<const uint16_t*>(P.wq) + h * DH + g;
  const __nv_bfloat16* kp = P.k + (size_t)(b * NH + h) * SK * DH;
  const uint16_t* vp = reinterpret_cast<const uint16_t*>(P.v) + (size_t)(b * NH + h) * SK * DH + g;
#pragma unroll 1
  for (int t = w; t < 8; t += 4) {
    const int r0 = 16 * t + g, r1 = r0 + 8;
    const __nv_bfloat16* x0 = P.x + (size_t)(b * SQ + row0 + r0) * DM + 2 * q;
    const __nv_bfloat16* x1 = P.x + (size_t)(b * SQ + row0 + min(r1, 119)) * DM + 2 * q;
    float o[16][4];
#pragma unroll
    for (int n = 0; n < 16; n++) o[n][0] = o[n][1] = o[n][2] = o[n][3] = 0.f;
#pragma unroll 1
    for (int k0 = 0; k0 < DM; k0 += 16) {
      uint32_t a[4] = {*(const uint32_t*)(x0 + k0), *(const uint32_t*)(x1 + k0), *(const uint32_t*)(x0 + k0 + 8), *(const uint32_t*)(x1 + k0 + 8)};
      const uint16_t* wr = wq + (size_t)(k0 + 2 * q) * HD;
#pragma unroll
      for (int n = 0; n < 16; n++) {
        if ((n & 3) == 0) __syncwarp();
        mma16816(o[n], a, wr[8 * n] | ((uint32_t)wr[8 * n + HD] << 16), wr[8 * n + 8 * HD] | ((uint32_t)wr[8 * n + 9 * HD] << 16));
      }
    }
    uint32_t qa[8][4];
#pragma unroll
    for (int k = 0; k < 8; k++) {
      qa[k][0] = pack(o[2 * k][0] * QSCALE, o[2 * k][1] * QSCALE);
      qa[k][1] = pack(o[2 * k][2] * QSCALE, o[2 * k][3] * QSCALE);
      qa[k][2] = pack(o[2 * k + 1][0] * QSCALE, o[2 * k + 1][1] * QSCALE);
      qa[k][3] = pack(o[2 * k + 1][2] * QSCALE, o[2 * k + 1][3] * QSCALE);
    }
#pragma unroll
    for (int n = 0; n < 16; n++) o[n][0] = o[n][1] = o[n][2] = o[n][3] = 0.f;
    float m0 = -INFINITY, m1 = -INFINITY, l0 = 0.f, l1 = 0.f;
#pragma unroll 1
    for (int key0 = 0; key0 < SK; key0 += 16) {
      float s[2][4];
#pragma unroll
      for (int nt = 0; nt < 2; nt++) {
        s[nt][0] = s[nt][1] = s[nt][2] = s[nt][3] = 0.f;
        const __nv_bfloat16* kr = kp + (size_t)(key0 + 8 * nt + g) * DH + 2 * q;
#pragma unroll
        for (int k = 0; k < 8; k++) mma16816(s[nt], qa[k], *(const uint32_t*)(kr + 16 * k), *(const uint32_t*)(kr + 16 * k + 8));
      }
      float n0 = fmaxf(fmaxf(s[0][0], s[0][1]), fmaxf(s[1][0], s[1][1])), n1 = fmaxf(fmaxf(s[0][2], s[0][3]), fmaxf(s[1][2], s[1][3]));
      n0 = fmaxf(n0, __shfl_xor_sync(~0u, n0, 1)); n1 = fmaxf(n1, __shfl_xor_sync(~0u, n1, 1));
      n0 = fmaxf(n0, __shfl_xor_sync(~0u, n0, 2)); n1 = fmaxf(n1, __shfl_xor_sync(~0u, n1, 2));
      n0 = fmaxf(n0, m0); n1 = fmaxf(n1, m1);
      const float z0 = n0 == -INFINITY ? 0.f : n0, z1 = n1 == -INFINITY ? 0.f : n1;
      const float c0 = ex2(m0 - z0), c1 = ex2(m1 - z1);
      m0 = n0; m1 = n1;
#pragma unroll
      for (int nt = 0; nt < 2; nt++) {
        s[nt][0] = ex2(s[nt][0] - z0); s[nt][1] = ex2(s[nt][1] - z0);
        s[nt][2] = ex2(s[nt][2] - z1); s[nt][3] = ex2(s[nt][3] - z1);
      }
      l0 = l0 * c0 + s[0][0] + s[0][1] + s[1][0] + s[1][1];
      l1 = l1 * c1 + s[0][2] + s[0][3] + s[1][2] + s[1][3];
      uint32_t pa[4] = {pack(s[0][0], s[0][1]), pack(s[0][2], s[0][3]), pack(s[1][0], s[1][1]), pack(s[1][2], s[1][3])};
      const uint16_t* vr = vp + (size_t)(key0 + 2 * q) * DH;
#pragma unroll
      for (int n = 0; n < 16; n++) {
        if ((n & 3) == 0) __syncwarp();
        o[n][0] *= c0; o[n][1] *= c0; o[n][2] *= c1; o[n][3] *= c1;
        mma16816(o[n], pa, vr[8 * n] | ((uint32_t)vr[8 * n + DH] << 16), vr[8 * n + 8 * DH] | ((uint32_t)vr[8 * n + 9 * DH] << 16));
      }
    }
    l0 += __shfl_xor_sync(~0u, l0, 1); l1 += __shfl_xor_sync(~0u, l1, 1);
    l0 += __shfl_xor_sync(~0u, l0, 2); l1 += __shfl_xor_sync(~0u, l1, 2);
    const float i0 = 1.f / l0, i1 = 1.f / l1;
    __nv_bfloat16* oc0 = P.o + o_idx(h * DH + 2 * q, o_pos(b, wg, r0));
    __nv_bfloat16* oc1 = P.o + o_idx(h * DH + 2 * q, o_pos(b, wg, min(r1, 119)));
#pragma unroll
    for (int n = 0; n < 16; n++) {
      oc0[8 * n * NROWS] = __float2bfloat16(o[n][0] * i0);
      oc0[8 * n * NROWS + 32] = __float2bfloat16(o[n][1] * i0);
      if (r1 < 120) {
        oc1[8 * n * NROWS] = __float2bfloat16(o[n][2] * i1);
        oc1[8 * n * NROWS + 32] = __float2bfloat16(o[n][3] * i1);
      }
    }
  }
}

__device__ __forceinline__ int bk(int ks) { return ks < 48 ? 32 - (ks & 48) + (ks & 15) : ks; }
__device__ __forceinline__ uint32_t x_slot(uint32_t wg, uint32_t j) { return j < 2 ? (2 * wg + j) * XB : (2 * j + wg) * XB; }
__device__ __forceinline__ int row_block(int t) { return t >= 44 ? (t >> 2) - 11 : (t >> 2) + 4; }
__device__ __forceinline__ int unit_batch(int u) { return (u & 63) >> 2; }
__device__ __forceinline__ int unit_head(int u, int rank) { return (u >> 6) * 8 + (u & 3) * 2 + rank; }

template <int NCL>
__global__ void __cluster_dims__(2, 1, 1) __launch_bounds__(384, 1)
fused_attn_kernel(const __grid_constant__ CUtensorMap tm_x, const __grid_constant__ CUtensorMap tm_wq,
                  const __grid_constant__ CUtensorMap tm_k, const __grid_constant__ CUtensorMap tm_v,
                  const __grid_constant__ CUtensorMap tm_o, const __grid_constant__ CUtensorMap tm_wo,
                  const __grid_constant__ Params P) {
  extern __shared__ uint8_t smem_raw[];
  const uint32_t sb = ((uint32_t)__cvta_generic_to_shared(smem_raw) + 1023) & ~1023u;
  const int warp = __shfl_sync(~0u, threadIdx.x >> 5, 0);
  const int lane = threadIdx.x & 31;
  const int rank = blockIdx.x & 1, cl = blockIdx.x >> 1, ncl = NCL ? NCL : gridDim.x >> 1;

  const int nsingle = NCL == 66 ? 44 : NOTILES;
  auto role = [&]() {
    mbar_wait(sb + BAR_ROLE + 16, 0);
    int id;
    asm volatile("ld.shared.u32 %0, [%1];" : "=r"(id) : "r"(sb + BAR_ROLE + 8) : "memory");
    return id;
  };

  if (threadIdx.x == 128) asm volatile("prefetch.tensormap [%0];" ::"l"(&tm_x) : "memory");
  if (threadIdx.x == 0) {
    asm volatile("prefetch.tensormap [%0];" ::"l"(&tm_wq) : "memory");
    for (int i = 0; i < 6; i++) {
      mbar_init(sb + BAR_RFULL + 8 * i, 1); mbar_init(sb + BAR_REMPTY + 8 * i, 8);
      mbar_init(sb + BAR_BFULL + 8 * i, 1); mbar_init(sb + BAR_BEMPTY + 8 * i, 16);
    }
    for (int i = 0; i < 8; i++) mbar_init(sb + BAR_XFULL + 8 * i, 1);
    for (int i = 0; i < 4; i++) mbar_init(sb + BAR_XEMPTY + 8 * i, 8);
    for (int i = 0; i < 2; i++) { mbar_init(sb + BAR_STAGE + 8 * i, 4); mbar_init(sb + BAR_LSUM + 8 * i, 4); mbar_init(sb + BAR_INV + 8 * i, 1); }
    mbar_init(sb + BAR_ROLE, 1); mbar_init(sb + BAR_ROLE + 16, 1);
    asm volatile("fence.mbarrier_init.release.cluster;" ::: "memory");
  }
  __syncwarp();
  asm volatile("barrier.cluster.arrive.relaxed.aligned;" ::: "memory");
  auto first_w = [&](int s) {
    mbar_expect(sb + BAR_RFULL + 8 * s, RING_BYTES);
    tma3d(sb + s * RING_BYTES, &tm_wq, 0, s * 64, 2 * unit_head(cl, rank), sb + BAR_RFULL + 8 * s);
  };
  if (threadIdx.x == 0) first_w(0);
  __syncwarp();
  asm volatile("barrier.cluster.wait.aligned;" ::: "memory");
  if (threadIdx.x == 128) {
#pragma unroll 1
    for (int s = 0; s < 2; s++) {
      const uint32_t fb = sb + BAR_XFULL + 32 * rank + 8 * s;
      mbar_expect(fb, XB);
      mbar_expect_cl(mapa(fb, rank ^ 1), XB);
      tma2d_mc(sb + OFF_Q + x_slot(rank, s), &tm_x, s * 64, unit_batch(cl) * SQ + rank * 120, fb);
      if (s == 0) first_w(1);
    }
  }
  __syncwarp();

  if (warp >= 8) {
    asm volatile("setmaxnreg.dec.sync.aligned.u32 24;");
    if (warp == 8) {
      uint64_t pol;
      asm volatile("createpolicy.fractional.L2::evict_first.b64 %0, 1.0;" : "=l"(pol));
      Ring r;
      r.slot = 2;
      auto load = [&](const CUtensorMap* m, int c1, int c2, bool ef) {
        mbar_sleep(sb + BAR_REMPTY + 8 * r.slot, r.phase ^ 1);
        if (lane == 0) {
          mbar_expect(sb + BAR_RFULL + 8 * r.slot, RING_BYTES);
          if (ef) tma3d_hint(sb + r.slot * RING_BYTES, m, 0, c1, c2, sb + BAR_RFULL + 8 * r.slot, pol);
          else tma3d(sb + r.slot * RING_BYTES, m, 0, c1, c2, sb + BAR_RFULL + 8 * r.slot);
        }
        r.next();
      };
      for (int u0 = 0;; u0 += ncl) {
        const int u = __shfl_sync(~0u, (u0 >= 3 * ncl ? role() : cl) + u0, 0);
        if (u >= NUNITS) break;
        if (NCL == 66 && u0 == 2 * 66) {
          const int id = role();
          if (id >= 44 && id < 58) {
            unsigned t0, t1;
            asm volatile("mov.u32 %0, %globaltimer_lo;" : "=r"(t0));
            do { __nanosleep(200); asm volatile("mov.u32 %0, %globaltimer_lo;" : "=r"(t1)); } while (t1 - t0 < PAUSE_NS);
          }
        }
        const int h = unit_head(u, rank);
        const int krow = (unit_batch(u) * NH + h) * SK;
#pragma unroll 1
        for (int s = u0 == 0 ? 2 : 0; s < 10; s++) {
          load(&tm_wq, s * 64, 2 * h, false);
          const int sp = u0 == 0 ? s - 6 : s;
          if (sp >= 0 && sp < PF_N && lane == 0) l2_prefetch(P.v + (size_t)(krow + (PF_J0 + sp * PF_STEP) * 64) * DH, 16384);
        }
#pragma unroll 1
        for (int j = 0; j <= 16; j++) {
          if (j < 16) load(&tm_k, krow + j * 64, 0, true);
          if (j == 2) load(&tm_v, krow, 0, true);
          if (j > 1) load(&tm_v, krow + (j - 1) * 64, 0, true);
        }
      }
      const int id = __shfl_sync(~0u, role(), 0);
      const bool dbl = NCL == 66 && id >= 58;
      for (int t = dbl ? 2 * id - 72 : id; t < (dbl ? NOTILES : nsingle); t += ncl) {
        const int row0 = row_block(t) * 256 + rank * 128;
        const int b0 = row0 / SQ, b1 = (row0 + 127) / SQ;
#pragma unroll 1
        for (int ks = 0; ks < 64; ks++) {
          if (dbl ? (ks & 15) == 0 : ks == 0 || ks == 48) {
            const unsigned* c = &g_cnt[((lane & 1 ? b1 : b0) * 4 + (ks || dbl ? ks >> 4 : min(lane >> 1, 2))) * 8];
            unsigned v, n = 0;
            do {
              asm volatile("ld.acquire.gpu.global.u32 %0, [%1];" : "=r"(v) : "l"(c) : "memory");
              if (++n > (1u << 26)) __trap();
            } while (v < 16);
            __syncwarp();
            asm volatile("fence.proxy.async.global;" ::: "memory");
          }
          mbar_wait(sb + BAR_REMPTY + 8 * r.slot, r.phase ^ 1);
          if (lane == 0) {
            mbar_expect(sb + BAR_RFULL + 8 * r.slot, RING_BYTES);
            asm volatile("cp.async.bulk.tensor.4d.shared::cluster.global.mbarrier::complete_tx::bytes.L2::cache_hint [%0], [%1, {%3, %3, %4, %5}], [%2], %6;"
                         ::"r"(sb + r.slot * RING_BYTES), "l"(&tm_o), "r"(sb + BAR_RFULL + 8 * r.slot), "r"(0), "r"((dbl ? ks : bk(ks)) * 8), "r"(row0 >> 6), "l"(pol) : "memory");
          }
          r.next();
        }
      }
      if (lane == 0 && atomicAdd(&g_cnt[64 * 8], 1) == gridDim.x - 1) {
        for (int i = 0; i < 67; i++) g_cnt[i * 8] = 0;
      }
    } else if (warp == 9) {
      if (lane == 0) {
        uint32_t it = 0;
        for (;; it++) {
          const int u = (it >= 3 ? role() : cl) + it * ncl;
          if (u >= NUNITS) break;
          const int row = unit_batch(u) * SQ + rank * 120;
#pragma unroll 1
          for (int s = it == 0 ? 2 : 0; s < 10; s++) {
            const uint32_t j = s & 3, par = ((s >> 2) + (j < 2 ? it : 0)) & 1;
            if (s == 0) mbar_sleep(sb + BAR_XEMPTY, par ^ 1);
            mbar_wait(sb + BAR_XEMPTY + 8 * j, par ^ 1);
            const uint32_t fb = sb + BAR_XFULL + 32 * rank + 8 * j;
            mbar_expect(fb, XB);
            mbar_expect_cl(mapa(fb, rank ^ 1), XB);
            tma2d_mc(sb + OFF_Q + x_slot(rank, j), &tm_x, s * 64, row, fb);
          }
        }
        const int id = role();
        const bool dbl = NCL == 66 && id >= 58;
        uint32_t slot = rank, phase = 0;
        if (dbl)
          asm volatile("cp.async.bulk.prefetch.tensor.3d.L2.global [%0, {%1, %2, %3}];" ::"l"(&tm_wo), "r"(0), "r"((2 + ((id >> 1) & 3)) * 64), "r"(((2 * id - 72 + rank) & 3) * 5) : "memory");
        if (dbl || id < nsingle) mbar_sleep(sb + BAR_BEMPTY + 8 * rank, 0);
        for (int t = dbl ? 2 * id - 72 + rank : id; t < (dbl ? NOTILES : nsingle); t += ncl) {
#pragma unroll 1
          for (int ks = dbl ? 0 : rank; ks < 64; ks += dbl ? 1 : 2) {
            mbar_wait(sb + BAR_BEMPTY + 8 * slot, phase);
            const uint32_t fb = sb + BAR_BFULL + 8 * slot;
            mbar_expect(fb, BB);
            mbar_expect_cl(mapa(fb, rank ^ 1), BB);
            tma3d_mc(sb + OFF_Q + slot * BB, &tm_wo, 0, (dbl ? ks : bk(ks)) * 64, (t & 3) * 5, fb);
            if (dbl && ks + WO_PF < 64 && (ks & 3) == ((id >> 1) & 3))
              asm volatile("cp.async.bulk.prefetch.tensor.3d.L2.global [%0, {%1, %2, %3}];" ::"l"(&tm_wo), "r"(0), "r"((ks + WO_PF) * 64), "r"((t & 3) * 5) : "memory");
            slot += 2;
            if (slot >= 6) { slot -= 6; phase ^= 1; }
          }
        }
      }
    } else {
      const int wg = warp - 10;
      {
        mbar_wait(sb + BAR_RFULL, 0);
        const __nv_bfloat16* xs = P.x + (size_t)(unit_batch(cl) * SQ + ((cl & 3) * 2 + rank) * 30 + min(lane, 29)) * DM + 256 + wg * 64;
#pragma unroll
        for (int i = 0; i < 3; i++) asm volatile("prefetch.global.L2 [%0];" ::"l"(xs + i * 128));
        if (lane < 16) asm volatile("prefetch.global.L2 [%0];" ::"l"(P.wq + (size_t)(384 + unit_batch(cl) * 16 + lane) * HD + unit_head(cl, rank) * DH + wg * 64));
      }
      for (uint32_t it = 0;; it++) {
        const int u = __shfl_sync(~0u, (it >= 3 ? role() : cl) + it * ncl, 0);
        if (u >= NUNITS) break;
        mbar_sleep(sb + BAR_LSUM + 8 * wg, it & 1);
        float l4[4], v[4];
        const uint32_t a = sb + OFF_L2 + wg * 2048 + lane * 16;
        asm volatile("ld.shared.v4.f32 {%0, %1, %2, %3}, [%4];" : "=f"(l4[0]), "=f"(l4[1]), "=f"(l4[2]), "=f"(l4[3]) : "r"(a) : "memory");
#pragma unroll
        for (int g = 1; g < 4; g++) {
          asm volatile("ld.shared.v4.f32 {%0, %1, %2, %3}, [%4];" : "=f"(v[0]), "=f"(v[1]), "=f"(v[2]), "=f"(v[3]) : "r"(a + g * 512) : "memory");
#pragma unroll
          for (int c = 0; c < 4; c++) l4[c] += v[c];
        }
#pragma unroll
        for (int c = 0; c < 4; c++) {
          float inv;
          asm("rcp.approx.ftz.f32 %0, %1;" : "=f"(inv) : "f"(l4[c]));
          l4[c] = l4[c] >= L_MIN && l4[c] <= L_MAX ? inv : __uint_as_float(0x7FFFFFFFu);
        }
        const uint32_t h0 = pack(l4[0], l4[1]), h1 = pack(l4[2], l4[3]);
        const uint32_t e0 = pack(l4[0] - __uint_as_float(h0 << 16), l4[1] - __uint_as_float(h0 & 0xFFFF0000u));
        const uint32_t e1 = pack(l4[2] - __uint_as_float(h1 << 16), l4[3] - __uint_as_float(h1 & 0xFFFF0000u));
        asm volatile("st.shared.v4.u32 [%0], {%1, %2, %3, %4};" ::"r"(sb + OFF_INV + wg * 640 + (lane & 3) * 144 + (lane >> 2) * 16), "r"(h0), "r"(e0), "r"(h1), "r"(e1) : "memory");
        __syncwarp();
        if (lane == 0) {
          mbar_arrive(sb + BAR_INV + 8 * wg);
          if (it == 0 && wg == 0) {
            if (rank == 0) {
              int id = cl;
              if (NCL == 66) {
                uint32_t smid;
                asm("mov.u32 %0, %smid;" : "=r"(smid));
                id = smid >= SMID_TOP ? 65 - atomicAdd(&g_cnt[65 * 8], 1) : atomicAdd(&g_cnt[66 * 8], 1);
              }
#pragma unroll
              for (int c = 0; c < 2; c++) {
                const uint32_t a = mapa(sb + BAR_ROLE, c);
                asm volatile("st.shared::cluster.u32 [%0 + 8], %1;\nmbarrier.arrive.release.cluster.shared::cluster.b64 _, [%0];" ::"r"(a), "r"(id) : "memory");
              }
            }
            mbar_wait_cl(sb + BAR_ROLE, 0);
            mbar_arrive(sb + BAR_ROLE + 16);
          }
          mbar_sleep(sb + BAR_STAGE + 8 * wg, it & 1);
          __threadfence();
          asm volatile("red.relaxed.gpu.global.add.u32 [%0], 1;" ::"l"(&g_cnt[(unit_batch(u) * 4 + (u >> 6)) * 8]) : "memory");
        }
        __syncwarp();
      }
    }
  } else {
    asm volatile("setmaxnreg.inc.sync.aligned.u32 240;");
    const int wg = warp >> 2, w = warp & 3;
    const uint32_t qreg = sb + OFF_Q + wg * 2 * XB, preg = sb + OFF_P + (2 + wg) * XB;
    const uint32_t st_off = ((lane >> 4) * 8 + (lane & 7)) * 128 + (((2 * w + ((lane >> 3) & 1)) ^ (lane & 7)) << 4);
    const uint32_t xempty = mapa(sb + BAR_XEMPTY, wg);
    Ring r;
    uint32_t it = 0;
    const uint32_t qd = (qreg & 0x3FFFF) >> 4, pd = (preg & 0x3FFFF) >> 4;
    auto ring_addr = [&]() { return ((sb & 0x3FFFF) + r.slot * RING_BYTES) >> 4; };
    auto ring_wait = [&]() { mbar_wait(sb + BAR_RFULL + 8 * r.slot, r.phase); };
    auto release = [&](uint32_t slot) { warp_arrive(sb + BAR_REMPTY + 8 * slot); };
    auto turn_wait = [&]() {
      if (wg == 0) asm volatile("bar.sync 3, 256;" ::: "memory");
      else asm volatile("bar.sync 4, 256;" ::: "memory");
    };
    auto turn_pass = [&]() {
      if (wg == 0) asm volatile("bar.arrive 4, 256;" ::: "memory");
      else asm volatile("bar.arrive 3, 256;" ::: "memory");
    };

    uint32_t chk = 0;
    auto sum_l = [&](const float (&l)[30], uint32_t tid) {
      float a[16], b[8], c[4];
      const bool b4 = tid & 16, b3 = tid & 8, b2 = tid & 4;
#pragma unroll
      for (int i = 0; i < 16; i++) {
        const float hi = i < 14 ? l[(16 + i) % 30] : 1.f;
        a[i] = (b4 ? hi : l[i]) + __shfl_xor_sync(~0u, b4 ? l[i] : hi, 16);
      }
#pragma unroll
      for (int i = 0; i < 8; i++) b[i] = (b3 ? a[8 + i] : a[i]) + __shfl_xor_sync(~0u, b3 ? a[i] : a[8 + i], 8);
#pragma unroll
      for (int i = 0; i < 4; i++) c[i] = (b2 ? b[4 + i] : b[i]) + __shfl_xor_sync(~0u, b2 ? b[i] : b[4 + i], 4);
      asm volatile("st.shared.v4.f32 [%0], {%1, %2, %3, %4};" ::"r"(sb + OFF_L2 + tid * 16), "f"(c[0]), "f"(c[1]),
                   "f"(c[2]), "f"(c[3]) : "memory");
      __syncwarp();
      warp_arrive(sb + BAR_LSUM + 8 * wg);
    };
    auto load_inv = [&](uint32_t (&iv)[30], uint32_t parity) {
      const int lane = fresh_tid() & 31;
      mbar_wait(sb + BAR_INV + 8 * wg, parity);
      chk = 0;
#pragma unroll
      for (int j = 0; j < 7; j++)
        asm volatile("ld.shared.v4.u32 {%0, %1, %2, %3}, [%4];" : "=r"(iv[4 * j]), "=r"(iv[4 * j + 1]), "=r"(iv[4 * j + 2]), "=r"(iv[4 * j + 3])
                     : "r"(sb + OFF_INV + wg * 640 + (lane & 3) * 144 + j * 16) : "memory");
      asm volatile("ld.shared.v2.u32 {%0, %1}, [%2];" : "=r"(iv[28]), "=r"(iv[29]) : "r"(sb + OFF_INV + wg * 640 + (lane & 3) * 144 + 112) : "memory");
    };
    auto norm = [&](uint32_t (&n)[8], const uint32_t (&po)[60], const uint32_t (&iv)[30], auto part) {
      constexpr int k = decltype(part)::value >> 1, j0 = (decltype(part)::value & 1) * 8;
#pragma unroll
      for (int j = 0; j < 8; j++)
        n[j] = j0 + j < 15 ? hfma2(po[15 * k + (j0 + j) % 15], iv[2 * ((j0 + j) % 15)], hfma2(po[15 * k + (j0 + j) % 15], iv[2 * ((j0 + j) % 15) + 1], 0x80008000u)) : 0x3F803F80u;
#pragma unroll
      for (int j = 0; j < 8; j += 2) chk = hfma2(n[j], n[j + 1], chk);
    };
    int od1, od2;
    auto store = [&](const uint32_t (&n)[8], const char* optr, auto part) {
      constexpr int k = decltype(part)::value >> 1, off = (8 * (k & 1) + 64 * (k >> 1)) * NROWS * 2;
      if ((decltype(part)::value & 1) == 0)
        asm volatile(
            "{\n.reg .pred p;\nsetp.ne.u64 p, %8, 0;\n"
            "@p st.global.v4.u32 [%8 + %9], {%0, %1, %2, %3};\n@p st.global.v4.u32 [%8 + %9 + 512], {%4, %5, %6, %7};\n}\n"
            ::"r"(n[0]), "r"(n[1]), "r"(n[2]), "r"(n[3]), "r"(n[4]), "r"(n[5]), "r"(n[6]), "r"(n[7]), "l"(optr), "n"(off) : "memory");
      else
        asm volatile(
            "{\n.reg .pred p;\n.reg .b64 b, c;\nsetp.ne.u64 p, %7, 0;\nmad.wide.s32 b, %9, 1, %7;\nmad.wide.s32 c, %10, 1, %7;\n"
            "@p st.global.v4.u32 [%7 + %8 + 1024], {%0, %1, %2, %3};\n@p st.global.v2.u32 [b + %8], {%4, %5};\n@p st.global.u32 [c + %8], %6;\n}\n"
            ::"r"(n[0]), "r"(n[1]), "r"(n[2]), "r"(n[3]), "r"(n[4]), "r"(n[5]), "r"(n[6]), "l"(optr), "n"(off), "r"(od1), "r"(od2) : "memory");
    };
    auto put = [&](const uint32_t (&po)[60], const uint32_t (&iv)[30], const char* optr, auto part) {
      uint32_t n[8];
      norm(n, po, iv, part);
      store(n, optr, part);
    };
    auto out_ptr = [&](int u) {
      const int lane = fresh_tid() & 31;
      const int k = unit_head(u, rank) * DH + 16 * w + (lane >> 2), b = unit_batch(u), q = lane & 3;
      const uint32_t i0 = o_idx(k, o_pos(b, wg, 2 * q));
      od1 = 2 * (int)(o_idx(k, o_pos(b, wg, 96 + 2 * q)) - i0);
      od2 = 2 * (int)(o_idx(k, o_pos(b, wg, 112 + 2 * q)) - i0);
      return reinterpret_cast<const char*>(P.o + i0);
    };
    auto unsafe = [&](bool valid) {
      const bool b = valid && ((chk & 0x7F80u) == 0x7F80u || (chk & 0x7F800000u) == 0x7F800000u);
      return __any_sync(~0u, bar_red_or(wg, b));
    };
    auto publish = [&]() { __syncwarp(); warp_arrive(sb + BAR_STAGE + 8 * wg); };

    uint32_t po[60];
#pragma unroll
    for (int i = 0; i < 60; i++) po[i] = 0;
    int id = 0;
    float o0[60], o1[60];
    ring_wait();
    mbar_wait(sb + BAR_XFULL + 32 * wg, 0);
    wg_fence();
    mma_tn(o0, o1, ring_addr(), qd, 0);
    wg_commit();
    while (true) {
      uint32_t prev = r.slot;
      r.next();
      auto qstep = [&](int s) {
        const uint32_t j = s & 3, par = ((s >> 2) + (j < 2 ? it : 0)) & 1;
        ring_wait();
        mbar_wait(sb + BAR_XFULL + 32 * wg + 8 * j, par);
        if (s >= ALT_FROM) turn_wait();
        wg_fence();
        mma_tn(o0, o1, ring_addr(), ((sb & 0x3FFFF) + OFF_Q + x_slot(wg, j)) >> 4, 1);
        wg_commit();
        if (s >= ALT_FROM || (s == ALT_FROM - 1 && wg == 1)) turn_pass();
        if (s <= 4) {
          wg_wait<1>();
          release(prev);
          warp_arrive_cl(xempty + 8 * ((s - 1) & 3));
        }
        prev = r.slot;
        r.next();
      };
      auto qdone = [&](int s) {
        wg_wait<0>();
        release(prev);
        if (s <= 5) warp_arrive_cl(xempty + 8 * (s & 3));
      };
      qstep(1);
      const int up = (it > 3 ? id : cl) + ((int)it - 1) * ncl;
      const char* optr = out_ptr(up);
      if (it == 0) optr = nullptr;
      uint32_t n7[8];
      {
        uint32_t iv[30];
        load_inv(iv, (it + 1) & 1); put(po, iv, optr, IC<0>());
        qstep(2); put(po, iv, optr, IC<1>());
        qstep(3); put(po, iv, optr, IC<2>());
        qstep(4); put(po, iv, optr, IC<3>()); qdone(4);
        qstep(5); put(po, iv, optr, IC<4>()); qdone(5);
        qstep(6); put(po, iv, optr, IC<5>()); qdone(6);
        qstep(7); put(po, iv, optr, IC<6>()); norm(n7, po, iv, IC<7>()); qdone(7);
      }
      ring_wait();
      mbar_wait(sb + BAR_XFULL + 32 * wg, it & 1);
      turn_wait();
      wg_fence();
      mma_tn(o0, o1, ring_addr(), qd, 1);
      wg_commit();
      prev = r.slot;
      r.next();
      ring_wait();
      mbar_wait(sb + BAR_XFULL + 32 * wg + 8, it & 1);
      wg_fence();
      mma_tn_split(o0, o1, ring_addr(), qd + (XB >> 4));
      turn_pass();
      wg_wait<2>();
      release(prev);
      auto put_q = [&](const float (&o)[60], uint32_t dst) {
#pragma unroll
        for (int j = 0; j < 14; j += 2)
          stsm4t(dst + j * 1024, pack(o[4 * j] * QSCALE, o[4 * j + 1] * QSCALE), pack(o[4 * j + 2] * QSCALE, o[4 * j + 3] * QSCALE),
                 pack(o[4 * j + 4] * QSCALE, o[4 * j + 5] * QSCALE), pack(o[4 * j + 6] * QSCALE, o[4 * j + 7] * QSCALE));
        stsm2t(dst + 14 * 1024, pack(o[56] * QSCALE, o[57] * QSCALE), pack(o[58] * QSCALE, o[59] * QSCALE));
      };
      wg_wait<1>();
      reg_fence(o0);
      const bool redo = unsafe(it > 0);
      put_q(o0, qreg + st_off);
      wg_wait<0>();
      reg_fence(o1);
      release(r.slot);
      r.next();
      bar_sync(wg);
      put_q(o1, qreg + XB + st_off);
      fence_async_smem();
      if (redo) {
        slow_path(P, unit_batch(up), unit_head(up, rank), wg, w, fresh_tid() & 31);
        optr = nullptr;
      }

      float sc[60], l[30];
      uint32_t slot0 = r.slot;
      ring_wait();
      turn_wait();
      wg_fence();
      mma_qk(sc, ring_addr(), qd);
      wg_commit();
      r.next();
      uint32_t slot1 = r.slot;
      ring_wait();
      wg_fence();
      mma_qk(o1, ring_addr(), qd);
      wg_commit();
      r.next();
      turn_pass();
      store(n7, optr, IC<7>());
      wg_wait<1>();
      reg_fence(sc);
      release(slot0);
      exp_store<0, 15, true>(sc, l, preg + st_off);
      slot0 = r.slot;
      ring_wait();
      wg_fence();
      mma_qk(sc, ring_addr(), qd);
      wg_commit();
      r.next();
      wg_wait<1>();
      reg_fence(o1);
      release(slot1);
      exp_store<0, 15>(o1, l, preg - 2 * XB + st_off);
      fence_async_smem();
      slot1 = r.slot;
      ring_wait();
      turn_wait();
      wg_fence();
      mma_tn(o0, o1, ring_addr(), pd, 0);
      wg_commit();
      r.next();
      ring_wait();
      wg_fence();
      mma_tn(o0, o1, ring_addr(), pd - (2 * XB >> 4), 1);
      wg_commit();
      turn_pass();
      if (it > 0) publish();
      id = __shfl_sync(~0u, it >= 2 ? role() : 0, 0);
      wg_wait<1>();
      reg_fence(sc);
      release(slot0);
      release(slot1);
      bar_sync(wg);
      exp_store<0, VREL>(sc, l, preg + st_off);
      wg_wait<0>();
      reg_fence(o0); reg_fence(o1);
      release(r.slot);
      r.next();
      exp_store<VREL, 15>(sc, l, preg + st_off);
      fence_async_smem();
      const bool more = id + ((int)it + 1) * ncl < NUNITS;
      const bool gemm = id < nsingle || (NCL == 66 && id >= 58);
#pragma unroll 1
      for (int s = 3; s < 16; s++) {
        const uint32_t kslot = r.slot;
        ring_wait();
        turn_wait();
        wg_fence();
        mma_qk(sc, ring_addr(), qd);
        wg_commit();
        r.next();
        ring_wait();
        wg_fence();
        mma_tn(o0, o1, ring_addr(), pd - ((s - 1) & 1) * (2 * XB >> 4), 1);
        wg_commit();
        if (wg == 0 || s < 15) turn_pass();
        wg_wait<1>();
        reg_fence(sc);
        release(kslot);
        if (s == 15) {
          if (more) { warp_arrive_cl(xempty); warp_arrive_cl(xempty + 8); }
          else if (gemm) for (int i = 0; i < 3; i++) warp_arrive_cl(mapa(sb + BAR_BEMPTY + 8 * i, i & 1));
        }
        exp_store<0, VREL>(sc, l, preg - (s & 1) * 2 * XB + st_off);
        wg_wait<0>();
        reg_fence(o0); reg_fence(o1);
        release(r.slot);
        r.next();
        exp_store<VREL, 15>(sc, l, preg - (s & 1) * 2 * XB + st_off);
        fence_async_smem();
      }
      const uint32_t tid = fresh_tid();
      bar_sync(wg);
      ring_wait();
      wg_fence();
      mma_tn_split(o0, o1, ring_addr(), pd - (2 * XB >> 4));
      sum_l(l, tid);
      const uint32_t vslot = r.slot;
      r.next();
      it++;
      auto pack_o = [&](const float (&o)[60], int first) {
#pragma unroll
        for (int j = 0; j < 15; j++) { po[first + j] = pack(o[4 * j], o[4 * j + 1]); po[first + 15 + j] = pack(o[4 * j + 2], o[4 * j + 3]); }
      };
      if (!more) {
        wg_wait<0>();
        reg_fence(o0); reg_fence(o1);
        release(vslot);
        if (gemm) for (int i = 3; i < 6; i++) warp_arrive_cl(mapa(sb + BAR_BEMPTY + 8 * i, i & 1));
        pack_o(o0, 0); pack_o(o1, 30);
        break;
      }
      ring_wait();
      mbar_wait(sb + BAR_XFULL + 32 * wg, it & 1);
      wg_wait<1>();
      reg_fence(o0);
      pack_o(o0, 0);
      wg_fence();
#pragma unroll
      for (int k = 0; k < 4; k++) wgmma_n120<1, 0>(o0, ring_addr() + k * 128, HI128, qd + k * 2, HI128, k != 0);
      wg_commit();
      wg_wait<1>();
      reg_fence(o1);
      pack_o(o1, 30);
      wg_fence();
#pragma unroll
      for (int k = 0; k < 4; k++) wgmma_n120<1, 0>(o1, ring_addr() + 512 + k * 128, HI128, qd + k * 2, HI128, k != 0);
      wg_commit();
      release(vslot);
      warp_arrive_cl(xempty + 16); warp_arrive_cl(xempty + 24);
    }
    const bool gemm = id < nsingle || (NCL == 66 && id >= 58);
    const int u = (it > 3 ? id : cl) + ((int)it - 1) * ncl;
    uint32_t pb[60];
#pragma unroll
    for (int i = 0; i < 60; i++) pb[i] = NCL != 66 ? po[i] ^ (gridDim.y - 1) : po[i];

    uint32_t bslot = 0, bphase = 0;
    auto out_row = [&](int lane) {
      const int row = lane & 15;
      return sb + wg * 8192 + (row < 12 ? w * RING_BYTES + row * 656 : (4 + (w >> 1)) * RING_BYTES + ((w & 1) * 4 + row - 12) * 656);
    };
    auto out_stage = [&](const float (&acc)[80], uint32_t col_off) {
      const int lane = fresh_tid() & 31;
      const uint32_t sa = out_row(lane) + col_off + (lane >> 4) * 16;
#pragma unroll
      for (int j = 0; j < 20; j += 2)
        asm volatile("stmatrix.sync.aligned.m8n8.x4.shared.b16 [%0], {%1,%2,%3,%4};" ::"r"(sa + j * 16), "r"(pack(acc[4 * j], acc[4 * j + 1])),
                     "r"(pack(acc[4 * j + 2], acc[4 * j + 3])), "r"(pack(acc[4 * j + 4], acc[4 * j + 5])), "r"(pack(acc[4 * j + 6], acc[4 * j + 7])) : "memory");
    };
    auto out_store = [&](int t, uint32_t bytes) {
      const int lane = fresh_tid() & 31;
      if (wg == 1) {
        __syncwarp();
#pragma unroll 1
        for (int h = 0; h < 2; h++) {
          const int row = h * 8 + (lane >> 2);
          const uint32_t src = out_row(row) + (lane & 3) * 16;
          char* dst = reinterpret_cast<char*>(P.out + (size_t)o_row(row_block(t) * 256 + rank * 128 + 64 + w * 16 + row) * DM + (t & 3) * 160) + (lane & 3) * 16;
#pragma unroll 1
          for (uint32_t c = 0; c < bytes; c += 320) {
            uint4 v[5];
#pragma unroll
            for (int i = 0; i < 5; i++)
              asm volatile("ld.shared.v4.u32 {%0, %1, %2, %3}, [%4];" : "=r"(v[i].x), "=r"(v[i].y), "=r"(v[i].z), "=r"(v[i].w) : "r"(src + c + i * 64) : "memory");
#pragma unroll
            for (int i = 0; i < 5; i++) *reinterpret_cast<uint4*>(dst + c + i * 64) = v[i];
          }
        }
        return;
      }
      fence_async_smem();
      __syncwarp();
      if (lane < 16) {
        __nv_bfloat16* dst = P.out + (size_t)o_row(row_block(t) * 256 + rank * 128 + wg * 64 + w * 16 + lane) * DM + (t & 3) * 160;
        asm volatile("cp.async.bulk.global.shared::cta.bulk_group [%0], [%1], %2;" ::"l"(dst), "r"(out_row(lane)), "r"(bytes) : "memory");
        asm volatile("cp.async.bulk.commit_group;" ::: "memory");
        asm volatile("cp.async.bulk.wait_group.read 0;" ::: "memory");
      }
    };
    for (int t = id; t == id || (NCL != 66 && t < nsingle); t += ncl) {
      float acc[80];
      uint32_t prev = 0, bprev = 0;
      const bool tile = t < nsingle;
      const bool last = NCL == 66 || t + ncl >= nsingle;
      auto bstep = [&](int ks, int accf) {
        ring_wait();
        mbar_wait(sb + BAR_BFULL + 8 * bslot, bphase);
        wg_fence();
        const uint32_t a = ring_addr() + wg * 512, bd = (((sb & 0x3FFFF) + OFF_Q + bslot * BB) >> 4) | ((4096u >> 4) << 16);
#pragma unroll
        for (int k = 0; k < 4; k++) wgmma_n160<1, 1>(acc, a + LBO64A + k * 128, HI64A, bd + k * 64, HI64, k == 0 ? accf : 1);
        wg_commit();
        if (ks > 0) {
          wg_wait<1>();
          release(prev);
          if (ks < 59 || !last) warp_arrive_cl(mapa(sb + BAR_BEMPTY + 8 * bprev, bprev & 1));
        }
        prev = r.slot; bprev = bslot;
        r.next();
        if (++bslot == 6) { bslot = 0; bphase ^= 1; }
      };
      const char* optr;
      uint32_t iv[30], n2[8], n3[8], n4[8], n5[8], n6[8], n7[8];
      if (tile) {
        bstep(0, 0);
        bstep(1, 1);
        optr = out_ptr(u);
        if (t != id) optr = nullptr;
        load_inv(iv, (it + 1) & 1);
#pragma unroll 1
        for (int ks = 2; ks < 17; ks++) {
          bstep(ks, 1);
          switch (ks) {
            case 2: put(pb, iv, optr, IC<0>()); break;
            case 4: put(pb, iv, optr, IC<1>()); break;
            case 6: put(pb, iv, optr, IC<2>()); break;
            case 8: put(pb, iv, optr, IC<3>()); break;
            case 10: put(pb, iv, optr, IC<4>()); break;
            case 12: put(pb, iv, optr, IC<5>()); break;
            case 14: put(pb, iv, optr, IC<6>()); break;
            case 16: put(pb, iv, optr, IC<7>()); break;
            default: break;
          }
        }
        wg_wait<0>();
        reg_fence(acc);
#pragma unroll
        for (int i = 0; i < 8; i++) n2[i] = n3[i] = n4[i] = n5[i] = n6[i] = n7[i] = 0;
      } else {
        Ring r2 = r;
        auto first = [&](int ks) {
          if (gemm) { mbar_wait(sb + BAR_RFULL + 8 * r2.slot, r2.phase); mbar_wait(sb + BAR_BFULL + 16 * ks, 0); }
          wg_fence();
          const uint32_t a = (((sb & 0x3FFFF) + r2.slot * RING_BYTES) >> 4) + wg * 512;
          const uint32_t bd = (((sb & 0x3FFFF) + OFF_Q + 2 * ks * BB) >> 4) | ((4096u >> 4) << 16);
#pragma unroll
          for (int k = 0; k < 4; k++) wgmma_n160<1, 1>(acc, a + LBO64A + k * 128, HI64A, bd + k * 64, HI64, k + ks != 0);
          wg_commit();
          r2.next();
        };
        first(0);
        first(1);
        optr = out_ptr(u);
        load_inv(iv, (it + 1) & 1);
        put(pb, iv, optr, IC<0>()); put(pb, iv, optr, IC<1>());
        norm(n2, pb, iv, IC<2>()); norm(n3, pb, iv, IC<3>()); norm(n4, pb, iv, IC<4>());
        norm(n5, pb, iv, IC<5>()); norm(n6, pb, iv, IC<6>()); norm(n7, pb, iv, IC<7>());
        wg_wait<0>();
        reg_fence(acc);
      }
      if (unsafe(t == id)) {
        slow_path(P, unit_batch(u), unit_head(u, rank), wg, w, fresh_tid() & 31);
        optr = nullptr;
#pragma unroll
        for (int i = 0; i < 8; i++) n2[i] = n3[i] = n4[i] = n5[i] = n6[i] = n7[i] = 0;
      }
      if (tile && t == id) publish();
      if (!tile && !gemm) {
        store(n2, optr, IC<2>()); store(n3, optr, IC<3>()); store(n4, optr, IC<4>()); store(n5, optr, IC<5>()); store(n6, optr, IC<6>()); store(n7, optr, IC<7>());
        publish();
        break;
      }
      if (!tile) {
        float ac1[80];
        auto half = [&](float (&ac)[80], bool rel, int accf) {
          mbar_wait(sb + BAR_BFULL + 8 * bslot, bphase);
          wg_fence();
          const uint32_t a = ring_addr() + wg * 512, bd = (((sb & 0x3FFFF) + OFF_Q + bslot * BB) >> 4) | ((4096u >> 4) << 16);
#pragma unroll
          for (int k = 0; k < 4; k++) wgmma_n160<1, 1>(ac, a + LBO64A + k * 128, HI64A, bd + k * 64, HI64, k == 0 ? accf : 1);
          wg_commit();
          wg_wait<1>();
          if (rel) warp_arrive_cl(mapa(sb + BAR_BEMPTY + 8 * bprev, bprev & 1));
          bprev = bslot;
        };
        auto dstep = [&](int ks) {
          ring_wait();
          half(acc, ks < 62, 1);
          release(prev);
          bslot++;
          half(ac1, ks < 61, 1);
          if (++bslot == 6) { bslot = 0; bphase ^= 1; }
          prev = r.slot; r.next();
        };
        warp_arrive_cl(mapa(sb + BAR_BEMPTY, 0));
        bprev = 2; bslot = 1;
        half(ac1, true, 0);
        prev = r.slot; r.next(); bslot = 3;
        half(ac1, true, 1);
        release(prev); prev = r.slot; r.next(); bslot = 4;
#pragma unroll 1
        for (int ks = 2; ks < 8; ks++) {
          dstep(ks);
          switch (ks) {
            case 2: store(n2, optr, IC<2>()); break;
            case 3: store(n3, optr, IC<3>()); break;
            case 4: store(n4, optr, IC<4>()); break;
            case 5: store(n5, optr, IC<5>()); break;
            case 6: store(n6, optr, IC<6>()); break;
            default: store(n7, optr, IC<7>()); break;
          }
        }
        publish();
#pragma unroll 1
        for (int ks = 8; ks < 64; ks++) {
          if (wg == 1 && ks == 62) turn_wait();
          dstep(ks);
        }
        if (wg == 0) turn_pass();
        wg_wait<0>();
        reg_fence(acc); reg_fence(ac1);
        bar_sync(wg);
        out_stage(ac1, 320);
      } else {
#pragma unroll 1
        for (int ks = 17; ks < 64; ks++) {
          if (wg == 1 && ks == 64 - END_SKEW) turn_wait();
          bstep(ks, 1);
        }
        if (wg == 0) turn_pass();
        wg_wait<0>();
        reg_fence(acc);
        release(prev);
        if (!last) warp_arrive_cl(mapa(sb + BAR_BEMPTY + 8 * bprev, bprev & 1));
      }
      const int pos0 = row_block(t) * 256 + rank * 128 + wg * 64 + w * 16;
      if (last) {
        bar_sync(wg);
        out_stage(acc, 0);
        out_store(tile ? t : 2 * id - 72, tile ? 320 : 640);
      } else {
        const int lane = fresh_tid() & 31;
        __nv_bfloat16* op0 = P.out + (size_t)o_row(pos0 + (lane >> 2)) * DM + (t & 3) * 160 + (lane & 3) * 2;
        __nv_bfloat16* op1 = P.out + (size_t)o_row(pos0 + (lane >> 2) + 8) * DM + (t & 3) * 160 + (lane & 3) * 2;
#pragma unroll
        for (int j = 0; j < 20; j++) {
          *reinterpret_cast<uint32_t*>(op0 + j * 8) = pack(acc[4 * j], acc[4 * j + 1]);
          *reinterpret_cast<uint32_t*>(op1 + j * 8) = pack(acc[4 * j + 2], acc[4 * j + 3]);
        }
      }
#pragma unroll
      for (int i = 0; i < 60; i++) pb[i] = 0;
    }
  }
}

typedef CUresult (*EncodeFn)(CUtensorMap*, CUtensorMapDataType, cuuint32_t, void*, const cuuint64_t*, const cuuint64_t*,
                             const cuuint32_t*, const cuuint32_t*, CUtensorMapInterleave, CUtensorMapSwizzle,
                             CUtensorMapL2promotion, CUtensorMapFloatOOBfill);

void make_map(EncodeFn enc, CUtensorMap* m, const void* p, int rank, const cuuint64_t* dims, const cuuint64_t* strides,
              const cuuint32_t* box, CUtensorMapSwizzle sw, CUtensorMapL2promotion promo) {
  cuuint32_t es[4] = {1, 1, 1, 1};
  enc(m, CU_TENSOR_MAP_DATA_TYPE_BFLOAT16, rank, const_cast<void*>(p), dims, strides, box, es, CU_TENSOR_MAP_INTERLEAVE_NONE, sw,
      promo, CU_TENSOR_MAP_FLOAT_OOB_FILL_NONE);
}

}

extern "C" void kernel_launch(void* const* d_in, const int* in_sizes, int n_in, void* d_out, int out_size) {
  static EncodeFn enc = nullptr;
  static int nclusters = 0;
  static void* o_ptr = nullptr;
  if (!enc) {
    cudaDriverEntryPointQueryResult qr;
    cudaGetDriverEntryPoint("cuTensorMapEncodeTiled", (void**)&enc, cudaEnableDefault, &qr);
    cudaFuncSetAttribute(fused_attn_kernel<66>, cudaFuncAttributeMaxDynamicSharedMemorySize, SMEM_BYTES);
    cudaFuncSetAttribute(fused_attn_kernel<0>, cudaFuncAttributeMaxDynamicSharedMemorySize, SMEM_BYTES);
    cudaGetSymbolAddress(&o_ptr, g_o);
    cudaLaunchConfig_t cfg = {};
    cfg.gridDim = 128; cfg.blockDim = 384; cfg.dynamicSmemBytes = SMEM_BYTES;
    cudaLaunchAttribute at; at.id = cudaLaunchAttributeClusterDimension;
    at.val.clusterDim.x = 2; at.val.clusterDim.y = 1; at.val.clusterDim.z = 1;
    cfg.attrs = &at; cfg.numAttrs = 1;
    int n = 0;
    cudaOccupancyMaxActiveClusters(&n, fused_attn_kernel<66>, &cfg);
    nclusters = n >= 66 ? MAXCL : (n >= 64 || n <= 0 ? 64 : n);
  }
  const __nv_bfloat16* x = (const __nv_bfloat16*)d_in[0];
  const __nv_bfloat16* k = (const __nv_bfloat16*)d_in[1];
  const __nv_bfloat16* v = (const __nv_bfloat16*)d_in[2];
  const __nv_bfloat16* wq = (const __nv_bfloat16*)d_in[3];
  const __nv_bfloat16* wo = (const __nv_bfloat16*)d_in[4];
  CUtensorMap tm_x, tm_wq, tm_k, tm_v, tm_o, tm_wo;
  const auto S128 = CU_TENSOR_MAP_SWIZZLE_128B;
  const auto P128 = CU_TENSOR_MAP_L2_PROMOTION_L2_128B, P256 = CU_TENSOR_MAP_L2_PROMOTION_L2_256B;
  { cuuint64_t d[2] = {DM, NB * SQ}, s[1] = {DM * 2}; cuuint32_t b[2] = {64, 120}; make_map(enc, &tm_x, x, 2, d, s, b, S128, P128); }
  { cuuint64_t d[3] = {64, DM, HD / 64}, s[2] = {HD * 2, 128}; cuuint32_t b[3] = {64, 64, 2}; make_map(enc, &tm_wq, wq, 3, d, s, b, S128, P256); }
  { cuuint64_t d[3] = {64, NB * NH * SK, 2}, s[2] = {DH * 2, 128}; cuuint32_t b[3] = {64, 64, 2};
    make_map(enc, &tm_k, k, 3, d, s, b, S128, P128); make_map(enc, &tm_v, v, 3, d, s, b, S128, P128); }
  { cuuint64_t d[4] = {256, 2, HD / 8, NROWS / 64}, s[3] = {512, NROWS * 16, 1024}; cuuint32_t b[4] = {256, 2, 8, 2};
    make_map(enc, &tm_o, o_ptr, 4, d, s, b, CU_TENSOR_MAP_SWIZZLE_NONE, P256); }
  { cuuint64_t d[3] = {32, HD, DM / 32}, s[2] = {DM * 2, 64}; cuuint32_t b[3] = {32, 64, 5};
    make_map(enc, &tm_wo, wo, 3, d, s, b, CU_TENSOR_MAP_SWIZZLE_64B, P128); }
  Params P{x, k, v, wq, (__nv_bfloat16*)d_out, (__nv_bfloat16*)o_ptr};
  if (nclusters == 66) fused_attn_kernel<66><<<132, 384, SMEM_BYTES>>>(tm_x, tm_wq, tm_k, tm_v, tm_o, tm_wo, P);
  else fused_attn_kernel<0><<<2 * nclusters, 384, SMEM_BYTES>>>(tm_x, tm_wq, tm_k, tm_v, tm_o, tm_wo, P);
}
```

```cpp
#include <cuda_runtime.h>
#include <cuda.h>
#include <cuda_bf16.h>
#include <stdint.h>

namespace {

constexpr int NB = 16, SQ = 240, DM = 640, NH = 32, SK = 1024, DH = 128, HD = NH * DH;
constexpr int NROWS = NB * SQ;
constexpr int NUNITS = 256;
#define ALT_FROM 4
#define END_SKEW 5
#define VREL 8
#define PF_N 4
#define PF_J0 3
#define PF_STEP 3
#define WO_PF 6
#define PAUSE_NS 11000
#define SMID_TOP 88
#define MAXCL 66
constexpr int NOTILES = 60;
constexpr float QSCALE = 0.08838834764831845f * 1.4426950408889634f;
constexpr float L_MIN = 1.f;
constexpr float L_MAX = 1.152921504606846976e18f;

constexpr uint32_t RING_SLOTS = 6, RING_BYTES = 16384;
constexpr uint32_t XB = 15360;
constexpr uint32_t BB = 20480;
constexpr uint32_t OFF_Q = RING_SLOTS * RING_BYTES;
constexpr uint32_t OFF_P = OFF_Q + 4 * XB;
constexpr uint32_t OFF_INV = OFF_P + 4 * XB;
constexpr uint32_t OFF_L2 = OFF_INV + 1280;
constexpr uint32_t OFF_BAR = OFF_L2 + 4096;
constexpr uint32_t BAR_RFULL = OFF_BAR, BAR_REMPTY = BAR_RFULL + 48, BAR_XFULL = BAR_REMPTY + 48,
    BAR_XEMPTY = BAR_XFULL + 64, BAR_BFULL = BAR_XEMPTY + 32, BAR_BEMPTY = BAR_BFULL + 48, BAR_STAGE = BAR_BEMPTY + 48;
constexpr uint32_t BAR_ROLE = BAR_STAGE + 16, BAR_LSUM = BAR_ROLE + 24, BAR_INV = BAR_LSUM + 16;
constexpr uint32_t OFF_TR = BAR_INV + 16;
constexpr uint32_t SMEM_BYTES = OFF_TR + 1024;

constexpr uint32_t HI128 = (1u << 30) | (1024 >> 4);
constexpr uint32_t HI64 = (2u << 30) | (512 >> 4);
constexpr uint32_t HI64A = (2u << 30) | (1024 >> 4), LBO64A = (512u >> 4) << 16;

__device__ __align__(1024) __nv_bfloat16 g_o[HD * NROWS];
__device__ __align__(128) unsigned g_cnt[67 * 8];

struct Params {
  const __nv_bfloat16 *x, *k, *v, *wq;
  __nv_bfloat16 *out, *o;
};

__device__ __forceinline__ void wg_fence() { asm volatile("wgmma.fence.sync.aligned;" ::: "memory"); }
__device__ __forceinline__ void wg_commit() { asm volatile("wgmma.commit_group.sync.aligned;" ::: "memory"); }
template <int N> __device__ __forceinline__ void wg_wait() { asm volatile("wgmma.wait_group.sync.aligned %0;" ::"n"(N) : "memory"); }
template <int N> __device__ __forceinline__ void reg_fence(float (&r)[N]) {
#pragma unroll
  for (int i = 0; i < N; i++) asm volatile("" : "+f"(r[i])::"memory");
}
template <int TA, int TB>
__device__ __forceinline__ void wgmma_n120(float (&d)[60], uint32_t a_lo, uint32_t a_hi, uint32_t b_lo, uint32_t b_hi, int acc) {
  asm volatile(
      "{\n.reg .pred p;\n.reg .b64 da, db;\nsetp.ne.b32 p, %64, 0;\n"
      "mov.b64 da, {%60, %61};\nmov.b64 db, {%62, %63};\n"
      "wgmma.mma_async.sync.aligned.m64n120k16.f32.bf16.bf16 {"
      "%0, %1, %2, %3, %4, %5, %6, %7, %8, %9, %10, %11, %12, %13, %14, %15, %16, %17, %18, %19, %20, %21, %22, %23, "
      "%24, %25, %26, %27, %28, %29, %30, %31, %32, %33, %34, %35, %36, %37, %38, %39, %40, %41, %42, %43, %44, %45, "
      "%46, %47, %48, %49, %50, %51, %52, %53, %54, %55, %56, %57, %58, %59"
      "}, da, db, p, 1, 1, %65, %66;\n}\n"
      : "+f"(d[0]), "+f"(d[1]), "+f"(d[2]), "+f"(d[3]), "+f"(d[4]), "+f"(d[5]), "+f"(d[6]), "+f"(d[7]), "+f"(d[8]),
        "+f"(d[9]), "+f"(d[10]), "+f"(d[11]), "+f"(d[12]), "+f"(d[13]), "+f"(d[14]), "+f"(d[15]), "+f"(d[16]),
        "+f"(d[17]), "+f"(d[18]), "+f"(d[19]), "+f"(d[20]), "+f"(d[21]), "+f"(d[22]), "+f"(d[23]), "+f"(d[24]),
        "+f"(d[25]), "+f"(d[26]), "+f"(d[27]), "+f"(d[28]), "+f"(d[29]), "+f"(d[30]), "+f"(d[31]), "+f"(d[32]),
        "+f"(d[33]), "+f"(d[34]), "+f"(d[35]), "+f"(d[36]), "+f"(d[37]), "+f"(d[38]), "+f"(d[39]), "+f"(d[40]),
        "+f"(d[41]), "+f"(d[42]), "+f"(d[43]), "+f"(d[44]), "+f"(d[45]), "+f"(d[46]), "+f"(d[47]), "+f"(d[48]),
        "+f"(d[49]), "+f"(d[50]), "+f"(d[51]), "+f"(d[52]), "+f"(d[53]), "+f"(d[54]), "+f"(d[55]), "+f"(d[56]),
        "+f"(d[57]), "+f"(d[58]), "+f"(d[59])
      : "r"(a_lo), "r"(a_hi), "r"(b_lo), "r"(b_hi), "r"(acc), "n"(TA), "n"(TB));
}

template <int TA, int TB>
__device__ __forceinline__ void wgmma_n160(float (&d)[80], uint32_t a_lo, uint32_t a_hi, uint32_t b_lo, uint32_t b_hi, int acc) {
  asm volatile(
      "{\n.reg .pred p;\n.reg .b64 da, db;\nsetp.ne.b32 p, %84, 0;\n"
      "mov.b64 da, {%80, %81};\nmov.b64 db, {%82, %83};\n"
      "wgmma.mma_async.sync.aligned.m64n160k16.f32.bf16.bf16 {"
      "%0, %1, %2, %3, %4, %5, %6, %7, %8, %9, %10, %11, %12, %13, %14, %15, %16, %17, %18, %19, %20, %21, %22, %23, "
      "%24, %25, %26, %27, %28, %29, %30, %31, %32, %33, %34, %35, %36, %37, %38, %39, %40, %41, %42, %43, %44, %45, "
      "%46, %47, %48, %49, %50, %51, %52, %53, %54, %55, %56, %57, %58, %59, %60, %61, %62, %63, %64, %65, %66, %67, "
      "%68, %69, %70, %71, %72, %73, %74, %75, %76, %77, %78, %79"
      "}, da, db, p, 1, 1, %85, %86;\n}\n"
      : "+f"(d[0]), "+f"(d[1]), "+f"(d[2]), "+f"(d[3]), "+f"(d[4]), "+f"(d[5]), "+f"(d[6]), "+f"(d[7]), "+f"(d[8]),
        "+f"(d[9]), "+f"(d[10]), "+f"(d[11]), "+f"(d[12]), "+f"(d[13]), "+f"(d[14]), "+f"(d[15]), "+f"(d[16]),
        "+f"(d[17]), "+f"(d[18]), "+f"(d[19]), "+f"(d[20]), "+f"(d[21]), "+f"(d[22]), "+f"(d[23]), "+f"(d[24]),
        "+f"(d[25]), "+f"(d[26]), "+f"(d[27]), "+f"(d[28]), "+f"(d[29]), "+f"(d[30]), "+f"(d[31]), "+f"(d[32]),
        "+f"(d[33]), "+f"(d[34]), "+f"(d[35]), "+f"(d[36]), "+f"(d[37]), "+f"(d[38]), "+f"(d[39]), "+f"(d[40]),
        "+f"(d[41]), "+f"(d[42]), "+f"(d[43]), "+f"(d[44]), "+f"(d[45]), "+f"(d[46]), "+f"(d[47]), "+f"(d[48]),
        "+f"(d[49]), "+f"(d[50]), "+f"(d[51]), "+f"(d[52]), "+f"(d[53]), "+f"(d[54]), "+f"(d[55]), "+f"(d[56]),
        "+f"(d[57]), "+f"(d[58]), "+f"(d[59]), "+f"(d[60]), "+f"(d[61]), "+f"(d[62]), "+f"(d[63]), "+f"(d[64]),
        "+f"(d[65]), "+f"(d[66]), "+f"(d[67]), "+f"(d[68]), "+f"(d[69]), "+f"(d[70]), "+f"(d[71]), "+f"(d[72]),
        "+f"(d[73]), "+f"(d[74]), "+f"(d[75]), "+f"(d[76]), "+f"(d[77]), "+f"(d[78]), "+f"(d[79])
      : "r"(a_lo), "r"(a_hi), "r"(b_lo), "r"(b_hi), "r"(acc), "n"(TA), "n"(TB));
}
__device__ __forceinline__ void mbar_init(uint32_t bar, int cnt) { asm volatile("mbarrier.init.shared::cta.b64 [%0], %1;" ::"r"(bar), "r"(cnt)); }
__device__ __forceinline__ void mbar_expect(uint32_t bar, uint32_t bytes) {
  asm volatile("mbarrier.arrive.expect_tx.shared::cta.b64 _, [%0], %1;" ::"r"(bar), "r"(bytes) : "memory");
}
__device__ __forceinline__ uint32_t mapa(uint32_t addr, uint32_t cta) {
  uint32_t r; asm("mapa.shared::cluster.u32 %0, %1, %2;" : "=r"(r) : "r"(addr), "r"(cta)); return r;
}
__device__ __forceinline__ void mbar_expect_cl(uint32_t cbar, uint32_t bytes) {
  asm volatile("mbarrier.arrive.expect_tx.shared::cluster.b64 _, [%0], %1;" ::"r"(cbar), "r"(bytes) : "memory");
}
__device__ __forceinline__ void mbar_arrive(uint32_t bar) { asm volatile("mbarrier.arrive.shared::cta.b64 _, [%0];" ::"r"(bar) : "memory"); }
__device__ __forceinline__ void mbar_arrive_cl(uint32_t cbar) { asm volatile("mbarrier.arrive.shared::cluster.b64 _, [%0];" ::"r"(cbar) : "memory"); }
__device__ __forceinline__ void warp_arrive(uint32_t bar) {
  asm volatile("{\n.reg .pred p;\nelect.sync _|p, 0xffffffff;\n@p mbarrier.arrive.shared::cta.b64 _, [%0];\n}\n" ::"r"(bar) : "memory");
}
__device__ __forceinline__ void warp_arrive_cl(uint32_t cbar) {
  asm volatile("{\n.reg .pred p;\nelect.sync _|p, 0xffffffff;\n@p mbarrier.arrive.shared::cluster.b64 _, [%0];\n}\n" ::"r"(cbar) : "memory");
}
__device__ __forceinline__ void mbar_wait(uint32_t bar, uint32_t parity) {
  asm volatile(
      "{\n.reg .pred p;\n.reg .u32 n;\n"
      "mbarrier.try_wait.parity.shared::cta.b64 p, [%0], %1;\n@p bra WAIT_DONE;\n"
      "mov.u32 n, 0;\n"
      "WAIT_LOOP:\n"
      "mbarrier.try_wait.parity.shared::cta.b64 p, [%0], %1;\n@p bra WAIT_DONE;\n"
      "add.u32 n, n, 1;\nsetp.lt.u32 p, n, 0x4000000;\n@p bra WAIT_LOOP;\ntrap;\n"
      "WAIT_DONE:\n}\n" ::"r"(bar), "r"(parity) : "memory");
}
__device__ __forceinline__ void mbar_sleep(uint32_t bar, uint32_t parity) {
  asm volatile(
      "{\n.reg .pred p;\n.reg .u32 n;\nmov.u32 n, 0;\n"
      "WAIT_LOOP:\n"
      "mbarrier.try_wait.parity.shared::cta.b64 p, [%0], %1, 4000;\n@p bra WAIT_DONE;\n"
      "add.u32 n, n, 1;\nsetp.lt.u32 p, n, 0x400000;\n@p bra WAIT_LOOP;\ntrap;\n"
      "WAIT_DONE:\n}\n" ::"r"(bar), "r"(parity) : "memory");
}
__device__ __forceinline__ void mbar_wait_cl(uint32_t bar, uint32_t parity) {
  asm volatile(
      "{\n.reg .pred p;\n.reg .u32 n;\nmov.u32 n, 0;\n"
      "WAIT_LOOP:\n"
      "mbarrier.try_wait.parity.acquire.cluster.shared::cta.b64 p, [%0], %1;\n@p bra WAIT_DONE;\n"
      "add.u32 n, n, 1;\nsetp.lt.u32 p, n, 0x4000000;\n@p bra WAIT_LOOP;\ntrap;\n"
      "WAIT_DONE:\n}\n" ::"r"(bar), "r"(parity) : "memory");
}
__device__ __forceinline__ void tma3d(uint32_t dst, const CUtensorMap* m, int c0, int c1, int c2, uint32_t bar) {
  asm volatile("cp.async.bulk.tensor.3d.shared::cluster.global.mbarrier::complete_tx::bytes [%0], [%1, {%3, %4, %5}], [%2];"
               ::"r"(dst), "l"(m), "r"(bar), "r"(c0), "r"(c1), "r"(c2) : "memory");
}
__device__ __forceinline__ void tma3d_hint(uint32_t dst, const CUtensorMap* m, int c0, int c1, int c2, uint32_t bar, uint64_t pol) {
  asm volatile("cp.async.bulk.tensor.3d.shared::cluster.global.mbarrier::complete_tx::bytes.L2::cache_hint [%0], [%1, {%3, %4, %5}], [%2], %6;"
               ::"r"(dst), "l"(m), "r"(bar), "r"(c0), "r"(c1), "r"(c2), "l"(pol) : "memory");
}
__device__ __forceinline__ void tma2d_mc(uint32_t dst, const CUtensorMap* m, int c0, int c1, uint32_t bar) {
  asm volatile("cp.async.bulk.tensor.2d.shared::cluster.global.mbarrier::complete_tx::bytes.multicast::cluster [%0], [%1, {%3, %4}], [%2], %5;"
               ::"r"(dst), "l"(m), "r"(bar), "r"(c0), "r"(c1), "h"((uint16_t)3) : "memory");
}
__device__ __forceinline__ void tma3d_mc(uint32_t dst, const CUtensorMap* m, int c0, int c1, int c2, uint32_t bar) {
  asm volatile("cp.async.bulk.tensor.3d.shared::cluster.global.mbarrier::complete_tx::bytes.multicast::cluster [%0], [%1, {%3, %4, %5}], [%2], %6;"
               ::"r"(dst), "l"(m), "r"(bar), "r"(c0), "r"(c1), "r"(c2), "h"((uint16_t)3) : "memory");
}
__device__ __forceinline__ void l2_prefetch(const void* p, uint32_t bytes) {
  asm volatile("cp.async.bulk.prefetch.L2.global [%0], %1;" ::"l"(p), "r"(bytes) : "memory");
}
__device__ __forceinline__ void fence_async_smem() { asm volatile("fence.proxy.async.shared::cta;" ::: "memory"); }
__device__ __forceinline__ void bar_sync(int wg) {
  if (wg == 0) asm volatile("bar.sync 1, 128;" ::: "memory");
  else asm volatile("bar.sync 2, 128;" ::: "memory");
}
__device__ __forceinline__ bool bar_red_or(int id, bool v) {
  uint32_t r;
  asm volatile("{\n.reg .pred p, q;\nsetp.ne.u32 p, %2, 0;\nbar.red.or.pred q, %1, 128, p;\nselp.u32 %0, 1, 0, q;\n}\n"
               : "=r"(r) : "r"(1 + id), "r"((uint32_t)v) : "memory");
  return r != 0;
}
__device__ __forceinline__ uint32_t hfma2(uint32_t a, uint32_t b, uint32_t c) { uint32_t r; asm("fma.rn.bf16x2 %0, %1, %2, %3;" : "=r"(r) : "r"(a), "r"(b), "r"(c)); return r; }
__device__ __forceinline__ float ex2(float x) { float y; asm("ex2.approx.ftz.f32 %0, %1;" : "=f"(y) : "f"(x)); return y; }
__device__ __forceinline__ uint32_t pack(float lo, float hi) { uint32_t r; asm("cvt.rn.bf16x2.f32 %0, %1, %2;" : "=r"(r) : "f"(hi), "f"(lo)); return r; }
__device__ __forceinline__ void stsm4t(uint32_t a, uint32_t r0, uint32_t r1, uint32_t r2, uint32_t r3) {
  asm volatile("stmatrix.sync.aligned.m8n8.x4.trans.shared.b16 [%0], {%1,%2,%3,%4};" ::"r"(a), "r"(r0), "r"(r1), "r"(r2), "r"(r3) : "memory");
}
__device__ __forceinline__ void stsm2t(uint32_t a, uint32_t r0, uint32_t r1) {
  asm volatile("stmatrix.sync.aligned.m8n8.x2.trans.shared.b16 [%0], {%1,%2};" ::"r"(a), "r"(r0), "r"(r1) : "memory");
}
__device__ __forceinline__ void mma16816(float (&d)[4], const uint32_t (&a)[4], uint32_t b0, uint32_t b1) {
  asm volatile("mma.sync.aligned.m16n8k16.row.col.f32.bf16.bf16.f32 {%0,%1,%2,%3}, {%4,%5,%6,%7}, {%8,%9}, {%0,%1,%2,%3};"
               : "+f"(d[0]), "+f"(d[1]), "+f"(d[2]), "+f"(d[3]) : "r"(a[0]), "r"(a[1]), "r"(a[2]), "r"(a[3]), "r"(b0), "r"(b1));
}

__device__ __forceinline__ uint32_t fresh_tid() { uint32_t t; asm volatile("mov.u32 %0, %tid.x;" : "=r"(t)); return t; }

template <int V> struct IC { static constexpr int value = V; };

struct Ring {
  uint32_t slot = 0, phase = 0;
  __device__ __forceinline__ void next() { if (++slot == RING_SLOTS) { slot = 0; phase ^= 1; } }
};

__device__ __forceinline__ void mma_tn(float (&o0)[60], float (&o1)[60], uint32_t a, uint32_t b, int acc) {
#pragma unroll
  for (int k = 0; k < 4; k++) {
    wgmma_n120<1, 0>(o0, a + k * 128, HI128, b + k * 2, HI128, k == 0 ? acc : 1);
    wgmma_n120<1, 0>(o1, a + 512 + k * 128, HI128, b + k * 2, HI128, k == 0 ? acc : 1);
  }
}
__device__ __forceinline__ void mma_tn_split(float (&o0)[60], float (&o1)[60], uint32_t a, uint32_t b) {
#pragma unroll
  for (int k = 0; k < 4; k++) wgmma_n120<1, 0>(o0, a + k * 128, HI128, b + k * 2, HI128, 1);
  wg_commit();
#pragma unroll
  for (int k = 0; k < 4; k++) wgmma_n120<1, 0>(o1, a + 512 + k * 128, HI128, b + k * 2, HI128, 1);
  wg_commit();
}
__device__ __forceinline__ void mma_qk(float (&s)[60], uint32_t a, uint32_t q) {
#pragma unroll
  for (int k = 0; k < 8; k++)
    wgmma_n120<0, 0>(s, a + (k >> 2) * 512 + (k & 3) * 2, HI128, q + (k >> 2) * (XB >> 4) + (k & 3) * 2, HI128, k != 0);
}
template <int J0, int J1, bool FIRST = false>
__device__ __forceinline__ void exp_store(const float (&s)[60], float (&l)[30], uint32_t dst) {
#pragma unroll
  for (int c = J0; c < J1; c++) {
    const float e0 = ex2(s[4 * c]), e1 = ex2(s[4 * c + 1]), e2 = ex2(s[4 * c + 2]), e3 = ex2(s[4 * c + 3]);
    if (FIRST) { l[2 * c] = e0 + e2; l[2 * c + 1] = e1 + e3; }
    else { l[2 * c] += e0; l[2 * c + 1] += e1; l[2 * c] += e2; l[2 * c + 1] += e3; }
    stsm2t(dst + c * 1024, pack(e0, e1), pack(e2, e3));
  }
}

__device__ __forceinline__ int o_pos(int b, int wg, int r) {
  const int j = r >> 3, q = (r >> 1) & 3, c = r & 1, o = b & 1, base = (b >> 1) * 480;
  if (j < 12) return base + (o * 9 + wg * 3 + (j >> 2)) * 32 + q * 8 + (j & 3) * 2 + c;
  if (j < 14) return base + (6 + 2 * o) * 32 + wg * 16 + q * 4 + (j - 12) * 2 + c;
  return base + 7 * 32 + (o * 2 + wg) * 8 + q * 2 + c;
}
__device__ __forceinline__ int o_row(int p) {
  const int pair = p / 480, a = (p - pair * 480) >> 5, in = p & 31, c = p & 1;
  int tile, row;
  if (a == 7) { tile = in >> 3; row = 112 + (in & 7); }
  else if (a == 6 || a == 8) { tile = a - 6 + (in >> 4); row = (12 + ((in >> 1) & 1)) * 8 + ((in >> 2) & 3) * 2 + c; }
  else { const int f = a > 8 ? a - 3 : a; tile = f / 3; row = ((f - tile * 3) * 4 + ((in >> 1) & 3)) * 8 + (in >> 3) * 2 + c; }
  return pair * 480 + tile * 120 + row;
}
__device__ __forceinline__ uint32_t o_idx(int k, int p) {
  return ((k >> 3) * (NROWS / 32) + (p >> 5)) * 256 + (k & 7) * 32 + ((((p >> 3) & 3) ^ ((k & 7) >> 1)) << 3) + (p & 7);
}

__device__ __forceinline__ void slow_path(const Params& P, int b, int h, int wg, int w, int lane) {
  const int g = lane >> 2, q = lane & 3, row0 = wg * 120;
  const uint16_t* wq = reinterpret_cast<const uint16_t*>(P.wq) + h * DH + g;
  const __nv_bfloat16* kp = P.k + (size_t)(b * NH + h) * SK * DH;
  const uint16_t* vp = reinterpret_cast<const uint16_t*>(P.v) + (size_t)(b * NH + h) * SK * DH + g;
#pragma unroll 1
  for (int t = w; t < 8; t += 4) {
    const int r0 = 16 * t + g, r1 = r0 + 8;
    const __nv_bfloat16* x0 = P.x + (size_t)(b * SQ + row0 + r0) * DM + 2 * q;
    const __nv_bfloat16* x1 = P.x + (size_t)(b * SQ + row0 + min(r1, 119)) * DM + 2 * q;
    float o[16][4];
#pragma unroll
    for (int n = 0; n < 16; n++) o[n][0] = o[n][1] = o[n][2] = o[n][3] = 0.f;
#pragma unroll 1
    for (int k0 = 0; k0 < DM; k0 += 16) {
      uint32_t a[4] = {*(const uint32_t*)(x0 + k0), *(const uint32_t*)(x1 + k0), *(const uint32_t*)(x0 + k0 + 8), *(const uint32_t*)(x1 + k0 + 8)};
      const uint16_t* wr = wq + (size_t)(k0 + 2 * q) * HD;
#pragma unroll
      for (int n = 0; n < 16; n++) {
        if ((n & 3) == 0) __syncwarp();
        mma16816(o[n], a, wr[8 * n] | ((uint32_t)wr[8 * n + HD] << 16), wr[8 * n + 8 * HD] | ((uint32_t)wr[8 * n + 9 * HD] << 16));
      }
    }
    uint32_t qa[8][4];
#pragma unroll
    for (int k = 0; k < 8; k++) {
      qa[k][0] = pack(o[2 * k][0] * QSCALE, o[2 * k][1] * QSCALE);
      qa[k][1] = pack(o[2 * k][2] * QSCALE, o[2 * k][3] * QSCALE);
      qa[k][2] = pack(o[2 * k + 1][0] * QSCALE, o[2 * k + 1][1] * QSCALE);
      qa[k][3] = pack(o[2 * k + 1][2] * QSCALE, o[2 * k + 1][3] * QSCALE);
    }
#pragma unroll
    for (int n = 0; n < 16; n++) o[n][0] = o[n][1] = o[n][2] = o[n][3] = 0.f;
    float m0 = -INFINITY, m1 = -INFINITY, l0 = 0.f, l1 = 0.f;
#pragma unroll 1
    for (int key0 = 0; key0 < SK; key0 += 16) {
      float s[2][4];
#pragma unroll
      for (int nt = 0; nt < 2; nt++) {
        s[nt][0] = s[nt][1] = s[nt][2] = s[nt][3] = 0.f;
        const __nv_bfloat16* kr = kp + (size_t)(key0 + 8 * nt + g) * DH + 2 * q;
#pragma unroll
        for (int k = 0; k < 8; k++) mma16816(s[nt], qa[k], *(const uint32_t*)(kr + 16 * k), *(const uint32_t*)(kr + 16 * k + 8));
      }
      float n0 = fmaxf(fmaxf(s[0][0], s[0][1]), fmaxf(s[1][0], s[1][1])), n1 = fmaxf(fmaxf(s[0][2], s[0][3]), fmaxf(s[1][2], s[1][3]));
      n0 = fmaxf(n0, __shfl_xor_sync(~0u, n0, 1)); n1 = fmaxf(n1, __shfl_xor_sync(~0u, n1, 1));
      n0 = fmaxf(n0, __shfl_xor_sync(~0u, n0, 2)); n1 = fmaxf(n1, __shfl_xor_sync(~0u, n1, 2));
      n0 = fmaxf(n0, m0); n1 = fmaxf(n1, m1);
      const float z0 = n0 == -INFINITY ? 0.f : n0, z1 = n1 == -INFINITY ? 0.f : n1;
      const float c0 = ex2(m0 - z0), c1 = ex2(m1 - z1);
      m0 = n0; m1 = n1;
#pragma unroll
      for (int nt = 0; nt < 2; nt++) {
        s[nt][0] = ex2(s[nt][0] - z0); s[nt][1] = ex2(s[nt][1] - z0);
        s[nt][2] = ex2(s[nt][2] - z1); s[nt][3] = ex2(s[nt][3] - z1);
      }
      l0 = l0 * c0 + s[0][0] + s[0][1] + s[1][0] + s[1][1];
      l1 = l1 * c1 + s[0][2] + s[0][3] + s[1][2] + s[1][3];
      uint32_t pa[4] = {pack(s[0][0], s[0][1]), pack(s[0][2], s[0][3]), pack(s[1][0], s[1][1]), pack(s[1][2], s[1][3])};
      const uint16_t* vr = vp + (size_t)(key0 + 2 * q) * DH;
#pragma unroll
      for (int n = 0; n < 16; n++) {
        if ((n & 3) == 0) __syncwarp();
        o[n][0] *= c0; o[n][1] *= c0; o[n][2] *= c1; o[n][3] *= c1;
        mma16816(o[n], pa, vr[8 * n] | ((uint32_t)vr[8 * n + DH] << 16), vr[8 * n + 8 * DH] | ((uint32_t)vr[8 * n + 9 * DH] << 16));
      }
    }
    l0 += __shfl_xor_sync(~0u, l0, 1); l1 += __shfl_xor_sync(~0u, l1, 1);
    l0 += __shfl_xor_sync(~0u, l0, 2); l1 += __shfl_xor_sync(~0u, l1, 2);
    const float i0 = 1.f / l0, i1 = 1.f / l1;
    __nv_bfloat16* oc0 = P.o + o_idx(h * DH + 2 * q, o_pos(b, wg, r0));
    __nv_bfloat16* oc1 = P.o + o_idx(h * DH + 2 * q, o_pos(b, wg, min(r1, 119)));
#pragma unroll
    for (int n = 0; n < 16; n++) {
      oc0[8 * n * NROWS] = __float2bfloat16(o[n][0] * i0);
      oc0[8 * n * NROWS + 32] = __float2bfloat16(o[n][1] * i0);
      if (r1 < 120) {
        oc1[8 * n * NROWS] = __float2bfloat16(o[n][2] * i1);
        oc1[8 * n * NROWS + 32] = __float2bfloat16(o[n][3] * i1);
      }
    }
  }
}

__device__ __forceinline__ int bk(int ks) { return ks < 48 ? 32 - (ks & 48) + (ks & 15) : ks; }
__device__ __forceinline__ uint32_t x_slot(uint32_t wg, uint32_t j) { return j < 2 ? (2 * wg + j) * XB : (2 * j + wg) * XB; }
__device__ __forceinline__ int row_block(int t) { return t >= 44 ? (t >> 2) - 11 : (t >> 2) + 4; }
__device__ __forceinline__ int unit_batch(int u) { return (u & 63) >> 2; }
__device__ __forceinline__ int unit_head(int u, int rank) { return (u >> 6) * 8 + (u & 3) * 2 + rank; }

template <int NCL>
__global__ void __cluster_dims__(2, 1, 1) __launch_bounds__(384, 1)
fused_attn_kernel(const __grid_constant__ CUtensorMap tm_x, const __grid_constant__ CUtensorMap tm_wq,
                  const __grid_constant__ CUtensorMap tm_k, const __grid_constant__ CUtensorMap tm_v,
                  const __grid_constant__ CUtensorMap tm_o, const __grid_constant__ CUtensorMap tm_wo,
                  const __grid_constant__ Params P) {
  extern __shared__ uint8_t smem_raw[];
  const uint32_t sb = ((uint32_t)__cvta_generic_to_shared(smem_raw) + 1023) & ~1023u;
  const int warp = __shfl_sync(~0u, threadIdx.x >> 5, 0);
  const int lane = threadIdx.x & 31;
  const int rank = blockIdx.x & 1, cl = blockIdx.x >> 1, ncl = NCL ? NCL : gridDim.x >> 1;

  const int nsingle = NCL == 66 ? 44 : NOTILES;
  auto role = [&]() {
    mbar_wait(sb + BAR_ROLE + 16, 0);
    int id;
    asm volatile("ld.shared.u32 %0, [%1];" : "=r"(id) : "r"(sb + BAR_ROLE + 8) : "memory");
    return id;
  };

  if (threadIdx.x == 128) asm volatile("prefetch.tensormap [%0];" ::"l"(&tm_x) : "memory");
  if (threadIdx.x == 0) {
    asm volatile("prefetch.tensormap [%0];" ::"l"(&tm_wq) : "memory");
    for (int i = 0; i < 6; i++) {
      mbar_init(sb + BAR_RFULL + 8 * i, 1); mbar_init(sb + BAR_REMPTY + 8 * i, 8);
      mbar_init(sb + BAR_BFULL + 8 * i, 1); mbar_init(sb + BAR_BEMPTY + 8 * i, 16);
    }
    for (int i = 0; i < 8; i++) mbar_init(sb + BAR_XFULL + 8 * i, 1);
    for (int i = 0; i < 4; i++) mbar_init(sb + BAR_XEMPTY + 8 * i, 8);
    for (int i = 0; i < 2; i++) { mbar_init(sb + BAR_STAGE + 8 * i, 4); mbar_init(sb + BAR_LSUM + 8 * i, 4); mbar_init(sb + BAR_INV + 8 * i, 1); }
    mbar_init(sb + BAR_ROLE, 1); mbar_init(sb + BAR_ROLE + 16, 1);
    asm volatile("fence.mbarrier_init.release.cluster;" ::: "memory");
  }
  __syncwarp();
  asm volatile("barrier.cluster.arrive.relaxed.aligned;" ::: "memory");
  auto first_w = [&](int s) {
    mbar_expect(sb + BAR_RFULL + 8 * s, RING_BYTES);
    tma3d(sb + s * RING_BYTES, &tm_wq, 0, s * 64, 2 * unit_head(cl, rank), sb + BAR_RFULL + 8 * s);
  };
  if (threadIdx.x == 0) first_w(0);
  __syncwarp();
  asm volatile("barrier.cluster.wait.aligned;" ::: "memory");
  if (threadIdx.x == 128) {
#pragma unroll 1
    for (int s = 0; s < 2; s++) {
      const uint32_t fb = sb + BAR_XFULL + 32 * rank + 8 * s;
      mbar_expect(fb, XB);
      mbar_expect_cl(mapa(fb, rank ^ 1), XB);
      tma2d_mc(sb + OFF_Q + x_slot(rank, s), &tm_x, s * 64, unit_batch(cl) * SQ + rank * 120, fb);
      if (s == 0) first_w(1);
    }
  }
  __syncwarp();

  if (warp >= 8) {
    asm volatile("setmaxnreg.dec.sync.aligned.u32 24;");
    if (warp == 8) {
      uint64_t pol;
      asm volatile("createpolicy.fractional.L2::evict_first.b64 %0, 1.0;" : "=l"(pol));
      Ring r;
      r.slot = 2;
      auto load = [&](const CUtensorMap* m, int c1, int c2, bool ef) {
        mbar_sleep(sb + BAR_REMPTY + 8 * r.slot, r.phase ^ 1);
        if (lane == 0) {
          mbar_expect(sb + BAR_RFULL + 8 * r.slot, RING_BYTES);
          if (ef) tma3d_hint(sb + r.slot * RING_BYTES, m, 0, c1, c2, sb + BAR_RFULL + 8 * r.slot, pol);
          else tma3d(sb + r.slot * RING_BYTES, m, 0, c1, c2, sb + BAR_RFULL + 8 * r.slot);
        }
        r.next();
      };
      for (int u0 = 0;; u0 += ncl) {
        const int u = __shfl_sync(~0u, (u0 >= 3 * ncl ? role() : cl) + u0, 0);
        if (u >= NUNITS) break;
        if (NCL == 66 && u0 == 2 * 66) {
          const int id = role();
          if (id >= 44 && id < 58) {
            unsigned t0, t1;
            asm volatile("mov.u32 %0, %globaltimer_lo;" : "=r"(t0));
            do { __nanosleep(200); asm volatile("mov.u32 %0, %globaltimer_lo;" : "=r"(t1)); } while (t1 - t0 < PAUSE_NS);
          }
        }
        const int h = unit_head(u, rank);
        const int krow = (unit_batch(u) * NH + h) * SK;
#pragma unroll 1
        for (int s = u0 == 0 ? 2 : 0; s < 10; s++) {
          load(&tm_wq, s * 64, 2 * h, false);
          const int sp = u0 == 0 ? s - 6 : s;
          if (sp >= 0 && sp < PF_N && lane == 0) l2_prefetch(P.v + (size_t)(krow + (PF_J0 + sp * PF_STEP) * 64) * DH, 16384);
        }
#pragma unroll 1
        for (int j = 0; j <= 16; j++) {
          if (j < 16) load(&tm_k, krow + j * 64, 0, true);
          if (j == 2) load(&tm_v, krow, 0, true);
          if (j > 1) load(&tm_v, krow + (j - 1) * 64, 0, true);
        }
      }
      const int id = __shfl_sync(~0u, role(), 0);
      const bool dbl = NCL == 66 && id >= 58;
      for (int t = dbl ? 2 * id - 72 : id; t < (dbl ? NOTILES : nsingle); t += ncl) {
        const int row0 = row_block(t) * 256 + rank * 128;
        const int b0 = row0 / SQ, b1 = (row0 + 127) / SQ;
#pragma unroll 1
        for (int ks = 0; ks < 64; ks++) {
          if (dbl ? (ks & 15) == 0 : ks == 0 || ks == 48) {
            const unsigned* c = &g_cnt[((lane & 1 ? b1 : b0) * 4 + (ks || dbl ? ks >> 4 : min(lane >> 1, 2))) * 8];
            unsigned v, n = 0;
            do {
              asm volatile("ld.acquire.gpu.global.u32 %0, [%1];" : "=r"(v) : "l"(c) : "memory");
              if (++n > (1u << 26)) __trap();
            } while (v < 16);
            __syncwarp();
            asm volatile("fence.proxy.async.global;" ::: "memory");
          }
          mbar_wait(sb + BAR_REMPTY + 8 * r.slot, r.phase ^ 1);
          if (lane == 0) {
            mbar_expect(sb + BAR_RFULL + 8 * r.slot, RING_BYTES);
            asm volatile("cp.async.bulk.tensor.4d.shared::cluster.global.mbarrier::complete_tx::bytes.L2::cache_hint [%0], [%1, {%3, %3, %4, %5}], [%2], %6;"
                         ::"r"(sb + r.slot * RING_BYTES), "l"(&tm_o), "r"(sb + BAR_RFULL + 8 * r.slot), "r"(0), "r"((dbl ? ks : bk(ks)) * 8), "r"(row0 >> 6), "l"(pol) : "memory");
          }
          r.next();
        }
      }
      if (lane == 0 && atomicAdd(&g_cnt[64 * 8], 1) == gridDim.x - 1) {
        for (int i = 0; i < 67; i++) g_cnt[i * 8] = 0;
      }
    } else if (warp == 9) {
      if (lane == 0) {
        uint32_t it = 0;
        for (;; it++) {
          const int u = (it >= 3 ? role() : cl) + it * ncl;
          if (u >= NUNITS) break;
          const int row = unit_batch(u) * SQ + rank * 120;
#pragma unroll 1
          for (int s = it == 0 ? 2 : 0; s < 10; s++) {
            const uint32_t j = s & 3, par = ((s >> 2) + (j < 2 ? it : 0)) & 1;
            if (s == 0) mbar_sleep(sb + BAR_XEMPTY, par ^ 1);
            mbar_wait(sb + BAR_XEMPTY + 8 * j, par ^ 1);
            const uint32_t fb = sb + BAR_XFULL + 32 * rank + 8 * j;
            mbar_expect(fb, XB);
            mbar_expect_cl(mapa(fb, rank ^ 1), XB);
            tma2d_mc(sb + OFF_Q + x_slot(rank, j), &tm_x, s * 64, row, fb);
          }
        }
        const int id = role();
        const bool dbl = NCL == 66 && id >= 58;
        uint32_t slot = rank, phase = 0;
        if (dbl)
          asm volatile("cp.async.bulk.prefetch.tensor.3d.L2.global [%0, {%1, %2, %3}];" ::"l"(&tm_wo), "r"(0), "r"((2 + ((id >> 1) & 3)) * 64), "r"(((2 * id - 72 + rank) & 3) * 5) : "memory");
        if (dbl || id < nsingle) mbar_sleep(sb + BAR_BEMPTY + 8 * rank, 0);
        for (int t = dbl ? 2 * id - 72 + rank : id; t < (dbl ? NOTILES : nsingle); t += ncl) {
#pragma unroll 1
          for (int ks = dbl ? 0 : rank; ks < 64; ks += dbl ? 1 : 2) {
            mbar_wait(sb + BAR_BEMPTY + 8 * slot, phase);
            const uint32_t fb = sb + BAR_BFULL + 8 * slot;
            mbar_expect(fb, BB);
            mbar_expect_cl(mapa(fb, rank ^ 1), BB);
            tma3d_mc(sb + OFF_Q + slot * BB, &tm_wo, 0, (dbl ? ks : bk(ks)) * 64, (t & 3) * 5, fb);
            if (dbl && ks + WO_PF < 64 && (ks & 3) == ((id >> 1) & 3))
              asm volatile("cp.async.bulk.prefetch.tensor.3d.L2.global [%0, {%1, %2, %3}];" ::"l"(&tm_wo), "r"(0), "r"((ks + WO_PF) * 64), "r"((t & 3) * 5) : "memory");
            slot += 2;
            if (slot >= 6) { slot -= 6; phase ^= 1; }
          }
        }
      }
    } else {
      const int wg = warp - 10;
      {
        mbar_wait(sb + BAR_RFULL, 0);
        const __nv_bfloat16* xs = P.x + (size_t)(unit_batch(cl) * SQ + ((cl & 3) * 2 + rank) * 30 + min(lane, 29)) * DM + 256 + wg * 64;
#pragma unroll
        for (int i = 0; i < 3; i++) asm volatile("prefetch.global.L2 [%0];" ::"l"(xs + i * 128));
        if (lane < 16) asm volatile("prefetch.global.L2 [%0];" ::"l"(P.wq + (size_t)(384 + unit_batch(cl) * 16 + lane) * HD + unit_head(cl, rank) * DH + wg * 64));
      }
      for (uint32_t it = 0;; it++) {
        const int u = __shfl_sync(~0u, (it >= 3 ? role() : cl) + it * ncl, 0);
        if (u >= NUNITS) break;
        mbar_sleep(sb + BAR_LSUM + 8 * wg, it & 1);
        float l4[4], v[4];
        const uint32_t a = sb + OFF_L2 + wg * 2048 + lane * 16;
        asm volatile("ld.shared.v4.f32 {%0, %1, %2, %3}, [%4];" : "=f"(l4[0]), "=f"(l4[1]), "=f"(l4[2]), "=f"(l4[3]) : "r"(a) : "memory");
#pragma unroll
        for (int g = 1; g < 4; g++) {
          asm volatile("ld.shared.v4.f32 {%0, %1, %2, %3}, [%4];" : "=f"(v[0]), "=f"(v[1]), "=f"(v[2]), "=f"(v[3]) : "r"(a + g * 512) : "memory");
#pragma unroll
          for (int c = 0; c < 4; c++) l4[c] += v[c];
        }
#pragma unroll
        for (int c = 0; c < 4; c++) {
          float inv;
          asm("rcp.approx.ftz.f32 %0, %1;" : "=f"(inv) : "f"(l4[c]));
          l4[c] = l4[c] >= L_MIN && l4[c] <= L_MAX ? inv : __uint_as_float(0x7FFFFFFFu);
        }
        const uint32_t h0 = pack(l4[0], l4[1]), h1 = pack(l4[2], l4[3]);
        const uint32_t e0 = pack(l4[0] - __uint_as_float(h0 << 16), l4[1] - __uint_as_float(h0 & 0xFFFF0000u));
        const uint32_t e1 = pack(l4[2] - __uint_as_float(h1 << 16), l4[3] - __uint_as_float(h1 & 0xFFFF0000u));
        asm volatile("st.shared.v4.u32 [%0], {%1, %2, %3, %4};" ::"r"(sb + OFF_INV + wg * 640 + (lane & 3) * 144 + (lane >> 2) * 16), "r"(h0), "r"(e0), "r"(h1), "r"(e1) : "memory");
        __syncwarp();
        if (lane == 0) {
          mbar_arrive(sb + BAR_INV + 8 * wg);
          if (it == 0 && wg == 0) {
            if (rank == 0) {
              int id = cl;
              if (NCL == 66) {
                uint32_t smid;
                asm("mov.u32 %0, %smid;" : "=r"(smid));
                id = smid >= SMID_TOP ? 65 - atomicAdd(&g_cnt[65 * 8], 1) : atomicAdd(&g_cnt[66 * 8], 1);
              }
#pragma unroll
              for (int c = 0; c < 2; c++) {
                const uint32_t a = mapa(sb + BAR_ROLE, c);
                asm volatile("st.shared::cluster.u32 [%0 + 8], %1;\nmbarrier.arrive.release.cluster.shared::cluster.b64 _, [%0];" ::"r"(a), "r"(id) : "memory");
              }
            }
            mbar_wait_cl(sb + BAR_ROLE, 0);
            mbar_arrive(sb + BAR_ROLE + 16);
          }
          mbar_sleep(sb + BAR_STAGE + 8 * wg, it & 1);
          __threadfence();
          asm volatile("red.relaxed.gpu.global.add.u32 [%0], 1;" ::"l"(&g_cnt[(unit_batch(u) * 4 + (u >> 6)) * 8]) : "memory");
        }
        __syncwarp();
      }
    }
  } else {
    asm volatile("setmaxnreg.inc.sync.aligned.u32 240;");
    const int wg = warp >> 2, w = warp & 3;
    const uint32_t qreg = sb + OFF_Q + wg * 2 * XB, preg = sb + OFF_P + (2 + wg) * XB;
    const uint32_t st_off = ((lane >> 4) * 8 + (lane & 7)) * 128 + (((2 * w + ((lane >> 3) & 1)) ^ (lane & 7)) << 4);
    const uint32_t xempty = mapa(sb + BAR_XEMPTY, wg);
    Ring r;
    uint32_t it = 0;
    const uint32_t qd = (qreg & 0x3FFFF) >> 4, pd = (preg & 0x3FFFF) >> 4;
    auto ring_addr = [&]() { return ((sb & 0x3FFFF) + r.slot * RING_BYTES) >> 4; };
    auto ring_wait = [&]() { mbar_wait(sb + BAR_RFULL + 8 * r.slot, r.phase); };
    auto release = [&](uint32_t slot) { warp_arrive(sb + BAR_REMPTY + 8 * slot); };
    auto turn_wait = [&]() {
      if (wg == 0) asm volatile("bar.sync 3, 256;" ::: "memory");
      else asm volatile("bar.sync 4, 256;" ::: "memory");
    };
    auto turn_pass = [&]() {
      if (wg == 0) asm volatile("bar.arrive 4, 256;" ::: "memory");
      else asm volatile("bar.arrive 3, 256;" ::: "memory");
    };

    uint32_t chk = 0;
    auto sum_l = [&](const float (&l)[30], uint32_t tid) {
      float a[16], b[8], c[4];
      const bool b4 = tid & 16, b3 = tid & 8, b2 = tid & 4;
#pragma unroll
      for (int i = 0; i < 16; i++) {
        const float hi = i < 14 ? l[(16 + i) % 30] : 1.f;
        a[i] = (b4 ? hi : l[i]) + __shfl_xor_sync(~0u, b4 ? l[i] : hi, 16);
      }
#pragma unroll
      for (int i = 0; i < 8; i++) b[i] = (b3 ? a[8 + i] : a[i]) + __shfl_xor_sync(~0u, b3 ? a[i] : a[8 + i], 8);
#pragma unroll
      for (int i = 0; i < 4; i++) c[i] = (b2 ? b[4 + i] : b[i]) + __shfl_xor_sync(~0u, b2 ? b[i] : b[4 + i], 4);
      asm volatile("st.shared.v4.f32 [%0], {%1, %2, %3, %4};" ::"r"(sb + OFF_L2 + tid * 16), "f"(c[0]), "f"(c[1]),
                   "f"(c[2]), "f"(c[3]) : "memory");
      __syncwarp();
      warp_arrive(sb + BAR_LSUM + 8 * wg);
    };
    auto load_inv = [&](uint32_t (&iv)[30], uint32_t parity) {
      const int lane = fresh_tid() & 31;
      mbar_wait(sb + BAR_INV + 8 * wg, parity);
      chk = 0;
#pragma unroll
      for (int j = 0; j < 7; j++)
        asm volatile("ld.shared.v4.u32 {%0, %1, %2, %3}, [%4];" : "=r"(iv[4 * j]), "=r"(iv[4 * j + 1]), "=r"(iv[4 * j + 2]), "=r"(iv[4 * j + 3])
                     : "r"(sb + OFF_INV + wg * 640 + (lane & 3) * 144 + j * 16) : "memory");
      asm volatile("ld.shared.v2.u32 {%0, %1}, [%2];" : "=r"(iv[28]), "=r"(iv[29]) : "r"(sb + OFF_INV + wg * 640 + (lane & 3) * 144 + 112) : "memory");
    };
    auto norm = [&](uint32_t (&n)[8], const uint32_t (&po)[60], const uint32_t (&iv)[30], auto part) {
      constexpr int k = decltype(part)::value >> 1, j0 = (decltype(part)::value & 1) * 8;
#pragma unroll
      for (int j = 0; j < 8; j++)
        n[j] = j0 + j < 15 ? hfma2(po[15 * k + (j0 + j) % 15], iv[2 * ((j0 + j) % 15)], hfma2(po[15 * k + (j0 + j) % 15], iv[2 * ((j0 + j) % 15) + 1], 0x80008000u)) : 0x3F803F80u;
#pragma unroll
      for (int j = 0; j < 8; j += 2) chk = hfma2(n[j], n[j + 1], chk);
    };
    int od1, od2;
    auto store = [&](const uint32_t (&n)[8], const char* optr, auto part) {
      constexpr int k = decltype(part)::value >> 1, off = (8 * (k & 1) + 64 * (k >> 1)) * NROWS * 2;
      if ((decltype(part)::value & 1) == 0)
        asm volatile(
            "{\n.reg .pred p;\nsetp.ne.u64 p, %8, 0;\n"
            "@p st.global.v4.u32 [%8 + %9], {%0, %1, %2, %3};\n@p st.global.v4.u32 [%8 + %9 + 512], {%4, %5, %6, %7};\n}\n"
            ::"r"(n[0]), "r"(n[1]), "r"(n[2]), "r"(n[3]), "r"(n[4]), "r"(n[5]), "r"(n[6]), "r"(n[7]), "l"(optr), "n"(off) : "memory");
      else
        asm volatile(
            "{\n.reg .pred p;\n.reg .b64 b, c;\nsetp.ne.u64 p, %7, 0;\nmad.wide.s32 b, %9, 1, %7;\nmad.wide.s32 c, %10, 1, %7;\n"
            "@p st.global.v4.u32 [%7 + %8 + 1024], {%0, %1, %2, %3};\n@p st.global.v2.u32 [b + %8], {%4, %5};\n@p st.global.u32 [c + %8], %6;\n}\n"
            ::"r"(n[0]), "r"(n[1]), "r"(n[2]), "r"(n[3]), "r"(n[4]), "r"(n[5]), "r"(n[6]), "l"(optr), "n"(off), "r"(od1), "r"(od2) : "memory");
    };
    auto put = [&](const uint32_t (&po)[60], const uint32_t (&iv)[30], const char* optr, auto part) {
      uint32_t n[8];
      norm(n, po, iv, part);
      store(n, optr, part);
    };
    auto out_ptr = [&](int u) {
      const int lane = fresh_tid() & 31;
      const int k = unit_head(u, rank) * DH + 16 * w + (lane >> 2), b = unit_batch(u), q = lane & 3;
      const uint32_t i0 = o_idx(k, o_pos(b, wg, 2 * q));
      od1 = 2 * (int)(o_idx(k, o_pos(b, wg, 96 + 2 * q)) - i0);
      od2 = 2 * (int)(o_idx(k, o_pos(b, wg, 112 + 2 * q)) - i0);
      return reinterpret_cast<const char*>(P.o + i0);
    };
    auto unsafe = [&](bool valid) {
      const bool b = valid && ((chk & 0x7F80u) == 0x7F80u || (chk & 0x7F800000u) == 0x7F800000u);
      return __any_sync(~0u, bar_red_or(wg, b));
    };
    auto publish = [&]() { __syncwarp(); warp_arrive(sb + BAR_STAGE + 8 * wg); };

    uint32_t po[60];
#pragma unroll
    for (int i = 0; i < 60; i++) po[i] = 0;
    int id = 0;
    float o0[60], o1[60];
    ring_wait();
    mbar_wait(sb + BAR_XFULL + 32 * wg, 0);
    wg_fence();
    mma_tn(o0, o1, ring_addr(), qd, 0);
    wg_commit();
    while (true) {
      uint32_t prev = r.slot;
      r.next();
      auto qstep = [&](int s) {
        const uint32_t j = s & 3, par = ((s >> 2) + (j < 2 ? it : 0)) & 1;
        ring_wait();
        mbar_wait(sb + BAR_XFULL + 32 * wg + 8 * j, par);
        if (s >= ALT_FROM) turn_wait();
        wg_fence();
        mma_tn(o0, o1, ring_addr(), ((sb & 0x3FFFF) + OFF_Q + x_slot(wg, j)) >> 4, 1);
        wg_commit();
        if (s >= ALT_FROM || (s == ALT_FROM - 1 && wg == 1)) turn_pass();
        if (s <= 4) {
          wg_wait<1>();
          release(prev);
          warp_arrive_cl(xempty + 8 * ((s - 1) & 3));
        }
        prev = r.slot;
        r.next();
      };
      auto qdone = [&](int s) {
        wg_wait<0>();
        release(prev);
        if (s <= 5) warp_arrive_cl(xempty + 8 * (s & 3));
      };
      qstep(1);
      const int up = (it > 3 ? id : cl) + ((int)it - 1) * ncl;
      const char* optr = out_ptr(up);
      if (it == 0) optr = nullptr;
      uint32_t n7[8];
      {
        uint32_t iv[30];
        load_inv(iv, (it + 1) & 1); put(po, iv, optr, IC<0>());
        qstep(2); put(po, iv, optr, IC<1>());
        qstep(3); put(po, iv, optr, IC<2>());
        qstep(4); put(po, iv, optr, IC<3>()); qdone(4);
        qstep(5); put(po, iv, optr, IC<4>()); qdone(5);
        qstep(6); put(po, iv, optr, IC<5>()); qdone(6);
        qstep(7); put(po, iv, optr, IC<6>()); norm(n7, po, iv, IC<7>()); qdone(7);
      }
      ring_wait();
      mbar_wait(sb + BAR_XFULL + 32 * wg, it & 1);
      turn_wait();
      wg_fence();
      mma_tn(o0, o1, ring_addr(), qd, 1);
      wg_commit();
      prev = r.slot;
      r.next();
      ring_wait();
      mbar_wait(sb + BAR_XFULL + 32 * wg + 8, it & 1);
      wg_fence();
      mma_tn_split(o0, o1, ring_addr(), qd + (XB >> 4));
      turn_pass();
      wg_wait<2>();
      release(prev);
      auto put_q = [&](const float (&o)[60], uint32_t dst) {
#pragma unroll
        for (int j = 0; j < 14; j += 2)
          stsm4t(dst + j * 1024, pack(o[4 * j] * QSCALE, o[4 * j + 1] * QSCALE), pack(o[4 * j + 2] * QSCALE, o[4 * j + 3] * QSCALE),
                 pack(o[4 * j + 4] * QSCALE, o[4 * j + 5] * QSCALE), pack(o[4 * j + 6] * QSCALE, o[4 * j + 7] * QSCALE));
        stsm2t(dst + 14 * 1024, pack(o[56] * QSCALE, o[57] * QSCALE), pack(o[58] * QSCALE, o[59] * QSCALE));
      };
      wg_wait<1>();
      reg_fence(o0);
      const bool redo = unsafe(it > 0);
      put_q(o0, qreg + st_off);
      wg_wait<0>();
      reg_fence(o1);
      release(r.slot);
      r.next();
      bar_sync(wg);
      put_q(o1, qreg + XB + st_off);
      fence_async_smem();
      if (redo) {
        slow_path(P, unit_batch(up), unit_head(up, rank), wg, w, fresh_tid() & 31);
        optr = nullptr;
      }

      float sc[60], l[30];
      uint32_t slot0 = r.slot;
      ring_wait();
      turn_wait();
      wg_fence();
      mma_qk(sc, ring_addr(), qd);
      wg_commit();
      r.next();
      uint32_t slot1 = r.slot;
      ring_wait();
      wg_fence();
      mma_qk(o1, ring_addr(), qd);
      wg_commit();
      r.next();
      turn_pass();
      store(n7, optr, IC<7>());
      wg_wait<1>();
      reg_fence(sc);
      release(slot0);
      exp_store<0, 15, true>(sc, l, preg + st_off);
      slot0 = r.slot;
      ring_wait();
      wg_fence();
      mma_qk(sc, ring_addr(), qd);
      wg_commit();
      r.next();
      wg_wait<1>();
      reg_fence(o1);
      release(slot1);
      exp_store<0, 15>(o1, l, preg - 2 * XB + st_off);
      fence_async_smem();
      slot1 = r.slot;
      ring_wait();
      turn_wait();
      wg_fence();
      mma_tn(o0, o1, ring_addr(), pd, 0);
      wg_commit();
      r.next();
      ring_wait();
      wg_fence();
      mma_tn(o0, o1, ring_addr(), pd - (2 * XB >> 4), 1);
      wg_commit();
      turn_pass();
      if (it > 0) publish();
      id = __shfl_sync(~0u, it >= 2 ? role() : 0, 0);
      wg_wait<1>();
      reg_fence(sc);
      release(slot0);
      release(slot1);
      bar_sync(wg);
      exp_store<0, VREL>(sc, l, preg + st_off);
      wg_wait<0>();
      reg_fence(o0); reg_fence(o1);
      release(r.slot);
      r.next();
      exp_store<VREL, 15>(sc, l, preg + st_off);
      fence_async_smem();
      const bool more = id + ((int)it + 1) * ncl < NUNITS;
      const bool gemm = id < nsingle || (NCL == 66 && id >= 58);
      uint32_t pw = preg + st_off;
#pragma unroll 1
      for (int s = 3; s < 16; s++) {
        const uint32_t kslot = r.slot;
        asm volatile("add.u32 %0, %0, %1;" : "+r"(pw) : "r"(s & 1 ? -2 * XB : 2 * XB));
        ring_wait();
        turn_wait();
        wg_fence();
        mma_qk(sc, ring_addr(), qd);
        wg_commit();
        r.next();
        ring_wait();
        wg_fence();
        mma_tn(o0, o1, ring_addr(), pd - ((s - 1) & 1) * (2 * XB >> 4), 1);
        wg_commit();
        if (wg == 0 || s < 15) turn_pass();
        wg_wait<1>();
        reg_fence(sc);
        release(kslot);
        if (s == 15) {
          if (more) { warp_arrive_cl(xempty); warp_arrive_cl(xempty + 8); }
          else if (gemm) for (int i = 0; i < 3; i++) warp_arrive_cl(mapa(sb + BAR_BEMPTY + 8 * i, i & 1));
        }
        exp_store<0, VREL>(sc, l, pw);
        wg_wait<0>();
        reg_fence(o0); reg_fence(o1);
        release(r.slot);
        r.next();
        exp_store<VREL, 15>(sc, l, pw);
        fence_async_smem();
      }
      const uint32_t tid = fresh_tid();
      bar_sync(wg);
      ring_wait();
      wg_fence();
      mma_tn_split(o0, o1, ring_addr(), pd - (2 * XB >> 4));
      sum_l(l, tid);
      const uint32_t vslot = r.slot;
      r.next();
      it++;
      auto pack_o = [&](const float (&o)[60], int first) {
#pragma unroll
        for (int j = 0; j < 15; j++) { po[first + j] = pack(o[4 * j], o[4 * j + 1]); po[first + 15 + j] = pack(o[4 * j + 2], o[4 * j + 3]); }
      };
      if (!more) {
        wg_wait<0>();
        reg_fence(o0); reg_fence(o1);
        release(vslot);
        if (gemm) for (int i = 3; i < 6; i++) warp_arrive_cl(mapa(sb + BAR_BEMPTY + 8 * i, i & 1));
        pack_o(o0, 0); pack_o(o1, 30);
        break;
      }
      ring_wait();
      mbar_wait(sb + BAR_XFULL + 32 * wg, it & 1);
      wg_wait<1>();
      reg_fence(o0);
      pack_o(o0, 0);
      wg_fence();
#pragma unroll
      for (int k = 0; k < 4; k++) wgmma_n120<1, 0>(o0, ring_addr() + k * 128, HI128, qd + k * 2, HI128, k != 0);
      wg_commit();
      wg_wait<1>();
      reg_fence(o1);
      pack_o(o1, 30);
      wg_fence();
#pragma unroll
      for (int k = 0; k < 4; k++) wgmma_n120<1, 0>(o1, ring_addr() + 512 + k * 128, HI128, qd + k * 2, HI128, k != 0);
      wg_commit();
      release(vslot);
      warp_arrive_cl(xempty + 16); warp_arrive_cl(xempty + 24);
    }
    const bool gemm = id < nsingle || (NCL == 66 && id >= 58);
    const int u = (it > 3 ? id : cl) + ((int)it - 1) * ncl;
    uint32_t pb[60];
#pragma unroll
    for (int i = 0; i < 60; i++) pb[i] = NCL != 66 ? po[i] ^ (gridDim.y - 1) : po[i];

    uint32_t bslot = 0, bphase = 0;
    auto out_row = [&](int lane) {
      const int row = lane & 15;
      return sb + wg * 8192 + (row < 12 ? w * RING_BYTES + row * 656 : (4 + (w >> 1)) * RING_BYTES + ((w & 1) * 4 + row - 12) * 656);
    };
    auto out_stage = [&](const float (&acc)[80], uint32_t col_off) {
      const int lane = fresh_tid() & 31;
      const uint32_t sa = out_row(lane) + col_off + (lane >> 4) * 16;
#pragma unroll
      for (int j = 0; j < 20; j += 2)
        asm volatile("stmatrix.sync.aligned.m8n8.x4.shared.b16 [%0], {%1,%2,%3,%4};" ::"r"(sa + j * 16), "r"(pack(acc[4 * j], acc[4 * j + 1])),
                     "r"(pack(acc[4 * j + 2], acc[4 * j + 3])), "r"(pack(acc[4 * j + 4], acc[4 * j + 5])), "r"(pack(acc[4 * j + 6], acc[4 * j + 7])) : "memory");
    };
    auto out_store = [&](int t, uint32_t bytes) {
      const int lane = fresh_tid() & 31;
      if (wg == 1) {
        __syncwarp();
#pragma unroll 1
        for (int h = 0; h < 2; h++) {
          const int row = h * 8 + (lane >> 2);
          const uint32_t src = out_row(row) + (lane & 3) * 16;
          char* dst = reinterpret_cast<char*>(P.out + (size_t)o_row(row_block(t) * 256 + rank * 128 + 64 + w * 16 + row) * DM + (t & 3) * 160) + (lane & 3) * 16;
#pragma unroll 1
          for (uint32_t c = 0; c < bytes; c += 320) {
            uint4 v[5];
#pragma unroll
            for (int i = 0; i < 5; i++)
              asm volatile("ld.shared.v4.u32 {%0, %1, %2, %3}, [%4];" : "=r"(v[i].x), "=r"(v[i].y), "=r"(v[i].z), "=r"(v[i].w) : "r"(src + c + i * 64) : "memory");
#pragma unroll
            for (int i = 0; i < 5; i++) *reinterpret_cast<uint4*>(dst + c + i * 64) = v[i];
          }
        }
        return;
      }
      fence_async_smem();
      __syncwarp();
      if (lane < 16) {
        __nv_bfloat16* dst = P.out + (size_t)o_row(row_block(t) * 256 + rank * 128 + wg * 64 + w * 16 + lane) * DM + (t & 3) * 160;
        asm volatile("cp.async.bulk.global.shared::cta.bulk_group [%0], [%1], %2;" ::"l"(dst), "r"(out_row(lane)), "r"(bytes) : "memory");
        asm volatile("cp.async.bulk.commit_group;" ::: "memory");
        asm volatile("cp.async.bulk.wait_group.read 0;" ::: "memory");
      }
    };
    for (int t = id; t == id || (NCL != 66 && t < nsingle); t += ncl) {
      float acc[80];
      uint32_t prev = 0, bprev = 0;
      const bool tile = t < nsingle;
      const bool last = NCL == 66 || t + ncl >= nsingle;
      auto bstep = [&](int ks, int accf) {
        ring_wait();
        mbar_wait(sb + BAR_BFULL + 8 * bslot, bphase);
        wg_fence();
        const uint32_t a = ring_addr() + wg * 512, bd = (((sb & 0x3FFFF) + OFF_Q + bslot * BB) >> 4) | ((4096u >> 4) << 16);
#pragma unroll
        for (int k = 0; k < 4; k++) wgmma_n160<1, 1>(acc, a + LBO64A + k * 128, HI64A, bd + k * 64, HI64, k == 0 ? accf : 1);
        wg_commit();
        if (ks > 0) {
          wg_wait<1>();
          release(prev);
          if (ks < 59 || !last) warp_arrive_cl(mapa(sb + BAR_BEMPTY + 8 * bprev, bprev & 1));
        }
        prev = r.slot; bprev = bslot;
        r.next();
        if (++bslot == 6) { bslot = 0; bphase ^= 1; }
      };
      const char* optr;
      uint32_t iv[30], n2[8], n3[8], n4[8], n5[8], n6[8], n7[8];
      if (tile) {
        bstep(0, 0);
        bstep(1, 1);
        optr = out_ptr(u);
        if (t != id) optr = nullptr;
        load_inv(iv, (it + 1) & 1);
#pragma unroll 1
        for (int ks = 2; ks < 17; ks++) {
          bstep(ks, 1);
          switch (ks) {
            case 2: put(pb, iv, optr, IC<0>()); break;
            case 4: put(pb, iv, optr, IC<1>()); break;
            case 6: put(pb, iv, optr, IC<2>()); break;
            case 8: put(pb, iv, optr, IC<3>()); break;
            case 10: put(pb, iv, optr, IC<4>()); break;
            case 12: put(pb, iv, optr, IC<5>()); break;
            case 14: put(pb, iv, optr, IC<6>()); break;
            case 16: put(pb, iv, optr, IC<7>()); break;
            default: break;
          }
        }
        wg_wait<0>();
        reg_fence(acc);
#pragma unroll
        for (int i = 0; i < 8; i++) n2[i] = n3[i] = n4[i] = n5[i] = n6[i] = n7[i] = 0;
      } else {
        Ring r2 = r;
        auto first = [&](int ks) {
          if (gemm) { mbar_wait(sb + BAR_RFULL + 8 * r2.slot, r2.phase); mbar_wait(sb + BAR_BFULL + 16 * ks, 0); }
          wg_fence();
          const uint32_t a = (((sb & 0x3FFFF) + r2.slot * RING_BYTES) >> 4) + wg * 512;
          const uint32_t bd = (((sb & 0x3FFFF) + OFF_Q + 2 * ks * BB) >> 4) | ((4096u >> 4) << 16);
#pragma unroll
          for (int k = 0; k < 4; k++) wgmma_n160<1, 1>(acc, a + LBO64A + k * 128, HI64A, bd + k * 64, HI64, k + ks != 0);
          wg_commit();
          r2.next();
        };
        first(0);
        first(1);
        optr = out_ptr(u);
        load_inv(iv, (it + 1) & 1);
        put(pb, iv, optr, IC<0>()); put(pb, iv, optr, IC<1>());
        norm(n2, pb, iv, IC<2>()); norm(n3, pb, iv, IC<3>()); norm(n4, pb, iv, IC<4>());
        norm(n5, pb, iv, IC<5>()); norm(n6, pb, iv, IC<6>()); norm(n7, pb, iv, IC<7>());
        wg_wait<0>();
        reg_fence(acc);
      }
      if (unsafe(t == id)) {
        slow_path(P, unit_batch(u), unit_head(u, rank), wg, w, fresh_tid() & 31);
        optr = nullptr;
#pragma unroll
        for (int i = 0; i < 8; i++) n2[i] = n3[i] = n4[i] = n5[i] = n6[i] = n7[i] = 0;
      }
      if (tile && t == id) publish();
      if (!tile && !gemm) {
        store(n2, optr, IC<2>()); store(n3, optr, IC<3>()); store(n4, optr, IC<4>()); store(n5, optr, IC<5>()); store(n6, optr, IC<6>()); store(n7, optr, IC<7>());
        publish();
        break;
      }
      if (!tile) {
        float ac1[80];
        auto half = [&](float (&ac)[80], bool rel, int accf) {
          mbar_wait(sb + BAR_BFULL + 8 * bslot, bphase);
          wg_fence();
          const uint32_t a = ring_addr() + wg * 512, bd = (((sb & 0x3FFFF) + OFF_Q + bslot * BB) >> 4) | ((4096u >> 4) << 16);
#pragma unroll
          for (int k = 0; k < 4; k++) wgmma_n160<1, 1>(ac, a + LBO64A + k * 128, HI64A, bd + k * 64, HI64, k == 0 ? accf : 1);
          wg_commit();
          wg_wait<1>();
          if (rel) warp_arrive_cl(mapa(sb + BAR_BEMPTY + 8 * bprev, bprev & 1));
          bprev = bslot;
        };
        auto dstep = [&](int ks) {
          ring_wait();
          half(acc, ks < 62, 1);
          release(prev);
          bslot++;
          half(ac1, ks < 61, 1);
          if (++bslot == 6) { bslot = 0; bphase ^= 1; }
          prev = r.slot; r.next();
        };
        warp_arrive_cl(mapa(sb + BAR_BEMPTY, 0));
        bprev = 2; bslot = 1;
        half(ac1, true, 0);
        prev = r.slot; r.next(); bslot = 3;
        half(ac1, true, 1);
        release(prev); prev = r.slot; r.next(); bslot = 4;
#pragma unroll 1
        for (int ks = 2; ks < 8; ks++) {
          dstep(ks);
          switch (ks) {
            case 2: store(n2, optr, IC<2>()); break;
            case 3: store(n3, optr, IC<3>()); break;
            case 4: store(n4, optr, IC<4>()); break;
            case 5: store(n5, optr, IC<5>()); break;
            case 6: store(n6, optr, IC<6>()); break;
            default: store(n7, optr, IC<7>()); break;
          }
        }
        publish();
#pragma unroll 1
        for (int ks = 8; ks < 64; ks++) {
          if (wg == 1 && ks == 62) turn_wait();
          dstep(ks);
        }
        if (wg == 0) turn_pass();
        wg_wait<0>();
        reg_fence(acc); reg_fence(ac1);
        bar_sync(wg);
        out_stage(ac1, 320);
      } else {
#pragma unroll 1
        for (int ks = 17; ks < 64; ks++) {
          if (wg == 1 && ks == 64 - END_SKEW) turn_wait();
          bstep(ks, 1);
        }
        if (wg == 0) turn_pass();
        wg_wait<0>();
        reg_fence(acc);
        release(prev);
        if (!last) warp_arrive_cl(mapa(sb + BAR_BEMPTY + 8 * bprev, bprev & 1));
      }
      const int pos0 = row_block(t) * 256 + rank * 128 + wg * 64 + w * 16;
      if (last) {
        bar_sync(wg);
        out_stage(acc, 0);
        out_store(tile ? t : 2 * id - 72, tile ? 320 : 640);
      } else {
        const int lane = fresh_tid() & 31;
        __nv_bfloat16* op0 = P.out + (size_t)o_row(pos0 + (lane >> 2)) * DM + (t & 3) * 160 + (lane & 3) * 2;
        __nv_bfloat16* op1 = P.out + (size_t)o_row(pos0 + (lane >> 2) + 8) * DM + (t & 3) * 160 + (lane & 3) * 2;
#pragma unroll
        for (int j = 0; j < 20; j++) {
          *reinterpret_cast<uint32_t*>(op0 + j * 8) = pack(acc[4 * j], acc[4 * j + 1]);
          *reinterpret_cast<uint32_t*>(op1 + j * 8) = pack(acc[4 * j + 2], acc[4 * j + 3]);
        }
      }
#pragma unroll
      for (int i = 0; i < 60; i++) pb[i] = 0;
    }
  }
}

typedef CUresult (*EncodeFn)(CUtensorMap*, CUtensorMapDataType, cuuint32_t, void*, const cuuint64_t*, const cuuint64_t*,
                             const cuuint32_t*, const cuuint32_t*, CUtensorMapInterleave, CUtensorMapSwizzle,
                             CUtensorMapL2promotion, CUtensorMapFloatOOBfill);

void make_map(EncodeFn enc, CUtensorMap* m, const void* p, int rank, const cuuint64_t* dims, const cuuint64_t* strides,
              const cuuint32_t* box, CUtensorMapSwizzle sw, CUtensorMapL2promotion promo) {
  cuuint32_t es[4] = {1, 1, 1, 1};
  enc(m, CU_TENSOR_MAP_DATA_TYPE_BFLOAT16, rank, const_cast<void*>(p), dims, strides, box, es, CU_TENSOR_MAP_INTERLEAVE_NONE, sw,
      promo, CU_TENSOR_MAP_FLOAT_OOB_FILL_NONE);
}

}

extern "C" void kernel_launch(void* const* d_in, const int* in_sizes, int n_in, void* d_out, int out_size) {
  static EncodeFn enc = nullptr;
  static int nclusters = 0;
  static void* o_ptr = nullptr;
  if (!enc) {
    cudaDriverEntryPointQueryResult qr;
    cudaGetDriverEntryPoint("cuTensorMapEncodeTiled", (void**)&enc, cudaEnableDefault, &qr);
    cudaFuncSetAttribute(fused_attn_kernel<66>, cudaFuncAttributeMaxDynamicSharedMemorySize, SMEM_BYTES);
    cudaFuncSetAttribute(fused_attn_kernel<0>, cudaFuncAttributeMaxDynamicSharedMemorySize, SMEM_BYTES);
    cudaGetSymbolAddress(&o_ptr, g_o);
    cudaLaunchConfig_t cfg = {};
    cfg.gridDim = 128; cfg.blockDim = 384; cfg.dynamicSmemBytes = SMEM_BYTES;
    cudaLaunchAttribute at; at.id = cudaLaunchAttributeClusterDimension;
    at.val.clusterDim.x = 2; at.val.clusterDim.y = 1; at.val.clusterDim.z = 1;
    cfg.attrs = &at; cfg.numAttrs = 1;
    int n = 0;
    cudaOccupancyMaxActiveClusters(&n, fused_attn_kernel<66>, &cfg);
    nclusters = n >= 66 ? MAXCL : (n >= 64 || n <= 0 ? 64 : n);
  }
  const __nv_bfloat16* x = (const __nv_bfloat16*)d_in[0];
  const __nv_bfloat16* k = (const __nv_bfloat16*)d_in[1];
  const __nv_bfloat16* v = (const __nv_bfloat16*)d_in[2];
  const __nv_bfloat16* wq = (const __nv_bfloat16*)d_in[3];
  const __nv_bfloat16* wo = (const __nv_bfloat16*)d_in[4];
  CUtensorMap tm_x, tm_wq, tm_k, tm_v, tm_o, tm_wo;
  const auto S128 = CU_TENSOR_MAP_SWIZZLE_128B;
  const auto P128 = CU_TENSOR_MAP_L2_PROMOTION_L2_128B, P256 = CU_TENSOR_MAP_L2_PROMOTION_L2_256B;
  { cuuint64_t d[2] = {DM, NB * SQ}, s[1] = {DM * 2}; cuuint32_t b[2] = {64, 120}; make_map(enc, &tm_x, x, 2, d, s, b, S128, P128); }
  { cuuint64_t d[3] = {64, DM, HD / 64}, s[2] = {HD * 2, 128}; cuuint32_t b[3] = {64, 64, 2}; make_map(enc, &tm_wq, wq, 3, d, s, b, S128, P256); }
  { cuuint64_t d[3] = {64, NB * NH * SK, 2}, s[2] = {DH * 2, 128}; cuuint32_t b[3] = {64, 64, 2};
    make_map(enc, &tm_k, k, 3, d, s, b, S128, P128); make_map(enc, &tm_v, v, 3, d, s, b, S128, P128); }
  { cuuint64_t d[4] = {256, 2, HD / 8, NROWS / 64}, s[3] = {512, NROWS * 16, 1024}; cuuint32_t b[4] = {256, 2, 8, 2};
    make_map(enc, &tm_o, o_ptr, 4, d, s, b, CU_TENSOR_MAP_SWIZZLE_NONE, P256); }
  { cuuint64_t d[3] = {32, HD, DM / 32}, s[2] = {DM * 2, 64}; cuuint32_t b[3] = {32, 64, 5};
    make_map(enc, &tm_wo, wo, 3, d, s, b, CU_TENSOR_MAP_SWIZZLE_64B, P128); }
  Params P{x, k, v, wq, (__nv_bfloat16*)d_out, (__nv_bfloat16*)o_ptr};
  if (nclusters == 66) fused_attn_kernel<66><<<132, 384, SMEM_BYTES>>>(tm_x, tm_wq, tm_k, tm_v, tm_o, tm_wo, P);
  else fused_attn_kernel<0><<<2 * nclusters, 384, SMEM_BYTES>>>(tm_x, tm_wq, tm_k, tm_v, tm_o, tm_wo, P);
}
```

```cpp
#include <cuda_runtime.h>
#include <cuda.h>
#include <cuda_bf16.h>
#include <stdint.h>

namespace {

constexpr int NB = 16, SQ = 240, DM = 640, NH = 32, SK = 1024, DH = 128, HD = NH * DH;
constexpr int NROWS = NB * SQ;
constexpr int NUNITS = 256;
#define ALT_FROM 4
#define END_SKEW 5
#define VREL 8
#define PF_N 4
#define PF_J0 3
#define PF_STEP 3
#define WO_PF 6
#define PAUSE_NS 11000
#define ROLEMAP 0
#define MAXCL 66
constexpr int NOTILES = 60;
constexpr float QSCALE = 0.08838834764831845f * 1.4426950408889634f;
constexpr float L_MIN = 1.f;
constexpr float L_MAX = 1.152921504606846976e18f;

constexpr uint32_t RING_SLOTS = 6, RING_BYTES = 16384;
constexpr uint32_t XB = 15360;
constexpr uint32_t BB = 20480;
constexpr uint32_t OFF_Q = RING_SLOTS * RING_BYTES;
constexpr uint32_t OFF_P = OFF_Q + 4 * XB;
constexpr uint32_t OFF_INV = OFF_P + 4 * XB;
constexpr uint32_t OFF_L2 = OFF_INV + 1280;
constexpr uint32_t OFF_BAR = OFF_L2 + 4096;
constexpr uint32_t BAR_RFULL = OFF_BAR, BAR_REMPTY = BAR_RFULL + 48, BAR_XFULL = BAR_REMPTY + 48,
    BAR_XEMPTY = BAR_XFULL + 64, BAR_BFULL = BAR_XEMPTY + 32, BAR_BEMPTY = BAR_BFULL + 48, BAR_STAGE = BAR_BEMPTY + 48;
constexpr uint32_t BAR_LSUM = BAR_STAGE + 16, BAR_INV = BAR_LSUM + 16;
constexpr uint32_t OFF_TR = BAR_INV + 16;
constexpr uint32_t SMEM_BYTES = OFF_TR + 1024;

constexpr uint32_t HI128 = (1u << 30) | (1024 >> 4);
constexpr uint32_t HI64 = (2u << 30) | (512 >> 4);
constexpr uint32_t HI64A = (2u << 30) | (1024 >> 4), LBO64A = (512u >> 4) << 16;

__device__ __align__(1024) __nv_bfloat16 g_o[HD * NROWS];
__device__ __align__(128) unsigned g_cnt[65 * 8];

struct Params {
  const __nv_bfloat16 *x, *k, *v, *wq;
  __nv_bfloat16 *out, *o;
};

__device__ __forceinline__ void wg_fence() { asm volatile("wgmma.fence.sync.aligned;" ::: "memory"); }
__device__ __forceinline__ void wg_commit() { asm volatile("wgmma.commit_group.sync.aligned;" ::: "memory"); }
template <int N> __device__ __forceinline__ void wg_wait() { asm volatile("wgmma.wait_group.sync.aligned %0;" ::"n"(N) : "memory"); }
template <int N> __device__ __forceinline__ void reg_fence(float (&r)[N]) {
#pragma unroll
  for (int i = 0; i < N; i++) asm volatile("" : "+f"(r[i])::"memory");
}
template <int TA, int TB>
__device__ __forceinline__ void wgmma_n120(float (&d)[60], uint32_t a_lo, uint32_t a_hi, uint32_t b_lo, uint32_t b_hi, int acc) {
  asm volatile(
      "{\n.reg .pred p;\n.reg .b64 da, db;\nsetp.ne.b32 p, %64, 0;\n"
      "mov.b64 da, {%60, %61};\nmov.b64 db, {%62, %63};\n"
      "wgmma.mma_async.sync.aligned.m64n120k16.f32.bf16.bf16 {"
      "%0, %1, %2, %3, %4, %5, %6, %7, %8, %9, %10, %11, %12, %13, %14, %15, %16, %17, %18, %19, %20, %21, %22, %23, "
      "%24, %25, %26, %27, %28, %29, %30, %31, %32, %33, %34, %35, %36, %37, %38, %39, %40, %41, %42, %43, %44, %45, "
      "%46, %47, %48, %49, %50, %51, %52, %53, %54, %55, %56, %57, %58, %59"
      "}, da, db, p, 1, 1, %65, %66;\n}\n"
      : "+f"(d[0]), "+f"(d[1]), "+f"(d[2]), "+f"(d[3]), "+f"(d[4]), "+f"(d[5]), "+f"(d[6]), "+f"(d[7]), "+f"(d[8]),
        "+f"(d[9]), "+f"(d[10]), "+f"(d[11]), "+f"(d[12]), "+f"(d[13]), "+f"(d[14]), "+f"(d[15]), "+f"(d[16]),
        "+f"(d[17]), "+f"(d[18]), "+f"(d[19]), "+f"(d[20]), "+f"(d[21]), "+f"(d[22]), "+f"(d[23]), "+f"(d[24]),
        "+f"(d[25]), "+f"(d[26]), "+f"(d[27]), "+f"(d[28]), "+f"(d[29]), "+f"(d[30]), "+f"(d[31]), "+f"(d[32]),
        "+f"(d[33]), "+f"(d[34]), "+f"(d[35]), "+f"(d[36]), "+f"(d[37]), "+f"(d[38]), "+f"(d[39]), "+f"(d[40]),
        "+f"(d[41]), "+f"(d[42]), "+f"(d[43]), "+f"(d[44]), "+f"(d[45]), "+f"(d[46]), "+f"(d[47]), "+f"(d[48]),
        "+f"(d[49]), "+f"(d[50]), "+f"(d[51]), "+f"(d[52]), "+f"(d[53]), "+f"(d[54]), "+f"(d[55]), "+f"(d[56]),
        "+f"(d[57]), "+f"(d[58]), "+f"(d[59])
      : "r"(a_lo), "r"(a_hi), "r"(b_lo), "r"(b_hi), "r"(acc), "n"(TA), "n"(TB));
}

template <int TA, int TB>
__device__ __forceinline__ void wgmma_n160(float (&d)[80], uint32_t a_lo, uint32_t a_hi, uint32_t b_lo, uint32_t b_hi, int acc) {
  asm volatile(
      "{\n.reg .pred p;\n.reg .b64 da, db;\nsetp.ne.b32 p, %84, 0;\n"
      "mov.b64 da, {%80, %81};\nmov.b64 db, {%82, %83};\n"
      "wgmma.mma_async.sync.aligned.m64n160k16.f32.bf16.bf16 {"
      "%0, %1, %2, %3, %4, %5, %6, %7, %8, %9, %10, %11, %12, %13, %14, %15, %16, %17, %18, %19, %20, %21, %22, %23, "
      "%24, %25, %26, %27, %28, %29, %30, %31, %32, %33, %34, %35, %36, %37, %38, %39, %40, %41, %42, %43, %44, %45, "
      "%46, %47, %48, %49, %50, %51, %52, %53, %54, %55, %56, %57, %58, %59, %60, %61, %62, %63, %64, %65, %66, %67, "
      "%68, %69, %70, %71, %72, %73, %74, %75, %76, %77, %78, %79"
      "}, da, db, p, 1, 1, %85, %86;\n}\n"
      : "+f"(d[0]), "+f"(d[1]), "+f"(d[2]), "+f"(d[3]), "+f"(d[4]), "+f"(d[5]), "+f"(d[6]), "+f"(d[7]), "+f"(d[8]),
        "+f"(d[9]), "+f"(d[10]), "+f"(d[11]), "+f"(d[12]), "+f"(d[13]), "+f"(d[14]), "+f"(d[15]), "+f"(d[16]),
        "+f"(d[17]), "+f"(d[18]), "+f"(d[19]), "+f"(d[20]), "+f"(d[21]), "+f"(d[22]), "+f"(d[23]), "+f"(d[24]),
        "+f"(d[25]), "+f"(d[26]), "+f"(d[27]), "+f"(d[28]), "+f"(d[29]), "+f"(d[30]), "+f"(d[31]), "+f"(d[32]),
        "+f"(d[33]), "+f"(d[34]), "+f"(d[35]), "+f"(d[36]), "+f"(d[37]), "+f"(d[38]), "+f"(d[39]), "+f"(d[40]),
        "+f"(d[41]), "+f"(d[42]), "+f"(d[43]), "+f"(d[44]), "+f"(d[45]), "+f"(d[46]), "+f"(d[47]), "+f"(d[48]),
        "+f"(d[49]), "+f"(d[50]), "+f"(d[51]), "+f"(d[52]), "+f"(d[53]), "+f"(d[54]), "+f"(d[55]), "+f"(d[56]),
        "+f"(d[57]), "+f"(d[58]), "+f"(d[59]), "+f"(d[60]), "+f"(d[61]), "+f"(d[62]), "+f"(d[63]), "+f"(d[64]),
        "+f"(d[65]), "+f"(d[66]), "+f"(d[67]), "+f"(d[68]), "+f"(d[69]), "+f"(d[70]), "+f"(d[71]), "+f"(d[72]),
        "+f"(d[73]), "+f"(d[74]), "+f"(d[75]), "+f"(d[76]), "+f"(d[77]), "+f"(d[78]), "+f"(d[79])
      : "r"(a_lo), "r"(a_hi), "r"(b_lo), "r"(b_hi), "r"(acc), "n"(TA), "n"(TB));
}
__device__ __forceinline__ void mbar_init(uint32_t bar, int cnt) { asm volatile("mbarrier.init.shared::cta.b64 [%0], %1;" ::"r"(bar), "r"(cnt)); }
__device__ __forceinline__ void mbar_expect(uint32_t bar, uint32_t bytes) {
  asm volatile("mbarrier.arrive.expect_tx.shared::cta.b64 _, [%0], %1;" ::"r"(bar), "r"(bytes) : "memory");
}
__device__ __forceinline__ uint32_t mapa(uint32_t addr, uint32_t cta) {
  uint32_t r; asm("mapa.shared::cluster.u32 %0, %1, %2;" : "=r"(r) : "r"(addr), "r"(cta)); return r;
}
__device__ __forceinline__ void mbar_expect_cl(uint32_t cbar, uint32_t bytes) {
  asm volatile("mbarrier.arrive.expect_tx.shared::cluster.b64 _, [%0], %1;" ::"r"(cbar), "r"(bytes) : "memory");
}
__device__ __forceinline__ void mbar_arrive(uint32_t bar) { asm volatile("mbarrier.arrive.shared::cta.b64 _, [%0];" ::"r"(bar) : "memory"); }
__device__ __forceinline__ void mbar_arrive_cl(uint32_t cbar) { asm volatile("mbarrier.arrive.shared::cluster.b64 _, [%0];" ::"r"(cbar) : "memory"); }
__device__ __forceinline__ void warp_arrive(uint32_t bar) {
  asm volatile("{\n.reg .pred p;\nelect.sync _|p, 0xffffffff;\n@p mbarrier.arrive.shared::cta.b64 _, [%0];\n}\n" ::"r"(bar) : "memory");
}
__device__ __forceinline__ void warp_arrive_cl(uint32_t cbar) {
  asm volatile("{\n.reg .pred p;\nelect.sync _|p, 0xffffffff;\n@p mbarrier.arrive.shared::cluster.b64 _, [%0];\n}\n" ::"r"(cbar) : "memory");
}
__device__ __forceinline__ void mbar_wait(uint32_t bar, uint32_t parity) {
  asm volatile(
      "{\n.reg .pred p;\n.reg .u32 n;\n"
      "mbarrier.try_wait.parity.shared::cta.b64 p, [%0], %1;\n@p bra WAIT_DONE;\n"
      "mov.u32 n, 0;\n"
      "WAIT_LOOP:\n"
      "mbarrier.try_wait.parity.shared::cta.b64 p, [%0], %1;\n@p bra WAIT_DONE;\n"
      "add.u32 n, n, 1;\nsetp.lt.u32 p, n, 0x4000000;\n@p bra WAIT_LOOP;\ntrap;\n"
      "WAIT_DONE:\n}\n" ::"r"(bar), "r"(parity) : "memory");
}
__device__ __forceinline__ void mbar_sleep(uint32_t bar, uint32_t parity) {
  asm volatile(
      "{\n.reg .pred p;\n.reg .u32 n;\nmov.u32 n, 0;\n"
      "WAIT_LOOP:\n"
      "mbarrier.try_wait.parity.shared::cta.b64 p, [%0], %1, 4000;\n@p bra WAIT_DONE;\n"
      "add.u32 n, n, 1;\nsetp.lt.u32 p, n, 0x400000;\n@p bra WAIT_LOOP;\ntrap;\n"
      "WAIT_DONE:\n}\n" ::"r"(bar), "r"(parity) : "memory");
}
__device__ __forceinline__ void tma3d(uint32_t dst, const CUtensorMap* m, int c0, int c1, int c2, uint32_t bar) {
  asm volatile("cp.async.bulk.tensor.3d.shared::cluster.global.mbarrier::complete_tx::bytes [%0], [%1, {%3, %4, %5}], [%2];"
               ::"r"(dst), "l"(m), "r"(bar), "r"(c0), "r"(c1), "r"(c2) : "memory");
}
__device__ __forceinline__ void tma3d_hint(uint32_t dst, const CUtensorMap* m, int c0, int c1, int c2, uint32_t bar, uint64_t pol) {
  asm volatile("cp.async.bulk.tensor.3d.shared::cluster.global.mbarrier::complete_tx::bytes.L2::cache_hint [%0], [%1, {%3, %4, %5}], [%2], %6;"
               ::"r"(dst), "l"(m), "r"(bar), "r"(c0), "r"(c1), "r"(c2), "l"(pol) : "memory");
}
__device__ __forceinline__ void tma2d_mc(uint32_t dst, const CUtensorMap* m, int c0, int c1, uint32_t bar) {
  asm volatile("cp.async.bulk.tensor.2d.shared::cluster.global.mbarrier::complete_tx::bytes.multicast::cluster [%0], [%1, {%3, %4}], [%2], %5;"
               ::"r"(dst), "l"(m), "r"(bar), "r"(c0), "r"(c1), "h"((uint16_t)3) : "memory");
}
__device__ __forceinline__ void tma3d_mc(uint32_t dst, const CUtensorMap* m, int c0, int c1, int c2, uint32_t bar) {
  asm volatile("cp.async.bulk.tensor.3d.shared::cluster.global.mbarrier::complete_tx::bytes.multicast::cluster [%0], [%1, {%3, %4, %5}], [%2], %6;"
               ::"r"(dst), "l"(m), "r"(bar), "r"(c0), "r"(c1), "r"(c2), "h"((uint16_t)3) : "memory");
}
__device__ __forceinline__ void l2_prefetch(const void* p, uint32_t bytes) {
  asm volatile("cp.async.bulk.prefetch.L2.global [%0], %1;" ::"l"(p), "r"(bytes) : "memory");
}
__device__ __forceinline__ void fence_async_smem() { asm volatile("fence.proxy.async.shared::cta;" ::: "memory"); }
__device__ __forceinline__ void bar_sync(int wg) {
  if (wg == 0) asm volatile("bar.sync 1, 128;" ::: "memory");
  else asm volatile("bar.sync 2, 128;" ::: "memory");
}
__device__ __forceinline__ bool bar_red_or(int id, bool v) {
  uint32_t r;
  asm volatile("{\n.reg .pred p, q;\nsetp.ne.u32 p, %2, 0;\nbar.red.or.pred q, %1, 128, p;\nselp.u32 %0, 1, 0, q;\n}\n"
               : "=r"(r) : "r"(1 + id), "r"((uint32_t)v) : "memory");
  return r != 0;
}
__device__ __forceinline__ uint32_t hfma2(uint32_t a, uint32_t b, uint32_t c) { uint32_t r; asm("fma.rn.bf16x2 %0, %1, %2, %3;" : "=r"(r) : "r"(a), "r"(b), "r"(c)); return r; }
__device__ __forceinline__ float ex2(float x) { float y; asm("ex2.approx.ftz.f32 %0, %1;" : "=f"(y) : "f"(x)); return y; }
__device__ __forceinline__ uint32_t pack(float lo, float hi) { uint32_t r; asm("cvt.rn.bf16x2.f32 %0, %1, %2;" : "=r"(r) : "f"(hi), "f"(lo)); return r; }
__device__ __forceinline__ void stsm4t(uint32_t a, uint32_t r0, uint32_t r1, uint32_t r2, uint32_t r3) {
  asm volatile("stmatrix.sync.aligned.m8n8.x4.trans.shared.b16 [%0], {%1,%2,%3,%4};" ::"r"(a), "r"(r0), "r"(r1), "r"(r2), "r"(r3) : "memory");
}
__device__ __forceinline__ void stsm2t(uint32_t a, uint32_t r0, uint32_t r1) {
  asm volatile("stmatrix.sync.aligned.m8n8.x2.trans.shared.b16 [%0], {%1,%2};" ::"r"(a), "r"(r0), "r"(r1) : "memory");
}
__device__ __forceinline__ void mma16816(float (&d)[4], const uint32_t (&a)[4], uint32_t b0, uint32_t b1) {
  asm volatile("mma.sync.aligned.m16n8k16.row.col.f32.bf16.bf16.f32 {%0,%1,%2,%3}, {%4,%5,%6,%7}, {%8,%9}, {%0,%1,%2,%3};"
               : "+f"(d[0]), "+f"(d[1]), "+f"(d[2]), "+f"(d[3]) : "r"(a[0]), "r"(a[1]), "r"(a[2]), "r"(a[3]), "r"(b0), "r"(b1));
}

__device__ __forceinline__ uint32_t fresh_tid() { uint32_t t; asm volatile("mov.u32 %0, %tid.x;" : "=r"(t)); return t; }

template <int V> struct IC { static constexpr int value = V; };

struct Ring {
  uint32_t slot = 0, phase = 0;
  __device__ __forceinline__ void next() { if (++slot == RING_SLOTS) { slot = 0; phase ^= 1; } }
};

__device__ __forceinline__ void mma_tn(float (&o0)[60], float (&o1)[60], uint32_t a, uint32_t b, int acc) {
#pragma unroll
  for (int k = 0; k < 4; k++) {
    wgmma_n120<1, 0>(o0, a + k * 128, HI128, b + k * 2, HI128, k == 0 ? acc : 1);
    wgmma_n120<1, 0>(o1, a + 512 + k * 128, HI128, b + k * 2, HI128, k == 0 ? acc : 1);
  }
}
__device__ __forceinline__ void mma_tn_split(float (&o0)[60], float (&o1)[60], uint32_t a, uint32_t b) {
#pragma unroll
  for (int k = 0; k < 4; k++) wgmma_n120<1, 0>(o0, a + k * 128, HI128, b + k * 2, HI128, 1);
  wg_commit();
#pragma unroll
  for (int k = 0; k < 4; k++) wgmma_n120<1, 0>(o1, a + 512 + k * 128, HI128, b + k * 2, HI128, 1);
  wg_commit();
}
__device__ __forceinline__ void mma_qk(float (&s)[60], uint32_t a, uint32_t q) {
#pragma unroll
  for (int k = 0; k < 8; k++)
    wgmma_n120<0, 0>(s, a + (k >> 2) * 512 + (k & 3) * 2, HI128, q + (k >> 2) * (XB >> 4) + (k & 3) * 2, HI128, k != 0);
}
template <int J0, int J1, bool FIRST = false>
__device__ __forceinline__ void exp_store(const float (&s)[60], float (&l)[30], uint32_t dst) {
#pragma unroll
  for (int c = J0; c < J1; c++) {
    const float e0 = ex2(s[4 * c]), e1 = ex2(s[4 * c + 1]), e2 = ex2(s[4 * c + 2]), e3 = ex2(s[4 * c + 3]);
    if (FIRST) { l[2 * c] = e0 + e2; l[2 * c + 1] = e1 + e3; }
    else { l[2 * c] += e0; l[2 * c + 1] += e1; l[2 * c] += e2; l[2 * c + 1] += e3; }
    stsm2t(dst + c * 1024, pack(e0, e1), pack(e2, e3));
  }
}

__device__ __forceinline__ int o_pos(int b, int wg, int r) {
  const int j = r >> 3, q = (r >> 1) & 3, c = r & 1, o = b & 1, base = (b >> 1) * 480;
  if (j < 12) return base + (o * 9 + wg * 3 + (j >> 2)) * 32 + q * 8 + (j & 3) * 2 + c;
  if (j < 14) return base + (6 + 2 * o) * 32 + wg * 16 + q * 4 + (j - 12) * 2 + c;
  return base + 7 * 32 + (o * 2 + wg) * 8 + q * 2 + c;
}
__device__ __forceinline__ int o_row(int p) {
  const int pair = p / 480, a = (p - pair * 480) >> 5, in = p & 31, c = p & 1;
  int tile, row;
  if (a == 7) { tile = in >> 3; row = 112 + (in & 7); }
  else if (a == 6 || a == 8) { tile = a - 6 + (in >> 4); row = (12 + ((in >> 1) & 1)) * 8 + ((in >> 2) & 3) * 2 + c; }
  else { const int f = a > 8 ? a - 3 : a; tile = f / 3; row = ((f - tile * 3) * 4 + ((in >> 1) & 3)) * 8 + (in >> 3) * 2 + c; }
  return pair * 480 + tile * 120 + row;
}
__device__ __forceinline__ uint32_t o_idx(int k, int p) {
  return ((k >> 3) * (NROWS / 32) + (p >> 5)) * 256 + (k & 7) * 32 + ((((p >> 3) & 3) ^ ((k & 7) >> 1)) << 3) + (p & 7);
}

__device__ __forceinline__ void slow_path(const Params& P, int b, int h, int wg, int w, int lane) {
  const int g = lane >> 2, q = lane & 3, row0 = wg * 120;
  const uint16_t* wq = reinterpret_cast<const uint16_t*>(P.wq) + h * DH + g;
  const __nv_bfloat16* kp = P.k + (size_t)(b * NH + h) * SK * DH;
  const uint16_t* vp = reinterpret_cast<const uint16_t*>(P.v) + (size_t)(b * NH + h) * SK * DH + g;
#pragma unroll 1
  for (int t = w; t < 8; t += 4) {
    const int r0 = 16 * t + g, r1 = r0 + 8;
    const __nv_bfloat16* x0 = P.x + (size_t)(b * SQ + row0 + r0) * DM + 2 * q;
    const __nv_bfloat16* x1 = P.x + (size_t)(b * SQ + row0 + min(r1, 119)) * DM + 2 * q;
    float o[16][4];
#pragma unroll
    for (int n = 0; n < 16; n++) o[n][0] = o[n][1] = o[n][2] = o[n][3] = 0.f;
#pragma unroll 1
    for (int k0 = 0; k0 < DM; k0 += 16) {
      uint32_t a[4] = {*(const uint32_t*)(x0 + k0), *(const uint32_t*)(x1 + k0), *(const uint32_t*)(x0 + k0 + 8), *(const uint32_t*)(x1 + k0 + 8)};
      const uint16_t* wr = wq + (size_t)(k0 + 2 * q) * HD;
#pragma unroll
      for (int n = 0; n < 16; n++) {
        if ((n & 3) == 0) __syncwarp();
        mma16816(o[n], a, wr[8 * n] | ((uint32_t)wr[8 * n + HD] << 16), wr[8 * n + 8 * HD] | ((uint32_t)wr[8 * n + 9 * HD] << 16));
      }
    }
    uint32_t qa[8][4];
#pragma unroll
    for (int k = 0; k < 8; k++) {
      qa[k][0] = pack(o[2 * k][0] * QSCALE, o[2 * k][1] * QSCALE);
      qa[k][1] = pack(o[2 * k][2] * QSCALE, o[2 * k][3] * QSCALE);
      qa[k][2] = pack(o[2 * k + 1][0] * QSCALE, o[2 * k + 1][1] * QSCALE);
      qa[k][3] = pack(o[2 * k + 1][2] * QSCALE, o[2 * k + 1][3] * QSCALE);
    }
#pragma unroll
    for (int n = 0; n < 16; n++) o[n][0] = o[n][1] = o[n][2] = o[n][3] = 0.f;
    float m0 = -INFINITY, m1 = -INFINITY, l0 = 0.f, l1 = 0.f;
#pragma unroll 1
    for (int key0 = 0; key0 < SK; key0 += 16) {
      float s[2][4];
#pragma unroll
      for (int nt = 0; nt < 2; nt++) {
        s[nt][0] = s[nt][1] = s[nt][2] = s[nt][3] = 0.f;
        const __nv_bfloat16* kr = kp + (size_t)(key0 + 8 * nt + g) * DH + 2 * q;
#pragma unroll
        for (int k = 0; k < 8; k++) mma16816(s[nt], qa[k], *(const uint32_t*)(kr + 16 * k), *(const uint32_t*)(kr + 16 * k + 8));
      }
      float n0 = fmaxf(fmaxf(s[0][0], s[0][1]), fmaxf(s[1][0], s[1][1])), n1 = fmaxf(fmaxf(s[0][2], s[0][3]), fmaxf(s[1][2], s[1][3]));
      n0 = fmaxf(n0, __shfl_xor_sync(~0u, n0, 1)); n1 = fmaxf(n1, __shfl_xor_sync(~0u, n1, 1));
      n0 = fmaxf(n0, __shfl_xor_sync(~0u, n0, 2)); n1 = fmaxf(n1, __shfl_xor_sync(~0u, n1, 2));
      n0 = fmaxf(n0, m0); n1 = fmaxf(n1, m1);
      const float z0 = n0 == -INFINITY ? 0.f : n0, z1 = n1 == -INFINITY ? 0.f : n1;
      const float c0 = ex2(m0 - z0), c1 = ex2(m1 - z1);
      m0 = n0; m1 = n1;
#pragma unroll
      for (int nt = 0; nt < 2; nt++) {
        s[nt][0] = ex2(s[nt][0] - z0); s[nt][1] = ex2(s[nt][1] - z0);
        s[nt][2] = ex2(s[nt][2] - z1); s[nt][3] = ex2(s[nt][3] - z1);
      }
      l0 = l0 * c0 + s[0][0] + s[0][1] + s[1][0] + s[1][1];
      l1 = l1 * c1 + s[0][2] + s[0][3] + s[1][2] + s[1][3];
      uint32_t pa[4] = {pack(s[0][0], s[0][1]), pack(s[0][2], s[0][3]), pack(s[1][0], s[1][1]), pack(s[1][2], s[1][3])};
      const uint16_t* vr = vp + (size_t)(key0 + 2 * q) * DH;
#pragma unroll
      for (int n = 0; n < 16; n++) {
        if ((n & 3) == 0) __syncwarp();
        o[n][0] *= c0; o[n][1] *= c0; o[n][2] *= c1; o[n][3] *= c1;
        mma16816(o[n], pa, vr[8 * n] | ((uint32_t)vr[8 * n + DH] << 16), vr[8 * n + 8 * DH] | ((uint32_t)vr[8 * n + 9 * DH] << 16));
      }
    }
    l0 += __shfl_xor_sync(~0u, l0, 1); l1 += __shfl_xor_sync(~0u, l1, 1);
    l0 += __shfl_xor_sync(~0u, l0, 2); l1 += __shfl_xor_sync(~0u, l1, 2);
    const float i0 = 1.f / l0, i1 = 1.f / l1;
    __nv_bfloat16* oc0 = P.o + o_idx(h * DH + 2 * q, o_pos(b, wg, r0));
    __nv_bfloat16* oc1 = P.o + o_idx(h * DH + 2 * q, o_pos(b, wg, min(r1, 119)));
#pragma unroll
    for (int n = 0; n < 16; n++) {
      oc0[8 * n * NROWS] = __float2bfloat16(o[n][0] * i0);
      oc0[8 * n * NROWS + 32] = __float2bfloat16(o[n][1] * i0);
      if (r1 < 120) {
        oc1[8 * n * NROWS] = __float2bfloat16(o[n][2] * i1);
        oc1[8 * n * NROWS + 32] = __float2bfloat16(o[n][3] * i1);
      }
    }
  }
}

__device__ __forceinline__ int bk(int ks) { return ks < 48 ? 32 - (ks & 48) + (ks & 15) : ks; }
__device__ __forceinline__ uint32_t x_slot(uint32_t wg, uint32_t j) { return j < 2 ? (2 * wg + j) * XB : (2 * j + wg) * XB; }
__device__ __forceinline__ int row_block(int t) { return t >= 44 ? (t >> 2) - 11 : (t >> 2) + 4; }
__device__ __forceinline__ int cluster_id(int c) {
  const int t = c >= 4 ? c - 4 : c + 62;
  return ROLEMAP == 0 || t < 44 || t >= 60 ? t : t < 46 ? t + 14 : t - 2;
}
__device__ __forceinline__ int unit_batch(int u) { return (u & 63) >> 2; }
__device__ __forceinline__ int unit_head(int u, int rank) { return (u >> 6) * 8 + (u & 3) * 2 + rank; }

template <int NCL>
__global__ void __cluster_dims__(2, 1, 1) __launch_bounds__(384, 1)
fused_attn_kernel(const __grid_constant__ CUtensorMap tm_x, const __grid_constant__ CUtensorMap tm_wq,
                  const __grid_constant__ CUtensorMap tm_k, const __grid_constant__ CUtensorMap tm_v,
                  const __grid_constant__ CUtensorMap tm_o, const __grid_constant__ CUtensorMap tm_wo,
                  const __grid_constant__ Params P) {
  extern __shared__ uint8_t smem_raw[];
  const uint32_t sb = ((uint32_t)__cvta_generic_to_shared(smem_raw) + 1023) & ~1023u;
  const int warp = __shfl_sync(~0u, threadIdx.x >> 5, 0);
  const int lane = threadIdx.x & 31;
  const int rank = blockIdx.x & 1, ncl = NCL ? NCL : gridDim.x >> 1;
  const int id = NCL == 66 ? cluster_id(blockIdx.x >> 1) : blockIdx.x >> 1;
  const int nsingle = NCL == 66 ? 44 : NOTILES;
  const bool dbl = NCL == 66 && id >= 58, gemm = id < nsingle || dbl;

  if (threadIdx.x == 128) asm volatile("prefetch.tensormap [%0];" ::"l"(&tm_x) : "memory");
  if (threadIdx.x == 0) {
    asm volatile("prefetch.tensormap [%0];" ::"l"(&tm_wq) : "memory");
    for (int i = 0; i < 6; i++) {
      mbar_init(sb + BAR_RFULL + 8 * i, 1); mbar_init(sb + BAR_REMPTY + 8 * i, 8);
      mbar_init(sb + BAR_BFULL + 8 * i, 1); mbar_init(sb + BAR_BEMPTY + 8 * i, 16);
    }
    for (int i = 0; i < 8; i++) mbar_init(sb + BAR_XFULL + 8 * i, 1);
    for (int i = 0; i < 4; i++) mbar_init(sb + BAR_XEMPTY + 8 * i, 8);
    for (int i = 0; i < 2; i++) { mbar_init(sb + BAR_STAGE + 8 * i, 4); mbar_init(sb + BAR_LSUM + 8 * i, 4); mbar_init(sb + BAR_INV + 8 * i, 1); }
    asm volatile("fence.mbarrier_init.release.cluster;" ::: "memory");
  }
  __syncwarp();
  asm volatile("barrier.cluster.arrive.relaxed.aligned;" ::: "memory");
  auto first_w = [&](int s) {
    mbar_expect(sb + BAR_RFULL + 8 * s, RING_BYTES);
    tma3d(sb + s * RING_BYTES, &tm_wq, 0, s * 64, 2 * unit_head(id, rank), sb + BAR_RFULL + 8 * s);
  };
  if (threadIdx.x == 0) first_w(0);
  __syncwarp();
  asm volatile("barrier.cluster.wait.aligned;" ::: "memory");
  if (threadIdx.x == 128) {
#pragma unroll 1
    for (int s = 0; s < 2; s++) {
      const uint32_t fb = sb + BAR_XFULL + 32 * rank + 8 * s;
      mbar_expect(fb, XB);
      mbar_expect_cl(mapa(fb, rank ^ 1), XB);
      tma2d_mc(sb + OFF_Q + x_slot(rank, s), &tm_x, s * 64, unit_batch(id) * SQ + rank * 120, fb);
      if (s == 0) first_w(1);
    }
  }
  __syncwarp();

  if (warp >= 8) {
    asm volatile("setmaxnreg.dec.sync.aligned.u32 24;");
    if (warp == 8) {
      uint64_t pol;
      asm volatile("createpolicy.fractional.L2::evict_first.b64 %0, 1.0;" : "=l"(pol));
      Ring r;
      r.slot = 2;
      auto load = [&](const CUtensorMap* m, int c1, int c2, bool ef) {
        mbar_sleep(sb + BAR_REMPTY + 8 * r.slot, r.phase ^ 1);
        if (lane == 0) {
          mbar_expect(sb + BAR_RFULL + 8 * r.slot, RING_BYTES);
          if (ef) tma3d_hint(sb + r.slot * RING_BYTES, m, 0, c1, c2, sb + BAR_RFULL + 8 * r.slot, pol);
          else tma3d(sb + r.slot * RING_BYTES, m, 0, c1, c2, sb + BAR_RFULL + 8 * r.slot);
        }
        r.next();
      };
      for (int u0 = 0; id + u0 < NUNITS; u0 += ncl) {
        const int u = id + u0;
        if (NCL == 66 && u0 == 2 * 66 && !gemm) {
          unsigned t0, t1;
          asm volatile("mov.u32 %0, %globaltimer_lo;" : "=r"(t0));
          do { __nanosleep(200); asm volatile("mov.u32 %0, %globaltimer_lo;" : "=r"(t1)); } while (t1 - t0 < PAUSE_NS);
        }
        const int h = unit_head(u, rank);
        const int krow = (unit_batch(u) * NH + h) * SK;
#pragma unroll 1
        for (int s = u0 == 0 ? 2 : 0; s < 10; s++) {
          load(&tm_wq, s * 64, 2 * h, false);
          const int sp = u0 == 0 ? s - 6 : s;
          if (sp >= 0 && sp < PF_N && lane == 0) l2_prefetch(P.v + (size_t)(krow + (PF_J0 + sp * PF_STEP) * 64) * DH, 16384);
        }
#pragma unroll 1
        for (int j = 0; j <= 16; j++) {
          if (j < 16) load(&tm_k, krow + j * 64, 0, true);
          if (j == 2) load(&tm_v, krow, 0, true);
          if (j > 1) load(&tm_v, krow + (j - 1) * 64, 0, true);
        }
      }
      for (int t = dbl ? 2 * id - 72 : id; t < (dbl ? NOTILES : nsingle); t += ncl) {
        const int row0 = row_block(t) * 256 + rank * 128;
        const int b0 = row0 / SQ, b1 = (row0 + 127) / SQ;
#pragma unroll 1
        for (int ks = 0; ks < 64; ks++) {
          if (dbl ? (ks & 15) == 0 : ks == 0 || ks == 48) {
            const unsigned* c = &g_cnt[((lane & 1 ? b1 : b0) * 4 + (ks || dbl ? ks >> 4 : min(lane >> 1, 2))) * 8];
            unsigned v, n = 0;
            do {
              asm volatile("ld.acquire.gpu.global.u32 %0, [%1];" : "=r"(v) : "l"(c) : "memory");
              if (++n > (1u << 26)) __trap();
            } while (v < 16);
            __syncwarp();
            asm volatile("fence.proxy.async.global;" ::: "memory");
          }
          mbar_wait(sb + BAR_REMPTY + 8 * r.slot, r.phase ^ 1);
          if (lane == 0) {
            mbar_expect(sb + BAR_RFULL + 8 * r.slot, RING_BYTES);
            asm volatile("cp.async.bulk.tensor.4d.shared::cluster.global.mbarrier::complete_tx::bytes.L2::cache_hint [%0], [%1, {%3, %3, %4, %5}], [%2], %6;"
                         ::"r"(sb + r.slot * RING_BYTES), "l"(&tm_o), "r"(sb + BAR_RFULL + 8 * r.slot), "r"(0), "r"((dbl ? ks : bk(ks)) * 8), "r"(row0 >> 6), "l"(pol) : "memory");
          }
          r.next();
        }
      }
      if (lane == 0 && atomicAdd(&g_cnt[64 * 8], 1) == gridDim.x - 1) {
        for (int i = 0; i < 65; i++) g_cnt[i * 8] = 0;
      }
    } else if (warp == 9) {
      if (lane == 0) {
        for (uint32_t it = 0; id + it * ncl < NUNITS; it++) {
          const int row = unit_batch(id + it * ncl) * SQ + rank * 120;
#pragma unroll 1
          for (int s = it == 0 ? 2 : 0; s < 10; s++) {
            const uint32_t j = s & 3, par = ((s >> 2) + (j < 2 ? it : 0)) & 1;
            if (s == 0) mbar_sleep(sb + BAR_XEMPTY, par ^ 1);
            mbar_wait(sb + BAR_XEMPTY + 8 * j, par ^ 1);
            const uint32_t fb = sb + BAR_XFULL + 32 * rank + 8 * j;
            mbar_expect(fb, XB);
            mbar_expect_cl(mapa(fb, rank ^ 1), XB);
            tma2d_mc(sb + OFF_Q + x_slot(rank, j), &tm_x, s * 64, row, fb);
          }
        }
        uint32_t slot = rank, phase = 0;
        if (dbl)
          asm volatile("cp.async.bulk.prefetch.tensor.3d.L2.global [%0, {%1, %2, %3}];" ::"l"(&tm_wo), "r"(0), "r"((2 + ((id >> 1) & 3)) * 64), "r"(((2 * id - 72 + rank) & 3) * 5) : "memory");
        if (gemm) mbar_sleep(sb + BAR_BEMPTY + 8 * rank, 0);
        for (int t = dbl ? 2 * id - 72 + rank : id; t < (dbl ? NOTILES : nsingle); t += ncl) {
#pragma unroll 1
          for (int ks = dbl ? 0 : rank; ks < 64; ks += dbl ? 1 : 2) {
            mbar_wait(sb + BAR_BEMPTY + 8 * slot, phase);
            const uint32_t fb = sb + BAR_BFULL + 8 * slot;
            mbar_expect(fb, BB);
            mbar_expect_cl(mapa(fb, rank ^ 1), BB);
            tma3d_mc(sb + OFF_Q + slot * BB, &tm_wo, 0, (dbl ? ks : bk(ks)) * 64, (t & 3) * 5, fb);
            if (dbl && ks + WO_PF < 64 && (ks & 3) == ((id >> 1) & 3))
              asm volatile("cp.async.bulk.prefetch.tensor.3d.L2.global [%0, {%1, %2, %3}];" ::"l"(&tm_wo), "r"(0), "r"((ks + WO_PF) * 64), "r"((t & 3) * 5) : "memory");
            slot += 2;
            if (slot >= 6) { slot -= 6; phase ^= 1; }
          }
        }
      }
    } else {
      const int wg = warp - 10;
      {
        mbar_wait(sb + BAR_RFULL, 0);
        const __nv_bfloat16* xs = P.x + (size_t)(unit_batch(id) * SQ + ((id & 3) * 2 + rank) * 30 + min(lane, 29)) * DM + 256 + wg * 64;
#pragma unroll
        for (int i = 0; i < 3; i++) asm volatile("prefetch.global.L2 [%0];" ::"l"(xs + i * 128));
        if (lane < 16) asm volatile("prefetch.global.L2 [%0];" ::"l"(P.wq + (size_t)(384 + unit_batch(id) * 16 + lane) * HD + unit_head(id, rank) * DH + wg * 64));
      }
      for (uint32_t it = 0; id + it * ncl < NUNITS; it++) {
        const int u = id + it * ncl;
        mbar_sleep(sb + BAR_LSUM + 8 * wg, it & 1);
        float l4[4], v[4];
        const uint32_t a = sb + OFF_L2 + wg * 2048 + (fresh_tid() & 31) * 16;
        asm volatile("ld.shared.v4.f32 {%0, %1, %2, %3}, [%4];" : "=f"(l4[0]), "=f"(l4[1]), "=f"(l4[2]), "=f"(l4[3]) : "r"(a) : "memory");
#pragma unroll
        for (int g = 1; g < 4; g++) {
          asm volatile("ld.shared.v4.f32 {%0, %1, %2, %3}, [%4];" : "=f"(v[0]), "=f"(v[1]), "=f"(v[2]), "=f"(v[3]) : "r"(a + g * 512) : "memory");
#pragma unroll
          for (int c = 0; c < 4; c++) l4[c] += v[c];
        }
#pragma unroll
        for (int c = 0; c < 4; c++) {
          float inv;
          asm("rcp.approx.ftz.f32 %0, %1;" : "=f"(inv) : "f"(l4[c]));
          l4[c] = l4[c] >= L_MIN && l4[c] <= L_MAX ? inv : __uint_as_float(0x7FFFFFFFu);
        }
        const uint32_t h0 = pack(l4[0], l4[1]), h1 = pack(l4[2], l4[3]);
        const uint32_t e0 = pack(l4[0] - __uint_as_float(h0 << 16), l4[1] - __uint_as_float(h0 & 0xFFFF0000u));
        const uint32_t e1 = pack(l4[2] - __uint_as_float(h1 << 16), l4[3] - __uint_as_float(h1 & 0xFFFF0000u));
        const uint32_t tid = fresh_tid();
        asm volatile("st.shared.v4.u32 [%0], {%1, %2, %3, %4};" ::"r"(sb + OFF_INV + wg * 640 + (tid & 3) * 144 + (tid & 28) * 4), "r"(h0), "r"(e0), "r"(h1), "r"(e1) : "memory");
        __syncwarp();
        warp_arrive(sb + BAR_INV + 8 * wg);
        mbar_sleep(sb + BAR_STAGE + 8 * wg, it & 1);
        if (lane == 0) {
          __threadfence();
          asm volatile("red.relaxed.gpu.global.add.u32 [%0], 1;" ::"l"(&g_cnt[(unit_batch(u) * 4 + (u >> 6)) * 8]) : "memory");
        }
        __syncwarp();
      }
    }
  } else {
    asm volatile("setmaxnreg.inc.sync.aligned.u32 240;");
    const int wg = warp >> 2, w = warp & 3;
    const uint32_t qreg = sb + OFF_Q + wg * 2 * XB, preg = sb + OFF_P + (2 + wg) * XB;
    const uint32_t st_off = ((lane >> 4) * 8 + (lane & 7)) * 128 + (((2 * w + ((lane >> 3) & 1)) ^ (lane & 7)) << 4);
    const uint32_t xempty = mapa(sb + BAR_XEMPTY, wg);
    Ring r;
    uint32_t it = 0;
    const uint32_t qd = (qreg & 0x3FFFF) >> 4, pd = (preg & 0x3FFFF) >> 4;
    auto ring_addr = [&]() { return ((sb & 0x3FFFF) + r.slot * RING_BYTES) >> 4; };
    auto ring_wait = [&]() { mbar_wait(sb + BAR_RFULL + 8 * r.slot, r.phase); };
    auto release = [&](uint32_t slot) { warp_arrive(sb + BAR_REMPTY + 8 * slot); };
    auto turn_wait = [&]() {
      if (wg == 0) asm volatile("bar.sync 3, 256;" ::: "memory");
      else asm volatile("bar.sync 4, 256;" ::: "memory");
    };
    auto turn_pass = [&]() {
      if (wg == 0) asm volatile("bar.arrive 4, 256;" ::: "memory");
      else asm volatile("bar.arrive 3, 256;" ::: "memory");
    };

    uint32_t chk = 0;
    auto sum_l = [&](const float (&l)[30], uint32_t tid) {
      float a[16], b[8], c[4];
      const bool b4 = tid & 16, b3 = tid & 8, b2 = tid & 4;
#pragma unroll
      for (int i = 0; i < 16; i++) {
        const float hi = i < 14 ? l[(16 + i) % 30] : 1.f;
        a[i] = (b4 ? hi : l[i]) + __shfl_xor_sync(~0u, b4 ? l[i] : hi, 16);
      }
#pragma unroll
      for (int i = 0; i < 8; i++) b[i] = (b3 ? a[8 + i] : a[i]) + __shfl_xor_sync(~0u, b3 ? a[i] : a[8 + i], 8);
#pragma unroll
      for (int i = 0; i < 4; i++) c[i] = (b2 ? b[4 + i] : b[i]) + __shfl_xor_sync(~0u, b2 ? b[i] : b[4 + i], 4);
      asm volatile("st.shared.v4.f32 [%0], {%1, %2, %3, %4};" ::"r"(sb + OFF_L2 + tid * 16), "f"(c[0]), "f"(c[1]),
                   "f"(c[2]), "f"(c[3]) : "memory");
      __syncwarp();
      warp_arrive(sb + BAR_LSUM + 8 * wg);
    };
    auto load_inv = [&](uint32_t (&iv)[30], uint32_t parity) {
      const int lane = fresh_tid() & 31;
      mbar_wait(sb + BAR_INV + 8 * wg, parity);
      chk = 0;
#pragma unroll
      for (int j = 0; j < 7; j++)
        asm volatile("ld.shared.v4.u32 {%0, %1, %2, %3}, [%4];" : "=r"(iv[4 * j]), "=r"(iv[4 * j + 1]), "=r"(iv[4 * j + 2]), "=r"(iv[4 * j + 3])
                     : "r"(sb + OFF_INV + wg * 640 + (lane & 3) * 144 + j * 16) : "memory");
      asm volatile("ld.shared.v2.u32 {%0, %1}, [%2];" : "=r"(iv[28]), "=r"(iv[29]) : "r"(sb + OFF_INV + wg * 640 + (lane & 3) * 144 + 112) : "memory");
    };
    auto norm = [&](uint32_t (&n)[8], const uint32_t (&po)[60], const uint32_t (&iv)[30], auto part) {
      constexpr int k = decltype(part)::value >> 1, j0 = (decltype(part)::value & 1) * 8;
#pragma unroll
      for (int j = 0; j < 8; j++)
        n[j] = j0 + j < 15 ? hfma2(po[15 * k + (j0 + j) % 15], iv[2 * ((j0 + j) % 15)], hfma2(po[15 * k + (j0 + j) % 15], iv[2 * ((j0 + j) % 15) + 1], 0x80008000u)) : 0x3F803F80u;
#pragma unroll
      for (int j = 0; j < 8; j += 2) chk = hfma2(n[j], n[j + 1], chk);
    };
    int od1, od2;
    auto store = [&](const uint32_t (&n)[8], const char* optr, auto part) {
      constexpr int k = decltype(part)::value >> 1, off = (8 * (k & 1) + 64 * (k >> 1)) * NROWS * 2;
      if ((decltype(part)::value & 1) == 0)
        asm volatile(
            "{\n.reg .pred p;\nsetp.ne.u64 p, %8, 0;\n"
            "@p st.global.v4.u32 [%8 + %9], {%0, %1, %2, %3};\n@p st.global.v4.u32 [%8 + %9 + 512], {%4, %5, %6, %7};\n}\n"
            ::"r"(n[0]), "r"(n[1]), "r"(n[2]), "r"(n[3]), "r"(n[4]), "r"(n[5]), "r"(n[6]), "r"(n[7]), "l"(optr), "n"(off) : "memory");
      else
        asm volatile(
            "{\n.reg .pred p;\n.reg .b64 b, c;\nsetp.ne.u64 p, %7, 0;\nmad.wide.s32 b, %9, 1, %7;\nmad.wide.s32 c, %10, 1, %7;\n"
            "@p st.global.v4.u32 [%7 + %8 + 1024], {%0, %1, %2, %3};\n@p st.global.v2.u32 [b + %8], {%4, %5};\n@p st.global.u32 [c + %8], %6;\n}\n"
            ::"r"(n[0]), "r"(n[1]), "r"(n[2]), "r"(n[3]), "r"(n[4]), "r"(n[5]), "r"(n[6]), "l"(optr), "n"(off), "r"(od1), "r"(od2) : "memory");
    };
    auto put = [&](const uint32_t (&po)[60], const uint32_t (&iv)[30], const char* optr, auto part) {
      uint32_t n[8];
      norm(n, po, iv, part);
      store(n, optr, part);
    };
    auto out_ptr = [&](int u) {
      const int lane = fresh_tid() & 31;
      const int k = unit_head(u, rank) * DH + 16 * w + (lane >> 2), b = unit_batch(u), q = lane & 3;
      const uint32_t i0 = o_idx(k, o_pos(b, wg, 2 * q));
      od1 = 2 * (int)(o_idx(k, o_pos(b, wg, 96 + 2 * q)) - i0);
      od2 = 2 * (int)(o_idx(k, o_pos(b, wg, 112 + 2 * q)) - i0);
      return reinterpret_cast<const char*>(P.o + i0);
    };
    auto unsafe = [&](bool valid) {
      const bool b = valid && ((chk & 0x7F80u) == 0x7F80u || (chk & 0x7F800000u) == 0x7F800000u);
      return __any_sync(~0u, bar_red_or(wg, b));
    };
    auto publish = [&]() { __syncwarp(); warp_arrive(sb + BAR_STAGE + 8 * wg); };

    uint32_t po[60];
#pragma unroll
    for (int i = 0; i < 60; i++) po[i] = 0;
    float o0[60], o1[60];
    ring_wait();
    mbar_wait(sb + BAR_XFULL + 32 * wg, 0);
    wg_fence();
    mma_tn(o0, o1, ring_addr(), qd, 0);
    wg_commit();
    while (true) {
      uint32_t prev = r.slot;
      r.next();
      auto qstep = [&](int s) {
        const uint32_t j = s & 3, par = ((s >> 2) + (j < 2 ? it : 0)) & 1;
        ring_wait();
        mbar_wait(sb + BAR_XFULL + 32 * wg + 8 * j, par);
        if (s >= ALT_FROM) turn_wait();
        wg_fence();
        mma_tn(o0, o1, ring_addr(), ((sb & 0x3FFFF) + OFF_Q + x_slot(wg, j)) >> 4, 1);
        wg_commit();
        if (s >= ALT_FROM || (s == ALT_FROM - 1 && wg == 1)) turn_pass();
        if (s <= 4) {
          wg_wait<1>();
          release(prev);
          warp_arrive_cl(xempty + 8 * ((s - 1) & 3));
        }
        prev = r.slot;
        r.next();
      };
      auto qdone = [&](int s) {
        wg_wait<0>();
        release(prev);
        if (s <= 5) warp_arrive_cl(xempty + 8 * (s & 3));
      };
      qstep(1);
      const int up = id + ((int)it - 1) * ncl;
      const char* optr = out_ptr(up);
      if (it == 0) optr = nullptr;
      uint32_t n7[8];
      {
        uint32_t iv[30];
        load_inv(iv, (it + 1) & 1); put(po, iv, optr, IC<0>());
        qstep(2); put(po, iv, optr, IC<1>());
        qstep(3); put(po, iv, optr, IC<2>());
        qstep(4); put(po, iv, optr, IC<3>()); qdone(4);
        qstep(5); put(po, iv, optr, IC<4>()); qdone(5);
        qstep(6); put(po, iv, optr, IC<5>()); qdone(6);
        qstep(7); put(po, iv, optr, IC<6>()); norm(n7, po, iv, IC<7>()); qdone(7);
      }
      ring_wait();
      mbar_wait(sb + BAR_XFULL + 32 * wg, it & 1);
      turn_wait();
      wg_fence();
      mma_tn(o0, o1, ring_addr(), qd, 1);
      wg_commit();
      prev = r.slot;
      r.next();
      ring_wait();
      mbar_wait(sb + BAR_XFULL + 32 * wg + 8, it & 1);
      wg_fence();
      mma_tn_split(o0, o1, ring_addr(), qd + (XB >> 4));
      turn_pass();
      wg_wait<2>();
      release(prev);
      auto put_q = [&](const float (&o)[60], uint32_t dst) {
#pragma unroll
        for (int j = 0; j < 14; j += 2)
          stsm4t(dst + j * 1024, pack(o[4 * j] * QSCALE, o[4 * j + 1] * QSCALE), pack(o[4 * j + 2] * QSCALE, o[4 * j + 3] * QSCALE),
                 pack(o[4 * j + 4] * QSCALE, o[4 * j + 5] * QSCALE), pack(o[4 * j + 6] * QSCALE, o[4 * j + 7] * QSCALE));
        stsm2t(dst + 14 * 1024, pack(o[56] * QSCALE, o[57] * QSCALE), pack(o[58] * QSCALE, o[59] * QSCALE));
      };
      wg_wait<1>();
      reg_fence(o0);
      const bool redo = unsafe(it > 0);
      put_q(o0, qreg + st_off);
      wg_wait<0>();
      reg_fence(o1);
      release(r.slot);
      r.next();
      bar_sync(wg);
      put_q(o1, qreg + XB + st_off);
      fence_async_smem();
      if (redo) {
        slow_path(P, unit_batch(up), unit_head(up, rank), wg, w, fresh_tid() & 31);
        optr = nullptr;
      }

      float sc[60], l[30];
      uint32_t slot0 = r.slot;
      ring_wait();
      turn_wait();
      wg_fence();
      mma_qk(sc, ring_addr(), qd);
      wg_commit();
      r.next();
      uint32_t slot1 = r.slot;
      ring_wait();
      wg_fence();
      mma_qk(o1, ring_addr(), qd);
      wg_commit();
      r.next();
      turn_pass();
      store(n7, optr, IC<7>());
      wg_wait<1>();
      reg_fence(sc);
      release(slot0);
      exp_store<0, 15, true>(sc, l, preg + st_off);
      slot0 = r.slot;
      ring_wait();
      wg_fence();
      mma_qk(sc, ring_addr(), qd);
      wg_commit();
      r.next();
      wg_wait<1>();
      reg_fence(o1);
      release(slot1);
      exp_store<0, 15>(o1, l, preg - 2 * XB + st_off);
      fence_async_smem();
      slot1 = r.slot;
      ring_wait();
      turn_wait();
      wg_fence();
      mma_tn(o0, o1, ring_addr(), pd, 0);
      wg_commit();
      r.next();
      ring_wait();
      wg_fence();
      mma_tn(o0, o1, ring_addr(), pd - (2 * XB >> 4), 1);
      wg_commit();
      turn_pass();
      if (it > 0) publish();
      wg_wait<1>();
      reg_fence(sc);
      release(slot0);
      release(slot1);
      bar_sync(wg);
      exp_store<0, VREL>(sc, l, preg + st_off);
      wg_wait<0>();
      reg_fence(o0); reg_fence(o1);
      release(r.slot);
      r.next();
      exp_store<VREL, 15>(sc, l, preg + st_off);
      fence_async_smem();
      const bool more = id + ((int)it + 1) * ncl < NUNITS;
      uint32_t pw = preg + st_off;
#pragma unroll 1
      for (int s = 3; s < 16; s++) {
        const uint32_t kslot = r.slot;
        asm volatile("add.u32 %0, %0, %1;" : "+r"(pw) : "r"(s & 1 ? -2 * XB : 2 * XB));
        ring_wait();
        turn_wait();
        wg_fence();
        mma_qk(sc, ring_addr(), qd);
        wg_commit();
        r.next();
        ring_wait();
        wg_fence();
        mma_tn(o0, o1, ring_addr(), pd - ((s - 1) & 1) * (2 * XB >> 4), 1);
        wg_commit();
        if (wg == 0 || s < 15) turn_pass();
        wg_wait<1>();
        reg_fence(sc);
        release(kslot);
        if (s == 15) {
          if (more) { warp_arrive_cl(xempty); warp_arrive_cl(xempty + 8); }
          else if (gemm) for (int i = 0; i < 3; i++) warp_arrive_cl(mapa(sb + BAR_BEMPTY + 8 * i, i & 1));
        }
        exp_store<0, VREL>(sc, l, pw);
        wg_wait<0>();
        reg_fence(o0); reg_fence(o1);
        release(r.slot);
        r.next();
        exp_store<VREL, 15>(sc, l, pw);
        fence_async_smem();
      }
      const uint32_t tid = fresh_tid();
      bar_sync(wg);
      ring_wait();
      wg_fence();
      mma_tn_split(o0, o1, ring_addr(), pd - (2 * XB >> 4));
      sum_l(l, tid);
      const uint32_t vslot = r.slot;
      r.next();
      it++;
      auto pack_o = [&](const float (&o)[60], int first) {
#pragma unroll
        for (int j = 0; j < 15; j++) { po[first + j] = pack(o[4 * j], o[4 * j + 1]); po[first + 15 + j] = pack(o[4 * j + 2], o[4 * j + 3]); }
      };
      if (!more) {
        wg_wait<0>();
        reg_fence(o0); reg_fence(o1);
        release(vslot);
        if (gemm) for (int i = 3; i < 6; i++) warp_arrive_cl(mapa(sb + BAR_BEMPTY + 8 * i, i & 1));
        pack_o(o0, 0); pack_o(o1, 30);
        break;
      }
      ring_wait();
      mbar_wait(sb + BAR_XFULL + 32 * wg, it & 1);
      wg_wait<1>();
      reg_fence(o0);
      pack_o(o0, 0);
      wg_fence();
#pragma unroll
      for (int k = 0; k < 4; k++) wgmma_n120<1, 0>(o0, ring_addr() + k * 128, HI128, qd + k * 2, HI128, k != 0);
      wg_commit();
      wg_wait<1>();
      reg_fence(o1);
      pack_o(o1, 30);
      wg_fence();
#pragma unroll
      for (int k = 0; k < 4; k++) wgmma_n120<1, 0>(o1, ring_addr() + 512 + k * 128, HI128, qd + k * 2, HI128, k != 0);
      wg_commit();
      release(vslot);
      warp_arrive_cl(xempty + 16); warp_arrive_cl(xempty + 24);
    }
    const int u = id + ((int)it - 1) * ncl;
    uint32_t pb[60];
#pragma unroll
    for (int i = 0; i < 60; i++) pb[i] = NCL != 66 ? po[i] ^ (gridDim.y - 1) : po[i];

    uint32_t bslot = 0, bphase = 0;
    auto out_row = [&](int lane) {
      const int row = lane & 15;
      return sb + wg * 8192 + (row < 12 ? w * RING_BYTES + row * 656 : (4 + (w >> 1)) * RING_BYTES + ((w & 1) * 4 + row - 12) * 656);
    };
    auto out_stage = [&](const float (&acc)[80], uint32_t col_off) {
      const int lane = fresh_tid() & 31;
      const uint32_t sa = out_row(lane) + col_off + (lane >> 4) * 16;
#pragma unroll
      for (int j = 0; j < 20; j += 2)
        asm volatile("stmatrix.sync.aligned.m8n8.x4.shared.b16 [%0], {%1,%2,%3,%4};" ::"r"(sa + j * 16), "r"(pack(acc[4 * j], acc[4 * j + 1])),
                     "r"(pack(acc[4 * j + 2], acc[4 * j + 3])), "r"(pack(acc[4 * j + 4], acc[4 * j + 5])), "r"(pack(acc[4 * j + 6], acc[4 * j + 7])) : "memory");
    };
    auto out_store = [&](int t, uint32_t bytes) {
      const int lane = fresh_tid() & 31;
      if (wg == 1) {
        __syncwarp();
#pragma unroll 1
        for (int h = 0; h < 2; h++) {
          const int row = h * 8 + (lane >> 2);
          const uint32_t src = out_row(row) + (lane & 3) * 16;
          char* dst = reinterpret_cast<char*>(P.out + (size_t)o_row(row_block(t) * 256 + rank * 128 + 64 + w * 16 + row) * DM + (t & 3) * 160) + (lane & 3) * 16;
#pragma unroll 1
          for (uint32_t c = 0; c < bytes; c += 320) {
            uint4 v[5];
#pragma unroll
            for (int i = 0; i < 5; i++)
              asm volatile("ld.shared.v4.u32 {%0, %1, %2, %3}, [%4];" : "=r"(v[i].x), "=r"(v[i].y), "=r"(v[i].z), "=r"(v[i].w) : "r"(src + c + i * 64) : "memory");
#pragma unroll
            for (int i = 0; i < 5; i++) *reinterpret_cast<uint4*>(dst + c + i * 64) = v[i];
          }
        }
        return;
      }
      fence_async_smem();
      __syncwarp();
      if (lane < 16) {
        __nv_bfloat16* dst = P.out + (size_t)o_row(row_block(t) * 256 + rank * 128 + wg * 64 + w * 16 + lane) * DM + (t & 3) * 160;
        asm volatile("cp.async.bulk.global.shared::cta.bulk_group [%0], [%1], %2;" ::"l"(dst), "r"(out_row(lane)), "r"(bytes) : "memory");
        asm volatile("cp.async.bulk.commit_group;" ::: "memory");
        asm volatile("cp.async.bulk.wait_group.read 0;" ::: "memory");
      }
    };
    for (int t = id; t == id || (NCL != 66 && t < nsingle); t += ncl) {
      float acc[80];
      uint32_t prev = 0, bprev = 0;
      const bool tile = t < nsingle;
      const bool last = NCL == 66 || t + ncl >= nsingle;
      auto bstep = [&](int ks, int accf) {
        ring_wait();
        mbar_wait(sb + BAR_BFULL + 8 * bslot, bphase);
        wg_fence();
        const uint32_t a = ring_addr() + wg * 512, bd = (((sb & 0x3FFFF) + OFF_Q + bslot * BB) >> 4) | ((4096u >> 4) << 16);
#pragma unroll
        for (int k = 0; k < 4; k++) wgmma_n160<1, 1>(acc, a + LBO64A + k * 128, HI64A, bd + k * 64, HI64, k == 0 ? accf : 1);
        wg_commit();
        if (ks > 0) {
          wg_wait<1>();
          release(prev);
          if (ks < 59 || !last) warp_arrive_cl(mapa(sb + BAR_BEMPTY + 8 * bprev, bprev & 1));
        }
        prev = r.slot; bprev = bslot;
        r.next();
        if (++bslot == 6) { bslot = 0; bphase ^= 1; }
      };
      const char* optr;
      uint32_t iv[30], n2[8], n3[8], n4[8], n5[8], n6[8], n7[8];
      if (tile) {
        bstep(0, 0);
        bstep(1, 1);
        optr = out_ptr(u);
        if (t != id) optr = nullptr;
        load_inv(iv, (it + 1) & 1);
#pragma unroll 1
        for (int ks = 2; ks < 17; ks++) {
          bstep(ks, 1);
          switch (ks) {
            case 2: put(pb, iv, optr, IC<0>()); break;
            case 4: put(pb, iv, optr, IC<1>()); break;
            case 6: put(pb, iv, optr, IC<2>()); break;
            case 8: put(pb, iv, optr, IC<3>()); break;
            case 10: put(pb, iv, optr, IC<4>()); break;
            case 12: put(pb, iv, optr, IC<5>()); break;
            case 14: put(pb, iv, optr, IC<6>()); break;
            case 16: put(pb, iv, optr, IC<7>()); break;
            default: break;
          }
        }
        wg_wait<0>();
        reg_fence(acc);
#pragma unroll
        for (int i = 0; i < 8; i++) n2[i] = n3[i] = n4[i] = n5[i] = n6[i] = n7[i] = 0;
      } else {
        Ring r2 = r;
        auto first = [&](int ks) {
          if (gemm) { mbar_wait(sb + BAR_RFULL + 8 * r2.slot, r2.phase); mbar_wait(sb + BAR_BFULL + 16 * ks, 0); }
          wg_fence();
          const uint32_t a = (((sb & 0x3FFFF) + r2.slot * RING_BYTES) >> 4) + wg * 512;
          const uint32_t bd = (((sb & 0x3FFFF) + OFF_Q + 2 * ks * BB) >> 4) | ((4096u >> 4) << 16);
#pragma unroll
          for (int k = 0; k < 4; k++) wgmma_n160<1, 1>(acc, a + LBO64A + k * 128, HI64A, bd + k * 64, HI64, k + ks != 0);
          wg_commit();
          r2.next();
        };
        first(0);
        first(1);
        optr = out_ptr(u);
        load_inv(iv, (it + 1) & 1);
        put(pb, iv, optr, IC<0>()); put(pb, iv, optr, IC<1>());
        norm(n2, pb, iv, IC<2>()); norm(n3, pb, iv, IC<3>()); norm(n4, pb, iv, IC<4>());
        norm(n5, pb, iv, IC<5>()); norm(n6, pb, iv, IC<6>()); norm(n7, pb, iv, IC<7>());
        wg_wait<0>();
        reg_fence(acc);
      }
      if (unsafe(t == id)) {
        slow_path(P, unit_batch(u), unit_head(u, rank), wg, w, fresh_tid() & 31);
        optr = nullptr;
#pragma unroll
        for (int i = 0; i < 8; i++) n2[i] = n3[i] = n4[i] = n5[i] = n6[i] = n7[i] = 0;
      }
      if (tile && t == id) publish();
      if (!tile && !gemm) {
        store(n2, optr, IC<2>()); store(n3, optr, IC<3>()); store(n4, optr, IC<4>()); store(n5, optr, IC<5>()); store(n6, optr, IC<6>()); store(n7, optr, IC<7>());
        publish();
        break;
      }
      if (!tile) {
        float ac1[80];
        auto half = [&](float (&ac)[80], bool rel, int accf) {
          mbar_wait(sb + BAR_BFULL + 8 * bslot, bphase);
          wg_fence();
          const uint32_t a = ring_addr() + wg * 512, bd = (((sb & 0x3FFFF) + OFF_Q + bslot * BB) >> 4) | ((4096u >> 4) << 16);
#pragma unroll
          for (int k = 0; k < 4; k++) wgmma_n160<1, 1>(ac, a + LBO64A + k * 128, HI64A, bd + k * 64, HI64, k == 0 ? accf : 1);
          wg_commit();
          wg_wait<1>();
          if (rel) warp_arrive_cl(mapa(sb + BAR_BEMPTY + 8 * bprev, bprev & 1));
          bprev = bslot;
        };
        auto dstep = [&](int ks) {
          ring_wait();
          half(acc, ks < 62, 1);
          release(prev);
          bslot++;
          half(ac1, ks < 61, 1);
          if (++bslot == 6) { bslot = 0; bphase ^= 1; }
          prev = r.slot; r.next();
        };
        warp_arrive_cl(mapa(sb + BAR_BEMPTY, 0));
        bprev = 2; bslot = 1;
        half(ac1, true, 0);
        prev = r.slot; r.next(); bslot = 3;
        half(ac1, true, 1);
        release(prev); prev = r.slot; r.next(); bslot = 4;
#pragma unroll 1
        for (int ks = 2; ks < 8; ks++) {
          dstep(ks);
          switch (ks) {
            case 2: store(n2, optr, IC<2>()); break;
            case 3: store(n3, optr, IC<3>()); break;
            case 4: store(n4, optr, IC<4>()); break;
            case 5: store(n5, optr, IC<5>()); break;
            case 6: store(n6, optr, IC<6>()); break;
            default: store(n7, optr, IC<7>()); break;
          }
        }
        publish();
#pragma unroll 1
        for (int ks = 8; ks < 64; ks++) {
          if (wg == 1 && ks == 62) turn_wait();
          dstep(ks);
        }
        if (wg == 0) turn_pass();
        wg_wait<0>();
        reg_fence(acc); reg_fence(ac1);
        bar_sync(wg);
        out_stage(ac1, 320);
      } else {
#pragma unroll 1
        for (int ks = 17; ks < 64; ks++) {
          if (wg == 1 && ks == 64 - END_SKEW) turn_wait();
          bstep(ks, 1);
        }
        if (wg == 0) turn_pass();
        wg_wait<0>();
        reg_fence(acc);
        release(prev);
        if (!last) warp_arrive_cl(mapa(sb + BAR_BEMPTY + 8 * bprev, bprev & 1));
      }
      const int pos0 = row_block(t) * 256 + rank * 128 + wg * 64 + w * 16;
      if (last) {
        bar_sync(wg);
        out_stage(acc, 0);
        out_store(tile ? t : 2 * id - 72, tile ? 320 : 640);
      } else {
        const int lane = fresh_tid() & 31;
        __nv_bfloat16* op0 = P.out + (size_t)o_row(pos0 + (lane >> 2)) * DM + (t & 3) * 160 + (lane & 3) * 2;
        __nv_bfloat16* op1 = P.out + (size_t)o_row(pos0 + (lane >> 2) + 8) * DM + (t & 3) * 160 + (lane & 3) * 2;
#pragma unroll
        for (int j = 0; j < 20; j++) {
          *reinterpret_cast<uint32_t*>(op0 + j * 8) = pack(acc[4 * j], acc[4 * j + 1]);
          *reinterpret_cast<uint32_t*>(op1 + j * 8) = pack(acc[4 * j + 2], acc[4 * j + 3]);
        }
      }
#pragma unroll
      for (int i = 0; i < 60; i++) pb[i] = 0;
    }
  }
}

typedef CUresult (*EncodeFn)(CUtensorMap*, CUtensorMapDataType, cuuint32_t, void*, const cuuint64_t*, const cuuint64_t*,
                             const cuuint32_t*, const cuuint32_t*, CUtensorMapInterleave, CUtensorMapSwizzle,
                             CUtensorMapL2promotion, CUtensorMapFloatOOBfill);

void make_map(EncodeFn enc, CUtensorMap* m, const void* p, int rank, const cuuint64_t* dims, const cuuint64_t* strides,
              const cuuint32_t* box, CUtensorMapSwizzle sw, CUtensorMapL2promotion promo) {
  cuuint32_t es[4] = {1, 1, 1, 1};
  enc(m, CU_TENSOR_MAP_DATA_TYPE_BFLOAT16, rank, const_cast<void*>(p), dims, strides, box, es, CU_TENSOR_MAP_INTERLEAVE_NONE, sw,
      promo, CU_TENSOR_MAP_FLOAT_OOB_FILL_NONE);
}

}

extern "C" void kernel_launch(void* const* d_in, const int* in_sizes, int n_in, void* d_out, int out_size) {
  static EncodeFn enc = nullptr;
  static int nclusters = 0;
  static void* o_ptr = nullptr;
  if (!enc) {
    cudaDriverEntryPointQueryResult qr;
    cudaGetDriverEntryPoint("cuTensorMapEncodeTiled", (void**)&enc, cudaEnableDefault, &qr);
    cudaFuncSetAttribute(fused_attn_kernel<66>, cudaFuncAttributeMaxDynamicSharedMemorySize, SMEM_BYTES);
    cudaFuncSetAttribute(fused_attn_kernel<0>, cudaFuncAttributeMaxDynamicSharedMemorySize, SMEM_BYTES);
    cudaGetSymbolAddress(&o_ptr, g_o);
    cudaLaunchConfig_t cfg = {};
    cfg.gridDim = 128; cfg.blockDim = 384; cfg.dynamicSmemBytes = SMEM_BYTES;
    cudaLaunchAttribute at; at.id = cudaLaunchAttributeClusterDimension;
    at.val.clusterDim.x = 2; at.val.clusterDim.y = 1; at.val.clusterDim.z = 1;
    cfg.attrs = &at; cfg.numAttrs = 1;
    int n = 0;
    cudaOccupancyMaxActiveClusters(&n, fused_attn_kernel<66>, &cfg);
    nclusters = n >= 66 ? MAXCL : (n >= 64 || n <= 0 ? 64 : n);
  }
  const __nv_bfloat16* x = (const __nv_bfloat16*)d_in[0];
  const __nv_bfloat16* k = (const __nv_bfloat16*)d_in[1];
  const __nv_bfloat16* v = (const __nv_bfloat16*)d_in[2];
  const __nv_bfloat16* wq = (const __nv_bfloat16*)d_in[3];
  const __nv_bfloat16* wo = (const __nv_bfloat16*)d_in[4];
  CUtensorMap tm_x, tm_wq, tm_k, tm_v, tm_o, tm_wo;
  const auto S128 = CU_TENSOR_MAP_SWIZZLE_128B;
  const auto P128 = CU_TENSOR_MAP_L2_PROMOTION_L2_128B, P256 = CU_TENSOR_MAP_L2_PROMOTION_L2_256B;
  { cuuint64_t d[2] = {DM, NB * SQ}, s[1] = {DM * 2}; cuuint32_t b[2] = {64, 120}; make_map(enc, &tm_x, x, 2, d, s, b, S128, P128); }
  { cuuint64_t d[3] = {64, DM, HD / 64}, s[2] = {HD * 2, 128}; cuuint32_t b[3] = {64, 64, 2}; make_map(enc, &tm_wq, wq, 3, d, s, b, S128, P256); }
  { cuuint64_t d[3] = {64, NB * NH * SK, 2}, s[2] = {DH * 2, 128}; cuuint32_t b[3] = {64, 64, 2};
    make_map(enc, &tm_k, k, 3, d, s, b, S128, P128); make_map(enc, &tm_v, v, 3, d, s, b, S128, P128); }
  { cuuint64_t d[4] = {256, 2, HD / 8, NROWS / 64}, s[3] = {512, NROWS * 16, 1024}; cuuint32_t b[4] = {256, 2, 8, 2};
    make_map(enc, &tm_o, o_ptr, 4, d, s, b, CU_TENSOR_MAP_SWIZZLE_NONE, P256); }
  { cuuint64_t d[3] = {32, HD, DM / 32}, s[2] = {DM * 2, 64}; cuuint32_t b[3] = {32, 64, 5};
    make_map(enc, &tm_wo, wo, 3, d, s, b, CU_TENSOR_MAP_SWIZZLE_64B, P128); }
  Params P{x, k, v, wq, (__nv_bfloat16*)d_out, (__nv_bfloat16*)o_ptr};
  if (nclusters == 66) fused_attn_kernel<66><<<132, 384, SMEM_BYTES>>>(tm_x, tm_wq, tm_k, tm_v, tm_o, tm_wo, P);
  else fused_attn_kernel<0><<<2 * nclusters, 384, SMEM_BYTES>>>(tm_x, tm_wq, tm_k, tm_v, tm_o, tm_wo, P);
}
```

```cpp
#include <cuda_runtime.h>
#include <cuda.h>
#include <cuda_bf16.h>
#include <stdint.h>

namespace {

constexpr int NB = 16, SQ = 240, DM = 640, NH = 32, SK = 1024, DH = 128, HD = NH * DH;
constexpr int NROWS = NB * SQ;
constexpr int NUNITS = 256;
#define ALT_FROM 4
#define END_SKEW 5
#define VREL 8
#define PF_N 4
#define PF_J0 3
#define PF_STEP 3
#define WO_PF 6
#define PAUSE_NS 11000
#define UMAP 1
#define ROLEMAP 0
#define MAXCL 66
constexpr int NOTILES = 60;
constexpr float QSCALE = 0.08838834764831845f * 1.4426950408889634f;
constexpr float L_MIN = 1.f;
constexpr float L_MAX = 1.152921504606846976e18f;

constexpr uint32_t RING_SLOTS = 6, RING_BYTES = 16384;
constexpr uint32_t XB = 15360;
constexpr uint32_t BB = 20480;
constexpr uint32_t OFF_Q = RING_SLOTS * RING_BYTES;
constexpr uint32_t OFF_P = OFF_Q + 4 * XB;
constexpr uint32_t OFF_INV = OFF_P + 4 * XB;
constexpr uint32_t OFF_L2 = OFF_INV + 1280;
constexpr uint32_t OFF_BAR = OFF_L2 + 4096;
constexpr uint32_t BAR_RFULL = OFF_BAR, BAR_REMPTY = BAR_RFULL + 48, BAR_XFULL = BAR_REMPTY + 48,
    BAR_XEMPTY = BAR_XFULL + 64, BAR_BFULL = BAR_XEMPTY + 32, BAR_BEMPTY = BAR_BFULL + 48, BAR_STAGE = BAR_BEMPTY + 48;
constexpr uint32_t BAR_LSUM = BAR_STAGE + 16, BAR_INV = BAR_LSUM + 16;
constexpr uint32_t OFF_TR = BAR_INV + 16;
constexpr uint32_t SMEM_BYTES = OFF_TR + 1024;

constexpr uint32_t HI128 = (1u << 30) | (1024 >> 4);
constexpr uint32_t HI64 = (2u << 30) | (512 >> 4);
constexpr uint32_t HI64A = (2u << 30) | (1024 >> 4), LBO64A = (512u >> 4) << 16;

__device__ __align__(1024) __nv_bfloat16 g_o[HD * NROWS];
__device__ __align__(128) unsigned g_cnt[65 * 8];

struct Params {
  const __nv_bfloat16 *x, *k, *v, *wq;
  __nv_bfloat16 *out, *o;
};

__device__ __forceinline__ void wg_fence() { asm volatile("wgmma.fence.sync.aligned;" ::: "memory"); }
__device__ __forceinline__ void wg_commit() { asm volatile("wgmma.commit_group.sync.aligned;" ::: "memory"); }
template <int N> __device__ __forceinline__ void wg_wait() { asm volatile("wgmma.wait_group.sync.aligned %0;" ::"n"(N) : "memory"); }
template <int N> __device__ __forceinline__ void reg_fence(float (&r)[N]) {
#pragma unroll
  for (int i = 0; i < N; i++) asm volatile("" : "+f"(r[i])::"memory");
}
template <int TA, int TB>
__device__ __forceinline__ void wgmma_n120(float (&d)[60], uint32_t a_lo, uint32_t a_hi, uint32_t b_lo, uint32_t b_hi, int acc) {
  asm volatile(
      "{\n.reg .pred p;\n.reg .b64 da, db;\nsetp.ne.b32 p, %64, 0;\n"
      "mov.b64 da, {%60, %61};\nmov.b64 db, {%62, %63};\n"
      "wgmma.mma_async.sync.aligned.m64n120k16.f32.bf16.bf16 {"
      "%0, %1, %2, %3, %4, %5, %6, %7, %8, %9, %10, %11, %12, %13, %14, %15, %16, %17, %18, %19, %20, %21, %22, %23, "
      "%24, %25, %26, %27, %28, %29, %30, %31, %32, %33, %34, %35, %36, %37, %38, %39, %40, %41, %42, %43, %44, %45, "
      "%46, %47, %48, %49, %50, %51, %52, %53, %54, %55, %56, %57, %58, %59"
      "}, da, db, p, 1, 1, %65, %66;\n}\n"
      : "+f"(d[0]), "+f"(d[1]), "+f"(d[2]), "+f"(d[3]), "+f"(d[4]), "+f"(d[5]), "+f"(d[6]), "+f"(d[7]), "+f"(d[8]),
        "+f"(d[9]), "+f"(d[10]), "+f"(d[11]), "+f"(d[12]), "+f"(d[13]), "+f"(d[14]), "+f"(d[15]), "+f"(d[16]),
        "+f"(d[17]), "+f"(d[18]), "+f"(d[19]), "+f"(d[20]), "+f"(d[21]), "+f"(d[22]), "+f"(d[23]), "+f"(d[24]),
        "+f"(d[25]), "+f"(d[26]), "+f"(d[27]), "+f"(d[28]), "+f"(d[29]), "+f"(d[30]), "+f"(d[31]), "+f"(d[32]),
        "+f"(d[33]), "+f"(d[34]), "+f"(d[35]), "+f"(d[36]), "+f"(d[37]), "+f"(d[38]), "+f"(d[39]), "+f"(d[40]),
        "+f"(d[41]), "+f"(d[42]), "+f"(d[43]), "+f"(d[44]), "+f"(d[45]), "+f"(d[46]), "+f"(d[47]), "+f"(d[48]),
        "+f"(d[49]), "+f"(d[50]), "+f"(d[51]), "+f"(d[52]), "+f"(d[53]), "+f"(d[54]), "+f"(d[55]), "+f"(d[56]),
        "+f"(d[57]), "+f"(d[58]), "+f"(d[59])
      : "r"(a_lo), "r"(a_hi), "r"(b_lo), "r"(b_hi), "r"(acc), "n"(TA), "n"(TB));
}

template <int TA, int TB>
__device__ __forceinline__ void wgmma_n160(float (&d)[80], uint32_t a_lo, uint32_t a_hi, uint32_t b_lo, uint32_t b_hi, int acc) {
  asm volatile(
      "{\n.reg .pred p;\n.reg .b64 da, db;\nsetp.ne.b32 p, %84, 0;\n"
      "mov.b64 da, {%80, %81};\nmov.b64 db, {%82, %83};\n"
      "wgmma.mma_async.sync.aligned.m64n160k16.f32.bf16.bf16 {"
      "%0, %1, %2, %3, %4, %5, %6, %7, %8, %9, %10, %11, %12, %13, %14, %15, %16, %17, %18, %19, %20, %21, %22, %23, "
      "%24, %25, %26, %27, %28, %29, %30, %31, %32, %33, %34, %35, %36, %37, %38, %39, %40, %41, %42, %43, %44, %45, "
      "%46, %47, %48, %49, %50, %51, %52, %53, %54, %55, %56, %57, %58, %59, %60, %61, %62, %63, %64, %65, %66, %67, "
      "%68, %69, %70, %71, %72, %73, %74, %75, %76, %77, %78, %79"
      "}, da, db, p, 1, 1, %85, %86;\n}\n"
      : "+f"(d[0]), "+f"(d[1]), "+f"(d[2]), "+f"(d[3]), "+f"(d[4]), "+f"(d[5]), "+f"(d[6]), "+f"(d[7]), "+f"(d[8]),
        "+f"(d[9]), "+f"(d[10]), "+f"(d[11]), "+f"(d[12]), "+f"(d[13]), "+f"(d[14]), "+f"(d[15]), "+f"(d[16]),
        "+f"(d[17]), "+f"(d[18]), "+f"(d[19]), "+f"(d[20]), "+f"(d[21]), "+f"(d[22]), "+f"(d[23]), "+f"(d[24]),
        "+f"(d[25]), "+f"(d[26]), "+f"(d[27]), "+f"(d[28]), "+f"(d[29]), "+f"(d[30]), "+f"(d[31]), "+f"(d[32]),
        "+f"(d[33]), "+f"(d[34]), "+f"(d[35]), "+f"(d[36]), "+f"(d[37]), "+f"(d[38]), "+f"(d[39]), "+f"(d[40]),
        "+f"(d[41]), "+f"(d[42]), "+f"(d[43]), "+f"(d[44]), "+f"(d[45]), "+f"(d[46]), "+f"(d[47]), "+f"(d[48]),
        "+f"(d[49]), "+f"(d[50]), "+f"(d[51]), "+f"(d[52]), "+f"(d[53]), "+f"(d[54]), "+f"(d[55]), "+f"(d[56]),
        "+f"(d[57]), "+f"(d[58]), "+f"(d[59]), "+f"(d[60]), "+f"(d[61]), "+f"(d[62]), "+f"(d[63]), "+f"(d[64]),
        "+f"(d[65]), "+f"(d[66]), "+f"(d[67]), "+f"(d[68]), "+f"(d[69]), "+f"(d[70]), "+f"(d[71]), "+f"(d[72]),
        "+f"(d[73]), "+f"(d[74]), "+f"(d[75]), "+f"(d[76]), "+f"(d[77]), "+f"(d[78]), "+f"(d[79])
      : "r"(a_lo), "r"(a_hi), "r"(b_lo), "r"(b_hi), "r"(acc), "n"(TA), "n"(TB));
}
__device__ __forceinline__ void mbar_init(uint32_t bar, int cnt) { asm volatile("mbarrier.init.shared::cta.b64 [%0], %1;" ::"r"(bar), "r"(cnt)); }
__device__ __forceinline__ void mbar_expect(uint32_t bar, uint32_t bytes) {
  asm volatile("mbarrier.arrive.expect_tx.shared::cta.b64 _, [%0], %1;" ::"r"(bar), "r"(bytes) : "memory");
}
__device__ __forceinline__ uint32_t mapa(uint32_t addr, uint32_t cta) {
  uint32_t r; asm("mapa.shared::cluster.u32 %0, %1, %2;" : "=r"(r) : "r"(addr), "r"(cta)); return r;
}
__device__ __forceinline__ void mbar_expect_cl(uint32_t cbar, uint32_t bytes) {
  asm volatile("mbarrier.arrive.expect_tx.shared::cluster.b64 _, [%0], %1;" ::"r"(cbar), "r"(bytes) : "memory");
}
__device__ __forceinline__ void mbar_arrive(uint32_t bar) { asm volatile("mbarrier.arrive.shared::cta.b64 _, [%0];" ::"r"(bar) : "memory"); }
__device__ __forceinline__ void mbar_arrive_cl(uint32_t cbar) { asm volatile("mbarrier.arrive.shared::cluster.b64 _, [%0];" ::"r"(cbar) : "memory"); }
__device__ __forceinline__ void warp_arrive(uint32_t bar) {
  asm volatile("{\n.reg .pred p;\nelect.sync _|p, 0xffffffff;\n@p mbarrier.arrive.shared::cta.b64 _, [%0];\n}\n" ::"r"(bar) : "memory");
}
__device__ __forceinline__ void warp_arrive_cl(uint32_t cbar) {
  asm volatile("{\n.reg .pred p;\nelect.sync _|p, 0xffffffff;\n@p mbarrier.arrive.shared::cluster.b64 _, [%0];\n}\n" ::"r"(cbar) : "memory");
}
__device__ __forceinline__ void mbar_wait(uint32_t bar, uint32_t parity) {
  asm volatile(
      "{\n.reg .pred p;\n.reg .u32 n;\n"
      "mbarrier.try_wait.parity.shared::cta.b64 p, [%0], %1;\n@p bra WAIT_DONE;\n"
      "mov.u32 n, 0;\n"
      "WAIT_LOOP:\n"
      "mbarrier.try_wait.parity.shared::cta.b64 p, [%0], %1;\n@p bra WAIT_DONE;\n"
      "add.u32 n, n, 1;\nsetp.lt.u32 p, n, 0x4000000;\n@p bra WAIT_LOOP;\ntrap;\n"
      "WAIT_DONE:\n}\n" ::"r"(bar), "r"(parity) : "memory");
}
__device__ __forceinline__ void mbar_sleep(uint32_t bar, uint32_t parity) {
  asm volatile(
      "{\n.reg .pred p;\n.reg .u32 n;\nmov.u32 n, 0;\n"
      "WAIT_LOOP:\n"
      "mbarrier.try_wait.parity.shared::cta.b64 p, [%0], %1, 4000;\n@p bra WAIT_DONE;\n"
      "add.u32 n, n, 1;\nsetp.lt.u32 p, n, 0x400000;\n@p bra WAIT_LOOP;\ntrap;\n"
      "WAIT_DONE:\n}\n" ::"r"(bar), "r"(parity) : "memory");
}
__device__ __forceinline__ void tma3d(uint32_t dst, const CUtensorMap* m, int c0, int c1, int c2, uint32_t bar) {
  asm volatile("cp.async.bulk.tensor.3d.shared::cluster.global.mbarrier::complete_tx::bytes [%0], [%1, {%3, %4, %5}], [%2];"
               ::"r"(dst), "l"(m), "r"(bar), "r"(c0), "r"(c1), "r"(c2) : "memory");
}
__device__ __forceinline__ void tma3d_hint(uint32_t dst, const CUtensorMap* m, int c0, int c1, int c2, uint32_t bar, uint64_t pol) {
  asm volatile("cp.async.bulk.tensor.3d.shared::cluster.global.mbarrier::complete_tx::bytes.L2::cache_hint [%0], [%1, {%3, %4, %5}], [%2], %6;"
               ::"r"(dst), "l"(m), "r"(bar), "r"(c0), "r"(c1), "r"(c2), "l"(pol) : "memory");
}
__device__ __forceinline__ void tma2d_mc(uint32_t dst, const CUtensorMap* m, int c0, int c1, uint32_t bar) {
  asm volatile("cp.async.bulk.tensor.2d.shared::cluster.global.mbarrier::complete_tx::bytes.multicast::cluster [%0], [%1, {%3, %4}], [%2], %5;"
               ::"r"(dst), "l"(m), "r"(bar), "r"(c0), "r"(c1), "h"((uint16_t)3) : "memory");
}
__device__ __forceinline__ void tma3d_mc(uint32_t dst, const CUtensorMap* m, int c0, int c1, int c2, uint32_t bar) {
  asm volatile("cp.async.bulk.tensor.3d.shared::cluster.global.mbarrier::complete_tx::bytes.multicast::cluster [%0], [%1, {%3, %4, %5}], [%2], %6;"
               ::"r"(dst), "l"(m), "r"(bar), "r"(c0), "r"(c1), "r"(c2), "h"((uint16_t)3) : "memory");
}
__device__ __forceinline__ void l2_prefetch(const void* p, uint32_t bytes) {
  asm volatile("cp.async.bulk.prefetch.L2.global [%0], %1;" ::"l"(p), "r"(bytes) : "memory");
}
__device__ __forceinline__ void fence_async_smem() { asm volatile("fence.proxy.async.shared::cta;" ::: "memory"); }
__device__ __forceinline__ void bar_sync(int wg) {
  if (wg == 0) asm volatile("bar.sync 1, 128;" ::: "memory");
  else asm volatile("bar.sync 2, 128;" ::: "memory");
}
__device__ __forceinline__ bool bar_red_or(int id, bool v) {
  uint32_t r;
  asm volatile("{\n.reg .pred p, q;\nsetp.ne.u32 p, %2, 0;\nbar.red.or.pred q, %1, 128, p;\nselp.u32 %0, 1, 0, q;\n}\n"
               : "=r"(r) : "r"(1 + id), "r"((uint32_t)v) : "memory");
  return r != 0;
}
__device__ __forceinline__ uint32_t hfma2(uint32_t a, uint32_t b, uint32_t c) { uint32_t r; asm("fma.rn.bf16x2 %0, %1, %2, %3;" : "=r"(r) : "r"(a), "r"(b), "r"(c)); return r; }
__device__ __forceinline__ float ex2(float x) { float y; asm("ex2.approx.ftz.f32 %0, %1;" : "=f"(y) : "f"(x)); return y; }
__device__ __forceinline__ uint32_t pack(float lo, float hi) { uint32_t r; asm("cvt.rn.bf16x2.f32 %0, %1, %2;" : "=r"(r) : "f"(hi), "f"(lo)); return r; }
__device__ __forceinline__ void stsm4t(uint32_t a, uint32_t r0, uint32_t r1, uint32_t r2, uint32_t r3) {
  asm volatile("stmatrix.sync.aligned.m8n8.x4.trans.shared.b16 [%0], {%1,%2,%3,%4};" ::"r"(a), "r"(r0), "r"(r1), "r"(r2), "r"(r3) : "memory");
}
__device__ __forceinline__ void stsm2t(uint32_t a, uint32_t r0, uint32_t r1) {
  asm volatile("stmatrix.sync.aligned.m8n8.x2.trans.shared.b16 [%0], {%1,%2};" ::"r"(a), "r"(r0), "r"(r1) : "memory");
}
__device__ __forceinline__ void mma16816(float (&d)[4], const uint32_t (&a)[4], uint32_t b0, uint32_t b1) {
  asm volatile("mma.sync.aligned.m16n8k16.row.col.f32.bf16.bf16.f32 {%0,%1,%2,%3}, {%4,%5,%6,%7}, {%8,%9}, {%0,%1,%2,%3};"
               : "+f"(d[0]), "+f"(d[1]), "+f"(d[2]), "+f"(d[3]) : "r"(a[0]), "r"(a[1]), "r"(a[2]), "r"(a[3]), "r"(b0), "r"(b1));
}

__device__ __forceinline__ uint32_t fresh_tid() { uint32_t t; asm volatile("mov.u32 %0, %tid.x;" : "=r"(t)); return t; }

template <int V> struct IC { static constexpr int value = V; };

struct Ring {
  uint32_t slot = 0, phase = 0;
  __device__ __forceinline__ void next() { if (++slot == RING_SLOTS) { slot = 0; phase ^= 1; } }
};

__device__ __forceinline__ void mma_tn(float (&o0)[60], float (&o1)[60], uint32_t a, uint32_t b, int acc) {
#pragma unroll
  for (int k = 0; k < 4; k++) {
    wgmma_n120<1, 0>(o0, a + k * 128, HI128, b + k * 2, HI128, k == 0 ? acc : 1);
    wgmma_n120<1, 0>(o1, a + 512 + k * 128, HI128, b + k * 2, HI128, k == 0 ? acc : 1);
  }
}
__device__ __forceinline__ void mma_tn_split(float (&o0)[60], float (&o1)[60], uint32_t a, uint32_t b) {
#pragma unroll
  for (int k = 0; k < 4; k++) wgmma_n120<1, 0>(o0, a + k * 128, HI128, b + k * 2, HI128, 1);
  wg_commit();
#pragma unroll
  for (int k = 0; k < 4; k++) wgmma_n120<1, 0>(o1, a + 512 + k * 128, HI128, b + k * 2, HI128, 1);
  wg_commit();
}
__device__ __forceinline__ void mma_qk(float (&s)[60], uint32_t a, uint32_t q) {
#pragma unroll
  for (int k = 0; k < 8; k++)
    wgmma_n120<0, 0>(s, a + (k >> 2) * 512 + (k & 3) * 2, HI128, q + (k >> 2) * (XB >> 4) + (k & 3) * 2, HI128, k != 0);
}
template <int J0, int J1, bool FIRST = false>
__device__ __forceinline__ void exp_store(const float (&s)[60], float (&l)[30], uint32_t dst) {
#pragma unroll
  for (int c = J0; c < J1; c++) {
    const float e0 = ex2(s[4 * c]), e1 = ex2(s[4 * c + 1]), e2 = ex2(s[4 * c + 2]), e3 = ex2(s[4 * c + 3]);
    if (FIRST) { l[2 * c] = e0 + e2; l[2 * c + 1] = e1 + e3; }
    else { l[2 * c] += e0; l[2 * c + 1] += e1; l[2 * c] += e2; l[2 * c + 1] += e3; }
    stsm2t(dst + c * 1024, pack(e0, e1), pack(e2, e3));
  }
}

__device__ __forceinline__ int o_pos(int b, int wg, int r) {
  const int j = r >> 3, q = (r >> 1) & 3, c = r & 1, o = b & 1, base = (b >> 1) * 480;
  if (j < 12) return base + (o * 9 + wg * 3 + (j >> 2)) * 32 + q * 8 + (j & 3) * 2 + c;
  if (j < 14) return base + (6 + 2 * o) * 32 + wg * 16 + q * 4 + (j - 12) * 2 + c;
  return base + 7 * 32 + (o * 2 + wg) * 8 + q * 2 + c;
}
__device__ __forceinline__ int o_row(int p) {
  const int pair = p / 480, a = (p - pair * 480) >> 5, in = p & 31, c = p & 1;
  int tile, row;
  if (a == 7) { tile = in >> 3; row = 112 + (in & 7); }
  else if (a == 6 || a == 8) { tile = a - 6 + (in >> 4); row = (12 + ((in >> 1) & 1)) * 8 + ((in >> 2) & 3) * 2 + c; }
  else { const int f = a > 8 ? a - 3 : a; tile = f / 3; row = ((f - tile * 3) * 4 + ((in >> 1) & 3)) * 8 + (in >> 3) * 2 + c; }
  return pair * 480 + tile * 120 + row;
}
__device__ __forceinline__ uint32_t o_idx(int k, int p) {
  return ((k >> 3) * (NROWS / 32) + (p >> 5)) * 256 + (k & 7) * 32 + ((((p >> 3) & 3) ^ ((k & 7) >> 1)) << 3) + (p & 7);
}

__device__ __forceinline__ void slow_path(const Params& P, int b, int h, int wg, int w, int lane) {
  const int g = lane >> 2, q = lane & 3, row0 = wg * 120;
  const uint16_t* wq = reinterpret_cast<const uint16_t*>(P.wq) + h * DH + g;
  const __nv_bfloat16* kp = P.k + (size_t)(b * NH + h) * SK * DH;
  const uint16_t* vp = reinterpret_cast<const uint16_t*>(P.v) + (size_t)(b * NH + h) * SK * DH + g;
#pragma unroll 1
  for (int t = w; t < 8; t += 4) {
    const int r0 = 16 * t + g, r1 = r0 + 8;
    const __nv_bfloat16* x0 = P.x + (size_t)(b * SQ + row0 + r0) * DM + 2 * q;
    const __nv_bfloat16* x1 = P.x + (size_t)(b * SQ + row0 + min(r1, 119)) * DM + 2 * q;
    float o[16][4];
#pragma unroll
    for (int n = 0; n < 16; n++) o[n][0] = o[n][1] = o[n][2] = o[n][3] = 0.f;
#pragma unroll 1
    for (int k0 = 0; k0 < DM; k0 += 16) {
      uint32_t a[4] = {*(const uint32_t*)(x0 + k0), *(const uint32_t*)(x1 + k0), *(const uint32_t*)(x0 + k0 + 8), *(const uint32_t*)(x1 + k0 + 8)};
      const uint16_t* wr = wq + (size_t)(k0 + 2 * q) * HD;
#pragma unroll
      for (int n = 0; n < 16; n++) {
        if ((n & 3) == 0) __syncwarp();
        mma16816(o[n], a, wr[8 * n] | ((uint32_t)wr[8 * n + HD] << 16), wr[8 * n + 8 * HD] | ((uint32_t)wr[8 * n + 9 * HD] << 16));
      }
    }
    uint32_t qa[8][4];
#pragma unroll
    for (int k = 0; k < 8; k++) {
      qa[k][0] = pack(o[2 * k][0] * QSCALE, o[2 * k][1] * QSCALE);
      qa[k][1] = pack(o[2 * k][2] * QSCALE, o[2 * k][3] * QSCALE);
      qa[k][2] = pack(o[2 * k + 1][0] * QSCALE, o[2 * k + 1][1] * QSCALE);
      qa[k][3] = pack(o[2 * k + 1][2] * QSCALE, o[2 * k + 1][3] * QSCALE);
    }
#pragma unroll
    for (int n = 0; n < 16; n++) o[n][0] = o[n][1] = o[n][2] = o[n][3] = 0.f;
    float m0 = -INFINITY, m1 = -INFINITY, l0 = 0.f, l1 = 0.f;
#pragma unroll 1
    for (int key0 = 0; key0 < SK; key0 += 16) {
      float s[2][4];
#pragma unroll
      for (int nt = 0; nt < 2; nt++) {
        s[nt][0] = s[nt][1] = s[nt][2] = s[nt][3] = 0.f;
        const __nv_bfloat16* kr = kp + (size_t)(key0 + 8 * nt + g) * DH + 2 * q;
#pragma unroll
        for (int k = 0; k < 8; k++) mma16816(s[nt], qa[k], *(const uint32_t*)(kr + 16 * k), *(const uint32_t*)(kr + 16 * k + 8));
      }
      float n0 = fmaxf(fmaxf(s[0][0], s[0][1]), fmaxf(s[1][0], s[1][1])), n1 = fmaxf(fmaxf(s[0][2], s[0][3]), fmaxf(s[1][2], s[1][3]));
      n0 = fmaxf(n0, __shfl_xor_sync(~0u, n0, 1)); n1 = fmaxf(n1, __shfl_xor_sync(~0u, n1, 1));
      n0 = fmaxf(n0, __shfl_xor_sync(~0u, n0, 2)); n1 = fmaxf(n1, __shfl_xor_sync(~0u, n1, 2));
      n0 = fmaxf(n0, m0); n1 = fmaxf(n1, m1);
      const float z0 = n0 == -INFINITY ? 0.f : n0, z1 = n1 == -INFINITY ? 0.f : n1;
      const float c0 = ex2(m0 - z0), c1 = ex2(m1 - z1);
      m0 = n0; m1 = n1;
#pragma unroll
      for (int nt = 0; nt < 2; nt++) {
        s[nt][0] = ex2(s[nt][0] - z0); s[nt][1] = ex2(s[nt][1] - z0);
        s[nt][2] = ex2(s[nt][2] - z1); s[nt][3] = ex2(s[nt][3] - z1);
      }
      l0 = l0 * c0 + s[0][0] + s[0][1] + s[1][0] + s[1][1];
      l1 = l1 * c1 + s[0][2] + s[0][3] + s[1][2] + s[1][3];
      uint32_t pa[4] = {pack(s[0][0], s[0][1]), pack(s[0][2], s[0][3]), pack(s[1][0], s[1][1]), pack(s[1][2], s[1][3])};
      const uint16_t* vr = vp + (size_t)(key0 + 2 * q) * DH;
#pragma unroll
      for (int n = 0; n < 16; n++) {
        if ((n & 3) == 0) __syncwarp();
        o[n][0] *= c0; o[n][1] *= c0; o[n][2] *= c1; o[n][3] *= c1;
        mma16816(o[n], pa, vr[8 * n] | ((uint32_t)vr[8 * n + DH] << 16), vr[8 * n + 8 * DH] | ((uint32_t)vr[8 * n + 9 * DH] << 16));
      }
    }
    l0 += __shfl_xor_sync(~0u, l0, 1); l1 += __shfl_xor_sync(~0u, l1, 1);
    l0 += __shfl_xor_sync(~0u, l0, 2); l1 += __shfl_xor_sync(~0u, l1, 2);
    const float i0 = 1.f / l0, i1 = 1.f / l1;
    __nv_bfloat16* oc0 = P.o + o_idx(h * DH + 2 * q, o_pos(b, wg, r0));
    __nv_bfloat16* oc1 = P.o + o_idx(h * DH + 2 * q, o_pos(b, wg, min(r1, 119)));
#pragma unroll
    for (int n = 0; n < 16; n++) {
      oc0[8 * n * NROWS] = __float2bfloat16(o[n][0] * i0);
      oc0[8 * n * NROWS + 32] = __float2bfloat16(o[n][1] * i0);
      if (r1 < 120) {
        oc1[8 * n * NROWS] = __float2bfloat16(o[n][2] * i1);
        oc1[8 * n * NROWS + 32] = __float2bfloat16(o[n][3] * i1);
      }
    }
  }
}

__device__ __forceinline__ int bk(int ks) { return ks < 48 ? 32 - (ks & 48) + (ks & 15) : ks; }
__device__ __forceinline__ uint32_t x_slot(uint32_t wg, uint32_t j) { return j < 2 ? (2 * wg + j) * XB : (2 * j + wg) * XB; }
__device__ __forceinline__ int row_block(int t) { return t >= 44 ? (t >> 2) - 11 : (t >> 2) + 4; }
__device__ __forceinline__ int cluster_id(int c) {
  const int t = c >= 4 ? c - 4 : c + 62;
  return ROLEMAP == 0 || t < 44 || t >= 60 ? t : t < 46 ? t + 14 : t - 2;
}
__device__ __forceinline__ int unit_batch(int u) { return (u & 63) >> 2; }
__device__ __forceinline__ int unit_head(int u, int rank) { return (u >> 6) * 8 + (u & 3) * 2 + rank; }

template <int NCL>
__global__ void __cluster_dims__(2, 1, 1) __launch_bounds__(384, 1)
fused_attn_kernel(const __grid_constant__ CUtensorMap tm_x, const __grid_constant__ CUtensorMap tm_wq,
                  const __grid_constant__ CUtensorMap tm_k, const __grid_constant__ CUtensorMap tm_v,
                  const __grid_constant__ CUtensorMap tm_o, const __grid_constant__ CUtensorMap tm_wo,
                  const __grid_constant__ Params P) {
  extern __shared__ uint8_t smem_raw[];
  const uint32_t sb = ((uint32_t)__cvta_generic_to_shared(smem_raw) + 1023) & ~1023u;
  const int warp = __shfl_sync(~0u, threadIdx.x >> 5, 0);
  const int lane = threadIdx.x & 31;
  const int rank = blockIdx.x & 1, ncl = NCL ? NCL : gridDim.x >> 1;
  const int id = NCL == 66 ? cluster_id(blockIdx.x >> 1) : blockIdx.x >> 1;
  const int id0 = NCL == 66 && UMAP ? (id >= 58 ? id - 58 : id + 8) : id;
  auto unit = [&](int it) { return (it < 3 ? id0 : id) + it * ncl; };
  const int nsingle = NCL == 66 ? 44 : NOTILES;
  const bool dbl = NCL == 66 && id >= 58, gemm = id < nsingle || dbl;

  if (threadIdx.x == 128) asm volatile("prefetch.tensormap [%0];" ::"l"(&tm_x) : "memory");
  if (threadIdx.x == 0) {
    asm volatile("prefetch.tensormap [%0];" ::"l"(&tm_wq) : "memory");
    for (int i = 0; i < 6; i++) {
      mbar_init(sb + BAR_RFULL + 8 * i, 1); mbar_init(sb + BAR_REMPTY + 8 * i, 8);
      mbar_init(sb + BAR_BFULL + 8 * i, 1); mbar_init(sb + BAR_BEMPTY + 8 * i, 16);
    }
    for (int i = 0; i < 8; i++) mbar_init(sb + BAR_XFULL + 8 * i, 1);
    for (int i = 0; i < 4; i++) mbar_init(sb + BAR_XEMPTY + 8 * i, 8);
    for (int i = 0; i < 2; i++) { mbar_init(sb + BAR_STAGE + 8 * i, 4); mbar_init(sb + BAR_LSUM + 8 * i, 4); mbar_init(sb + BAR_INV + 8 * i, 1); }
    asm volatile("fence.mbarrier_init.release.cluster;" ::: "memory");
  }
  __syncwarp();
  asm volatile("barrier.cluster.arrive.relaxed.aligned;" ::: "memory");
  auto first_w = [&](int s) {
    mbar_expect(sb + BAR_RFULL + 8 * s, RING_BYTES);
    tma3d(sb + s * RING_BYTES, &tm_wq, 0, s * 64, 2 * unit_head(id0, rank), sb + BAR_RFULL + 8 * s);
  };
  if (threadIdx.x == 0) first_w(0);
  __syncwarp();
  asm volatile("barrier.cluster.wait.aligned;" ::: "memory");
  if (threadIdx.x == 128) {
#pragma unroll 1
    for (int s = 0; s < 2; s++) {
      const uint32_t fb = sb + BAR_XFULL + 32 * rank + 8 * s;
      mbar_expect(fb, XB);
      mbar_expect_cl(mapa(fb, rank ^ 1), XB);
      tma2d_mc(sb + OFF_Q + x_slot(rank, s), &tm_x, s * 64, unit_batch(id0) * SQ + rank * 120, fb);
      if (s == 0) first_w(1);
    }
  }
  __syncwarp();

  if (warp >= 8) {
    asm volatile("setmaxnreg.dec.sync.aligned.u32 24;");
    if (warp == 8) {
      uint64_t pol;
      asm volatile("createpolicy.fractional.L2::evict_first.b64 %0, 1.0;" : "=l"(pol));
      Ring r;
      r.slot = 2;
      auto load = [&](const CUtensorMap* m, int c1, int c2, bool ef) {
        mbar_sleep(sb + BAR_REMPTY + 8 * r.slot, r.phase ^ 1);
        if (lane == 0) {
          mbar_expect(sb + BAR_RFULL + 8 * r.slot, RING_BYTES);
          if (ef) tma3d_hint(sb + r.slot * RING_BYTES, m, 0, c1, c2, sb + BAR_RFULL + 8 * r.slot, pol);
          else tma3d(sb + r.slot * RING_BYTES, m, 0, c1, c2, sb + BAR_RFULL + 8 * r.slot);
        }
        r.next();
      };
      for (int u0 = 0; id + u0 < NUNITS; u0 += ncl) {
        const int u = (u0 < 3 * ncl ? id0 : id) + u0;
        if (NCL == 66 && u0 == 2 * 66 && !gemm) {
          unsigned t0, t1;
          asm volatile("mov.u32 %0, %globaltimer_lo;" : "=r"(t0));
          do { __nanosleep(200); asm volatile("mov.u32 %0, %globaltimer_lo;" : "=r"(t1)); } while (t1 - t0 < PAUSE_NS);
        }
        const int h = unit_head(u, rank);
        const int krow = (unit_batch(u) * NH + h) * SK;
#pragma unroll 1
        for (int s = u0 == 0 ? 2 : 0; s < 10; s++) {
          load(&tm_wq, s * 64, 2 * h, false);
          const int sp = u0 == 0 ? s - 6 : s;
          if (sp >= 0 && sp < PF_N && lane == 0) l2_prefetch(P.v + (size_t)(krow + (PF_J0 + sp * PF_STEP) * 64) * DH, 16384);
        }
#pragma unroll 1
        for (int j = 0; j <= 16; j++) {
          if (j < 16) load(&tm_k, krow + j * 64, 0, true);
          if (j == 2) load(&tm_v, krow, 0, true);
          if (j > 1) load(&tm_v, krow + (j - 1) * 64, 0, true);
        }
      }
      for (int t = dbl ? 2 * id - 72 : id; t < (dbl ? NOTILES : nsingle); t += ncl) {
        const int row0 = row_block(t) * 256 + rank * 128;
        const int b0 = row0 / SQ, b1 = (row0 + 127) / SQ;
#pragma unroll 1
        for (int ks = 0; ks < 64; ks++) {
          if (dbl ? (ks & 15) == 0 : ks == 0 || ks == 48) {
            const unsigned* c = &g_cnt[((lane & 1 ? b1 : b0) * 4 + (ks || dbl ? ks >> 4 : min(lane >> 1, 2))) * 8];
            unsigned v, n = 0;
            do {
              asm volatile("ld.acquire.gpu.global.u32 %0, [%1];" : "=r"(v) : "l"(c) : "memory");
              if (++n > (1u << 26)) __trap();
            } while (v < 16);
            __syncwarp();
            asm volatile("fence.proxy.async.global;" ::: "memory");
          }
          mbar_wait(sb + BAR_REMPTY + 8 * r.slot, r.phase ^ 1);
          if (lane == 0) {
            mbar_expect(sb + BAR_RFULL + 8 * r.slot, RING_BYTES);
            asm volatile("cp.async.bulk.tensor.4d.shared::cluster.global.mbarrier::complete_tx::bytes.L2::cache_hint [%0], [%1, {%3, %3, %4, %5}], [%2], %6;"
                         ::"r"(sb + r.slot * RING_BYTES), "l"(&tm_o), "r"(sb + BAR_RFULL + 8 * r.slot), "r"(0), "r"((dbl ? ks : bk(ks)) * 8), "r"(row0 >> 6), "l"(pol) : "memory");
          }
          r.next();
        }
      }
      if (lane == 0 && atomicAdd(&g_cnt[64 * 8], 1) == gridDim.x - 1) {
        for (int i = 0; i < 65; i++) g_cnt[i * 8] = 0;
      }
    } else if (warp == 9) {
      if (lane == 0) {
        for (uint32_t it = 0; id + it * ncl < NUNITS; it++) {
          const int row = unit_batch(unit(it)) * SQ + rank * 120;
#pragma unroll 1
          for (int s = it == 0 ? 2 : 0; s < 10; s++) {
            const uint32_t j = s & 3, par = ((s >> 2) + (j < 2 ? it : 0)) & 1;
            if (s == 0) mbar_sleep(sb + BAR_XEMPTY, par ^ 1);
            mbar_wait(sb + BAR_XEMPTY + 8 * j, par ^ 1);
            const uint32_t fb = sb + BAR_XFULL + 32 * rank + 8 * j;
            mbar_expect(fb, XB);
            mbar_expect_cl(mapa(fb, rank ^ 1), XB);
            tma2d_mc(sb + OFF_Q + x_slot(rank, j), &tm_x, s * 64, row, fb);
          }
        }
        uint32_t slot = rank, phase = 0;
        if (dbl) {
#pragma unroll 1
          for (int ks = (id >> 1) & 3; ks < WO_PF; ks += 4)
            asm volatile("cp.async.bulk.prefetch.tensor.3d.L2.global [%0, {%1, %2, %3}];" ::"l"(&tm_wo), "r"(0), "r"(ks * 64), "r"(((2 * id - 72 + rank) & 3) * 5) : "memory");
        }
        if (gemm) mbar_sleep(sb + BAR_BEMPTY + 8 * rank, 0);
        for (int t = dbl ? 2 * id - 72 + rank : id; t < (dbl ? NOTILES : nsingle); t += ncl) {
#pragma unroll 1
          for (int ks = dbl ? 0 : rank; ks < 64; ks += dbl ? 1 : 2) {
            mbar_wait(sb + BAR_BEMPTY + 8 * slot, phase);
            const uint32_t fb = sb + BAR_BFULL + 8 * slot;
            mbar_expect(fb, BB);
            mbar_expect_cl(mapa(fb, rank ^ 1), BB);
            tma3d_mc(sb + OFF_Q + slot * BB, &tm_wo, 0, (dbl ? ks : bk(ks)) * 64, (t & 3) * 5, fb);
            if (dbl && ks + WO_PF < 64 && (ks & 3) == ((id >> 1) & 3))
              asm volatile("cp.async.bulk.prefetch.tensor.3d.L2.global [%0, {%1, %2, %3}];" ::"l"(&tm_wo), "r"(0), "r"((ks + WO_PF) * 64), "r"((t & 3) * 5) : "memory");
            slot += 2;
            if (slot >= 6) { slot -= 6; phase ^= 1; }
          }
        }
      }
    } else {
      const int wg = warp - 10;
      {
        mbar_wait(sb + BAR_RFULL, 0);
        const __nv_bfloat16* xs = P.x + (size_t)(unit_batch(id0) * SQ + ((id0 & 3) * 2 + rank) * 30 + min(lane, 29)) * DM + 256 + wg * 64;
#pragma unroll
        for (int i = 0; i < 3; i++) asm volatile("prefetch.global.L2 [%0];" ::"l"(xs + i * 128));
        if (lane < 16) asm volatile("prefetch.global.L2 [%0];" ::"l"(P.wq + (size_t)(384 + unit_batch(id0) * 16 + lane) * HD + unit_head(id0, rank) * DH + wg * 64));
      }
      for (uint32_t it = 0; id + it * ncl < NUNITS; it++) {
        const int u = unit(it);
        mbar_sleep(sb + BAR_LSUM + 8 * wg, it & 1);
        float l4[4], v[4];
        const uint32_t a = sb + OFF_L2 + wg * 2048 + (fresh_tid() & 31) * 16;
        asm volatile("ld.shared.v4.f32 {%0, %1, %2, %3}, [%4];" : "=f"(l4[0]), "=f"(l4[1]), "=f"(l4[2]), "=f"(l4[3]) : "r"(a) : "memory");
#pragma unroll
        for (int g = 1; g < 4; g++) {
          asm volatile("ld.shared.v4.f32 {%0, %1, %2, %3}, [%4];" : "=f"(v[0]), "=f"(v[1]), "=f"(v[2]), "=f"(v[3]) : "r"(a + g * 512) : "memory");
#pragma unroll
          for (int c = 0; c < 4; c++) l4[c] += v[c];
        }
#pragma unroll
        for (int c = 0; c < 4; c++) {
          float inv;
          asm("rcp.approx.ftz.f32 %0, %1;" : "=f"(inv) : "f"(l4[c]));
          l4[c] = l4[c] >= L_MIN && l4[c] <= L_MAX ? inv : __uint_as_float(0x7FFFFFFFu);
        }
        const uint32_t h0 = pack(l4[0], l4[1]), h1 = pack(l4[2], l4[3]);
        const uint32_t e0 = pack(l4[0] - __uint_as_float(h0 << 16), l4[1] - __uint_as_float(h0 & 0xFFFF0000u));
        const uint32_t e1 = pack(l4[2] - __uint_as_float(h1 << 16), l4[3] - __uint_as_float(h1 & 0xFFFF0000u));
        const uint32_t tid = fresh_tid();
        asm volatile("st.shared.v4.u32 [%0], {%1, %2, %3, %4};" ::"r"(sb + OFF_INV + wg * 640 + (tid & 3) * 144 + (tid & 28) * 4), "r"(h0), "r"(e0), "r"(h1), "r"(e1) : "memory");
        __syncwarp();
        warp_arrive(sb + BAR_INV + 8 * wg);
        mbar_sleep(sb + BAR_STAGE + 8 * wg, it & 1);
        if (lane == 0) {
          __threadfence();
          asm volatile("red.relaxed.gpu.global.add.u32 [%0], 1;" ::"l"(&g_cnt[(unit_batch(u) * 4 + (u >> 6)) * 8]) : "memory");
        }
        __syncwarp();
      }
    }
  } else {
    asm volatile("setmaxnreg.inc.sync.aligned.u32 240;");
    const int wg = warp >> 2, w = warp & 3;
    const uint32_t qreg = sb + OFF_Q + wg * 2 * XB, preg = sb + OFF_P + (2 + wg) * XB;
    const uint32_t st_off = ((lane >> 4) * 8 + (lane & 7)) * 128 + (((2 * w + ((lane >> 3) & 1)) ^ (lane & 7)) << 4);
    const uint32_t xempty = mapa(sb + BAR_XEMPTY, wg);
    Ring r;
    uint32_t it = 0;
    const uint32_t qd = (qreg & 0x3FFFF) >> 4, pd = (preg & 0x3FFFF) >> 4;
    auto ring_addr = [&]() { return ((sb & 0x3FFFF) + r.slot * RING_BYTES) >> 4; };
    auto ring_wait = [&]() { mbar_wait(sb + BAR_RFULL + 8 * r.slot, r.phase); };
    auto release = [&](uint32_t slot) { warp_arrive(sb + BAR_REMPTY + 8 * slot); };
    auto turn_wait = [&]() {
      if (wg == 0) asm volatile("bar.sync 3, 256;" ::: "memory");
      else asm volatile("bar.sync 4, 256;" ::: "memory");
    };
    auto turn_pass = [&]() {
      if (wg == 0) asm volatile("bar.arrive 4, 256;" ::: "memory");
      else asm volatile("bar.arrive 3, 256;" ::: "memory");
    };

    uint32_t chk = 0;
    auto sum_l = [&](const float (&l)[30], uint32_t tid) {
      float a[16], b[8], c[4];
      const bool b4 = tid & 16, b3 = tid & 8, b2 = tid & 4;
#pragma unroll
      for (int i = 0; i < 16; i++) {
        const float hi = i < 14 ? l[(16 + i) % 30] : 1.f;
        a[i] = (b4 ? hi : l[i]) + __shfl_xor_sync(~0u, b4 ? l[i] : hi, 16);
      }
#pragma unroll
      for (int i = 0; i < 8; i++) b[i] = (b3 ? a[8 + i] : a[i]) + __shfl_xor_sync(~0u, b3 ? a[i] : a[8 + i], 8);
#pragma unroll
      for (int i = 0; i < 4; i++) c[i] = (b2 ? b[4 + i] : b[i]) + __shfl_xor_sync(~0u, b2 ? b[i] : b[4 + i], 4);
      asm volatile("st.shared.v4.f32 [%0], {%1, %2, %3, %4};" ::"r"(sb + OFF_L2 + tid * 16), "f"(c[0]), "f"(c[1]),
                   "f"(c[2]), "f"(c[3]) : "memory");
      __syncwarp();
      warp_arrive(sb + BAR_LSUM + 8 * wg);
    };
    auto load_inv = [&](uint32_t (&iv)[30], uint32_t parity) {
      const int lane = fresh_tid() & 31;
      mbar_wait(sb + BAR_INV + 8 * wg, parity);
      chk = 0;
#pragma unroll
      for (int j = 0; j < 7; j++)
        asm volatile("ld.shared.v4.u32 {%0, %1, %2, %3}, [%4];" : "=r"(iv[4 * j]), "=r"(iv[4 * j + 1]), "=r"(iv[4 * j + 2]), "=r"(iv[4 * j + 3])
                     : "r"(sb + OFF_INV + wg * 640 + (lane & 3) * 144 + j * 16) : "memory");
      asm volatile("ld.shared.v2.u32 {%0, %1}, [%2];" : "=r"(iv[28]), "=r"(iv[29]) : "r"(sb + OFF_INV + wg * 640 + (lane & 3) * 144 + 112) : "memory");
    };
    auto norm = [&](uint32_t (&n)[8], const uint32_t (&po)[60], const uint32_t (&iv)[30], auto part) {
      constexpr int k = decltype(part)::value >> 1, j0 = (decltype(part)::value & 1) * 8;
#pragma unroll
      for (int j = 0; j < 8; j++)
        n[j] = j0 + j < 15 ? hfma2(po[15 * k + (j0 + j) % 15], iv[2 * ((j0 + j) % 15)], hfma2(po[15 * k + (j0 + j) % 15], iv[2 * ((j0 + j) % 15) + 1], 0x80008000u)) : 0x3F803F80u;
#pragma unroll
      for (int j = 0; j < 8; j += 2) chk = hfma2(n[j], n[j + 1], chk);
    };
    int od1, od2;
    auto store = [&](const uint32_t (&n)[8], const char* optr, auto part) {
      constexpr int k = decltype(part)::value >> 1, off = (8 * (k & 1) + 64 * (k >> 1)) * NROWS * 2;
      if ((decltype(part)::value & 1) == 0)
        asm volatile(
            "{\n.reg .pred p;\nsetp.ne.u64 p, %8, 0;\n"
            "@p st.global.v4.u32 [%8 + %9], {%0, %1, %2, %3};\n@p st.global.v4.u32 [%8 + %9 + 512], {%4, %5, %6, %7};\n}\n"
            ::"r"(n[0]), "r"(n[1]), "r"(n[2]), "r"(n[3]), "r"(n[4]), "r"(n[5]), "r"(n[6]), "r"(n[7]), "l"(optr), "n"(off) : "memory");
      else
        asm volatile(
            "{\n.reg .pred p;\n.reg .b64 b, c;\nsetp.ne.u64 p, %7, 0;\nmad.wide.s32 b, %9, 1, %7;\nmad.wide.s32 c, %10, 1, %7;\n"
            "@p st.global.v4.u32 [%7 + %8 + 1024], {%0, %1, %2, %3};\n@p st.global.v2.u32 [b + %8], {%4, %5};\n@p st.global.u32 [c + %8], %6;\n}\n"
            ::"r"(n[0]), "r"(n[1]), "r"(n[2]), "r"(n[3]), "r"(n[4]), "r"(n[5]), "r"(n[6]), "l"(optr), "n"(off), "r"(od1), "r"(od2) : "memory");
    };
    auto put = [&](const uint32_t (&po)[60], const uint32_t (&iv)[30], const char* optr, auto part) {
      uint32_t n[8];
      norm(n, po, iv, part);
      store(n, optr, part);
    };
    auto out_ptr = [&](int u) {
      const int lane = fresh_tid() & 31;
      const int k = unit_head(u, rank) * DH + 16 * w + (lane >> 2), b = unit_batch(u), q = lane & 3;
      const uint32_t i0 = o_idx(k, o_pos(b, wg, 2 * q));
      od1 = 2 * (int)(o_idx(k, o_pos(b, wg, 96 + 2 * q)) - i0);
      od2 = 2 * (int)(o_idx(k, o_pos(b, wg, 112 + 2 * q)) - i0);
      return reinterpret_cast<const char*>(P.o + i0);
    };
    auto unsafe = [&](bool valid) {
      const bool b = valid && ((chk & 0x7F80u) == 0x7F80u || (chk & 0x7F800000u) == 0x7F800000u);
      return __any_sync(~0u, bar_red_or(wg, b));
    };
    auto publish = [&]() { __syncwarp(); warp_arrive(sb + BAR_STAGE + 8 * wg); };

    uint32_t po[60];
#pragma unroll
    for (int i = 0; i < 60; i++) po[i] = 0;
    float o0[60], o1[60];
    ring_wait();
    mbar_wait(sb + BAR_XFULL + 32 * wg, 0);
    wg_fence();
    mma_tn(o0, o1, ring_addr(), qd, 0);
    wg_commit();
    while (true) {
      uint32_t prev = r.slot;
      r.next();
      auto qstep = [&](int s) {
        const uint32_t j = s & 3, par = ((s >> 2) + (j < 2 ? it : 0)) & 1;
        ring_wait();
        mbar_wait(sb + BAR_XFULL + 32 * wg + 8 * j, par);
        if (s >= ALT_FROM) turn_wait();
        wg_fence();
        mma_tn(o0, o1, ring_addr(), ((sb & 0x3FFFF) + OFF_Q + x_slot(wg, j)) >> 4, 1);
        wg_commit();
        if (s >= ALT_FROM || (s == ALT_FROM - 1 && wg == 1)) turn_pass();
        if (s <= 4) {
          wg_wait<1>();
          release(prev);
          warp_arrive_cl(xempty + 8 * ((s - 1) & 3));
        }
        prev = r.slot;
        r.next();
      };
      auto qdone = [&](int s) {
        wg_wait<0>();
        release(prev);
        if (s <= 5) warp_arrive_cl(xempty + 8 * (s & 3));
      };
      qstep(1);
      const int up = unit((int)it - 1);
      const char* optr = out_ptr(up);
      if (it == 0) optr = nullptr;
      uint32_t n7[8];
      {
        uint32_t iv[30];
        load_inv(iv, (it + 1) & 1); put(po, iv, optr, IC<0>());
        qstep(2); put(po, iv, optr, IC<1>());
        qstep(3); put(po, iv, optr, IC<2>());
        qstep(4); put(po, iv, optr, IC<3>()); qdone(4);
        qstep(5); put(po, iv, optr, IC<4>()); qdone(5);
        qstep(6); put(po, iv, optr, IC<5>()); qdone(6);
        qstep(7); put(po, iv, optr, IC<6>()); norm(n7, po, iv, IC<7>()); qdone(7);
      }
      ring_wait();
      mbar_wait(sb + BAR_XFULL + 32 * wg, it & 1);
      turn_wait();
      wg_fence();
      mma_tn(o0, o1, ring_addr(), qd, 1);
      wg_commit();
      prev = r.slot;
      r.next();
      ring_wait();
      mbar_wait(sb + BAR_XFULL + 32 * wg + 8, it & 1);
      wg_fence();
      mma_tn_split(o0, o1, ring_addr(), qd + (XB >> 4));
      turn_pass();
      wg_wait<2>();
      release(prev);
      auto put_q = [&](const float (&o)[60], uint32_t dst) {
#pragma unroll
        for (int j = 0; j < 14; j += 2)
          stsm4t(dst + j * 1024, pack(o[4 * j] * QSCALE, o[4 * j + 1] * QSCALE), pack(o[4 * j + 2] * QSCALE, o[4 * j + 3] * QSCALE),
                 pack(o[4 * j + 4] * QSCALE, o[4 * j + 5] * QSCALE), pack(o[4 * j + 6] * QSCALE, o[4 * j + 7] * QSCALE));
        stsm2t(dst + 14 * 1024, pack(o[56] * QSCALE, o[57] * QSCALE), pack(o[58] * QSCALE, o[59] * QSCALE));
      };
      wg_wait<1>();
      reg_fence(o0);
      const bool redo = unsafe(it > 0);
      put_q(o0, qreg + st_off);
      wg_wait<0>();
      reg_fence(o1);
      release(r.slot);
      r.next();
      bar_sync(wg);
      put_q(o1, qreg + XB + st_off);
      fence_async_smem();
      if (redo) {
        slow_path(P, unit_batch(up), unit_head(up, rank), wg, w, fresh_tid() & 31);
        optr = nullptr;
      }

      float sc[60], l[30];
      uint32_t slot0 = r.slot;
      ring_wait();
      turn_wait();
      wg_fence();
      mma_qk(sc, ring_addr(), qd);
      wg_commit();
      r.next();
      uint32_t slot1 = r.slot;
      ring_wait();
      wg_fence();
      mma_qk(o1, ring_addr(), qd);
      wg_commit();
      r.next();
      turn_pass();
      store(n7, optr, IC<7>());
      wg_wait<1>();
      reg_fence(sc);
      release(slot0);
      exp_store<0, 15, true>(sc, l, preg + st_off);
      slot0 = r.slot;
      ring_wait();
      wg_fence();
      mma_qk(sc, ring_addr(), qd);
      wg_commit();
      r.next();
      wg_wait<1>();
      reg_fence(o1);
      release(slot1);
      exp_store<0, 15>(o1, l, preg - 2 * XB + st_off);
      fence_async_smem();
      slot1 = r.slot;
      ring_wait();
      turn_wait();
      wg_fence();
      mma_tn(o0, o1, ring_addr(), pd, 0);
      wg_commit();
      r.next();
      ring_wait();
      wg_fence();
      mma_tn(o0, o1, ring_addr(), pd - (2 * XB >> 4), 1);
      wg_commit();
      turn_pass();
      if (it > 0) publish();
      wg_wait<1>();
      reg_fence(sc);
      release(slot0);
      release(slot1);
      bar_sync(wg);
      exp_store<0, VREL>(sc, l, preg + st_off);
      wg_wait<0>();
      reg_fence(o0); reg_fence(o1);
      release(r.slot);
      r.next();
      exp_store<VREL, 15>(sc, l, preg + st_off);
      fence_async_smem();
      const bool more = id + ((int)it + 1) * ncl < NUNITS;
      uint32_t pw = preg + st_off;
#pragma unroll 1
      for (int s = 3; s < 16; s++) {
        const uint32_t kslot = r.slot;
        asm volatile("add.u32 %0, %0, %1;" : "+r"(pw) : "r"(s & 1 ? -2 * XB : 2 * XB));
        ring_wait();
        turn_wait();
        wg_fence();
        mma_qk(sc, ring_addr(), qd);
        wg_commit();
        r.next();
        ring_wait();
        wg_fence();
        mma_tn(o0, o1, ring_addr(), pd - ((s - 1) & 1) * (2 * XB >> 4), 1);
        wg_commit();
        if (wg == 0 || s < 15) turn_pass();
        wg_wait<1>();
        reg_fence(sc);
        release(kslot);
        if (s == 15) {
          if (more) { warp_arrive_cl(xempty); warp_arrive_cl(xempty + 8); }
          else if (gemm) for (int i = 0; i < 3; i++) warp_arrive_cl(mapa(sb + BAR_BEMPTY + 8 * i, i & 1));
        }
        exp_store<0, VREL>(sc, l, pw);
        wg_wait<0>();
        reg_fence(o0); reg_fence(o1);
        release(r.slot);
        r.next();
        exp_store<VREL, 15>(sc, l, pw);
        fence_async_smem();
      }
      const uint32_t tid = fresh_tid();
      bar_sync(wg);
      ring_wait();
      wg_fence();
      mma_tn_split(o0, o1, ring_addr(), pd - (2 * XB >> 4));
      sum_l(l, tid);
      const uint32_t vslot = r.slot;
      r.next();
      it++;
      auto pack_o = [&](const float (&o)[60], int first) {
#pragma unroll
        for (int j = 0; j < 15; j++) { po[first + j] = pack(o[4 * j], o[4 * j + 1]); po[first + 15 + j] = pack(o[4 * j + 2], o[4 * j + 3]); }
      };
      if (!more) {
        wg_wait<0>();
        reg_fence(o0); reg_fence(o1);
        release(vslot);
        if (gemm) for (int i = 3; i < 6; i++) warp_arrive_cl(mapa(sb + BAR_BEMPTY + 8 * i, i & 1));
        pack_o(o0, 0); pack_o(o1, 30);
        break;
      }
      ring_wait();
      mbar_wait(sb + BAR_XFULL + 32 * wg, it & 1);
      wg_wait<1>();
      reg_fence(o0);
      pack_o(o0, 0);
      wg_fence();
#pragma unroll
      for (int k = 0; k < 4; k++) wgmma_n120<1, 0>(o0, ring_addr() + k * 128, HI128, qd + k * 2, HI128, k != 0);
      wg_commit();
      wg_wait<1>();
      reg_fence(o1);
      pack_o(o1, 30);
      wg_fence();
#pragma unroll
      for (int k = 0; k < 4; k++) wgmma_n120<1, 0>(o1, ring_addr() + 512 + k * 128, HI128, qd + k * 2, HI128, k != 0);
      wg_commit();
      release(vslot);
      warp_arrive_cl(xempty + 16); warp_arrive_cl(xempty + 24);
    }
    const int u = unit((int)it - 1);
    uint32_t pb[60];
#pragma unroll
    for (int i = 0; i < 60; i++) pb[i] = NCL != 66 ? po[i] ^ (gridDim.y - 1) : po[i];

    uint32_t bslot = 0, bphase = 0;
    auto out_row = [&](int lane) {
      const int row = lane & 15;
      return sb + wg * 8192 + (row < 12 ? w * RING_BYTES + row * 656 : (4 + (w >> 1)) * RING_BYTES + ((w & 1) * 4 + row - 12) * 656);
    };
    auto out_stage = [&](const float (&acc)[80], uint32_t col_off) {
      const int lane = fresh_tid() & 31;
      const uint32_t sa = out_row(lane) + col_off + (lane >> 4) * 16;
#pragma unroll
      for (int j = 0; j < 20; j += 2)
        asm volatile("stmatrix.sync.aligned.m8n8.x4.shared.b16 [%0], {%1,%2,%3,%4};" ::"r"(sa + j * 16), "r"(pack(acc[4 * j], acc[4 * j + 1])),
                     "r"(pack(acc[4 * j + 2], acc[4 * j + 3])), "r"(pack(acc[4 * j + 4], acc[4 * j + 5])), "r"(pack(acc[4 * j + 6], acc[4 * j + 7])) : "memory");
    };
    auto out_store = [&](int t, uint32_t bytes) {
      const int lane = fresh_tid() & 31;
      if (wg == 1) {
        __syncwarp();
#pragma unroll 1
        for (int h = 0; h < 2; h++) {
          const int row = h * 8 + (lane >> 2);
          const uint32_t src = out_row(row) + (lane & 3) * 16;
          char* dst = reinterpret_cast<char*>(P.out + (size_t)o_row(row_block(t) * 256 + rank * 128 + 64 + w * 16 + row) * DM + (t & 3) * 160) + (lane & 3) * 16;
#pragma unroll 1
          for (uint32_t c = 0; c < bytes; c += 320) {
            uint4 v[5];
#pragma unroll
            for (int i = 0; i < 5; i++)
              asm volatile("ld.shared.v4.u32 {%0, %1, %2, %3}, [%4];" : "=r"(v[i].x), "=r"(v[i].y), "=r"(v[i].z), "=r"(v[i].w) : "r"(src + c + i * 64) : "memory");
#pragma unroll
            for (int i = 0; i < 5; i++) *reinterpret_cast<uint4*>(dst + c + i * 64) = v[i];
          }
        }
        return;
      }
      fence_async_smem();
      __syncwarp();
      if (lane < 16) {
        __nv_bfloat16* dst = P.out + (size_t)o_row(row_block(t) * 256 + rank * 128 + wg * 64 + w * 16 + lane) * DM + (t & 3) * 160;
        asm volatile("cp.async.bulk.global.shared::cta.bulk_group [%0], [%1], %2;" ::"l"(dst), "r"(out_row(lane)), "r"(bytes) : "memory");
        asm volatile("cp.async.bulk.commit_group;" ::: "memory");
        asm volatile("cp.async.bulk.wait_group.read 0;" ::: "memory");
      }
    };
    for (int t = id; t == id || (NCL != 66 && t < nsingle); t += ncl) {
      float acc[80];
      uint32_t prev = 0, bprev = 0;
      const bool tile = t < nsingle;
      const bool last = NCL == 66 || t + ncl >= nsingle;
      auto bstep = [&](int ks, int accf) {
        ring_wait();
        mbar_wait(sb + BAR_BFULL + 8 * bslot, bphase);
        wg_fence();
        const uint32_t a = ring_addr() + wg * 512, bd = (((sb & 0x3FFFF) + OFF_Q + bslot * BB) >> 4) | ((4096u >> 4) << 16);
#pragma unroll
        for (int k = 0; k < 4; k++) wgmma_n160<1, 1>(acc, a + LBO64A + k * 128, HI64A, bd + k * 64, HI64, k == 0 ? accf : 1);
        wg_commit();
        if (ks > 0) {
          wg_wait<1>();
          release(prev);
          if (ks < 59 || !last) warp_arrive_cl(mapa(sb + BAR_BEMPTY + 8 * bprev, bprev & 1));
        }
        prev = r.slot; bprev = bslot;
        r.next();
        if (++bslot == 6) { bslot = 0; bphase ^= 1; }
      };
      const char* optr;
      uint32_t iv[30], n2[8], n3[8], n4[8], n5[8], n6[8], n7[8];
      if (tile) {
        bstep(0, 0);
        bstep(1, 1);
        optr = out_ptr(u);
        if (t != id) optr = nullptr;
        load_inv(iv, (it + 1) & 1);
#pragma unroll 1
        for (int ks = 2; ks < 17; ks++) {
          bstep(ks, 1);
          switch (ks) {
            case 2: put(pb, iv, optr, IC<0>()); break;
            case 4: put(pb, iv, optr, IC<1>()); break;
            case 6: put(pb, iv, optr, IC<2>()); break;
            case 8: put(pb, iv, optr, IC<3>()); break;
            case 10: put(pb, iv, optr, IC<4>()); break;
            case 12: put(pb, iv, optr, IC<5>()); break;
            case 14: put(pb, iv, optr, IC<6>()); break;
            case 16: put(pb, iv, optr, IC<7>()); break;
            default: break;
          }
        }
        wg_wait<0>();
        reg_fence(acc);
#pragma unroll
        for (int i = 0; i < 8; i++) n2[i] = n3[i] = n4[i] = n5[i] = n6[i] = n7[i] = 0;
      } else {
        Ring r2 = r;
        auto first = [&](int ks) {
          if (gemm) { mbar_wait(sb + BAR_RFULL + 8 * r2.slot, r2.phase); mbar_wait(sb + BAR_BFULL + 16 * ks, 0); }
          wg_fence();
          const uint32_t a = (((sb & 0x3FFFF) + r2.slot * RING_BYTES) >> 4) + wg * 512;
          const uint32_t bd = (((sb & 0x3FFFF) + OFF_Q + 2 * ks * BB) >> 4) | ((4096u >> 4) << 16);
#pragma unroll
          for (int k = 0; k < 4; k++) wgmma_n160<1, 1>(acc, a + LBO64A + k * 128, HI64A, bd + k * 64, HI64, k + ks != 0);
          wg_commit();
          r2.next();
        };
        first(0);
        first(1);
        optr = out_ptr(u);
        load_inv(iv, (it + 1) & 1);
        put(pb, iv, optr, IC<0>()); put(pb, iv, optr, IC<1>());
        norm(n2, pb, iv, IC<2>()); norm(n3, pb, iv, IC<3>()); norm(n4, pb, iv, IC<4>());
        norm(n5, pb, iv, IC<5>()); norm(n6, pb, iv, IC<6>()); norm(n7, pb, iv, IC<7>());
        wg_wait<0>();
        reg_fence(acc);
      }
      if (unsafe(t == id)) {
        slow_path(P, unit_batch(u), unit_head(u, rank), wg, w, fresh_tid() & 31);
        optr = nullptr;
#pragma unroll
        for (int i = 0; i < 8; i++) n2[i] = n3[i] = n4[i] = n5[i] = n6[i] = n7[i] = 0;
      }
      if (tile && t == id) publish();
      if (!tile && !gemm) {
        store(n2, optr, IC<2>()); store(n3, optr, IC<3>()); store(n4, optr, IC<4>()); store(n5, optr, IC<5>()); store(n6, optr, IC<6>()); store(n7, optr, IC<7>());
        publish();
        break;
      }
      if (!tile) {
        float ac1[80];
        auto half = [&](float (&ac)[80], bool rel, int accf) {
          mbar_wait(sb + BAR_BFULL + 8 * bslot, bphase);
          wg_fence();
          const uint32_t a = ring_addr() + wg * 512, bd = (((sb & 0x3FFFF) + OFF_Q + bslot * BB) >> 4) | ((4096u >> 4) << 16);
#pragma unroll
          for (int k = 0; k < 4; k++) wgmma_n160<1, 1>(ac, a + LBO64A + k * 128, HI64A, bd + k * 64, HI64, k == 0 ? accf : 1);
          wg_commit();
          wg_wait<1>();
          if (rel) warp_arrive_cl(mapa(sb + BAR_BEMPTY + 8 * bprev, bprev & 1));
          bprev = bslot;
        };
        auto dstep = [&](int ks) {
          ring_wait();
          half(acc, ks < 62, 1);
          release(prev);
          bslot++;
          half(ac1, ks < 61, 1);
          if (++bslot == 6) { bslot = 0; bphase ^= 1; }
          prev = r.slot; r.next();
        };
        warp_arrive_cl(mapa(sb + BAR_BEMPTY, 0));
        bprev = 2; bslot = 1;
        half(ac1, true, 0);
        prev = r.slot; r.next(); bslot = 3;
        half(ac1, true, 1);
        release(prev); prev = r.slot; r.next(); bslot = 4;
#pragma unroll 1
        for (int ks = 2; ks < 8; ks++) {
          dstep(ks);
          switch (ks) {
            case 2: store(n2, optr, IC<2>()); break;
            case 3: store(n3, optr, IC<3>()); break;
            case 4: store(n4, optr, IC<4>()); break;
            case 5: store(n5, optr, IC<5>()); break;
            case 6: store(n6, optr, IC<6>()); break;
            default: store(n7, optr, IC<7>()); break;
          }
        }
        publish();
#pragma unroll 1
        for (int ks = 8; ks < 64; ks++) {
          if (wg == 1 && ks == 62) turn_wait();
          dstep(ks);
        }
        if (wg == 0) turn_pass();
        wg_wait<0>();
        reg_fence(acc); reg_fence(ac1);
        bar_sync(wg);
        out_stage(ac1, 320);
      } else {
#pragma unroll 1
        for (int ks = 17; ks < 64; ks++) {
          if (wg == 1 && ks == 64 - END_SKEW) turn_wait();
          bstep(ks, 1);
        }
        if (wg == 0) turn_pass();
        wg_wait<0>();
        reg_fence(acc);
        release(prev);
        if (!last) warp_arrive_cl(mapa(sb + BAR_BEMPTY + 8 * bprev, bprev & 1));
      }
      const int pos0 = row_block(t) * 256 + rank * 128 + wg * 64 + w * 16;
      if (last) {
        bar_sync(wg);
        out_stage(acc, 0);
        out_store(tile ? t : 2 * id - 72, tile ? 320 : 640);
      } else {
        const int lane = fresh_tid() & 31;
        __nv_bfloat16* op0 = P.out + (size_t)o_row(pos0 + (lane >> 2)) * DM + (t & 3) * 160 + (lane & 3) * 2;
        __nv_bfloat16* op1 = P.out + (size_t)o_row(pos0 + (lane >> 2) + 8) * DM + (t & 3) * 160 + (lane & 3) * 2;
#pragma unroll
        for (int j = 0; j < 20; j++) {
          *reinterpret_cast<uint32_t*>(op0 + j * 8) = pack(acc[4 * j], acc[4 * j + 1]);
          *reinterpret_cast<uint32_t*>(op1 + j * 8) = pack(acc[4 * j + 2], acc[4 * j + 3]);
        }
      }
#pragma unroll
      for (int i = 0; i < 60; i++) pb[i] = 0;
    }
  }
}

typedef CUresult (*EncodeFn)(CUtensorMap*, CUtensorMapDataType, cuuint32_t, void*, const cuuint64_t*, const cuuint64_t*,
                             const cuuint32_t*, const cuuint32_t*, CUtensorMapInterleave, CUtensorMapSwizzle,
                             CUtensorMapL2promotion, CUtensorMapFloatOOBfill);

void make_map(EncodeFn enc, CUtensorMap* m, const void* p, int rank, const cuuint64_t* dims, const cuuint64_t* strides,
              const cuuint32_t* box, CUtensorMapSwizzle sw, CUtensorMapL2promotion promo) {
  cuuint32_t es[4] = {1, 1, 1, 1};
  enc(m, CU_TENSOR_MAP_DATA_TYPE_BFLOAT16, rank, const_cast<void*>(p), dims, strides, box, es, CU_TENSOR_MAP_INTERLEAVE_NONE, sw,
      promo, CU_TENSOR_MAP_FLOAT_OOB_FILL_NONE);
}

}

extern "C" void kernel_launch(void* const* d_in, const int* in_sizes, int n_in, void* d_out, int out_size) {
  static EncodeFn enc = nullptr;
  static int nclusters = 0;
  static void* o_ptr = nullptr;
  if (!enc) {
    cudaDriverEntryPointQueryResult qr;
    cudaGetDriverEntryPoint("cuTensorMapEncodeTiled", (void**)&enc, cudaEnableDefault, &qr);
    cudaFuncSetAttribute(fused_attn_kernel<66>, cudaFuncAttributeMaxDynamicSharedMemorySize, SMEM_BYTES);
    cudaFuncSetAttribute(fused_attn_kernel<0>, cudaFuncAttributeMaxDynamicSharedMemorySize, SMEM_BYTES);
    cudaGetSymbolAddress(&o_ptr, g_o);
    cudaLaunchConfig_t cfg = {};
    cfg.gridDim = 128; cfg.blockDim = 384; cfg.dynamicSmemBytes = SMEM_BYTES;
    cudaLaunchAttribute at; at.id = cudaLaunchAttributeClusterDimension;
    at.val.clusterDim.x = 2; at.val.clusterDim.y = 1; at.val.clusterDim.z = 1;
    cfg.attrs = &at; cfg.numAttrs = 1;
    int n = 0;
    cudaOccupancyMaxActiveClusters(&n, fused_attn_kernel<66>, &cfg);
    nclusters = n >= 66 ? MAXCL : (n >= 64 || n <= 0 ? 64 : n);
  }
  const __nv_bfloat16* x = (const __nv_bfloat16*)d_in[0];
  const __nv_bfloat16* k = (const __nv_bfloat16*)d_in[1];
  const __nv_bfloat16* v = (const __nv_bfloat16*)d_in[2];
  const __nv_bfloat16* wq = (const __nv_bfloat16*)d_in[3];
  const __nv_bfloat16* wo = (const __nv_bfloat16*)d_in[4];
  CUtensorMap tm_x, tm_wq, tm_k, tm_v, tm_o, tm_wo;
  const auto S128 = CU_TENSOR_MAP_SWIZZLE_128B;
  const auto P128 = CU_TENSOR_MAP_L2_PROMOTION_L2_128B, P256 = CU_TENSOR_MAP_L2_PROMOTION_L2_256B;
  { cuuint64_t d[2] = {DM, NB * SQ}, s[1] = {DM * 2}; cuuint32_t b[2] = {64, 120}; make_map(enc, &tm_x, x, 2, d, s, b, S128, P128); }
  { cuuint64_t d[3] = {64, DM, HD / 64}, s[2] = {HD * 2, 128}; cuuint32_t b[3] = {64, 64, 2}; make_map(enc, &tm_wq, wq, 3, d, s, b, S128, P256); }
  { cuuint64_t d[3] = {64, NB * NH * SK, 2}, s[2] = {DH * 2, 128}; cuuint32_t b[3] = {64, 64, 2};
    make_map(enc, &tm_k, k, 3, d, s, b, S128, P128); make_map(enc, &tm_v, v, 3, d, s, b, S128, P128); }
  { cuuint64_t d[4] = {256, 2, HD / 8, NROWS / 64}, s[3] = {512, NROWS * 16, 1024}; cuuint32_t b[4] = {256, 2, 8, 2};
    make_map(enc, &tm_o, o_ptr, 4, d, s, b, CU_TENSOR_MAP_SWIZZLE_NONE, P256); }
  { cuuint64_t d[3] = {32, HD, DM / 32}, s[2] = {DM * 2, 64}; cuuint32_t b[3] = {32, 64, 5};
    make_map(enc, &tm_wo, wo, 3, d, s, b, CU_TENSOR_MAP_SWIZZLE_64B, P128); }
  Params P{x, k, v, wq, (__nv_bfloat16*)d_out, (__nv_bfloat16*)o_ptr};
  if (nclusters == 66) fused_attn_kernel<66><<<132, 384, SMEM_BYTES>>>(tm_x, tm_wq, tm_k, tm_v, tm_o, tm_wo, P);
  else fused_attn_kernel<0><<<2 * nclusters, 384, SMEM_BYTES>>>(tm_x, tm_wq, tm_k, tm_v, tm_o, tm_wo, P);
}
```

```cpp
#include <cuda_runtime.h>
#include <cuda.h>
#include <cuda_bf16.h>
#include <stdint.h>

namespace {

constexpr int NB = 16, SQ = 240, DM = 640, NH = 32, SK = 1024, DH = 128, HD = NH * DH;
constexpr int NROWS = NB * SQ;
constexpr int NUNITS = 256;
#define ALT_FROM 4
#define END_SKEW 5
#define VREL 8
#define PF_N 4
#define PF_J0 3
#define PF_STEP 3
#define WO_PF 6
#define PAUSE_NS 11000
#define UMAP 1
#define ROLEMAP 0
#define MAXCL 66
constexpr int NOTILES = 60;
constexpr float QSCALE = 0.08838834764831845f * 1.4426950408889634f;
constexpr float L_MIN = 1.f;
constexpr float L_MAX = 1.152921504606846976e18f;

constexpr uint32_t RING_SLOTS = 6, RING_BYTES = 16384;
constexpr uint32_t XB = 15360;
constexpr uint32_t BB = 20480;
constexpr uint32_t OFF_Q = RING_SLOTS * RING_BYTES;
constexpr uint32_t OFF_P = OFF_Q + 4 * XB;
constexpr uint32_t OFF_INV = OFF_P + 4 * XB;
constexpr uint32_t OFF_L2 = OFF_INV + 1280;
constexpr uint32_t OFF_BAR = OFF_L2 + 4096;
constexpr uint32_t BAR_RFULL = OFF_BAR, BAR_REMPTY = BAR_RFULL + 48, BAR_XFULL = BAR_REMPTY + 48,
    BAR_XEMPTY = BAR_XFULL + 64, BAR_BFULL = BAR_XEMPTY + 32, BAR_BEMPTY = BAR_BFULL + 48, BAR_STAGE = BAR_BEMPTY + 48;
constexpr uint32_t BAR_LSUM = BAR_STAGE + 16, BAR_INV = BAR_LSUM + 16;
constexpr uint32_t OFF_TR = BAR_INV + 16;
constexpr uint32_t SMEM_BYTES = OFF_TR + 1024;

constexpr uint32_t HI128 = (1u << 30) | (1024 >> 4);
constexpr uint32_t HI64 = (2u << 30) | (512 >> 4);
constexpr uint32_t HI64A = (2u << 30) | (1024 >> 4), LBO64A = (512u >> 4) << 16;

__device__ __align__(1024) __nv_bfloat16 g_o[HD * NROWS];
__device__ __align__(128) unsigned g_cnt[65 * 8];

struct Params {
  const __nv_bfloat16 *x, *k, *v, *wq;
  __nv_bfloat16 *out, *o;
};

__device__ __forceinline__ void wg_fence() { asm volatile("wgmma.fence.sync.aligned;" ::: "memory"); }
__device__ __forceinline__ void wg_commit() { asm volatile("wgmma.commit_group.sync.aligned;" ::: "memory"); }
template <int N> __device__ __forceinline__ void wg_wait() { asm volatile("wgmma.wait_group.sync.aligned %0;" ::"n"(N) : "memory"); }
template <int N> __device__ __forceinline__ void reg_fence(float (&r)[N]) {
#pragma unroll
  for (int i = 0; i < N; i++) asm volatile("" : "+f"(r[i])::"memory");
}
template <int TA, int TB>
__device__ __forceinline__ void wgmma_n120(float (&d)[60], uint32_t a_lo, uint32_t a_hi, uint32_t b_lo, uint32_t b_hi, int acc) {
  asm volatile(
      "{\n.reg .pred p;\n.reg .b64 da, db;\nsetp.ne.b32 p, %64, 0;\n"
      "mov.b64 da, {%60, %61};\nmov.b64 db, {%62, %63};\n"
      "wgmma.mma_async.sync.aligned.m64n120k16.f32.bf16.bf16 {"
      "%0, %1, %2, %3, %4, %5, %6, %7, %8, %9, %10, %11, %12, %13, %14, %15, %16, %17, %18, %19, %20, %21, %22, %23, "
      "%24, %25, %26, %27, %28, %29, %30, %31, %32, %33, %34, %35, %36, %37, %38, %39, %40, %41, %42, %43, %44, %45, "
      "%46, %47, %48, %49, %50, %51, %52, %53, %54, %55, %56, %57, %58, %59"
      "}, da, db, p, 1, 1, %65, %66;\n}\n"
      : "+f"(d[0]), "+f"(d[1]), "+f"(d[2]), "+f"(d[3]), "+f"(d[4]), "+f"(d[5]), "+f"(d[6]), "+f"(d[7]), "+f"(d[8]),
        "+f"(d[9]), "+f"(d[10]), "+f"(d[11]), "+f"(d[12]), "+f"(d[13]), "+f"(d[14]), "+f"(d[15]), "+f"(d[16]),
        "+f"(d[17]), "+f"(d[18]), "+f"(d[19]), "+f"(d[20]), "+f"(d[21]), "+f"(d[22]), "+f"(d[23]), "+f"(d[24]),
        "+f"(d[25]), "+f"(d[26]), "+f"(d[27]), "+f"(d[28]), "+f"(d[29]), "+f"(d[30]), "+f"(d[31]), "+f"(d[32]),
        "+f"(d[33]), "+f"(d[34]), "+f"(d[35]), "+f"(d[36]), "+f"(d[37]), "+f"(d[38]), "+f"(d[39]), "+f"(d[40]),
        "+f"(d[41]), "+f"(d[42]), "+f"(d[43]), "+f"(d[44]), "+f"(d[45]), "+f"(d[46]), "+f"(d[47]), "+f"(d[48]),
        "+f"(d[49]), "+f"(d[50]), "+f"(d[51]), "+f"(d[52]), "+f"(d[53]), "+f"(d[54]), "+f"(d[55]), "+f"(d[56]),
        "+f"(d[57]), "+f"(d[58]), "+f"(d[59])
      : "r"(a_lo), "r"(a_hi), "r"(b_lo), "r"(b_hi), "r"(acc), "n"(TA), "n"(TB));
}

template <int TA, int TB>
__device__ __forceinline__ void wgmma_n160(float (&d)[80], uint32_t a_lo, uint32_t a_hi, uint32_t b_lo, uint32_t b_hi, int acc) {
  asm volatile(
      "{\n.reg .pred p;\n.reg .b64 da, db;\nsetp.ne.b32 p, %84, 0;\n"
      "mov.b64 da, {%80, %81};\nmov.b64 db, {%82, %83};\n"
      "wgmma.mma_async.sync.aligned.m64n160k16.f32.bf16.bf16 {"
      "%0, %1, %2, %3, %4, %5, %6, %7, %8, %9, %10, %11, %12, %13, %14, %15, %16, %17, %18, %19, %20, %21, %22, %23, "
      "%24, %25, %26, %27, %28, %29, %30, %31, %32, %33, %34, %35, %36, %37, %38, %39, %40, %41, %42, %43, %44, %45, "
      "%46, %47, %48, %49, %50, %51, %52, %53, %54, %55, %56, %57, %58, %59, %60, %61, %62, %63, %64, %65, %66, %67, "
      "%68, %69, %70, %71, %72, %73, %74, %75, %76, %77, %78, %79"
      "}, da, db, p, 1, 1, %85, %86;\n}\n"
      : "+f"(d[0]), "+f"(d[1]), "+f"(d[2]), "+f"(d[3]), "+f"(d[4]), "+f"(d[5]), "+f"(d[6]), "+f"(d[7]), "+f"(d[8]),
        "+f"(d[9]), "+f"(d[10]), "+f"(d[11]), "+f"(d[12]), "+f"(d[13]), "+f"(d[14]), "+f"(d[15]), "+f"(d[16]),
        "+f"(d[17]), "+f"(d[18]), "+f"(d[19]), "+f"(d[20]), "+f"(d[21]), "+f"(d[22]), "+f"(d[23]), "+f"(d[24]),
        "+f"(d[25]), "+f"(d[26]), "+f"(d[27]), "+f"(d[28]), "+f"(d[29]), "+f"(d[30]), "+f"(d[31]), "+f"(d[32]),
        "+f"(d[33]), "+f"(d[34]), "+f"(d[35]), "+f"(d[36]), "+f"(d[37]), "+f"(d[38]), "+f"(d[39]), "+f"(d[40]),
        "+f"(d[41]), "+f"(d[42]), "+f"(d[43]), "+f"(d[44]), "+f"(d[45]), "+f"(d[46]), "+f"(d[47]), "+f"(d[48]),
        "+f"(d[49]), "+f"(d[50]), "+f"(d[51]), "+f"(d[52]), "+f"(d[53]), "+f"(d[54]), "+f"(d[55]), "+f"(d[56]),
        "+f"(d[57]), "+f"(d[58]), "+f"(d[59]), "+f"(d[60]), "+f"(d[61]), "+f"(d[62]), "+f"(d[63]), "+f"(d[64]),
        "+f"(d[65]), "+f"(d[66]), "+f"(d[67]), "+f"(d[68]), "+f"(d[69]), "+f"(d[70]), "+f"(d[71]), "+f"(d[72]),
        "+f"(d[73]), "+f"(d[74]), "+f"(d[75]), "+f"(d[76]), "+f"(d[77]), "+f"(d[78]), "+f"(d[79])
      : "r"(a_lo), "r"(a_hi), "r"(b_lo), "r"(b_hi), "r"(acc), "n"(TA), "n"(TB));
}
__device__ __forceinline__ void mbar_init(uint32_t bar, int cnt) { asm volatile("mbarrier.init.shared::cta.b64 [%0], %1;" ::"r"(bar), "r"(cnt)); }
__device__ __forceinline__ void mbar_expect(uint32_t bar, uint32_t bytes) {
  asm volatile("mbarrier.arrive.expect_tx.shared::cta.b64 _, [%0], %1;" ::"r"(bar), "r"(bytes) : "memory");
}
__device__ __forceinline__ uint32_t mapa(uint32_t addr, uint32_t cta) {
  uint32_t r; asm("mapa.shared::cluster.u32 %0, %1, %2;" : "=r"(r) : "r"(addr), "r"(cta)); return r;
}
__device__ __forceinline__ void mbar_expect_cl(uint32_t cbar, uint32_t bytes) {
  asm volatile("mbarrier.arrive.expect_tx.shared::cluster.b64 _, [%0], %1;" ::"r"(cbar), "r"(bytes) : "memory");
}
__device__ __forceinline__ void warp_arrive(uint32_t bar) {
  asm volatile("{\n.reg .pred p;\nelect.sync _|p, 0xffffffff;\n@p mbarrier.arrive.shared::cta.b64 _, [%0];\n}\n" ::"r"(bar) : "memory");
}
__device__ __forceinline__ void warp_arrive_cl(uint32_t cbar) {
  asm volatile("{\n.reg .pred p;\nelect.sync _|p, 0xffffffff;\n@p mbarrier.arrive.shared::cluster.b64 _, [%0];\n}\n" ::"r"(cbar) : "memory");
}
__device__ __forceinline__ void mbar_wait(uint32_t bar, uint32_t parity) {
  asm volatile(
      "{\n.reg .pred p;\n.reg .u32 n;\n"
      "mbarrier.try_wait.parity.shared::cta.b64 p, [%0], %1;\n@p bra WAIT_DONE;\n"
      "mov.u32 n, 0;\n"
      "WAIT_LOOP:\n"
      "mbarrier.try_wait.parity.shared::cta.b64 p, [%0], %1;\n@p bra WAIT_DONE;\n"
      "add.u32 n, n, 1;\nsetp.lt.u32 p, n, 0x4000000;\n@p bra WAIT_LOOP;\ntrap;\n"
      "WAIT_DONE:\n}\n" ::"r"(bar), "r"(parity) : "memory");
}
__device__ __forceinline__ void mbar_sleep(uint32_t bar, uint32_t parity) {
  asm volatile(
      "{\n.reg .pred p;\n.reg .u32 n;\nmov.u32 n, 0;\n"
      "WAIT_LOOP:\n"
      "mbarrier.try_wait.parity.shared::cta.b64 p, [%0], %1, 4000;\n@p bra WAIT_DONE;\n"
      "add.u32 n, n, 1;\nsetp.lt.u32 p, n, 0x400000;\n@p bra WAIT_LOOP;\ntrap;\n"
      "WAIT_DONE:\n}\n" ::"r"(bar), "r"(parity) : "memory");
}
__device__ __forceinline__ void tma3d(uint32_t dst, const CUtensorMap* m, int c0, int c1, int c2, uint32_t bar) {
  asm volatile("cp.async.bulk.tensor.3d.shared::cluster.global.mbarrier::complete_tx::bytes [%0], [%1, {%3, %4, %5}], [%2];"
               ::"r"(dst), "l"(m), "r"(bar), "r"(c0), "r"(c1), "r"(c2) : "memory");
}
__device__ __forceinline__ void tma3d_hint(uint32_t dst, const CUtensorMap* m, int c0, int c1, int c2, uint32_t bar, uint64_t pol) {
  asm volatile("cp.async.bulk.tensor.3d.shared::cluster.global.mbarrier::complete_tx::bytes.L2::cache_hint [%0], [%1, {%3, %4, %5}], [%2], %6;"
               ::"r"(dst), "l"(m), "r"(bar), "r"(c0), "r"(c1), "r"(c2), "l"(pol) : "memory");
}
__device__ __forceinline__ void tma2d_mc(uint32_t dst, const CUtensorMap* m, int c0, int c1, uint32_t bar) {
  asm volatile("cp.async.bulk.tensor.2d.shared::cluster.global.mbarrier::complete_tx::bytes.multicast::cluster [%0], [%1, {%3, %4}], [%2], %5;"
               ::"r"(dst), "l"(m), "r"(bar), "r"(c0), "r"(c1), "h"((uint16_t)3) : "memory");
}
__device__ __forceinline__ void tma3d_mc(uint32_t dst, const CUtensorMap* m, int c0, int c1, int c2, uint32_t bar) {
  asm volatile("cp.async.bulk.tensor.3d.shared::cluster.global.mbarrier::complete_tx::bytes.multicast::cluster [%0], [%1, {%3, %4, %5}], [%2], %6;"
               ::"r"(dst), "l"(m), "r"(bar), "r"(c0), "r"(c1), "r"(c2), "h"((uint16_t)3) : "memory");
}
__device__ __forceinline__ void l2_prefetch(const void* p, uint32_t bytes) {
  asm volatile("cp.async.bulk.prefetch.L2.global [%0], %1;" ::"l"(p), "r"(bytes) : "memory");
}
__device__ __forceinline__ void fence_async_smem() { asm volatile("fence.proxy.async.shared::cta;" ::: "memory"); }
__device__ __forceinline__ void bar_sync(int wg) {
  if (wg == 0) asm volatile("bar.sync 1, 128;" ::: "memory");
  else asm volatile("bar.sync 2, 128;" ::: "memory");
}
__device__ __forceinline__ bool bar_red_or(int wg, bool v) {
  uint32_t r;
  if (wg == 0) asm volatile("{\n.reg .pred p, q;\nsetp.ne.u32 p, %1, 0;\nbar.red.or.pred q, 1, 128, p;\nselp.u32 %0, 1, 0, q;\n}\n" : "=r"(r) : "r"((uint32_t)v) : "memory");
  else asm volatile("{\n.reg .pred p, q;\nsetp.ne.u32 p, %1, 0;\nbar.red.or.pred q, 2, 128, p;\nselp.u32 %0, 1, 0, q;\n}\n" : "=r"(r) : "r"((uint32_t)v) : "memory");
  return r != 0;
}
__device__ __forceinline__ uint32_t hfma2(uint32_t a, uint32_t b, uint32_t c) { uint32_t r; asm("fma.rn.bf16x2 %0, %1, %2, %3;" : "=r"(r) : "r"(a), "r"(b), "r"(c)); return r; }
__device__ __forceinline__ float ex2(float x) { float y; asm("ex2.approx.ftz.f32 %0, %1;" : "=f"(y) : "f"(x)); return y; }
__device__ __forceinline__ uint32_t pack(float lo, float hi) { uint32_t r; asm("cvt.rn.bf16x2.f32 %0, %1, %2;" : "=r"(r) : "f"(hi), "f"(lo)); return r; }
__device__ __forceinline__ void stsm4t(uint32_t a, uint32_t r0, uint32_t r1, uint32_t r2, uint32_t r3) {
  asm volatile("stmatrix.sync.aligned.m8n8.x4.trans.shared.b16 [%0], {%1,%2,%3,%4};" ::"r"(a), "r"(r0), "r"(r1), "r"(r2), "r"(r3) : "memory");
}
__device__ __forceinline__ void stsm2t(uint32_t a, uint32_t r0, uint32_t r1) {
  asm volatile("stmatrix.sync.aligned.m8n8.x2.trans.shared.b16 [%0], {%1,%2};" ::"r"(a), "r"(r0), "r"(r1) : "memory");
}
__device__ __forceinline__ void mma16816(float (&d)[4], const uint32_t (&a)[4], uint32_t b0, uint32_t b1) {
  asm volatile("mma.sync.aligned.m16n8k16.row.col.f32.bf16.bf16.f32 {%0,%1,%2,%3}, {%4,%5,%6,%7}, {%8,%9}, {%0,%1,%2,%3};"
               : "+f"(d[0]), "+f"(d[1]), "+f"(d[2]), "+f"(d[3]) : "r"(a[0]), "r"(a[1]), "r"(a[2]), "r"(a[3]), "r"(b0), "r"(b1));
}

__device__ __forceinline__ uint32_t fresh_tid() { uint32_t t; asm volatile("mov.u32 %0, %tid.x;" : "=r"(t)); return t; }

template <int V> struct IC { static constexpr int value = V; };

struct Ring {
  uint32_t slot = 0, phase = 0;
  __device__ __forceinline__ void next() { if (++slot == RING_SLOTS) { slot = 0; phase ^= 1; } }
};

__device__ __forceinline__ void mma_tn(float (&o0)[60], float (&o1)[60], uint32_t a, uint32_t b, int acc) {
#pragma unroll
  for (int k = 0; k < 4; k++) {
    wgmma_n120<1, 0>(o0, a + k * 128, HI128, b + k * 2, HI128, k == 0 ? acc : 1);
    wgmma_n120<1, 0>(o1, a + 512 + k * 128, HI128, b + k * 2, HI128, k == 0 ? acc : 1);
  }
}
__device__ __forceinline__ void mma_tn_split(float (&o0)[60], float (&o1)[60], uint32_t a, uint32_t b) {
#pragma unroll
  for (int k = 0; k < 4; k++) wgmma_n120<1, 0>(o0, a + k * 128, HI128, b + k * 2, HI128, 1);
  wg_commit();
#pragma unroll
  for (int k = 0; k < 4; k++) wgmma_n120<1, 0>(o1, a + 512 + k * 128, HI128, b + k * 2, HI128, 1);
  wg_commit();
}
__device__ __forceinline__ void mma_qk(float (&s)[60], uint32_t a, uint32_t q) {
#pragma unroll
  for (int k = 0; k < 8; k++)
    wgmma_n120<0, 0>(s, a + (k >> 2) * 512 + (k & 3) * 2, HI128, q + (k >> 2) * (XB >> 4) + (k & 3) * 2, HI128, k != 0);
}
template <int J0, int J1, bool FIRST = false>
__device__ __forceinline__ void exp_store(const float (&s)[60], float (&l)[30], uint32_t dst) {
#pragma unroll
  for (int c = J0; c < J1; c++) {
    const float e0 = ex2(s[4 * c]), e1 = ex2(s[4 * c + 1]), e2 = ex2(s[4 * c + 2]), e3 = ex2(s[4 * c + 3]);
    if (FIRST) { l[2 * c] = e0 + e2; l[2 * c + 1] = e1 + e3; }
    else { l[2 * c] += e0; l[2 * c + 1] += e1; l[2 * c] += e2; l[2 * c + 1] += e3; }
    stsm2t(dst + c * 1024, pack(e0, e1), pack(e2, e3));
  }
}

__device__ __forceinline__ int o_pos(int b, int wg, int r) {
  const int j = r >> 3, q = (r >> 1) & 3, c = r & 1, o = b & 1, base = (b >> 1) * 480;
  if (j < 12) return base + (o * 9 + wg * 3 + (j >> 2)) * 32 + q * 8 + (j & 3) * 2 + c;
  if (j < 14) return base + (6 + 2 * o) * 32 + wg * 16 + q * 4 + (j - 12) * 2 + c;
  return base + 7 * 32 + (o * 2 + wg) * 8 + q * 2 + c;
}
__device__ __forceinline__ int o_row(int p) {
  const int pair = p / 480, a = (p - pair * 480) >> 5, in = p & 31, c = p & 1;
  int tile, row;
  if (a == 7) { tile = in >> 3; row = 112 + (in & 7); }
  else if (a == 6 || a == 8) { tile = a - 6 + (in >> 4); row = (12 + ((in >> 1) & 1)) * 8 + ((in >> 2) & 3) * 2 + c; }
  else { const int f = a > 8 ? a - 3 : a; tile = f / 3; row = ((f - tile * 3) * 4 + ((in >> 1) & 3)) * 8 + (in >> 3) * 2 + c; }
  return pair * 480 + tile * 120 + row;
}
__device__ __forceinline__ uint32_t o_idx(int k, int p) {
  return ((k >> 3) * (NROWS / 32) + (p >> 5)) * 256 + (k & 7) * 32 + ((((p >> 3) & 3) ^ ((k & 7) >> 1)) << 3) + (p & 7);
}

__device__ __noinline__ void slow_path(const Params P, int b, int h, int wg, int w, int lane) {
  const int g = lane >> 2, q = lane & 3, row0 = wg * 120;
  const uint16_t* wq = reinterpret_cast<const uint16_t*>(P.wq) + h * DH + g;
  const __nv_bfloat16* kp = P.k + (size_t)(b * NH + h) * SK * DH;
  const uint16_t* vp = reinterpret_cast<const uint16_t*>(P.v) + (size_t)(b * NH + h) * SK * DH + g;
#pragma unroll 1
  for (int t = w; t < 8; t += 4) {
    const int r0 = 16 * t + g, r1 = r0 + 8;
    const __nv_bfloat16* x0 = P.x + (size_t)(b * SQ + row0 + r0) * DM + 2 * q;
    const __nv_bfloat16* x1 = P.x + (size_t)(b * SQ + row0 + min(r1, 119)) * DM + 2 * q;
    float o[16][4];
#pragma unroll
    for (int n = 0; n < 16; n++) o[n][0] = o[n][1] = o[n][2] = o[n][3] = 0.f;
#pragma unroll 1
    for (int k0 = 0; k0 < DM; k0 += 16) {
      uint32_t a[4] = {*(const uint32_t*)(x0 + k0), *(const uint32_t*)(x1 + k0), *(const uint32_t*)(x0 + k0 + 8), *(const uint32_t*)(x1 + k0 + 8)};
      const uint16_t* wr = wq + (size_t)(k0 + 2 * q) * HD;
#pragma unroll
      for (int n = 0; n < 16; n++) {
        if ((n & 3) == 0) __syncwarp();
        mma16816(o[n], a, wr[8 * n] | ((uint32_t)wr[8 * n + HD] << 16), wr[8 * n + 8 * HD] | ((uint32_t)wr[8 * n + 9 * HD] << 16));
      }
    }
    uint32_t qa[8][4];
#pragma unroll
    for (int k = 0; k < 8; k++) {
      qa[k][0] = pack(o[2 * k][0] * QSCALE, o[2 * k][1] * QSCALE);
      qa[k][1] = pack(o[2 * k][2] * QSCALE, o[2 * k][3] * QSCALE);
      qa[k][2] = pack(o[2 * k + 1][0] * QSCALE, o[2 * k + 1][1] * QSCALE);
      qa[k][3] = pack(o[2 * k + 1][2] * QSCALE, o[2 * k + 1][3] * QSCALE);
    }
#pragma unroll
    for (int n = 0; n < 16; n++) o[n][0] = o[n][1] = o[n][2] = o[n][3] = 0.f;
    float m0 = -INFINITY, m1 = -INFINITY, l0 = 0.f, l1 = 0.f;
#pragma unroll 1
    for (int key0 = 0; key0 < SK; key0 += 16) {
      float s[2][4];
#pragma unroll
      for (int nt = 0; nt < 2; nt++) {
        s[nt][0] = s[nt][1] = s[nt][2] = s[nt][3] = 0.f;
        const __nv_bfloat16* kr = kp + (size_t)(key0 + 8 * nt + g) * DH + 2 * q;
#pragma unroll
        for (int k = 0; k < 8; k++) mma16816(s[nt], qa[k], *(const uint32_t*)(kr + 16 * k), *(const uint32_t*)(kr + 16 * k + 8));
      }
      float n0 = fmaxf(fmaxf(s[0][0], s[0][1]), fmaxf(s[1][0], s[1][1])), n1 = fmaxf(fmaxf(s[0][2], s[0][3]), fmaxf(s[1][2], s[1][3]));
      n0 = fmaxf(n0, __shfl_xor_sync(~0u, n0, 1)); n1 = fmaxf(n1, __shfl_xor_sync(~0u, n1, 1));
      n0 = fmaxf(n0, __shfl_xor_sync(~0u, n0, 2)); n1 = fmaxf(n1, __shfl_xor_sync(~0u, n1, 2));
      n0 = fmaxf(n0, m0); n1 = fmaxf(n1, m1);
      const float z0 = n0 == -INFINITY ? 0.f : n0, z1 = n1 == -INFINITY ? 0.f : n1;
      const float c0 = ex2(m0 - z0), c1 = ex2(m1 - z1);
      m0 = n0; m1 = n1;
#pragma unroll
      for (int nt = 0; nt < 2; nt++) {
        s[nt][0] = ex2(s[nt][0] - z0); s[nt][1] = ex2(s[nt][1] - z0);
        s[nt][2] = ex2(s[nt][2] - z1); s[nt][3] = ex2(s[nt][3] - z1);
      }
      l0 = l0 * c0 + s[0][0] + s[0][1] + s[1][0] + s[1][1];
      l1 = l1 * c1 + s[0][2] + s[0][3] + s[1][2] + s[1][3];
      uint32_t pa[4] = {pack(s[0][0], s[0][1]), pack(s[0][2], s[0][3]), pack(s[1][0], s[1][1]), pack(s[1][2], s[1][3])};
      const uint16_t* vr = vp + (size_t)(key0 + 2 * q) * DH;
#pragma unroll
      for (int n = 0; n < 16; n++) {
        if ((n & 3) == 0) __syncwarp();
        o[n][0] *= c0; o[n][1] *= c0; o[n][2] *= c1; o[n][3] *= c1;
        mma16816(o[n], pa, vr[8 * n] | ((uint32_t)vr[8 * n + DH] << 16), vr[8 * n + 8 * DH] | ((uint32_t)vr[8 * n + 9 * DH] << 16));
      }
    }
    l0 += __shfl_xor_sync(~0u, l0, 1); l1 += __shfl_xor_sync(~0u, l1, 1);
    l0 += __shfl_xor_sync(~0u, l0, 2); l1 += __shfl_xor_sync(~0u, l1, 2);
    const float i0 = __fdividef(1.f, l0), i1 = __fdividef(1.f, l1);
    __nv_bfloat16* oc0 = P.o + o_idx(h * DH + 2 * q, o_pos(b, wg, r0));
    __nv_bfloat16* oc1 = P.o + o_idx(h * DH + 2 * q, o_pos(b, wg, min(r1, 119)));
#pragma unroll
    for (int n = 0; n < 16; n++) {
      oc0[8 * n * NROWS] = __float2bfloat16(o[n][0] * i0);
      oc0[8 * n * NROWS + 32] = __float2bfloat16(o[n][1] * i0);
      if (r1 < 120) {
        oc1[8 * n * NROWS] = __float2bfloat16(o[n][2] * i1);
        oc1[8 * n * NROWS + 32] = __float2bfloat16(o[n][3] * i1);
      }
    }
  }
}

__device__ __forceinline__ int bk(int ks) { return ks < 48 ? 32 - (ks & 48) + (ks & 15) : ks; }
__device__ __forceinline__ uint32_t x_slot(uint32_t wg, uint32_t j) { return j < 2 ? (2 * wg + j) * XB : (2 * j + wg) * XB; }
__device__ __forceinline__ int row_block(int t) { return t >= 44 ? (t >> 2) - 11 : (t >> 2) + 4; }
__device__ __forceinline__ int cluster_id(int c) {
  const int t = c >= 4 ? c - 4 : c + 62;
  return ROLEMAP == 0 || t < 44 || t >= 60 ? t : t < 46 ? t + 14 : t - 2;
}
__device__ __forceinline__ int unit_batch(int u) { return (u & 63) >> 2; }
__device__ __forceinline__ int unit_head(int u, int rank) { return (u >> 6) * 8 + (u & 3) * 2 + rank; }

template <int NCL>
__global__ void __cluster_dims__(2, 1, 1) __launch_bounds__(384, 1)
fused_attn_kernel(const __grid_constant__ CUtensorMap tm_x, const __grid_constant__ CUtensorMap tm_wq,
                  const __grid_constant__ CUtensorMap tm_k, const __grid_constant__ CUtensorMap tm_v,
                  const __grid_constant__ CUtensorMap tm_o, const __grid_constant__ CUtensorMap tm_wo,
                  const __grid_constant__ Params P) {
  extern __shared__ uint8_t smem_raw[];
  const uint32_t sb = ((uint32_t)__cvta_generic_to_shared(smem_raw) + 1023) & ~1023u;
  const int warp = __shfl_sync(~0u, threadIdx.x >> 5, 0);
  const int lane = threadIdx.x & 31;
  const int rank = blockIdx.x & 1, ncl = NCL ? NCL : gridDim.x >> 1;
  const int id = NCL == 66 ? cluster_id(blockIdx.x >> 1) : blockIdx.x >> 1;
  const int id0 = NCL == 66 && UMAP ? (id >= 58 ? id - 58 : id + 8) : id;
  auto unit = [&](int it) { return (it < 3 ? id0 : id) + it * ncl; };
  const int nsingle = NCL == 66 ? 44 : NOTILES;
  const bool dbl = NCL == 66 && id >= 58, gemm = id < nsingle || dbl;

  if (threadIdx.x == 128) asm volatile("prefetch.tensormap [%0];" ::"l"(&tm_x) : "memory");
  if (threadIdx.x == 0) {
    asm volatile("prefetch.tensormap [%0];" ::"l"(&tm_wq) : "memory");
    for (int i = 0; i < 6; i++) {
      mbar_init(sb + BAR_RFULL + 8 * i, 1); mbar_init(sb + BAR_REMPTY + 8 * i, 8);
      mbar_init(sb + BAR_BFULL + 8 * i, 1); mbar_init(sb + BAR_BEMPTY + 8 * i, 16);
    }
    for (int i = 0; i < 8; i++) mbar_init(sb + BAR_XFULL + 8 * i, 1);
    for (int i = 0; i < 4; i++) mbar_init(sb + BAR_XEMPTY + 8 * i, 8);
    for (int i = 0; i < 2; i++) { mbar_init(sb + BAR_STAGE + 8 * i, 4); mbar_init(sb + BAR_LSUM + 8 * i, 4); mbar_init(sb + BAR_INV + 8 * i, 1); }
    asm volatile("fence.mbarrier_init.release.cluster;" ::: "memory");
  }
  __syncwarp();
  asm volatile("barrier.cluster.arrive.relaxed.aligned;" ::: "memory");
  auto first_w = [&](int s) {
    mbar_expect(sb + BAR_RFULL + 8 * s, RING_BYTES);
    tma3d(sb + s * RING_BYTES, &tm_wq, 0, s * 64, 2 * unit_head(id0, rank), sb + BAR_RFULL + 8 * s);
  };
  if (threadIdx.x == 0) first_w(0);
  __syncwarp();
  asm volatile("barrier.cluster.wait.aligned;" ::: "memory");
  if (threadIdx.x == 128) {
#pragma unroll 1
    for (int s = 0; s < 2; s++) {
      const uint32_t fb = sb + BAR_XFULL + 32 * rank + 8 * s;
      mbar_expect(fb, XB);
      mbar_expect_cl(mapa(fb, rank ^ 1), XB);
      tma2d_mc(sb + OFF_Q + x_slot(rank, s), &tm_x, s * 64, unit_batch(id0) * SQ + rank * 120, fb);
      if (s == 0) first_w(1);
    }
  }
  __syncwarp();

  if (warp >= 8) {
    asm volatile("setmaxnreg.dec.sync.aligned.u32 24;");
    if (warp == 8) {
      uint64_t pol;
      asm volatile("createpolicy.fractional.L2::evict_first.b64 %0, 1.0;" : "=l"(pol));
      Ring r;
      r.slot = 2;
      auto load = [&](const CUtensorMap* m, int c1, int c2, bool ef) {
        mbar_sleep(sb + BAR_REMPTY + 8 * r.slot, r.phase ^ 1);
        if (lane == 0) {
          mbar_expect(sb + BAR_RFULL + 8 * r.slot, RING_BYTES);
          if (ef) tma3d_hint(sb + r.slot * RING_BYTES, m, 0, c1, c2, sb + BAR_RFULL + 8 * r.slot, pol);
          else tma3d(sb + r.slot * RING_BYTES, m, 0, c1, c2, sb + BAR_RFULL + 8 * r.slot);
        }
        r.next();
      };
      for (int u0 = 0; id + u0 < NUNITS; u0 += ncl) {
        const int u = (u0 < 3 * ncl ? id0 : id) + u0;
        if (NCL == 66 && u0 == 2 * 66 && !gemm) {
          unsigned t0, t1;
          asm volatile("mov.u32 %0, %globaltimer_lo;" : "=r"(t0));
          do { __nanosleep(200); asm volatile("mov.u32 %0, %globaltimer_lo;" : "=r"(t1)); } while (t1 - t0 < PAUSE_NS);
        }
        const int h = unit_head(u, rank);
        const int krow = (unit_batch(u) * NH + h) * SK;
#pragma unroll 1
        for (int s = u0 == 0 ? 2 : 0; s < 10; s++) {
          load(&tm_wq, s * 64, 2 * h, false);
          const int sp = u0 == 0 ? s - 6 : s;
          if (sp >= 0 && sp < PF_N && lane == 0) l2_prefetch(P.v + (size_t)(krow + (PF_J0 + sp * PF_STEP) * 64) * DH, 16384);
        }
#pragma unroll 1
        for (int j = 0; j <= 16; j++) {
          if (j < 16) load(&tm_k, krow + j * 64, 0, true);
          if (j == 2) load(&tm_v, krow, 0, true);
          if (j > 1) load(&tm_v, krow + (j - 1) * 64, 0, true);
        }
      }
      for (int t = dbl ? 2 * id - 72 : id; t < (dbl ? NOTILES : nsingle); t += ncl) {
        const int row0 = row_block(t) * 256 + rank * 128;
        const int b0 = row0 / SQ, b1 = (row0 + 127) / SQ;
#pragma unroll 1
        for (int ks = 0; ks < 64; ks++) {
          if (dbl ? (ks & 15) == 0 : ks == 0 || ks == 48) {
            const unsigned* c = &g_cnt[((lane & 1 ? b1 : b0) * 4 + (ks || dbl ? ks >> 4 : min(lane >> 1, 2))) * 8];
            unsigned v, n = 0;
            do {
              asm volatile("ld.acquire.gpu.global.u32 %0, [%1];" : "=r"(v) : "l"(c) : "memory");
              if (++n > (1u << 26)) __trap();
            } while (v < 16);
            __syncwarp();
            asm volatile("fence.proxy.async.global;" ::: "memory");
          }
          mbar_wait(sb + BAR_REMPTY + 8 * r.slot, r.phase ^ 1);
          if (lane == 0) {
            mbar_expect(sb + BAR_RFULL + 8 * r.slot, RING_BYTES);
            asm volatile("cp.async.bulk.tensor.4d.shared::cluster.global.mbarrier::complete_tx::bytes.L2::cache_hint [%0], [%1, {%3, %3, %4, %5}], [%2], %6;"
                         ::"r"(sb + r.slot * RING_BYTES), "l"(&tm_o), "r"(sb + BAR_RFULL + 8 * r.slot), "r"(0), "r"((dbl ? ks : bk(ks)) * 8), "r"(row0 >> 6), "l"(pol) : "memory");
          }
          r.next();
        }
      }
      if (lane == 0 && atomicAdd(&g_cnt[64 * 8], 1) == gridDim.x - 1) {
        for (int i = 0; i < 65; i++) g_cnt[i * 8] = 0;
      }
    } else if (warp == 9) {
      if (lane == 0) {
        for (uint32_t it = 0; id + it * ncl < NUNITS; it++) {
          const int row = unit_batch(unit(it)) * SQ + rank * 120;
#pragma unroll 1
          for (int s = it == 0 ? 2 : 0; s < 10; s++) {
            const uint32_t j = s & 3, par = ((s >> 2) + (j < 2 ? it : 0)) & 1;
            if (s == 0) mbar_sleep(sb + BAR_XEMPTY, par ^ 1);
            mbar_wait(sb + BAR_XEMPTY + 8 * j, par ^ 1);
            const uint32_t fb = sb + BAR_XFULL + 32 * rank + 8 * j;
            mbar_expect(fb, XB);
            mbar_expect_cl(mapa(fb, rank ^ 1), XB);
            tma2d_mc(sb + OFF_Q + x_slot(rank, j), &tm_x, s * 64, row, fb);
          }
        }
        uint32_t slot = rank, phase = 0;
        if (dbl) {
#pragma unroll 1
          for (int ks = (id >> 1) & 3; ks < WO_PF; ks += 4)
            asm volatile("cp.async.bulk.prefetch.tensor.3d.L2.global [%0, {%1, %2, %3}];" ::"l"(&tm_wo), "r"(0), "r"(ks * 64), "r"(((2 * id - 72 + rank) & 3) * 5) : "memory");
        }
        if (gemm) mbar_sleep(sb + BAR_BEMPTY + 8 * rank, 0);
        for (int t = dbl ? 2 * id - 72 + rank : id; t < (dbl ? NOTILES : nsingle); t += ncl) {
#pragma unroll 1
          for (int ks = dbl ? 0 : rank; ks < 64; ks += dbl ? 1 : 2) {
            mbar_wait(sb + BAR_BEMPTY + 8 * slot, phase);
            const uint32_t fb = sb + BAR_BFULL + 8 * slot;
            mbar_expect(fb, BB);
            mbar_expect_cl(mapa(fb, rank ^ 1), BB);
            tma3d_mc(sb + OFF_Q + slot * BB, &tm_wo, 0, (dbl ? ks : bk(ks)) * 64, (t & 3) * 5, fb);
            if (dbl && ks + WO_PF < 64 && (ks & 3) == ((id >> 1) & 3))
              asm volatile("cp.async.bulk.prefetch.tensor.3d.L2.global [%0, {%1, %2, %3}];" ::"l"(&tm_wo), "r"(0), "r"((ks + WO_PF) * 64), "r"((t & 3) * 5) : "memory");
            slot += 2;
            if (slot >= 6) { slot -= 6; phase ^= 1; }
          }
        }
      }
    } else {
      const int wg = warp - 10;
      {
        mbar_wait(sb + BAR_RFULL, 0);
        const __nv_bfloat16* xs = P.x + (size_t)(unit_batch(id0) * SQ + ((id0 & 3) * 2 + rank) * 30 + min(lane, 29)) * DM + 256 + wg * 64;
#pragma unroll
        for (int i = 0; i < 3; i++) asm volatile("prefetch.global.L2 [%0];" ::"l"(xs + i * 128));
        if (lane < 16) asm volatile("prefetch.global.L2 [%0];" ::"l"(P.wq + (size_t)(384 + unit_batch(id0) * 16 + lane) * HD + unit_head(id0, rank) * DH + wg * 64));
      }
      for (uint32_t it = 0; id + it * ncl < NUNITS; it++) {
        const int u = unit(it);
        mbar_sleep(sb + BAR_LSUM + 8 * wg, it & 1);
        float l4[4], v[4];
        const uint32_t a = sb + OFF_L2 + wg * 2048 + (fresh_tid() & 31) * 16;
        asm volatile("ld.shared.v4.f32 {%0, %1, %2, %3}, [%4];" : "=f"(l4[0]), "=f"(l4[1]), "=f"(l4[2]), "=f"(l4[3]) : "r"(a) : "memory");
#pragma unroll
        for (int g = 1; g < 4; g++) {
          asm volatile("ld.shared.v4.f32 {%0, %1, %2, %3}, [%4];" : "=f"(v[0]), "=f"(v[1]), "=f"(v[2]), "=f"(v[3]) : "r"(a + g * 512) : "memory");
#pragma unroll
          for (int c = 0; c < 4; c++) l4[c] += v[c];
        }
#pragma unroll
        for (int c = 0; c < 4; c++) {
          float inv;
          asm("rcp.approx.ftz.f32 %0, %1;" : "=f"(inv) : "f"(l4[c]));
          l4[c] = l4[c] >= L_MIN && l4[c] <= L_MAX ? inv : __uint_as_float(0x7FFFFFFFu);
        }
        const uint32_t h0 = pack(l4[0], l4[1]), h1 = pack(l4[2], l4[3]);
        const uint32_t e0 = pack(l4[0] - __uint_as_float(h0 << 16), l4[1] - __uint_as_float(h0 & 0xFFFF0000u));
        const uint32_t e1 = pack(l4[2] - __uint_as_float(h1 << 16), l4[3] - __uint_as_float(h1 & 0xFFFF0000u));
        const uint32_t tid = fresh_tid();
        asm volatile("st.shared.v4.u32 [%0], {%1, %2, %3, %4};" ::"r"(sb + OFF_INV + wg * 640 + (tid & 3) * 144 + (tid & 28) * 4), "r"(h0), "r"(e0), "r"(h1), "r"(e1) : "memory");
        __syncwarp();
        warp_arrive(sb + BAR_INV + 8 * wg);
        mbar_sleep(sb + BAR_STAGE + 8 * wg, it & 1);
        if (lane == 0) {
          __threadfence();
          asm volatile("red.relaxed.gpu.global.add.u32 [%0], 1;" ::"l"(&g_cnt[(unit_batch(u) * 4 + (u >> 6)) * 8]) : "memory");
        }
        __syncwarp();
      }
    }
  } else {
    asm volatile("setmaxnreg.inc.sync.aligned.u32 240;");
    const int wg = warp >> 2, w = warp & 3;
    const uint32_t qreg = sb + OFF_Q + wg * 2 * XB, preg = sb + OFF_P + (2 + wg) * XB;
    const uint32_t st_off = ((lane >> 4) * 8 + (lane & 7)) * 128 + (((2 * w + ((lane >> 3) & 1)) ^ (lane & 7)) << 4);
    const uint32_t xempty = mapa(sb + BAR_XEMPTY, wg);
    Ring r;
    uint32_t it = 0;
    const uint32_t qd = (qreg & 0x3FFFF) >> 4, pd = (preg & 0x3FFFF) >> 4;
    auto ring_addr = [&]() { return ((sb & 0x3FFFF) + r.slot * RING_BYTES) >> 4; };
    auto ring_wait = [&]() { mbar_wait(sb + BAR_RFULL + 8 * r.slot, r.phase); };
    auto release = [&](uint32_t slot) { warp_arrive(sb + BAR_REMPTY + 8 * slot); };
    auto turn_wait = [&]() {
      if (wg == 0) asm volatile("bar.sync 3, 256;" ::: "memory");
      else asm volatile("bar.sync 4, 256;" ::: "memory");
    };
    auto turn_pass = [&]() {
      if (wg == 0) asm volatile("bar.arrive 4, 256;" ::: "memory");
      else asm volatile("bar.arrive 3, 256;" ::: "memory");
    };

    uint32_t chk = 0;
    auto sum_l = [&](const float (&l)[30], uint32_t tid) {
      float a[16], b[8], c[4];
      const bool b4 = tid & 16, b3 = tid & 8, b2 = tid & 4;
#pragma unroll
      for (int i = 0; i < 16; i++) {
        const float hi = i < 14 ? l[(16 + i) % 30] : 1.f;
        a[i] = (b4 ? hi : l[i]) + __shfl_xor_sync(~0u, b4 ? l[i] : hi, 16);
      }
#pragma unroll
      for (int i = 0; i < 8; i++) b[i] = (b3 ? a[8 + i] : a[i]) + __shfl_xor_sync(~0u, b3 ? a[i] : a[8 + i], 8);
#pragma unroll
      for (int i = 0; i < 4; i++) c[i] = (b2 ? b[4 + i] : b[i]) + __shfl_xor_sync(~0u, b2 ? b[i] : b[4 + i], 4);
      asm volatile("st.shared.v4.f32 [%0], {%1, %2, %3, %4};" ::"r"(sb + OFF_L2 + tid * 16), "f"(c[0]), "f"(c[1]),
                   "f"(c[2]), "f"(c[3]) : "memory");
      __syncwarp();
      warp_arrive(sb + BAR_LSUM + 8 * wg);
    };
    auto load_inv = [&](uint32_t (&iv)[30], uint32_t parity) {
      const int lane = fresh_tid() & 31;
      mbar_wait(sb + BAR_INV + 8 * wg, parity);
      chk = 0;
#pragma unroll
      for (int j = 0; j < 7; j++)
        asm volatile("ld.shared.v4.u32 {%0, %1, %2, %3}, [%4];" : "=r"(iv[4 * j]), "=r"(iv[4 * j + 1]), "=r"(iv[4 * j + 2]), "=r"(iv[4 * j + 3])
                     : "r"(sb + OFF_INV + wg * 640 + (lane & 3) * 144 + j * 16) : "memory");
      asm volatile("ld.shared.v2.u32 {%0, %1}, [%2];" : "=r"(iv[28]), "=r"(iv[29]) : "r"(sb + OFF_INV + wg * 640 + (lane & 3) * 144 + 112) : "memory");
    };
    auto norm = [&](uint32_t (&n)[8], const uint32_t (&po)[60], const uint32_t (&iv)[30], auto part) {
      constexpr int k = decltype(part)::value >> 1, j0 = (decltype(part)::value & 1) * 8;
#pragma unroll
      for (int j = 0; j < 8; j++)
        n[j] = j0 + j < 15 ? hfma2(po[15 * k + (j0 + j) % 15], iv[2 * ((j0 + j) % 15)], hfma2(po[15 * k + (j0 + j) % 15], iv[2 * ((j0 + j) % 15) + 1], 0x80008000u)) : 0x3F803F80u;
#pragma unroll
      for (int j = 0; j < 8; j += 2) chk = hfma2(n[j], n[j + 1], chk);
    };
    int od1, od2;
    auto store = [&](const uint32_t (&n)[8], const char* optr, auto part) {
      constexpr int k = decltype(part)::value >> 1, off = (8 * (k & 1) + 64 * (k >> 1)) * NROWS * 2;
      if ((decltype(part)::value & 1) == 0)
        asm volatile(
            "{\n.reg .pred p;\nsetp.ne.u64 p, %8, 0;\n"
            "@p st.global.v4.u32 [%8 + %9], {%0, %1, %2, %3};\n@p st.global.v4.u32 [%8 + %9 + 512], {%4, %5, %6, %7};\n}\n"
            ::"r"(n[0]), "r"(n[1]), "r"(n[2]), "r"(n[3]), "r"(n[4]), "r"(n[5]), "r"(n[6]), "r"(n[7]), "l"(optr), "n"(off) : "memory");
      else
        asm volatile(
            "{\n.reg .pred p;\n.reg .b64 b, c;\nsetp.ne.u64 p, %7, 0;\nmad.wide.s32 b, %9, 1, %7;\nmad.wide.s32 c, %10, 1, %7;\n"
            "@p st.global.v4.u32 [%7 + %8 + 1024], {%0, %1, %2, %3};\n@p st.global.v2.u32 [b + %8], {%4, %5};\n@p st.global.u32 [c + %8], %6;\n}\n"
            ::"r"(n[0]), "r"(n[1]), "r"(n[2]), "r"(n[3]), "r"(n[4]), "r"(n[5]), "r"(n[6]), "l"(optr), "n"(off), "r"(od1), "r"(od2) : "memory");
    };
    auto put = [&](const uint32_t (&po)[60], const uint32_t (&iv)[30], const char* optr, auto part) {
      uint32_t n[8];
      norm(n, po, iv, part);
      store(n, optr, part);
    };
    auto out_ptr = [&](int u) {
      const int lane = fresh_tid() & 31;
      const int k = unit_head(u, rank) * DH + 16 * w + (lane >> 2), b = unit_batch(u), q = lane & 3;
      const uint32_t i0 = o_idx(k, o_pos(b, wg, 2 * q));
      od1 = 2 * (int)(o_idx(k, o_pos(b, wg, 96 + 2 * q)) - i0);
      od2 = 2 * (int)(o_idx(k, o_pos(b, wg, 112 + 2 * q)) - i0);
      return reinterpret_cast<const char*>(P.o + i0);
    };
    auto unsafe = [&](bool valid) {
      const bool b = valid && ((chk & 0x7F80u) == 0x7F80u || (chk & 0x7F800000u) == 0x7F800000u);
      return __any_sync(~0u, bar_red_or(wg, b));
    };
    auto publish = [&]() { __syncwarp(); warp_arrive(sb + BAR_STAGE + 8 * wg); };

    uint32_t po[60];
#pragma unroll
    for (int i = 0; i < 60; i++) po[i] = 0;
    float o0[60], o1[60];
    ring_wait();
    mbar_wait(sb + BAR_XFULL + 32 * wg, 0);
    wg_fence();
    mma_tn(o0, o1, ring_addr(), qd, 0);
    wg_commit();
    while (true) {
      uint32_t prev = r.slot;
      r.next();
      auto qstep = [&](int s) {
        const uint32_t j = s & 3, par = ((s >> 2) + (j < 2 ? it : 0)) & 1;
        ring_wait();
        mbar_wait(sb + BAR_XFULL + 32 * wg + 8 * j, par);
        if (s >= ALT_FROM) turn_wait();
        wg_fence();
        mma_tn(o0, o1, ring_addr(), ((sb & 0x3FFFF) + OFF_Q + x_slot(wg, j)) >> 4, 1);
        wg_commit();
        if (s >= ALT_FROM || (s == ALT_FROM - 1 && wg == 1)) turn_pass();
        if (s <= 4) {
          wg_wait<1>();
          release(prev);
          warp_arrive_cl(xempty + 8 * ((s - 1) & 3));
        }
        prev = r.slot;
        r.next();
      };
      auto qdone = [&](int s) {
        wg_wait<0>();
        release(prev);
        if (s <= 5) warp_arrive_cl(xempty + 8 * (s & 3));
      };
      qstep(1);
      const int up = unit((int)it - 1);
      const char* optr = out_ptr(up);
      if (it == 0) optr = nullptr;
      uint32_t n7[8];
      {
        uint32_t iv[30];
        load_inv(iv, (it + 1) & 1); put(po, iv, optr, IC<0>());
        qstep(2); put(po, iv, optr, IC<1>());
        qstep(3); put(po, iv, optr, IC<2>());
        qstep(4); put(po, iv, optr, IC<3>()); qdone(4);
        qstep(5); put(po, iv, optr, IC<4>()); qdone(5);
        qstep(6); put(po, iv, optr, IC<5>()); qdone(6);
        qstep(7); put(po, iv, optr, IC<6>()); norm(n7, po, iv, IC<7>()); qdone(7);
      }
      ring_wait();
      mbar_wait(sb + BAR_XFULL + 32 * wg, it & 1);
      turn_wait();
      wg_fence();
      mma_tn(o0, o1, ring_addr(), qd, 1);
      wg_commit();
      prev = r.slot;
      r.next();
      ring_wait();
      mbar_wait(sb + BAR_XFULL + 32 * wg + 8, it & 1);
      wg_fence();
      mma_tn_split(o0, o1, ring_addr(), qd + (XB >> 4));
      turn_pass();
      wg_wait<2>();
      release(prev);
      auto put_q = [&](const float (&o)[60], uint32_t dst) {
#pragma unroll
        for (int j = 0; j < 14; j += 2)
          stsm4t(dst + j * 1024, pack(o[4 * j] * QSCALE, o[4 * j + 1] * QSCALE), pack(o[4 * j + 2] * QSCALE, o[4 * j + 3] * QSCALE),
                 pack(o[4 * j + 4] * QSCALE, o[4 * j + 5] * QSCALE), pack(o[4 * j + 6] * QSCALE, o[4 * j + 7] * QSCALE));
        stsm2t(dst + 14 * 1024, pack(o[56] * QSCALE, o[57] * QSCALE), pack(o[58] * QSCALE, o[59] * QSCALE));
      };
      wg_wait<1>();
      reg_fence(o0);
      const bool redo = unsafe(it > 0);
      put_q(o0, qreg + st_off);
      wg_wait<0>();
      reg_fence(o1);
      release(r.slot);
      r.next();
      bar_sync(wg);
      put_q(o1, qreg + XB + st_off);
      fence_async_smem();
      if (redo) {
        slow_path(P, unit_batch(up), unit_head(up, rank), wg, w, fresh_tid() & 31);
        optr = nullptr; od1 = od2 = 0;
#pragma unroll
        for (int i = 0; i < 8; i++) n7[i] = 0;
      }

      float sc[60], l[30];
      uint32_t slot0 = r.slot;
      ring_wait();
      turn_wait();
      wg_fence();
      mma_qk(sc, ring_addr(), qd);
      wg_commit();
      r.next();
      uint32_t slot1 = r.slot;
      ring_wait();
      wg_fence();
      mma_qk(o1, ring_addr(), qd);
      wg_commit();
      r.next();
      turn_pass();
      store(n7, optr, IC<7>());
      wg_wait<1>();
      reg_fence(sc);
      release(slot0);
      exp_store<0, 15, true>(sc, l, preg + st_off);
      slot0 = r.slot;
      ring_wait();
      wg_fence();
      mma_qk(sc, ring_addr(), qd);
      wg_commit();
      r.next();
      wg_wait<1>();
      reg_fence(o1);
      release(slot1);
      exp_store<0, 15>(o1, l, preg - 2 * XB + st_off);
      fence_async_smem();
      slot1 = r.slot;
      ring_wait();
      turn_wait();
      wg_fence();
      mma_tn(o0, o1, ring_addr(), pd, 0);
      wg_commit();
      r.next();
      ring_wait();
      wg_fence();
      mma_tn(o0, o1, ring_addr(), pd - (2 * XB >> 4), 1);
      wg_commit();
      turn_pass();
      if (it > 0) publish();
      wg_wait<1>();
      reg_fence(sc);
      release(slot0);
      release(slot1);
      bar_sync(wg);
      exp_store<0, VREL>(sc, l, preg + st_off);
      wg_wait<0>();
      reg_fence(o0); reg_fence(o1);
      release(r.slot);
      r.next();
      exp_store<VREL, 15>(sc, l, preg + st_off);
      fence_async_smem();
      const bool more = id + ((int)it + 1) * ncl < NUNITS;
      uint32_t pw = preg + st_off;
#pragma unroll 1
      for (int s = 3; s < 16; s++) {
        const uint32_t kslot = r.slot;
        asm volatile("add.u32 %0, %0, %1;" : "+r"(pw) : "r"(s & 1 ? -2 * (int)XB : 2 * (int)XB));
        ring_wait();
        turn_wait();
        wg_fence();
        mma_qk(sc, ring_addr(), qd);
        wg_commit();
        r.next();
        ring_wait();
        wg_fence();
        mma_tn(o0, o1, ring_addr(), pd - ((s - 1) & 1) * (2 * XB >> 4), 1);
        wg_commit();
        if (wg == 0 || s < 15) turn_pass();
        wg_wait<1>();
        reg_fence(sc);
        release(kslot);
        if (s == 15) {
          if (more) { warp_arrive_cl(xempty); warp_arrive_cl(xempty + 8); }
          else if (gemm) for (int i = 0; i < 3; i++) warp_arrive_cl(mapa(sb + BAR_BEMPTY + 8 * i, i & 1));
        }
        exp_store<0, VREL>(sc, l, pw);
        wg_wait<0>();
        reg_fence(o0); reg_fence(o1);
        release(r.slot);
        r.next();
        exp_store<VREL, 15>(sc, l, pw);
        fence_async_smem();
      }
      const uint32_t tid = fresh_tid();
      bar_sync(wg);
      ring_wait();
      wg_fence();
      mma_tn_split(o0, o1, ring_addr(), pd - (2 * XB >> 4));
      sum_l(l, tid);
      const uint32_t vslot = r.slot;
      r.next();
      it++;
      auto pack_o = [&](const float (&o)[60], int first) {
#pragma unroll
        for (int j = 0; j < 15; j++) { po[first + j] = pack(o[4 * j], o[4 * j + 1]); po[first + 15 + j] = pack(o[4 * j + 2], o[4 * j + 3]); }
      };
      if (!more) {
        wg_wait<0>();
        reg_fence(o0); reg_fence(o1);
        release(vslot);
        if (gemm) for (int i = 3; i < 6; i++) warp_arrive_cl(mapa(sb + BAR_BEMPTY + 8 * i, i & 1));
        pack_o(o0, 0); pack_o(o1, 30);
        break;
      }
      ring_wait();
      mbar_wait(sb + BAR_XFULL + 32 * wg, it & 1);
      wg_wait<1>();
      reg_fence(o0);
      pack_o(o0, 0);
      wg_fence();
#pragma unroll
      for (int k = 0; k < 4; k++) wgmma_n120<1, 0>(o0, ring_addr() + k * 128, HI128, qd + k * 2, HI128, k != 0);
      wg_commit();
      wg_wait<1>();
      reg_fence(o1);
      pack_o(o1, 30);
      wg_fence();
#pragma unroll
      for (int k = 0; k < 4; k++) wgmma_n120<1, 0>(o1, ring_addr() + 512 + k * 128, HI128, qd + k * 2, HI128, k != 0);
      wg_commit();
      release(vslot);
      warp_arrive_cl(xempty + 16); warp_arrive_cl(xempty + 24);
    }
    const int u = unit((int)it - 1);
    uint32_t pb[60];
#pragma unroll
    for (int i = 0; i < 60; i++) pb[i] = NCL != 66 ? po[i] ^ (gridDim.y - 1) : po[i];

    uint32_t bslot = 0, bphase = 0;
    auto out_row = [&](int lane) {
      const int row = lane & 15;
      return sb + wg * 8192 + (row < 12 ? w * RING_BYTES + row * 656 : (4 + (w >> 1)) * RING_BYTES + ((w & 1) * 4 + row - 12) * 656);
    };
    auto out_stage = [&](const float (&acc)[80], uint32_t col_off) {
      const int lane = fresh_tid() & 31;
      const uint32_t sa = out_row(lane) + col_off + (lane >> 4) * 16;
#pragma unroll
      for (int j = 0; j < 20; j += 2)
        asm volatile("stmatrix.sync.aligned.m8n8.x4.shared.b16 [%0], {%1,%2,%3,%4};" ::"r"(sa + j * 16), "r"(pack(acc[4 * j], acc[4 * j + 1])),
                     "r"(pack(acc[4 * j + 2], acc[4 * j + 3])), "r"(pack(acc[4 * j + 4], acc[4 * j + 5])), "r"(pack(acc[4 * j + 6], acc[4 * j + 7])) : "memory");
    };
    auto out_store = [&](int t, uint32_t bytes) {
      const int lane = fresh_tid() & 31;
      if (wg == 1) {
        __syncwarp();
#pragma unroll 1
        for (int h = 0; h < 2; h++) {
          const int row = h * 8 + (lane >> 2);
          const uint32_t src = out_row(row) + (lane & 3) * 16;
          char* dst = reinterpret_cast<char*>(P.out + (size_t)o_row(row_block(t) * 256 + rank * 128 + 64 + w * 16 + row) * DM + (t & 3) * 160) + (lane & 3) * 16;
#pragma unroll 1
          for (uint32_t c = 0; c < bytes; c += 320) {
            uint4 v[5];
#pragma unroll
            for (int i = 0; i < 5; i++)
              asm volatile("ld.shared.v4.u32 {%0, %1, %2, %3}, [%4];" : "=r"(v[i].x), "=r"(v[i].y), "=r"(v[i].z), "=r"(v[i].w) : "r"(src + c + i * 64) : "memory");
#pragma unroll
            for (int i = 0; i < 5; i++) *reinterpret_cast<uint4*>(dst + c + i * 64) = v[i];
          }
        }
        return;
      }
      fence_async_smem();
      __syncwarp();
      if (lane < 16) {
        __nv_bfloat16* dst = P.out + (size_t)o_row(row_block(t) * 256 + rank * 128 + wg * 64 + w * 16 + lane) * DM + (t & 3) * 160;
        asm volatile("cp.async.bulk.global.shared::cta.bulk_group [%0], [%1], %2;" ::"l"(dst), "r"(out_row(lane)), "r"(bytes) : "memory");
        asm volatile("cp.async.bulk.commit_group;" ::: "memory");
        asm volatile("cp.async.bulk.wait_group.read 0;" ::: "memory");
      }
    };
    for (int t = id; t == id || (NCL != 66 && t < nsingle); t += ncl) {
      float acc[80];
      uint32_t prev = 0, bprev = 0;
      const bool tile = t < nsingle;
      const bool last = NCL == 66 || t + ncl >= nsingle;
      auto bstep = [&](int ks, int accf) {
        ring_wait();
        mbar_wait(sb + BAR_BFULL + 8 * bslot, bphase);
        wg_fence();
        const uint32_t a = ring_addr() + wg * 512, bd = (((sb & 0x3FFFF) + OFF_Q + bslot * BB) >> 4) | ((4096u >> 4) << 16);
#pragma unroll
        for (int k = 0; k < 4; k++) wgmma_n160<1, 1>(acc, a + LBO64A + k * 128, HI64A, bd + k * 64, HI64, k == 0 ? accf : 1);
        wg_commit();
        if (ks > 0) {
          wg_wait<1>();
          release(prev);
          if (ks < 59 || !last) warp_arrive_cl(mapa(sb + BAR_BEMPTY + 8 * bprev, bprev & 1));
        }
        prev = r.slot; bprev = bslot;
        r.next();
        if (++bslot == 6) { bslot = 0; bphase ^= 1; }
      };
      const char* optr;
      uint32_t iv[30];
      if (tile) {
        bstep(0, 0);
        bstep(1, 1);
        optr = out_ptr(u);
        if (t != id) optr = nullptr;
        load_inv(iv, (it + 1) & 1);
#pragma unroll 1
        for (int ks = 2; ks < 17; ks++) {
          bstep(ks, 1);
          switch (ks) {
            case 2: put(pb, iv, optr, IC<0>()); break;
            case 4: put(pb, iv, optr, IC<1>()); break;
            case 6: put(pb, iv, optr, IC<2>()); break;
            case 8: put(pb, iv, optr, IC<3>()); break;
            case 10: put(pb, iv, optr, IC<4>()); break;
            case 12: put(pb, iv, optr, IC<5>()); break;
            case 14: put(pb, iv, optr, IC<6>()); break;
            case 16: put(pb, iv, optr, IC<7>()); break;
            default: break;
          }
        }
        wg_wait<0>();
        reg_fence(acc);
        if (unsafe(t == id)) slow_path(P, unit_batch(u), unit_head(u, rank), wg, w, fresh_tid() & 31);
        if (t == id) publish();
#pragma unroll 1
        for (int ks = 17; ks < 64; ks++) {
          if (wg == 1 && ks == 64 - END_SKEW) turn_wait();
          bstep(ks, 1);
        }
        if (wg == 0) turn_pass();
        wg_wait<0>();
        reg_fence(acc);
        release(prev);
        if (!last) warp_arrive_cl(mapa(sb + BAR_BEMPTY + 8 * bprev, bprev & 1));
      } else {
        uint32_t n3[8], n4[8], n5[8], n6[8], n7[8];
        Ring r2 = r;
        auto first = [&](int ks) {
          if (gemm) { mbar_wait(sb + BAR_RFULL + 8 * r2.slot, r2.phase); mbar_wait(sb + BAR_BFULL + 16 * ks, 0); }
          wg_fence();
          const uint32_t a = (((sb & 0x3FFFF) + r2.slot * RING_BYTES) >> 4) + wg * 512;
          const uint32_t bd = (((sb & 0x3FFFF) + OFF_Q + 2 * ks * BB) >> 4) | ((4096u >> 4) << 16);
#pragma unroll
          for (int k = 0; k < 4; k++) wgmma_n160<1, 1>(acc, a + LBO64A + k * 128, HI64A, bd + k * 64, HI64, k + ks != 0);
          wg_commit();
          r2.next();
        };
        first(0);
        first(1);
        optr = out_ptr(u);
        load_inv(iv, (it + 1) & 1);
        put(pb, iv, optr, IC<0>()); put(pb, iv, optr, IC<1>()); put(pb, iv, optr, IC<2>());
        norm(n3, pb, iv, IC<3>()); norm(n4, pb, iv, IC<4>());
        norm(n5, pb, iv, IC<5>()); norm(n6, pb, iv, IC<6>()); norm(n7, pb, iv, IC<7>());
        wg_wait<0>();
        reg_fence(acc);
        if (unsafe(true)) {
          slow_path(P, unit_batch(u), unit_head(u, rank), wg, w, fresh_tid() & 31);
          optr = nullptr; od1 = od2 = 0;
#pragma unroll
          for (int i = 0; i < 8; i++) n3[i] = n4[i] = n5[i] = n6[i] = n7[i] = 0;
        }
        if (!gemm) {
          store(n3, optr, IC<3>()); store(n4, optr, IC<4>()); store(n5, optr, IC<5>()); store(n6, optr, IC<6>()); store(n7, optr, IC<7>());
          publish();
          break;
        }
        float ac1[80];
        auto half = [&](float (&ac)[80], bool rel, int accf) {
          mbar_wait(sb + BAR_BFULL + 8 * bslot, bphase);
          wg_fence();
          const uint32_t a = ring_addr() + wg * 512, bd = (((sb & 0x3FFFF) + OFF_Q + bslot * BB) >> 4) | ((4096u >> 4) << 16);
#pragma unroll
          for (int k = 0; k < 4; k++) wgmma_n160<1, 1>(ac, a + LBO64A + k * 128, HI64A, bd + k * 64, HI64, k == 0 ? accf : 1);
          wg_commit();
          wg_wait<1>();
          if (rel) warp_arrive_cl(mapa(sb + BAR_BEMPTY + 8 * bprev, bprev & 1));
          bprev = bslot;
        };
        auto dstep = [&](int ks) {
          ring_wait();
          half(acc, ks < 62, 1);
          release(prev);
          bslot++;
          half(ac1, ks < 61, 1);
          if (++bslot == 6) { bslot = 0; bphase ^= 1; }
          prev = r.slot; r.next();
        };
        warp_arrive_cl(mapa(sb + BAR_BEMPTY, 0));
        bprev = 2; bslot = 1;
        half(ac1, true, 0);
        prev = r.slot; r.next(); bslot = 3;
        half(ac1, true, 1);
        release(prev); prev = r.slot; r.next(); bslot = 4;
#pragma unroll 1
        for (int ks = 2; ks < 7; ks++) {
          dstep(ks);
          switch (ks) {
            case 2: store(n3, optr, IC<3>()); break;
            case 3: store(n4, optr, IC<4>()); break;
            case 4: store(n5, optr, IC<5>()); break;
            case 5: store(n6, optr, IC<6>()); break;
            default: store(n7, optr, IC<7>()); break;
          }
        }
        publish();
#pragma unroll 1
        for (int ks = 7; ks < 64; ks++) {
          if (wg == 1 && ks == 62) turn_wait();
          dstep(ks);
        }
        if (wg == 0) turn_pass();
        wg_wait<0>();
        reg_fence(acc); reg_fence(ac1);
        bar_sync(wg);
        out_stage(ac1, 320);
      }
      const int pos0 = row_block(t) * 256 + rank * 128 + wg * 64 + w * 16;
      if (last) {
        bar_sync(wg);
        out_stage(acc, 0);
        out_store(tile ? t : 2 * id - 72, tile ? 320 : 640);
      } else {
        const int lane = fresh_tid() & 31;
        __nv_bfloat16* op0 = P.out + (size_t)o_row(pos0 + (lane >> 2)) * DM + (t & 3) * 160 + (lane & 3) * 2;
        __nv_bfloat16* op1 = P.out + (size_t)o_row(pos0 + (lane >> 2) + 8) * DM + (t & 3) * 160 + (lane & 3) * 2;
#pragma unroll
        for (int j = 0; j < 20; j++) {
          *reinterpret_cast<uint32_t*>(op0 + j * 8) = pack(acc[4 * j], acc[4 * j + 1]);
          *reinterpret_cast<uint32_t*>(op1 + j * 8) = pack(acc[4 * j + 2], acc[4 * j + 3]);
        }
      }
#pragma unroll
      for (int i = 0; i < 60; i++) pb[i] = 0;
    }
  }
}

typedef CUresult (*EncodeFn)(CUtensorMap*, CUtensorMapDataType, cuuint32_t, void*, const cuuint64_t*, const cuuint64_t*,
                             const cuuint32_t*, const cuuint32_t*, CUtensorMapInterleave, CUtensorMapSwizzle,
                             CUtensorMapL2promotion, CUtensorMapFloatOOBfill);

void make_map(EncodeFn enc, CUtensorMap* m, const void* p, int rank, const cuuint64_t* dims, const cuuint64_t* strides,
              const cuuint32_t* box, CUtensorMapSwizzle sw, CUtensorMapL2promotion promo) {
  cuuint32_t es[4] = {1, 1, 1, 1};
  enc(m, CU_TENSOR_MAP_DATA_TYPE_BFLOAT16, rank, const_cast<void*>(p), dims, strides, box, es, CU_TENSOR_MAP_INTERLEAVE_NONE, sw,
      promo, CU_TENSOR_MAP_FLOAT_OOB_FILL_NONE);
}

}

extern "C" void kernel_launch(void* const* d_in, const int* in_sizes, int n_in, void* d_out, int out_size) {
  static EncodeFn enc = nullptr;
  static int nclusters = 0;
  static void* o_ptr = nullptr;
  if (!enc) {
    cudaDriverEntryPointQueryResult qr;
    cudaGetDriverEntryPoint("cuTensorMapEncodeTiled", (void**)&enc, cudaEnableDefault, &qr);
    cudaFuncSetAttribute(fused_attn_kernel<66>, cudaFuncAttributeMaxDynamicSharedMemorySize, SMEM_BYTES);
    cudaFuncSetAttribute(fused_attn_kernel<0>, cudaFuncAttributeMaxDynamicSharedMemorySize, SMEM_BYTES);
    cudaGetSymbolAddress(&o_ptr, g_o);
    cudaLaunchConfig_t cfg = {};
    cfg.gridDim = 128; cfg.blockDim = 384; cfg.dynamicSmemBytes = SMEM_BYTES;
    cudaLaunchAttribute at; at.id = cudaLaunchAttributeClusterDimension;
    at.val.clusterDim.x = 2; at.val.clusterDim.y = 1; at.val.clusterDim.z = 1;
    cfg.attrs = &at; cfg.numAttrs = 1;
    int n = 0;
    cudaOccupancyMaxActiveClusters(&n, fused_attn_kernel<66>, &cfg);
    nclusters = n >= 66 ? MAXCL : (n >= 64 || n <= 0 ? 64 : n);
  }
  const __nv_bfloat16* x = (const __nv_bfloat16*)d_in[0];
  const __nv_bfloat16* k = (const __nv_bfloat16*)d_in[1];
  const __nv_bfloat16* v = (const __nv_bfloat16*)d_in[2];
  const __nv_bfloat16* wq = (const __nv_bfloat16*)d_in[3];
  const __nv_bfloat16* wo = (const __nv_bfloat16*)d_in[4];
  CUtensorMap tm_x, tm_wq, tm_k, tm_v, tm_o, tm_wo;
  const auto S128 = CU_TENSOR_MAP_SWIZZLE_128B;
  const auto P128 = CU_TENSOR_MAP_L2_PROMOTION_L2_128B, P256 = CU_TENSOR_MAP_L2_PROMOTION_L2_256B;
  { cuuint64_t d[2] = {DM, NB * SQ}, s[1] = {DM * 2}; cuuint32_t b[2] = {64, 120}; make_map(enc, &tm_x, x, 2, d, s, b, S128, P128); }
  { cuuint64_t d[3] = {64, DM, HD / 64}, s[2] = {HD * 2, 128}; cuuint32_t b[3] = {64, 64, 2}; make_map(enc, &tm_wq, wq, 3, d, s, b, S128, P256); }
  { cuuint64_t d[3] = {64, NB * NH * SK, 2}, s[2] = {DH * 2, 128}; cuuint32_t b[3] = {64, 64, 2};
    make_map(enc, &tm_k, k, 3, d, s, b, S128, P128); make_map(enc, &tm_v, v, 3, d, s, b, S128, P128); }
  { cuuint64_t d[4] = {256, 2, HD / 8, NROWS / 64}, s[3] = {512, NROWS * 16, 1024}; cuuint32_t b[4] = {256, 2, 8, 2};
    make_map(enc, &tm_o, o_ptr, 4, d, s, b, CU_TENSOR_MAP_SWIZZLE_NONE, P256); }
  { cuuint64_t d[3] = {32, HD, DM / 32}, s[2] = {DM * 2, 64}; cuuint32_t b[3] = {32, 64, 5};
    make_map(enc, &tm_wo, wo, 3, d, s, b, CU_TENSOR_MAP_SWIZZLE_64B, P128); }
  Params P{x, k, v, wq, (__nv_bfloat16*)d_out, (__nv_bfloat16*)o_ptr};
  if (nclusters == 66) fused_attn_kernel<66><<<132, 384, SMEM_BYTES>>>(tm_x, tm_wq, tm_k, tm_v, tm_o, tm_wo, P);
  else fused_attn_kernel<0><<<2 * nclusters, 384, SMEM_BYTES>>>(tm_x, tm_wq, tm_k, tm_v, tm_o, tm_wo, P);
}
```

```cpp
#include <cuda_runtime.h>
#include <cuda.h>
#include <cuda_bf16.h>
#include <stdint.h>

namespace {

constexpr int NB = 16, SQ = 240, DM = 640, NH = 32, SK = 1024, DH = 128, HD = NH * DH;
constexpr int NROWS = NB * SQ;
constexpr int NUNITS = 256;
#define ALT_FROM 4
#define END_SKEW 5
#define VREL 8
#define PF_N 4
#define PF_J0 3
#define PF_STEP 3
#define WO_PF 6
#define PAUSE_CYC 18000
#define MAXCL 66
constexpr int NOTILES = 60;
constexpr float QSCALE = 0.08838834764831845f * 1.4426950408889634f;
constexpr float L_MIN = 1.f;
constexpr float L_MAX = 1.152921504606846976e18f;

constexpr uint32_t RING_SLOTS = 6, RING_BYTES = 16384;
constexpr uint32_t XB = 15360;
constexpr uint32_t BB = 20480;
constexpr uint32_t OFF_Q = RING_SLOTS * RING_BYTES;
constexpr uint32_t OFF_P = OFF_Q + 4 * XB;
constexpr uint32_t OFF_INV = OFF_P + 4 * XB;
constexpr uint32_t OFF_L2 = OFF_INV + 1280;
constexpr uint32_t OFF_BAR = OFF_L2 + 4096;
constexpr uint32_t BAR_RFULL = OFF_BAR, BAR_REMPTY = BAR_RFULL + 48, BAR_XFULL = BAR_REMPTY + 48,
    BAR_XEMPTY = BAR_XFULL + 64, BAR_BFULL = BAR_XEMPTY + 32, BAR_BEMPTY = BAR_BFULL + 48, BAR_STAGE = BAR_BEMPTY + 48;
constexpr uint32_t BAR_LSUM = BAR_STAGE + 16, BAR_INV = BAR_LSUM + 16;
constexpr uint32_t OFF_TR = BAR_INV + 16;
constexpr uint32_t SMEM_BYTES = OFF_TR + 1024;

constexpr uint32_t HI128 = (1u << 30) | (1024 >> 4);
constexpr uint32_t HI64 = (2u << 30) | (512 >> 4);
constexpr uint32_t HI64A = (2u << 30) | (1024 >> 4), LBO64A = (512u >> 4) << 16;

__device__ __align__(1024) __nv_bfloat16 g_o[HD * NROWS];
__device__ __align__(128) unsigned g_cnt[65 * 8];

struct Params {
  const __nv_bfloat16 *x, *k, *v, *wq;
  __nv_bfloat16 *out, *o;
};

__device__ __forceinline__ void wg_fence() { asm volatile("wgmma.fence.sync.aligned;" ::: "memory"); }
__device__ __forceinline__ void wg_commit() { asm volatile("wgmma.commit_group.sync.aligned;" ::: "memory"); }
template <int N> __device__ __forceinline__ void wg_wait() { asm volatile("wgmma.wait_group.sync.aligned %0;" ::"n"(N) : "memory"); }
template <int N> __device__ __forceinline__ void reg_fence(float (&r)[N]) {
#pragma unroll
  for (int i = 0; i < N; i++) asm volatile("" : "+f"(r[i])::"memory");
}
template <int TA, int TB>
__device__ __forceinline__ void wgmma_n120(float (&d)[60], uint32_t a_lo, uint32_t a_hi, uint32_t b_lo, uint32_t b_hi, int acc) {
  asm volatile(
      "{\n.reg .pred p;\n.reg .b64 da, db;\nsetp.ne.b32 p, %64, 0;\n"
      "mov.b64 da, {%60, %61};\nmov.b64 db, {%62, %63};\n"
      "wgmma.mma_async.sync.aligned.m64n120k16.f32.bf16.bf16 {"
      "%0, %1, %2, %3, %4, %5, %6, %7, %8, %9, %10, %11, %12, %13, %14, %15, %16, %17, %18, %19, %20, %21, %22, %23, "
      "%24, %25, %26, %27, %28, %29, %30, %31, %32, %33, %34, %35, %36, %37, %38, %39, %40, %41, %42, %43, %44, %45, "
      "%46, %47, %48, %49, %50, %51, %52, %53, %54, %55, %56, %57, %58, %59"
      "}, da, db, p, 1, 1, %65, %66;\n}\n"
      : "+f"(d[0]), "+f"(d[1]), "+f"(d[2]), "+f"(d[3]), "+f"(d[4]), "+f"(d[5]), "+f"(d[6]), "+f"(d[7]), "+f"(d[8]),
        "+f"(d[9]), "+f"(d[10]), "+f"(d[11]), "+f"(d[12]), "+f"(d[13]), "+f"(d[14]), "+f"(d[15]), "+f"(d[16]),
        "+f"(d[17]), "+f"(d[18]), "+f"(d[19]), "+f"(d[20]), "+f"(d[21]), "+f"(d[22]), "+f"(d[23]), "+f"(d[24]),
        "+f"(d[25]), "+f"(d[26]), "+f"(d[27]), "+f"(d[28]), "+f"(d[29]), "+f"(d[30]), "+f"(d[31]), "+f"(d[32]),
        "+f"(d[33]), "+f"(d[34]), "+f"(d[35]), "+f"(d[36]), "+f"(d[37]), "+f"(d[38]), "+f"(d[39]), "+f"(d[40]),
        "+f"(d[41]), "+f"(d[42]), "+f"(d[43]), "+f"(d[44]), "+f"(d[45]), "+f"(d[46]), "+f"(d[47]), "+f"(d[48]),
        "+f"(d[49]), "+f"(d[50]), "+f"(d[51]), "+f"(d[52]), "+f"(d[53]), "+f"(d[54]), "+f"(d[55]), "+f"(d[56]),
        "+f"(d[57]), "+f"(d[58]), "+f"(d[59])
      : "r"(a_lo), "r"(a_hi), "r"(b_lo), "r"(b_hi), "r"(acc), "n"(TA), "n"(TB));
}

template <int TA, int TB>
__device__ __forceinline__ void wgmma_n160(float (&d)[80], uint32_t a_lo, uint32_t a_hi, uint32_t b_lo, uint32_t b_hi, int acc) {
  asm volatile(
      "{\n.reg .pred p;\n.reg .b64 da, db;\nsetp.ne.b32 p, %84, 0;\n"
      "mov.b64 da, {%80, %81};\nmov.b64 db, {%82, %83};\n"
      "wgmma.mma_async.sync.aligned.m64n160k16.f32.bf16.bf16 {"
      "%0, %1, %2, %3, %4, %5, %6, %7, %8, %9, %10, %11, %12, %13, %14, %15, %16, %17, %18, %19, %20, %21, %22, %23, "
      "%24, %25, %26, %27, %28, %29, %30, %31, %32, %33, %34, %35, %36, %37, %38, %39, %40, %41, %42, %43, %44, %45, "
      "%46, %47, %48, %49, %50, %51, %52, %53, %54, %55, %56, %57, %58, %59, %60, %61, %62, %63, %64, %65, %66, %67, "
      "%68, %69, %70, %71, %72, %73, %74, %75, %76, %77, %78, %79"
      "}, da, db, p, 1, 1, %85, %86;\n}\n"
      : "+f"(d[0]), "+f"(d[1]), "+f"(d[2]), "+f"(d[3]), "+f"(d[4]), "+f"(d[5]), "+f"(d[6]), "+f"(d[7]), "+f"(d[8]),
        "+f"(d[9]), "+f"(d[10]), "+f"(d[11]), "+f"(d[12]), "+f"(d[13]), "+f"(d[14]), "+f"(d[15]), "+f"(d[16]),
        "+f"(d[17]), "+f"(d[18]), "+f"(d[19]), "+f"(d[20]), "+f"(d[21]), "+f"(d[22]), "+f"(d[23]), "+f"(d[24]),
        "+f"(d[25]), "+f"(d[26]), "+f"(d[27]), "+f"(d[28]), "+f"(d[29]), "+f"(d[30]), "+f"(d[31]), "+f"(d[32]),
        "+f"(d[33]), "+f"(d[34]), "+f"(d[35]), "+f"(d[36]), "+f"(d[37]), "+f"(d[38]), "+f"(d[39]), "+f"(d[40]),
        "+f"(d[41]), "+f"(d[42]), "+f"(d[43]), "+f"(d[44]), "+f"(d[45]), "+f"(d[46]), "+f"(d[47]), "+f"(d[48]),
        "+f"(d[49]), "+f"(d[50]), "+f"(d[51]), "+f"(d[52]), "+f"(d[53]), "+f"(d[54]), "+f"(d[55]), "+f"(d[56]),
        "+f"(d[57]), "+f"(d[58]), "+f"(d[59]), "+f"(d[60]), "+f"(d[61]), "+f"(d[62]), "+f"(d[63]), "+f"(d[64]),
        "+f"(d[65]), "+f"(d[66]), "+f"(d[67]), "+f"(d[68]), "+f"(d[69]), "+f"(d[70]), "+f"(d[71]), "+f"(d[72]),
        "+f"(d[73]), "+f"(d[74]), "+f"(d[75]), "+f"(d[76]), "+f"(d[77]), "+f"(d[78]), "+f"(d[79])
      : "r"(a_lo), "r"(a_hi), "r"(b_lo), "r"(b_hi), "r"(acc), "n"(TA), "n"(TB));
}
__device__ __forceinline__ void mbar_init(uint32_t bar, int cnt) { asm volatile("mbarrier.init.shared::cta.b64 [%0], %1;" ::"r"(bar), "r"(cnt)); }
__device__ __forceinline__ void mbar_expect(uint32_t bar, uint32_t bytes) {
  asm volatile("mbarrier.arrive.expect_tx.shared::cta.b64 _, [%0], %1;" ::"r"(bar), "r"(bytes) : "memory");
}
__device__ __forceinline__ uint32_t mapa(uint32_t addr, uint32_t cta) {
  uint32_t r; asm("mapa.shared::cluster.u32 %0, %1, %2;" : "=r"(r) : "r"(addr), "r"(cta)); return r;
}
__device__ __forceinline__ void mbar_expect_cl(uint32_t cbar, uint32_t bytes) {
  asm volatile("mbarrier.arrive.expect_tx.shared::cluster.b64 _, [%0], %1;" ::"r"(cbar), "r"(bytes) : "memory");
}
__device__ __forceinline__ void warp_arrive(uint32_t bar) {
  asm volatile("{\n.reg .pred p;\nelect.sync _|p, 0xffffffff;\n@p mbarrier.arrive.shared::cta.b64 _, [%0];\n}\n" ::"r"(bar) : "memory");
}
__device__ __forceinline__ void warp_arrive_cl(uint32_t cbar) {
  asm volatile("{\n.reg .pred p;\nelect.sync _|p, 0xffffffff;\n@p mbarrier.arrive.shared::cluster.b64 _, [%0];\n}\n" ::"r"(cbar) : "memory");
}
__device__ __forceinline__ void mbar_wait(uint32_t bar, uint32_t parity) {
  asm volatile(
      "{\n.reg .pred p;\n.reg .u32 n;\n"
      "mbarrier.try_wait.parity.shared::cta.b64 p, [%0], %1;\n@p bra WAIT_DONE;\n"
      "mov.u32 n, 0;\n"
      "WAIT_LOOP:\n"
      "mbarrier.try_wait.parity.shared::cta.b64 p, [%0], %1;\n@p bra WAIT_DONE;\n"
      "add.u32 n, n, 1;\nsetp.lt.u32 p, n, 0x4000000;\n@p bra WAIT_LOOP;\ntrap;\n"
      "WAIT_DONE:\n}\n" ::"r"(bar), "r"(parity) : "memory");
}
__device__ __forceinline__ void mbar_sleep(uint32_t bar, uint32_t parity) {
  asm volatile(
      "{\n.reg .pred p;\n.reg .u32 n;\nmov.u32 n, 0;\n"
      "WAIT_LOOP:\n"
      "mbarrier.try_wait.parity.shared::cta.b64 p, [%0], %1, 4000;\n@p bra WAIT_DONE;\n"
      "add.u32 n, n, 1;\nsetp.lt.u32 p, n, 0x400000;\n@p bra WAIT_LOOP;\ntrap;\n"
      "WAIT_DONE:\n}\n" ::"r"(bar), "r"(parity) : "memory");
}
__device__ __forceinline__ void tma3d(uint32_t dst, const CUtensorMap* m, int c0, int c1, int c2, uint32_t bar) {
  asm volatile("cp.async.bulk.tensor.3d.shared::cluster.global.mbarrier::complete_tx::bytes [%0], [%1, {%3, %4, %5}], [%2];"
               ::"r"(dst), "l"(m), "r"(bar), "r"(c0), "r"(c1), "r"(c2) : "memory");
}
__device__ __forceinline__ void tma3d_hint(uint32_t dst, const CUtensorMap* m, int c0, int c1, int c2, uint32_t bar, uint64_t pol) {
  asm volatile("cp.async.bulk.tensor.3d.shared::cluster.global.mbarrier::complete_tx::bytes.L2::cache_hint [%0], [%1, {%3, %4, %5}], [%2], %6;"
               ::"r"(dst), "l"(m), "r"(bar), "r"(c0), "r"(c1), "r"(c2), "l"(pol) : "memory");
}
__device__ __forceinline__ void tma2d_mc(uint32_t dst, const CUtensorMap* m, int c0, int c1, uint32_t bar) {
  asm volatile("cp.async.bulk.tensor.2d.shared::cluster.global.mbarrier::complete_tx::bytes.multicast::cluster [%0], [%1, {%3, %4}], [%2], %5;"
               ::"r"(dst), "l"(m), "r"(bar), "r"(c0), "r"(c1), "h"((uint16_t)3) : "memory");
}
__device__ __forceinline__ void tma3d_mc(uint32_t dst, const CUtensorMap* m, int c0, int c1, int c2, uint32_t bar) {
  asm volatile("cp.async.bulk.tensor.3d.shared::cluster.global.mbarrier::complete_tx::bytes.multicast::cluster [%0], [%1, {%3, %4, %5}], [%2], %6;"
               ::"r"(dst), "l"(m), "r"(bar), "r"(c0), "r"(c1), "r"(c2), "h"((uint16_t)3) : "memory");
}
__device__ __forceinline__ void l2_prefetch(const void* p, uint32_t bytes) {
  asm volatile("cp.async.bulk.prefetch.L2.global [%0], %1;" ::"l"(p), "r"(bytes) : "memory");
}
__device__ __forceinline__ void fence_async_smem() { asm volatile("fence.proxy.async.shared::cta;" ::: "memory"); }
__device__ __forceinline__ void bar_sync(int wg) {
  if (wg == 0) asm volatile("bar.sync 1, 128;" ::: "memory");
  else asm volatile("bar.sync 2, 128;" ::: "memory");
}
__device__ __forceinline__ bool bar_red_or(int wg, bool v) {
  uint32_t r;
  if (wg == 0) asm volatile("{\n.reg .pred p, q;\nsetp.ne.u32 p, %1, 0;\nbar.red.or.pred q, 1, 128, p;\nselp.u32 %0, 1, 0, q;\n}\n" : "=r"(r) : "r"((uint32_t)v) : "memory");
  else asm volatile("{\n.reg .pred p, q;\nsetp.ne.u32 p, %1, 0;\nbar.red.or.pred q, 2, 128, p;\nselp.u32 %0, 1, 0, q;\n}\n" : "=r"(r) : "r"((uint32_t)v) : "memory");
  return r != 0;
}
__device__ __forceinline__ uint32_t hfma2(uint32_t a, uint32_t b, uint32_t c) { uint32_t r; asm("fma.rn.bf16x2 %0, %1, %2, %3;" : "=r"(r) : "r"(a), "r"(b), "r"(c)); return r; }
__device__ __forceinline__ float ex2(float x) { float y; asm("ex2.approx.ftz.f32 %0, %1;" : "=f"(y) : "f"(x)); return y; }
__device__ __forceinline__ uint32_t pack(float lo, float hi) { uint32_t r; asm("cvt.rn.bf16x2.f32 %0, %1, %2;" : "=r"(r) : "f"(hi), "f"(lo)); return r; }
__device__ __forceinline__ void stsm4t(uint32_t a, uint32_t r0, uint32_t r1, uint32_t r2, uint32_t r3) {
  asm volatile("stmatrix.sync.aligned.m8n8.x4.trans.shared.b16 [%0], {%1,%2,%3,%4};" ::"r"(a), "r"(r0), "r"(r1), "r"(r2), "r"(r3) : "memory");
}
__device__ __forceinline__ void stsm2t(uint32_t a, uint32_t r0, uint32_t r1) {
  asm volatile("stmatrix.sync.aligned.m8n8.x2.trans.shared.b16 [%0], {%1,%2};" ::"r"(a), "r"(r0), "r"(r1) : "memory");
}
__device__ __forceinline__ void mma16816(float (&d)[4], const uint32_t (&a)[4], uint32_t b0, uint32_t b1) {
  asm volatile("mma.sync.aligned.m16n8k16.row.col.f32.bf16.bf16.f32 {%0,%1,%2,%3}, {%4,%5,%6,%7}, {%8,%9}, {%0,%1,%2,%3};"
               : "+f"(d[0]), "+f"(d[1]), "+f"(d[2]), "+f"(d[3]) : "r"(a[0]), "r"(a[1]), "r"(a[2]), "r"(a[3]), "r"(b0), "r"(b1));
}

__device__ __forceinline__ uint32_t fresh_tid() { uint32_t t; asm volatile("mov.u32 %0, %tid.x;" : "=r"(t)); return t; }

template <int V> struct IC { static constexpr int value = V; };

struct Ring {
  uint32_t slot = 0, phase = 0;
  __device__ __forceinline__ void next() { if (++slot == RING_SLOTS) { slot = 0; phase ^= 1; } }
};

__device__ __forceinline__ void mma_tn(float (&o0)[60], float (&o1)[60], uint32_t a, uint32_t b, int acc) {
#pragma unroll
  for (int k = 0; k < 4; k++) {
    wgmma_n120<1, 0>(o0, a + k * 128, HI128, b + k * 2, HI128, k == 0 ? acc : 1);
    wgmma_n120<1, 0>(o1, a + 512 + k * 128, HI128, b + k * 2, HI128, k == 0 ? acc : 1);
  }
}
__device__ __forceinline__ void mma_tn_split(float (&o0)[60], float (&o1)[60], uint32_t a, uint32_t b) {
#pragma unroll
  for (int k = 0; k < 4; k++) wgmma_n120<1, 0>(o0, a + k * 128, HI128, b + k * 2, HI128, 1);
  wg_commit();
#pragma unroll
  for (int k = 0; k < 4; k++) wgmma_n120<1, 0>(o1, a + 512 + k * 128, HI128, b + k * 2, HI128, 1);
  wg_commit();
}
__device__ __forceinline__ void mma_qk(float (&s)[60], uint32_t a, uint32_t q) {
#pragma unroll
  for (int k = 0; k < 8; k++)
    wgmma_n120<0, 0>(s, a + (k >> 2) * 512 + (k & 3) * 2, HI128, q + (k >> 2) * (XB >> 4) + (k & 3) * 2, HI128, k != 0);
}
template <int J0, int J1, bool FIRST = false>
__device__ __forceinline__ void exp_store(const float (&s)[60], float (&l)[30], uint32_t dst) {
#pragma unroll
  for (int c = J0; c < J1; c++) {
    const float e0 = ex2(s[4 * c]), e1 = ex2(s[4 * c + 1]), e2 = ex2(s[4 * c + 2]), e3 = ex2(s[4 * c + 3]);
    if (FIRST) { l[2 * c] = e0 + e2; l[2 * c + 1] = e1 + e3; }
    else { l[2 * c] += e0; l[2 * c + 1] += e1; l[2 * c] += e2; l[2 * c + 1] += e3; }
    stsm2t(dst + c * 1024, pack(e0, e1), pack(e2, e3));
  }
}

__device__ __forceinline__ int o_pos(int b, int wg, int r) {
  const int j = r >> 3, q = (r >> 1) & 3, c = r & 1, o = b & 1, base = (b >> 1) * 480;
  if (j < 12) return base + (o * 9 + wg * 3 + (j >> 2)) * 32 + q * 8 + (j & 3) * 2 + c;
  if (j < 14) return base + (6 + 2 * o) * 32 + wg * 16 + q * 4 + (j - 12) * 2 + c;
  return base + 7 * 32 + (o * 2 + wg) * 8 + q * 2 + c;
}
__device__ __forceinline__ int o_row(int p) {
  const int pair = p / 480, a = (p - pair * 480) >> 5, in = p & 31, c = p & 1;
  int tile, row;
  if (a == 7) { tile = in >> 3; row = 112 + (in & 7); }
  else if (a == 6 || a == 8) { tile = a - 6 + (in >> 4); row = (12 + ((in >> 1) & 1)) * 8 + ((in >> 2) & 3) * 2 + c; }
  else { const int f = a > 8 ? a - 3 : a; tile = f / 3; row = ((f - tile * 3) * 4 + ((in >> 1) & 3)) * 8 + (in >> 3) * 2 + c; }
  return pair * 480 + tile * 120 + row;
}
__device__ __forceinline__ uint32_t o_idx(int k, int p) {
  return ((k >> 3) * (NROWS / 32) + (p >> 5)) * 256 + (k & 7) * 32 + ((((p >> 3) & 3) ^ ((k & 7) >> 1)) << 3) + (p & 7);
}

__device__ __noinline__ void slow_path(const Params P, int b, int h, int wg, int w, int lane) {
  const int g = lane >> 2, q = lane & 3, row0 = wg * 120;
  const uint16_t* wq = reinterpret_cast<const uint16_t*>(P.wq) + h * DH + g;
  const __nv_bfloat16* kp = P.k + (size_t)(b * NH + h) * SK * DH;
  const uint16_t* vp = reinterpret_cast<const uint16_t*>(P.v) + (size_t)(b * NH + h) * SK * DH + g;
#pragma unroll 1
  for (int t = w; t < 8; t += 4) {
    const int r0 = 16 * t + g, r1 = r0 + 8;
    const __nv_bfloat16* x0 = P.x + (size_t)(b * SQ + row0 + r0) * DM + 2 * q;
    const __nv_bfloat16* x1 = P.x + (size_t)(b * SQ + row0 + min(r1, 119)) * DM + 2 * q;
    float o[16][4];
#pragma unroll
    for (int n = 0; n < 16; n++) o[n][0] = o[n][1] = o[n][2] = o[n][3] = 0.f;
#pragma unroll 1
    for (int k0 = 0; k0 < DM; k0 += 16) {
      uint32_t a[4] = {*(const uint32_t*)(x0 + k0), *(const uint32_t*)(x1 + k0), *(const uint32_t*)(x0 + k0 + 8), *(const uint32_t*)(x1 + k0 + 8)};
      const uint16_t* wr = wq + (size_t)(k0 + 2 * q) * HD;
#pragma unroll
      for (int n = 0; n < 16; n++) {
        if ((n & 3) == 0) __syncwarp();
        mma16816(o[n], a, wr[8 * n] | ((uint32_t)wr[8 * n + HD] << 16), wr[8 * n + 8 * HD] | ((uint32_t)wr[8 * n + 9 * HD] << 16));
      }
    }
    uint32_t qa[8][4];
#pragma unroll
    for (int k = 0; k < 8; k++) {
      qa[k][0] = pack(o[2 * k][0] * QSCALE, o[2 * k][1] * QSCALE);
      qa[k][1] = pack(o[2 * k][2] * QSCALE, o[2 * k][3] * QSCALE);
      qa[k][2] = pack(o[2 * k + 1][0] * QSCALE, o[2 * k + 1][1] * QSCALE);
      qa[k][3] = pack(o[2 * k + 1][2] * QSCALE, o[2 * k + 1][3] * QSCALE);
    }
#pragma unroll
    for (int n = 0; n < 16; n++) o[n][0] = o[n][1] = o[n][2] = o[n][3] = 0.f;
    float m0 = -INFINITY, m1 = -INFINITY, l0 = 0.f, l1 = 0.f;
#pragma unroll 1
    for (int key0 = 0; key0 < SK; key0 += 16) {
      float s[2][4];
#pragma unroll
      for (int nt = 0; nt < 2; nt++) {
        s[nt][0] = s[nt][1] = s[nt][2] = s[nt][3] = 0.f;
        const __nv_bfloat16* kr = kp + (size_t)(key0 + 8 * nt + g) * DH + 2 * q;
#pragma unroll
        for (int k = 0; k < 8; k++) mma16816(s[nt], qa[k], *(const uint32_t*)(kr + 16 * k), *(const uint32_t*)(kr + 16 * k + 8));
      }
      float n0 = fmaxf(fmaxf(s[0][0], s[0][1]), fmaxf(s[1][0], s[1][1])), n1 = fmaxf(fmaxf(s[0][2], s[0][3]), fmaxf(s[1][2], s[1][3]));
      n0 = fmaxf(n0, __shfl_xor_sync(~0u, n0, 1)); n1 = fmaxf(n1, __shfl_xor_sync(~0u, n1, 1));
      n0 = fmaxf(n0, __shfl_xor_sync(~0u, n0, 2)); n1 = fmaxf(n1, __shfl_xor_sync(~0u, n1, 2));
      n0 = fmaxf(n0, m0); n1 = fmaxf(n1, m1);
      const float z0 = n0 == -INFINITY ? 0.f : n0, z1 = n1 == -INFINITY ? 0.f : n1;
      const float c0 = ex2(m0 - z0), c1 = ex2(m1 - z1);
      m0 = n0; m1 = n1;
#pragma unroll
      for (int nt = 0; nt < 2; nt++) {
        s[nt][0] = ex2(s[nt][0] - z0); s[nt][1] = ex2(s[nt][1] - z0);
        s[nt][2] = ex2(s[nt][2] - z1); s[nt][3] = ex2(s[nt][3] - z1);
      }
      l0 = l0 * c0 + s[0][0] + s[0][1] + s[1][0] + s[1][1];
      l1 = l1 * c1 + s[0][2] + s[0][3] + s[1][2] + s[1][3];
      uint32_t pa[4] = {pack(s[0][0], s[0][1]), pack(s[0][2], s[0][3]), pack(s[1][0], s[1][1]), pack(s[1][2], s[1][3])};
      const uint16_t* vr = vp + (size_t)(key0 + 2 * q) * DH;
#pragma unroll
      for (int n = 0; n < 16; n++) {
        if ((n & 3) == 0) __syncwarp();
        o[n][0] *= c0; o[n][1] *= c0; o[n][2] *= c1; o[n][3] *= c1;
        mma16816(o[n], pa, vr[8 * n] | ((uint32_t)vr[8 * n + DH] << 16), vr[8 * n + 8 * DH] | ((uint32_t)vr[8 * n + 9 * DH] << 16));
      }
    }
    l0 += __shfl_xor_sync(~0u, l0, 1); l1 += __shfl_xor_sync(~0u, l1, 1);
    l0 += __shfl_xor_sync(~0u, l0, 2); l1 += __shfl_xor_sync(~0u, l1, 2);
    const float i0 = __fdividef(1.f, l0), i1 = __fdividef(1.f, l1);
    __nv_bfloat16* oc0 = P.o + o_idx(h * DH + 2 * q, o_pos(b, wg, r0));
    __nv_bfloat16* oc1 = P.o + o_idx(h * DH + 2 * q, o_pos(b, wg, min(r1, 119)));
#pragma unroll
    for (int n = 0; n < 16; n++) {
      oc0[8 * n * NROWS] = __float2bfloat16(o[n][0] * i0);
      oc0[8 * n * NROWS + 32] = __float2bfloat16(o[n][1] * i0);
      if (r1 < 120) {
        oc1[8 * n * NROWS] = __float2bfloat16(o[n][2] * i1);
        oc1[8 * n * NROWS + 32] = __float2bfloat16(o[n][3] * i1);
      }
    }
  }
}

__device__ __forceinline__ int bk(int ks) { return ks < 48 ? 32 - (ks & 48) + (ks & 15) : ks; }
__device__ __forceinline__ uint32_t x_slot(uint32_t wg, uint32_t j) { return j < 2 ? (2 * wg + j) * XB : (2 * j + wg) * XB; }
__device__ __forceinline__ int row_block(int t) { return t >= 44 ? (t >> 2) - 11 : (t >> 2) + 4; }
__device__ __forceinline__ int cluster_id(int c) {
  const int t = c >= 4 ? c - 4 : c + 62;
  return t < 44 || t >= 64 ? t : t < 50 ? t + 14 : t - 6;
}
__device__ __forceinline__ int unit_batch(int u) { return (u & 63) >> 2; }
__device__ __forceinline__ int unit_head(int u, int rank) { return (u >> 6) * 8 + (u & 3) * 2 + rank; }

template <int NCL>
__global__ void __cluster_dims__(2, 1, 1) __launch_bounds__(384, 1)
fused_attn_kernel(const __grid_constant__ CUtensorMap tm_x, const __grid_constant__ CUtensorMap tm_wq,
                  const __grid_constant__ CUtensorMap tm_k, const __grid_constant__ CUtensorMap tm_v,
                  const __grid_constant__ CUtensorMap tm_o, const __grid_constant__ CUtensorMap tm_wo,
                  const __grid_constant__ Params P) {
  extern __shared__ uint8_t smem_raw[];
  const uint32_t sb = ((uint32_t)__cvta_generic_to_shared(smem_raw) + 1023) & ~1023u;
  const int warp = __shfl_sync(~0u, threadIdx.x >> 5, 0);
  const int lane = threadIdx.x & 31;
  const int rank = blockIdx.x & 1, ncl = NCL ? NCL : gridDim.x >> 1;
  const int id = NCL == 66 ? cluster_id(blockIdx.x >> 1) : blockIdx.x >> 1;
  const int id0 = NCL == 66 ? (id >= 58 ? id - 58 : id + 8) : id;
  auto unit = [&](int it) { return (it < 3 ? id0 : id) + it * ncl; };
  const int nsingle = NCL == 66 ? 44 : NOTILES;
  const bool dbl = NCL == 66 && id >= 58, gemm = id < nsingle || dbl;

  if (threadIdx.x == 128) asm volatile("prefetch.tensormap [%0];" ::"l"(&tm_x) : "memory");
  if (threadIdx.x == 0) {
    asm volatile("prefetch.tensormap [%0];" ::"l"(&tm_wq) : "memory");
    for (int i = 0; i < 6; i++) {
      mbar_init(sb + BAR_RFULL + 8 * i, 1); mbar_init(sb + BAR_REMPTY + 8 * i, 8);
      mbar_init(sb + BAR_BFULL + 8 * i, 1); mbar_init(sb + BAR_BEMPTY + 8 * i, 16);
    }
    for (int i = 0; i < 8; i++) mbar_init(sb + BAR_XFULL + 8 * i, 1);
    for (int i = 0; i < 4; i++) mbar_init(sb + BAR_XEMPTY + 8 * i, 8);
    for (int i = 0; i < 2; i++) { mbar_init(sb + BAR_STAGE + 8 * i, 4); mbar_init(sb + BAR_LSUM + 8 * i, 4); mbar_init(sb + BAR_INV + 8 * i, 1); }
    asm volatile("fence.mbarrier_init.release.cluster;" ::: "memory");
  }
  __syncwarp();
  asm volatile("barrier.cluster.arrive.relaxed.aligned;" ::: "memory");
  auto first_w = [&](int s) {
    mbar_expect(sb + BAR_RFULL + 8 * s, RING_BYTES);
    tma3d(sb + s * RING_BYTES, &tm_wq, 0, s * 64, 2 * unit_head(id0, rank), sb + BAR_RFULL + 8 * s);
  };
  if (threadIdx.x == 0) first_w(0);
  __syncwarp();
  asm volatile("barrier.cluster.wait.aligned;" ::: "memory");
  if (threadIdx.x == 128) {
#pragma unroll 1
    for (int s = 0; s < 2; s++) {
      const uint32_t fb = sb + BAR_XFULL + 32 * rank + 8 * s;
      mbar_expect(fb, XB);
      mbar_expect_cl(mapa(fb, rank ^ 1), XB);
      tma2d_mc(sb + OFF_Q + x_slot(rank, s), &tm_x, s * 64, unit_batch(id0) * SQ + rank * 120, fb);
      if (s == 0) first_w(1);
    }
  }
  __syncwarp();

  if (warp >= 8) {
    asm volatile("setmaxnreg.dec.sync.aligned.u32 24;");
    if (warp == 8) {
      uint64_t pol;
      asm volatile("createpolicy.fractional.L2::evict_first.b64 %0, 1.0;" : "=l"(pol));
      Ring r;
      r.slot = 2;
      auto load = [&](const CUtensorMap* m, int c1, int c2, bool ef) {
        mbar_sleep(sb + BAR_REMPTY + 8 * r.slot, r.phase ^ 1);
        if (lane == 0) {
          mbar_expect(sb + BAR_RFULL + 8 * r.slot, RING_BYTES);
          if (ef) tma3d_hint(sb + r.slot * RING_BYTES, m, 0, c1, c2, sb + BAR_RFULL + 8 * r.slot, pol);
          else tma3d(sb + r.slot * RING_BYTES, m, 0, c1, c2, sb + BAR_RFULL + 8 * r.slot);
        }
        r.next();
      };
      for (int u0 = 0; id + u0 < NUNITS; u0 += ncl) {
        const int u = (u0 < 3 * ncl ? id0 : id) + u0;
        if (NCL == 66 && u0 == 2 * 66 && !gemm) {
          unsigned t0, t1;
          asm volatile("mov.u32 %0, %clock;" : "=r"(t0));
          do { __nanosleep(200); asm volatile("mov.u32 %0, %clock;" : "=r"(t1)); } while (t1 - t0 < PAUSE_CYC);
        }
        const int h = unit_head(u, rank);
        const int krow = (unit_batch(u) * NH + h) * SK;
#pragma unroll 1
        for (int s = u0 == 0 ? 2 : 0; s < 10; s++) {
          load(&tm_wq, s * 64, 2 * h, false);
          const int sp = u0 == 0 ? s - 6 : s;
          if (sp >= 0 && sp < PF_N && lane == 0) l2_prefetch(P.v + (size_t)(krow + (PF_J0 + sp * PF_STEP) * 64) * DH, 16384);
        }
#pragma unroll 1
        for (int j = 0; j <= 16; j++) {
          if (j < 16) load(&tm_k, krow + j * 64, 0, true);
          if (j == 2) load(&tm_v, krow, 0, true);
          if (j > 1) load(&tm_v, krow + (j - 1) * 64, 0, true);
        }
      }
      for (int t = dbl ? 2 * id - 72 : id; t < (dbl ? NOTILES : nsingle); t += ncl) {
        const int row0 = row_block(t) * 256 + rank * 128;
        const int b0 = row0 / SQ, b1 = (row0 + 127) / SQ;
#pragma unroll 1
        for (int ks = 0; ks < 64; ks++) {
          if (dbl ? (ks & 15) == 0 : ks == 0 || ks == 48) {
            const unsigned* c = &g_cnt[((lane & 1 ? b1 : b0) * 4 + (ks || dbl ? ks >> 4 : min(lane >> 1, 2))) * 8];
            unsigned v, n = 0;
            do {
              asm volatile("ld.acquire.gpu.global.u32 %0, [%1];" : "=r"(v) : "l"(c) : "memory");
              if (++n > (1u << 26)) __trap();
            } while (v < 16);
            __syncwarp();
            asm volatile("fence.proxy.async.global;" ::: "memory");
          }
          mbar_wait(sb + BAR_REMPTY + 8 * r.slot, r.phase ^ 1);
          if (lane == 0) {
            mbar_expect(sb + BAR_RFULL + 8 * r.slot, RING_BYTES);
            asm volatile("cp.async.bulk.tensor.4d.shared::cluster.global.mbarrier::complete_tx::bytes.L2::cache_hint [%0], [%1, {%3, %3, %4, %5}], [%2], %6;"
                         ::"r"(sb + r.slot * RING_BYTES), "l"(&tm_o), "r"(sb + BAR_RFULL + 8 * r.slot), "r"(0), "r"((dbl ? ks : bk(ks)) * 8), "r"(row0 >> 6), "l"(pol) : "memory");
          }
          r.next();
        }
      }
      if (lane == 0 && atomicAdd(&g_cnt[64 * 8], 1) == gridDim.x - 1) {
        for (int i = 0; i < 65; i++) g_cnt[i * 8] = 0;
      }
    } else if (warp == 9) {
      if (lane == 0) {
        for (uint32_t it = 0; id + it * ncl < NUNITS; it++) {
          const int row = unit_batch(unit(it)) * SQ + rank * 120;
#pragma unroll 1
          for (int s = it == 0 ? 2 : 0; s < 10; s++) {
            const uint32_t j = s & 3, par = ((s >> 2) + (j < 2 ? it : 0)) & 1;
            if (s == 0) mbar_sleep(sb + BAR_XEMPTY, par ^ 1);
            mbar_wait(sb + BAR_XEMPTY + 8 * j, par ^ 1);
            const uint32_t fb = sb + BAR_XFULL + 32 * rank + 8 * j;
            mbar_expect(fb, XB);
            mbar_expect_cl(mapa(fb, rank ^ 1), XB);
            tma2d_mc(sb + OFF_Q + x_slot(rank, j), &tm_x, s * 64, row, fb);
          }
        }
        uint32_t slot = rank, phase = 0;
        if (dbl) {
#pragma unroll 1
          for (int ks = (id >> 1) & 3; ks < WO_PF; ks += 4)
            asm volatile("cp.async.bulk.prefetch.tensor.3d.L2.global [%0, {%1, %2, %3}];" ::"l"(&tm_wo), "r"(0), "r"(ks * 64), "r"(((2 * id - 72 + rank) & 3) * 5) : "memory");
        }
        if (gemm) mbar_sleep(sb + BAR_BEMPTY + 8 * rank, 0);
        for (int t = dbl ? 2 * id - 72 + rank : id; t < (dbl ? NOTILES : nsingle); t += ncl) {
#pragma unroll 1
          for (int ks = dbl ? 0 : rank; ks < 64; ks += dbl ? 1 : 2) {
            mbar_wait(sb + BAR_BEMPTY + 8 * slot, phase);
            const uint32_t fb = sb + BAR_BFULL + 8 * slot;
            mbar_expect(fb, BB);
            mbar_expect_cl(mapa(fb, rank ^ 1), BB);
            tma3d_mc(sb + OFF_Q + slot * BB, &tm_wo, 0, (dbl ? ks : bk(ks)) * 64, (t & 3) * 5, fb);
            if (dbl && ks + WO_PF < 64 && (ks & 3) == ((id >> 1) & 3))
              asm volatile("cp.async.bulk.prefetch.tensor.3d.L2.global [%0, {%1, %2, %3}];" ::"l"(&tm_wo), "r"(0), "r"((ks + WO_PF) * 64), "r"((t & 3) * 5) : "memory");
            slot += 2;
            if (slot >= 6) { slot -= 6; phase ^= 1; }
          }
        }
      }
    } else {
      const int wg = warp - 10;
      {
        mbar_wait(sb + BAR_RFULL, 0);
        const __nv_bfloat16* xs = P.x + (size_t)(unit_batch(id0) * SQ + ((id0 & 3) * 2 + rank) * 30 + min(lane, 29)) * DM + 256 + wg * 64;
#pragma unroll
        for (int i = 0; i < 3; i++) asm volatile("prefetch.global.L2 [%0];" ::"l"(xs + i * 128));
        if (lane < 16) asm volatile("prefetch.global.L2 [%0];" ::"l"(P.wq + (size_t)(384 + unit_batch(id0) * 16 + lane) * HD + unit_head(id0, rank) * DH + wg * 64));
      }
      for (uint32_t it = 0; id + it * ncl < NUNITS; it++) {
        const int u = unit(it);
        mbar_sleep(sb + BAR_LSUM + 8 * wg, it & 1);
        float l4[4], v[4];
        const uint32_t a = sb + OFF_L2 + wg * 2048 + (fresh_tid() & 31) * 16;
        asm volatile("ld.shared.v4.f32 {%0, %1, %2, %3}, [%4];" : "=f"(l4[0]), "=f"(l4[1]), "=f"(l4[2]), "=f"(l4[3]) : "r"(a) : "memory");
#pragma unroll
        for (int g = 1; g < 4; g++) {
          asm volatile("ld.shared.v4.f32 {%0, %1, %2, %3}, [%4];" : "=f"(v[0]), "=f"(v[1]), "=f"(v[2]), "=f"(v[3]) : "r"(a + g * 512) : "memory");
#pragma unroll
          for (int c = 0; c < 4; c++) l4[c] += v[c];
        }
#pragma unroll
        for (int c = 0; c < 4; c++) {
          float inv;
          asm("rcp.approx.ftz.f32 %0, %1;" : "=f"(inv) : "f"(l4[c]));
          l4[c] = l4[c] >= L_MIN && l4[c] <= L_MAX ? inv : __uint_as_float(0x7FFFFFFFu);
        }
        const uint32_t h0 = pack(l4[0], l4[1]), h1 = pack(l4[2], l4[3]);
        const uint32_t e0 = pack(l4[0] - __uint_as_float(h0 << 16), l4[1] - __uint_as_float(h0 & 0xFFFF0000u));
        const uint32_t e1 = pack(l4[2] - __uint_as_float(h1 << 16), l4[3] - __uint_as_float(h1 & 0xFFFF0000u));
        const uint32_t tid = fresh_tid();
        asm volatile("st.shared.v4.u32 [%0], {%1, %2, %3, %4};" ::"r"(sb + OFF_INV + wg * 640 + (tid & 3) * 144 + (tid & 28) * 4), "r"(h0), "r"(e0), "r"(h1), "r"(e1) : "memory");
        __syncwarp();
        warp_arrive(sb + BAR_INV + 8 * wg);
        mbar_sleep(sb + BAR_STAGE + 8 * wg, it & 1);
        if (lane == 0) {
          __threadfence();
          asm volatile("red.relaxed.gpu.global.add.u32 [%0], 1;" ::"l"(&g_cnt[(unit_batch(u) * 4 + (u >> 6)) * 8]) : "memory");
        }
        __syncwarp();
      }
    }
  } else {
    asm volatile("setmaxnreg.inc.sync.aligned.u32 240;");
    const int wg = warp >> 2, w = warp & 3;
    const uint32_t qreg = sb + OFF_Q + wg * 2 * XB, preg = sb + OFF_P + (2 + wg) * XB;
    const uint32_t st_off = ((lane >> 4) * 8 + (lane & 7)) * 128 + (((2 * w + ((lane >> 3) & 1)) ^ (lane & 7)) << 4);
    const uint32_t xempty = mapa(sb + BAR_XEMPTY, wg);
    Ring r;
    uint32_t it = 0;
    const uint32_t qd = (qreg & 0x3FFFF) >> 4, pd = (preg & 0x3FFFF) >> 4;
    auto ring_addr = [&]() { return ((sb & 0x3FFFF) + r.slot * RING_BYTES) >> 4; };
    auto ring_wait = [&]() { mbar_wait(sb + BAR_RFULL + 8 * r.slot, r.phase); };
    auto release = [&](uint32_t slot) { warp_arrive(sb + BAR_REMPTY + 8 * slot); };
    auto turn_wait = [&]() {
      if (wg == 0) asm volatile("bar.sync 3, 256;" ::: "memory");
      else asm volatile("bar.sync 4, 256;" ::: "memory");
    };
    auto turn_pass = [&]() {
      if (wg == 0) asm volatile("bar.arrive 4, 256;" ::: "memory");
      else asm volatile("bar.arrive 3, 256;" ::: "memory");
    };

    uint32_t chk = 0;
    auto sum_l = [&](const float (&l)[30], uint32_t tid) {
      float a[16], b[8], c[4];
      const bool b4 = tid & 16, b3 = tid & 8, b2 = tid & 4;
#pragma unroll
      for (int i = 0; i < 16; i++) {
        const float hi = i < 14 ? l[(16 + i) % 30] : 1.f;
        a[i] = (b4 ? hi : l[i]) + __shfl_xor_sync(~0u, b4 ? l[i] : hi, 16);
      }
#pragma unroll
      for (int i = 0; i < 8; i++) b[i] = (b3 ? a[8 + i] : a[i]) + __shfl_xor_sync(~0u, b3 ? a[i] : a[8 + i], 8);
#pragma unroll
      for (int i = 0; i < 4; i++) c[i] = (b2 ? b[4 + i] : b[i]) + __shfl_xor_sync(~0u, b2 ? b[i] : b[4 + i], 4);
      asm volatile("st.shared.v4.f32 [%0], {%1, %2, %3, %4};" ::"r"(sb + OFF_L2 + tid * 16), "f"(c[0]), "f"(c[1]),
                   "f"(c[2]), "f"(c[3]) : "memory");
      __syncwarp();
      warp_arrive(sb + BAR_LSUM + 8 * wg);
    };
    auto load_inv = [&](uint32_t (&iv)[30], uint32_t parity) {
      const int lane = fresh_tid() & 31;
      mbar_wait(sb + BAR_INV + 8 * wg, parity);
      chk = 0;
#pragma unroll
      for (int j = 0; j < 7; j++)
        asm volatile("ld.shared.v4.u32 {%0, %1, %2, %3}, [%4];" : "=r"(iv[4 * j]), "=r"(iv[4 * j + 1]), "=r"(iv[4 * j + 2]), "=r"(iv[4 * j + 3])
                     : "r"(sb + OFF_INV + wg * 640 + (lane & 3) * 144 + j * 16) : "memory");
      asm volatile("ld.shared.v2.u32 {%0, %1}, [%2];" : "=r"(iv[28]), "=r"(iv[29]) : "r"(sb + OFF_INV + wg * 640 + (lane & 3) * 144 + 112) : "memory");
    };
    auto norm = [&](uint32_t (&n)[8], const uint32_t (&po)[60], const uint32_t (&iv)[30], auto part) {
      constexpr int k = decltype(part)::value >> 1, j0 = (decltype(part)::value & 1) * 8;
#pragma unroll
      for (int j = 0; j < 8; j++)
        n[j] = j0 + j < 15 ? hfma2(po[15 * k + (j0 + j) % 15], iv[2 * ((j0 + j) % 15)], hfma2(po[15 * k + (j0 + j) % 15], iv[2 * ((j0 + j) % 15) + 1], 0x80008000u)) : 0x3F803F80u;
#pragma unroll
      for (int j = 0; j < 8; j += 2) chk = hfma2(n[j], n[j + 1], chk);
    };
    int od1, od2;
    auto store = [&](const uint32_t (&n)[8], const char* optr, auto part) {
      constexpr int k = decltype(part)::value >> 1, off = (8 * (k & 1) + 64 * (k >> 1)) * NROWS * 2;
      if ((decltype(part)::value & 1) == 0)
        asm volatile(
            "{\n.reg .pred p;\nsetp.ne.u64 p, %8, 0;\n"
            "@p st.global.v4.u32 [%8 + %9], {%0, %1, %2, %3};\n@p st.global.v4.u32 [%8 + %9 + 512], {%4, %5, %6, %7};\n}\n"
            ::"r"(n[0]), "r"(n[1]), "r"(n[2]), "r"(n[3]), "r"(n[4]), "r"(n[5]), "r"(n[6]), "r"(n[7]), "l"(optr), "n"(off) : "memory");
      else
        asm volatile(
            "{\n.reg .pred p;\n.reg .b64 b, c;\nsetp.ne.u64 p, %7, 0;\nmad.wide.s32 b, %9, 1, %7;\nmad.wide.s32 c, %10, 1, %7;\n"
            "@p st.global.v4.u32 [%7 + %8 + 1024], {%0, %1, %2, %3};\n@p st.global.v2.u32 [b + %8], {%4, %5};\n@p st.global.u32 [c + %8], %6;\n}\n"
            ::"r"(n[0]), "r"(n[1]), "r"(n[2]), "r"(n[3]), "r"(n[4]), "r"(n[5]), "r"(n[6]), "l"(optr), "n"(off), "r"(od1), "r"(od2) : "memory");
    };
    auto put = [&](const uint32_t (&po)[60], const uint32_t (&iv)[30], const char* optr, auto part) {
      uint32_t n[8];
      norm(n, po, iv, part);
      store(n, optr, part);
    };
    auto out_ptr = [&](int u) {
      const int lane = fresh_tid() & 31;
      const int k = unit_head(u, rank) * DH + 16 * w + (lane >> 2), b = unit_batch(u), q = lane & 3;
      const uint32_t i0 = o_idx(k, o_pos(b, wg, 2 * q));
      od1 = 2 * (int)(o_idx(k, o_pos(b, wg, 96 + 2 * q)) - i0);
      od2 = 2 * (int)(o_idx(k, o_pos(b, wg, 112 + 2 * q)) - i0);
      return reinterpret_cast<const char*>(P.o + i0);
    };
    auto unsafe = [&](bool valid) {
      const bool b = valid && ((chk & 0x7F80u) == 0x7F80u || (chk & 0x7F800000u) == 0x7F800000u);
      return __any_sync(~0u, bar_red_or(wg, b));
    };
    auto publish = [&]() { __syncwarp(); warp_arrive(sb + BAR_STAGE + 8 * wg); };

    uint32_t po[60];
#pragma unroll
    for (int i = 0; i < 60; i++) po[i] = 0;
    float o0[60], o1[60];
    ring_wait();
    mbar_wait(sb + BAR_XFULL + 32 * wg, 0);
    wg_fence();
    mma_tn(o0, o1, ring_addr(), qd, 0);
    wg_commit();
    while (true) {
      uint32_t prev = r.slot;
      r.next();
      auto qstep = [&](int s) {
        const uint32_t j = s & 3, par = ((s >> 2) + (j < 2 ? it : 0)) & 1;
        ring_wait();
        mbar_wait(sb + BAR_XFULL + 32 * wg + 8 * j, par);
        if (s >= ALT_FROM) turn_wait();
        wg_fence();
        mma_tn(o0, o1, ring_addr(), ((sb & 0x3FFFF) + OFF_Q + x_slot(wg, j)) >> 4, 1);
        wg_commit();
        if (s >= ALT_FROM || (s == ALT_FROM - 1 && wg == 1)) turn_pass();
        if (s <= 4) {
          wg_wait<1>();
          release(prev);
          warp_arrive_cl(xempty + 8 * ((s - 1) & 3));
        }
        prev = r.slot;
        r.next();
      };
      auto qdone = [&](int s) {
        wg_wait<0>();
        release(prev);
        if (s <= 5) warp_arrive_cl(xempty + 8 * (s & 3));
      };
      qstep(1);
      const int up = unit((int)it - 1);
      const char* optr = out_ptr(up);
      if (it == 0) optr = nullptr;
      uint32_t n7[8];
      {
        uint32_t iv[30];
        load_inv(iv, (it + 1) & 1); put(po, iv, optr, IC<0>());
        qstep(2); put(po, iv, optr, IC<1>());
        qstep(3); put(po, iv, optr, IC<2>());
        qstep(4); put(po, iv, optr, IC<3>()); qdone(4);
        qstep(5); put(po, iv, optr, IC<4>()); qdone(5);
        qstep(6); put(po, iv, optr, IC<5>()); qdone(6);
        qstep(7); put(po, iv, optr, IC<6>()); norm(n7, po, iv, IC<7>()); qdone(7);
      }
      ring_wait();
      mbar_wait(sb + BAR_XFULL + 32 * wg, it & 1);
      turn_wait();
      wg_fence();
      mma_tn(o0, o1, ring_addr(), qd, 1);
      wg_commit();
      prev = r.slot;
      r.next();
      ring_wait();
      mbar_wait(sb + BAR_XFULL + 32 * wg + 8, it & 1);
      wg_fence();
      mma_tn_split(o0, o1, ring_addr(), qd + (XB >> 4));
      turn_pass();
      wg_wait<2>();
      release(prev);
      auto put_q = [&](const float (&o)[60], uint32_t dst) {
#pragma unroll
        for (int j = 0; j < 14; j += 2)
          stsm4t(dst + j * 1024, pack(o[4 * j] * QSCALE, o[4 * j + 1] * QSCALE), pack(o[4 * j + 2] * QSCALE, o[4 * j + 3] * QSCALE),
                 pack(o[4 * j + 4] * QSCALE, o[4 * j + 5] * QSCALE), pack(o[4 * j + 6] * QSCALE, o[4 * j + 7] * QSCALE));
        stsm2t(dst + 14 * 1024, pack(o[56] * QSCALE, o[57] * QSCALE), pack(o[58] * QSCALE, o[59] * QSCALE));
      };
      wg_wait<1>();
      reg_fence(o0);
      const bool redo = unsafe(it > 0);
      put_q(o0, qreg + st_off);
      wg_wait<0>();
      reg_fence(o1);
      release(r.slot);
      r.next();
      bar_sync(wg);
      put_q(o1, qreg + XB + st_off);
      fence_async_smem();
      if (redo) {
        slow_path(P, unit_batch(up), unit_head(up, rank), wg, w, fresh_tid() & 31);
        optr = nullptr; od1 = od2 = 0;
#pragma unroll
        for (int i = 0; i < 8; i++) n7[i] = 0;
      }

      float sc[60], l[30];
      uint32_t slot0 = r.slot;
      ring_wait();
      turn_wait();
      wg_fence();
      mma_qk(sc, ring_addr(), qd);
      wg_commit();
      r.next();
      uint32_t slot1 = r.slot;
      ring_wait();
      wg_fence();
      mma_qk(o1, ring_addr(), qd);
      wg_commit();
      r.next();
      turn_pass();
      store(n7, optr, IC<7>());
      wg_wait<1>();
      reg_fence(sc);
      release(slot0);
      exp_store<0, 15, true>(sc, l, preg + st_off);
      slot0 = r.slot;
      ring_wait();
      wg_fence();
      mma_qk(sc, ring_addr(), qd);
      wg_commit();
      r.next();
      wg_wait<1>();
      reg_fence(o1);
      release(slot1);
      exp_store<0, 15>(o1, l, preg - 2 * XB + st_off);
      fence_async_smem();
      slot1 = r.slot;
      ring_wait();
      turn_wait();
      wg_fence();
      mma_tn(o0, o1, ring_addr(), pd, 0);
      wg_commit();
      r.next();
      ring_wait();
      wg_fence();
      mma_tn(o0, o1, ring_addr(), pd - (2 * XB >> 4), 1);
      wg_commit();
      turn_pass();
      if (it > 0) publish();
      wg_wait<1>();
      reg_fence(sc);
      release(slot0);
      release(slot1);
      bar_sync(wg);
      exp_store<0, VREL>(sc, l, preg + st_off);
      wg_wait<0>();
      reg_fence(o0); reg_fence(o1);
      release(r.slot);
      r.next();
      exp_store<VREL, 15>(sc, l, preg + st_off);
      fence_async_smem();
      const bool more = id + ((int)it + 1) * ncl < NUNITS;
      uint32_t pw = preg + st_off;
#pragma unroll 1
      for (int s = 3; s < 16; s++) {
        const uint32_t kslot = r.slot;
        asm volatile("add.u32 %0, %0, %1;" : "+r"(pw) : "r"(s & 1 ? -2 * (int)XB : 2 * (int)XB));
        ring_wait();
        turn_wait();
        wg_fence();
        mma_qk(sc, ring_addr(), qd);
        wg_commit();
        r.next();
        ring_wait();
        wg_fence();
        mma_tn(o0, o1, ring_addr(), pd - ((s - 1) & 1) * (2 * XB >> 4), 1);
        wg_commit();
        if (wg == 0 || s < 15) turn_pass();
        wg_wait<1>();
        reg_fence(sc);
        release(kslot);
        if (s == 15) {
          if (more) { warp_arrive_cl(xempty); warp_arrive_cl(xempty + 8); }
          else if (gemm) for (int i = 0; i < 3; i++) warp_arrive_cl(mapa(sb + BAR_BEMPTY + 8 * i, i & 1));
        }
        exp_store<0, VREL>(sc, l, pw);
        wg_wait<0>();
        reg_fence(o0); reg_fence(o1);
        release(r.slot);
        r.next();
        exp_store<VREL, 15>(sc, l, pw);
        fence_async_smem();
      }
      const uint32_t tid = fresh_tid();
      bar_sync(wg);
      ring_wait();
      wg_fence();
      mma_tn_split(o0, o1, ring_addr(), pd - (2 * XB >> 4));
      sum_l(l, tid);
      const uint32_t vslot = r.slot;
      r.next();
      it++;
      auto pack_o = [&](const float (&o)[60], int first) {
#pragma unroll
        for (int j = 0; j < 15; j++) { po[first + j] = pack(o[4 * j], o[4 * j + 1]); po[first + 15 + j] = pack(o[4 * j + 2], o[4 * j + 3]); }
      };
      if (!more) {
        wg_wait<0>();
        reg_fence(o0); reg_fence(o1);
        release(vslot);
        if (gemm) for (int i = 3; i < 6; i++) warp_arrive_cl(mapa(sb + BAR_BEMPTY + 8 * i, i & 1));
        pack_o(o0, 0); pack_o(o1, 30);
        break;
      }
      ring_wait();
      mbar_wait(sb + BAR_XFULL + 32 * wg, it & 1);
      wg_wait<1>();
      reg_fence(o0);
      pack_o(o0, 0);
      wg_fence();
#pragma unroll
      for (int k = 0; k < 4; k++) wgmma_n120<1, 0>(o0, ring_addr() + k * 128, HI128, qd + k * 2, HI128, k != 0);
      wg_commit();
      wg_wait<1>();
      reg_fence(o1);
      pack_o(o1, 30);
      wg_fence();
#pragma unroll
      for (int k = 0; k < 4; k++) wgmma_n120<1, 0>(o1, ring_addr() + 512 + k * 128, HI128, qd + k * 2, HI128, k != 0);
      wg_commit();
      release(vslot);
      warp_arrive_cl(xempty + 16); warp_arrive_cl(xempty + 24);
    }
    const int u = unit((int)it - 1);
    uint32_t pb[60];
#pragma unroll
    for (int i = 0; i < 60; i++) pb[i] = NCL != 66 ? po[i] ^ (gridDim.y - 1) : po[i];

    uint32_t bslot = 0, bphase = 0;
    auto out_row = [&](int lane) {
      const int row = lane & 15;
      return sb + wg * 8192 + (row < 12 ? w * RING_BYTES + row * 656 : (4 + (w >> 1)) * RING_BYTES + ((w & 1) * 4 + row - 12) * 656);
    };
    auto out_stage = [&](const float (&acc)[80], uint32_t col_off) {
      const int lane = fresh_tid() & 31;
      const uint32_t sa = out_row(lane) + col_off + (lane >> 4) * 16;
#pragma unroll
      for (int j = 0; j < 20; j += 2)
        asm volatile("stmatrix.sync.aligned.m8n8.x4.shared.b16 [%0], {%1,%2,%3,%4};" ::"r"(sa + j * 16), "r"(pack(acc[4 * j], acc[4 * j + 1])),
                     "r"(pack(acc[4 * j + 2], acc[4 * j + 3])), "r"(pack(acc[4 * j + 4], acc[4 * j + 5])), "r"(pack(acc[4 * j + 6], acc[4 * j + 7])) : "memory");
    };
    auto out_store = [&](int t, uint32_t bytes) {
      const int lane = fresh_tid() & 31;
      if (wg == 1) {
        __syncwarp();
#pragma unroll 1
        for (int h = 0; h < 2; h++) {
          const int row = h * 8 + (lane >> 2);
          const uint32_t src = out_row(row) + (lane & 3) * 16;
          char* dst = reinterpret_cast<char*>(P.out + (size_t)o_row(row_block(t) * 256 + rank * 128 + 64 + w * 16 + row) * DM + (t & 3) * 160) + (lane & 3) * 16;
#pragma unroll 1
          for (uint32_t c = 0; c < bytes; c += 320) {
            uint4 v[5];
#pragma unroll
            for (int i = 0; i < 5; i++)
              asm volatile("ld.shared.v4.u32 {%0, %1, %2, %3}, [%4];" : "=r"(v[i].x), "=r"(v[i].y), "=r"(v[i].z), "=r"(v[i].w) : "r"(src + c + i * 64) : "memory");
#pragma unroll
            for (int i = 0; i < 5; i++) *reinterpret_cast<uint4*>(dst + c + i * 64) = v[i];
          }
        }
        return;
      }
      fence_async_smem();
      __syncwarp();
      if (lane < 16) {
        __nv_bfloat16* dst = P.out + (size_t)o_row(row_block(t) * 256 + rank * 128 + wg * 64 + w * 16 + lane) * DM + (t & 3) * 160;
        asm volatile("cp.async.bulk.global.shared::cta.bulk_group [%0], [%1], %2;" ::"l"(dst), "r"(out_row(lane)), "r"(bytes) : "memory");
        asm volatile("cp.async.bulk.commit_group;" ::: "memory");
        asm volatile("cp.async.bulk.wait_group.read 0;" ::: "memory");
      }
    };
    for (int t = id; t == id || (NCL != 66 && t < nsingle); t += ncl) {
      float acc[80];
      uint32_t prev = 0, bprev = 0;
      const bool tile = t < nsingle;
      const bool last = NCL == 66 || t + ncl >= nsingle;
      auto bstep = [&](int ks, int accf) {
        ring_wait();
        mbar_wait(sb + BAR_BFULL + 8 * bslot, bphase);
        wg_fence();
        const uint32_t a = ring_addr() + wg * 512, bd = (((sb & 0x3FFFF) + OFF_Q + bslot * BB) >> 4) | ((4096u >> 4) << 16);
#pragma unroll
        for (int k = 0; k < 4; k++) wgmma_n160<1, 1>(acc, a + LBO64A + k * 128, HI64A, bd + k * 64, HI64, k == 0 ? accf : 1);
        wg_commit();
        if (ks > 0) {
          wg_wait<1>();
          release(prev);
          if (ks < 59 || !last) warp_arrive_cl(mapa(sb + BAR_BEMPTY + 8 * bprev, bprev & 1));
        }
        prev = r.slot; bprev = bslot;
        r.next();
        if (++bslot == 6) { bslot = 0; bphase ^= 1; }
      };
      const char* optr;
      uint32_t iv[30];
      if (tile) {
        bstep(0, 0);
        bstep(1, 1);
        optr = out_ptr(u);
        if (t != id) optr = nullptr;
        load_inv(iv, (it + 1) & 1);
#pragma unroll 1
        for (int ks = 2; ks < 17; ks++) {
          bstep(ks, 1);
          switch (ks) {
            case 2: put(pb, iv, optr, IC<0>()); break;
            case 4: put(pb, iv, optr, IC<1>()); break;
            case 6: put(pb, iv, optr, IC<2>()); break;
            case 8: put(pb, iv, optr, IC<3>()); break;
            case 10: put(pb, iv, optr, IC<4>()); break;
            case 12: put(pb, iv, optr, IC<5>()); break;
            case 14: put(pb, iv, optr, IC<6>()); break;
            case 16: put(pb, iv, optr, IC<7>()); break;
            default: break;
          }
        }
        wg_wait<0>();
        reg_fence(acc);
        if (unsafe(t == id)) slow_path(P, unit_batch(u), unit_head(u, rank), wg, w, fresh_tid() & 31);
        if (t == id) publish();
#pragma unroll 1
        for (int ks = 17; ks < 64; ks++) {
          if (wg == 1 && ks == 64 - END_SKEW) turn_wait();
          bstep(ks, 1);
        }
        if (wg == 0) turn_pass();
        wg_wait<0>();
        reg_fence(acc);
        release(prev);
        if (!last) warp_arrive_cl(mapa(sb + BAR_BEMPTY + 8 * bprev, bprev & 1));
      } else {
        uint32_t n3[8], n4[8], n5[8], n6[8], n7[8];
        Ring r2 = r;
        auto first = [&](int ks) {
          if (gemm) { mbar_wait(sb + BAR_RFULL + 8 * r2.slot, r2.phase); mbar_wait(sb + BAR_BFULL + 16 * ks, 0); }
          wg_fence();
          const uint32_t a = (((sb & 0x3FFFF) + r2.slot * RING_BYTES) >> 4) + wg * 512;
          const uint32_t bd = (((sb & 0x3FFFF) + OFF_Q + 2 * ks * BB) >> 4) | ((4096u >> 4) << 16);
#pragma unroll
          for (int k = 0; k < 4; k++) wgmma_n160<1, 1>(acc, a + LBO64A + k * 128, HI64A, bd + k * 64, HI64, k + ks != 0);
          wg_commit();
          r2.next();
        };
        first(0);
        first(1);
        optr = out_ptr(u);
        load_inv(iv, (it + 1) & 1);
        put(pb, iv, optr, IC<0>()); put(pb, iv, optr, IC<1>()); put(pb, iv, optr, IC<2>());
        norm(n3, pb, iv, IC<3>()); norm(n4, pb, iv, IC<4>());
        norm(n5, pb, iv, IC<5>()); norm(n6, pb, iv, IC<6>()); norm(n7, pb, iv, IC<7>());
        wg_wait<0>();
        reg_fence(acc);
        if (unsafe(true)) {
          slow_path(P, unit_batch(u), unit_head(u, rank), wg, w, fresh_tid() & 31);
          optr = nullptr; od1 = od2 = 0;
#pragma unroll
          for (int i = 0; i < 8; i++) n3[i] = n4[i] = n5[i] = n6[i] = n7[i] = 0;
        }
        if (!gemm) {
          store(n3, optr, IC<3>()); store(n4, optr, IC<4>()); store(n5, optr, IC<5>()); store(n6, optr, IC<6>()); store(n7, optr, IC<7>());
          publish();
          break;
        }
        float ac1[80];
        auto half = [&](float (&ac)[80], bool rel, int accf) {
          mbar_wait(sb + BAR_BFULL + 8 * bslot, bphase);
          wg_fence();
          const uint32_t a = ring_addr() + wg * 512, bd = (((sb & 0x3FFFF) + OFF_Q + bslot * BB) >> 4) | ((4096u >> 4) << 16);
#pragma unroll
          for (int k = 0; k < 4; k++) wgmma_n160<1, 1>(ac, a + LBO64A + k * 128, HI64A, bd + k * 64, HI64, k == 0 ? accf : 1);
          wg_commit();
          wg_wait<1>();
          if (rel) warp_arrive_cl(mapa(sb + BAR_BEMPTY + 8 * bprev, bprev & 1));
          bprev = bslot;
        };
        auto dstep = [&](int ks) {
          ring_wait();
          half(acc, ks < 62, 1);
          release(prev);
          bslot++;
          half(ac1, ks < 61, 1);
          if (++bslot == 6) { bslot = 0; bphase ^= 1; }
          prev = r.slot; r.next();
        };
        warp_arrive_cl(mapa(sb + BAR_BEMPTY, 0));
        bprev = 2; bslot = 1;
        half(ac1, true, 0);
        prev = r.slot; r.next(); bslot = 3;
        half(ac1, true, 1);
        release(prev); prev = r.slot; r.next(); bslot = 4;
#pragma unroll 1
        for (int ks = 2; ks < 7; ks++) {
          dstep(ks);
          switch (ks) {
            case 2: store(n3, optr, IC<3>()); break;
            case 3: store(n4, optr, IC<4>()); break;
            case 4: store(n5, optr, IC<5>()); break;
            case 5: store(n6, optr, IC<6>()); break;
            default: store(n7, optr, IC<7>()); break;
          }
        }
        publish();
#pragma unroll 1
        for (int ks = 7; ks < 64; ks++) {
          if (wg == 1 && ks == 62) turn_wait();
          dstep(ks);
        }
        if (wg == 0) turn_pass();
        wg_wait<0>();
        reg_fence(acc); reg_fence(ac1);
        bar_sync(wg);
        out_stage(ac1, 320);
      }
      const int pos0 = row_block(t) * 256 + rank * 128 + wg * 64 + w * 16;
      if (last) {
        bar_sync(wg);
        out_stage(acc, 0);
        out_store(tile ? t : 2 * id - 72, tile ? 320 : 640);
      } else {
        const int lane = fresh_tid() & 31;
        __nv_bfloat16* op0 = P.out + (size_t)o_row(pos0 + (lane >> 2)) * DM + (t & 3) * 160 + (lane & 3) * 2;
        __nv_bfloat16* op1 = P.out + (size_t)o_row(pos0 + (lane >> 2) + 8) * DM + (t & 3) * 160 + (lane & 3) * 2;
#pragma unroll
        for (int j = 0; j < 20; j++) {
          *reinterpret_cast<uint32_t*>(op0 + j * 8) = pack(acc[4 * j], acc[4 * j + 1]);
          *reinterpret_cast<uint32_t*>(op1 + j * 8) = pack(acc[4 * j + 2], acc[4 * j + 3]);
        }
      }
#pragma unroll
      for (int i = 0; i < 60; i++) pb[i] = 0;
    }
  }
}

typedef CUresult (*EncodeFn)(CUtensorMap*, CUtensorMapDataType, cuuint32_t, void*, const cuuint64_t*, const cuuint64_t*,
                             const cuuint32_t*, const cuuint32_t*, CUtensorMapInterleave, CUtensorMapSwizzle,
                             CUtensorMapL2promotion, CUtensorMapFloatOOBfill);

void make_map(EncodeFn enc, CUtensorMap* m, const void* p, int rank, const cuuint64_t* dims, const cuuint64_t* strides,
              const cuuint32_t* box, CUtensorMapSwizzle sw, CUtensorMapL2promotion promo) {
  cuuint32_t es[4] = {1, 1, 1, 1};
  enc(m, CU_TENSOR_MAP_DATA_TYPE_BFLOAT16, rank, const_cast<void*>(p), dims, strides, box, es, CU_TENSOR_MAP_INTERLEAVE_NONE, sw,
      promo, CU_TENSOR_MAP_FLOAT_OOB_FILL_NONE);
}

}

extern "C" void kernel_launch(void* const* d_in, const int* in_sizes, int n_in, void* d_out, int out_size) {
  static EncodeFn enc = nullptr;
  static int nclusters = 0;
  static void* o_ptr = nullptr;
  if (!enc) {
    cudaDriverEntryPointQueryResult qr;
    cudaGetDriverEntryPoint("cuTensorMapEncodeTiled", (void**)&enc, cudaEnableDefault, &qr);
    cudaFuncSetAttribute(fused_attn_kernel<66>, cudaFuncAttributeMaxDynamicSharedMemorySize, SMEM_BYTES);
    cudaFuncSetAttribute(fused_attn_kernel<0>, cudaFuncAttributeMaxDynamicSharedMemorySize, SMEM_BYTES);
    cudaGetSymbolAddress(&o_ptr, g_o);
    cudaLaunchConfig_t cfg = {};
    cfg.gridDim = 128; cfg.blockDim = 384; cfg.dynamicSmemBytes = SMEM_BYTES;
    cudaLaunchAttribute at; at.id = cudaLaunchAttributeClusterDimension;
    at.val.clusterDim.x = 2; at.val.clusterDim.y = 1; at.val.clusterDim.z = 1;
    cfg.attrs = &at; cfg.numAttrs = 1;
    int n = 0;
    cudaOccupancyMaxActiveClusters(&n, fused_attn_kernel<66>, &cfg);
    nclusters = n >= 66 ? MAXCL : (n >= 64 || n <= 0 ? 64 : n);
  }
  const __nv_bfloat16* x = (const __nv_bfloat16*)d_in[0];
  const __nv_bfloat16* k = (const __nv_bfloat16*)d_in[1];
  const __nv_bfloat16* v = (const __nv_bfloat16*)d_in[2];
  const __nv_bfloat16* wq = (const __nv_bfloat16*)d_in[3];
  const __nv_bfloat16* wo = (const __nv_bfloat16*)d_in[4];
  CUtensorMap tm_x, tm_wq, tm_k, tm_v, tm_o, tm_wo;
  const auto S128 = CU_TENSOR_MAP_SWIZZLE_128B;
  const auto P128 = CU_TENSOR_MAP_L2_PROMOTION_L2_128B, P256 = CU_TENSOR_MAP_L2_PROMOTION_L2_256B;
  { cuuint64_t d[2] = {DM, NB * SQ}, s[1] = {DM * 2}; cuuint32_t b[2] = {64, 120}; make_map(enc, &tm_x, x, 2, d, s, b, S128, P128); }
  { cuuint64_t d[3] = {64, DM, HD / 64}, s[2] = {HD * 2, 128}; cuuint32_t b[3] = {64, 64, 2}; make_map(enc, &tm_wq, wq, 3, d, s, b, S128, P256); }
  { cuuint64_t d[3] = {64, NB * NH * SK, 2}, s[2] = {DH * 2, 128}; cuuint32_t b[3] = {64, 64, 2};
    make_map(enc, &tm_k, k, 3, d, s, b, S128, P128); make_map(enc, &tm_v, v, 3, d, s, b, S128, P128); }
  { cuuint64_t d[4] = {256, 2, HD / 8, NROWS / 64}, s[3] = {512, NROWS * 16, 1024}; cuuint32_t b[4] = {256, 2, 8, 2};
    make_map(enc, &tm_o, o_ptr, 4, d, s, b, CU_TENSOR_MAP_SWIZZLE_NONE, P256); }
  { cuuint64_t d[3] = {32, HD, DM / 32}, s[2] = {DM * 2, 64}; cuuint32_t b[3] = {32, 64, 5};
    make_map(enc, &tm_wo, wo, 3, d, s, b, CU_TENSOR_MAP_SWIZZLE_64B, P128); }
  Params P{x, k, v, wq, (__nv_bfloat16*)d_out, (__nv_bfloat16*)o_ptr};
  if (nclusters == 66) fused_attn_kernel<66><<<132, 384, SMEM_BYTES>>>(tm_x, tm_wq, tm_k, tm_v, tm_o, tm_wo, P);
  else fused_attn_kernel<0><<<2 * nclusters, 384, SMEM_BYTES>>>(tm_x, tm_wq, tm_k, tm_v, tm_o, tm_wo, P);
}
```
